```python
import torch

def _softmax(x, axis=-1):
    return torch.softmax(x, dim=axis)
def _gelu(x):
    return torch.nn.functional.gelu(x, approximate="tanh")
def _silu(x):
    return torch.nn.functional.silu(x)
def _sigmoid(x):
    return torch.sigmoid(x)
def _layernorm(x, axis=-1, eps=1e-5):
    m = x.mean(dim=axis, keepdim=True)
    v = x.var(dim=axis, keepdim=True, unbiased=False)
    return (x - m) / torch.sqrt(v + eps)
def _scatter_add(tgt, idx, src, axis=0):
    return tgt.clone().index_add_(axis, idx, src)
def _segment_sum(src, seg, n):
    out = torch.zeros((n,) + src.shape[1:], dtype=src.dtype)
    return out.index_add_(0, seg, src)
def _pad(x, pw):
    flat = tuple(v for pair in reversed(pw) for v in pair)
    return torch.nn.functional.pad(x, flat)

kernel_name = 'recurrent_scan__gqa_block_cached__moe_arch_mod__prompt'

def setup_inputs():

    _w = (lambda a: (lambda t: t.to(torch.bfloat16) if t.is_floating_point() else t)(torch.as_tensor(a)))
    def _A_setup():
        B, Sq, D = 1, 2048, 576
        Hq, Hkv, Sk, Dh = 32, 16, 2048, 128
        assert Hq % Hkv == 0, (Hq, Hkv)
        return {
            "x": _w((lambda *s: torch.randn(*s, dtype=torch.bfloat16) * 0.05)(B, Sq, D)),
            "k_cache": _w((lambda *s: torch.randn(*s, dtype=torch.bfloat16) * 0.8)(B, Hkv, Sk, Dh)),
            "v_cache": _w((lambda *s: torch.randn(*s, dtype=torch.bfloat16) * 0.2)(B, Hkv, Sk, Dh)),
            "wq": _w((lambda *s: torch.randn(*s, dtype=torch.bfloat16) * 0.8)(D, Hq * Dh) * (D ** -0.5)),
            "wo": _w((lambda *s: torch.randn(*s, dtype=torch.bfloat16) * 0.2)(Hq * Dh, D) * ((Hq * Dh) ** -0.5)),
        }
    _A_in = _A_setup()

    def _B_setup():
        B, S, D, F, C = 1, 2048, 576, 4608, 8
        return {
            "x": _w((lambda *s: torch.randn(*s, dtype=torch.bfloat16) * 0.05)(B, S, D)),
            "w_r": _w((lambda *s: torch.randn(*s, dtype=torch.bfloat16) * 0.2)(D)),
            "w_gate": _w((lambda *s: torch.randn(*s, dtype=torch.bfloat16) * 0.1)(D, F)),
            "w_up": _w((lambda *s: torch.randn(*s, dtype=torch.bfloat16) * 0.1)(D, F)),
            "w_down": _w((lambda *s: torch.randn(*s, dtype=torch.bfloat16) * 0.1)(F, D)),
        }
    _B_in = _B_setup()

    return {
        "A_x": _A_in["x"],
        "A_k_cache": _A_in["k_cache"],
        "A_v_cache": _A_in["v_cache"],
        "A_wq": _A_in["wq"],
        "A_wo": _A_in["wo"],
        "B_x": _B_in["x"],
        "B_w_r": _B_in["w_r"],
        "B_w_gate": _B_in["w_gate"],
        "B_w_up": _B_in["w_up"],
        "B_w_down": _B_in["w_down"],
    }

def reference(A_x, A_k_cache, A_v_cache, A_wq, A_wo, B_x, B_w_r, B_w_gate, B_w_up, B_w_down):
    def _A_ref(x, k_cache, v_cache, wq, wo):
        B, Sq, D = x.shape
        Hq, Dh = 32, 128
        Hkv = k_cache.shape[1]
        rep = Hq // Hkv
        q = (lambda x, *d: x.permute(*d))((x @ wq).reshape(B, Sq, Hq, Dh), 0, 2, 1, 3)
        k = (lambda x, n, axis: torch.repeat_interleave(x, n, dim=axis))(k_cache, rep, axis=1)
        v = (lambda x, n, axis: torch.repeat_interleave(x, n, dim=axis))(v_cache, rep, axis=1)
        scores = torch.einsum("bhqd,bhkd->bhqk", q, k) * (Dh ** -0.5)
        p = _softmax(scores, axis=-1)
        o = torch.einsum("bhqk,bhkd->bhqd", p, v)
        return (lambda x, *d: x.permute(*d))(o, 0, 2, 1, 3).reshape(B, Sq, Hq * Dh) @ wo

    def _B_ref(x, w_r, w_gate, w_up, w_down):
        B, S, D = x.shape
        C = 8
        r = x @ w_r
        idx = torch.argsort(-r, axis=-1)[:, :C]
        idx_e = (lambda x, n, axis: torch.repeat_interleave(x, n, dim=axis))(idx.reshape(B, C, 1), D, axis=2)
        x_sel = (lambda x, i, axis: torch.take_along_dim(x, i, dim=axis))(x, idx_e, axis=1)
        g = _silu(x_sel @ w_gate)
        u = x_sel @ w_up
        y = (g * u) @ w_down
        r_sel = _sigmoid((lambda x, i, axis: torch.take_along_dim(x, i, dim=axis))(r, idx, axis=1))
        y = y * r_sel.reshape(B, C, 1)
        b_off = (torch.arange(B) * S).reshape(B, 1)
        flat_idx = (idx + b_off).reshape(B * C)
        zero = (x * 0.0).reshape(B * S, D)
        upd = _scatter_add(zero, flat_idx, y.reshape(B * C, D), axis=0)
        return x + upd.reshape(B, S, D)

    x = A_x
    xn = _layernorm(x, axis=-1)
    s = _A_ref(xn, A_k_cache, A_v_cache, A_wq, A_wo)
    g = _silu(_B_ref(xn, B_w_r, B_w_gate, B_w_up, B_w_down))
    return x + s * g
```

```cpp
#include <cuda_runtime.h>
#include <cuda_bf16.h>
#include <cuda.h>
#include <stdint.h>

namespace {

constexpr int SEQ = 2048, DM = 576, DH = 128, FF = 4608, TOPC = 8;
constexpr int N_ATT_CTA = 128, N_CTA = 132;
constexpr int THREADS = 384;

constexpr uint32_t SM_RING = 0;
constexpr uint32_t STAGE = 32768;
constexpr uint32_t SM_SLOT = 131072;
constexpr uint32_t FSTAGE = 24576;
constexpr uint32_t SM_XSEL = 196608;
constexpr uint32_t SM_H = 205824;
constexpr uint32_t SM_MISC = 229376;
constexpr uint32_t SM_FULL = SM_MISC, SM_EMPTY = SM_MISC + 64, SM_BAR_MISC = SM_MISC + 128,
                   SM_COLD = SM_MISC + 136, SM_TAG = SM_MISC + 144, SM_IDX = SM_MISC + 160,
                   SM_TOPK = SM_MISC + 192, SM_XFULL = SM_MISC + 256, SM_BAR_XG = SM_MISC + 304, SM_STATS = SM_MISC + 320;
constexpr uint32_t SM_TOTAL = SM_MISC + 1344;
constexpr uint32_t SM_X = SM_MISC - 147456;

constexpr int BAR_GATE = 6, BAR_HELPER = 7, BAR_OA = 8;
constexpr int NST_Q = 20, NST_KV = 76, NST_O = 18;
__device__ __forceinline__ bool blk_big(int j) { return (unsigned)(j - 5) < 28; }
__device__ __forceinline__ int blk_row(int j) { return 112 * j - 16 * (min(j, 5) + max(j - 33, 0)); }
constexpr float SM_SCALE_LOG2 = 0.08838834764831845f * 1.4426950408889634f;

__device__ __align__(1024) uint4 g_part[16 * 64 * 2 * 4 * 128];
__device__ __align__(1024) uint4 g_gate[SEQ * DM / 8];
__device__ __align__(128) float g_r[SEQ];
__device__ __align__(128) float2 g_stats[SEQ];
__device__ __align__(128) float g_ypart[4 * TOPC * DM];
__device__ __align__(128) float g_upd[TOPC * DM];
__device__ __align__(128) int g_idx[TOPC];
__device__ __align__(128) unsigned g_launch[N_CTA];
__device__ unsigned g_rcnt, g_ycnt, g_ffn_flag;

__device__ __forceinline__ void prof(int, int, int = 0) {}

#define TS(id) {}
#define TS_DUMP() {}
#define TS1(id) TS(id)
#define TS2(k) {}

__device__ __forceinline__ uint32_t smem_u32(const void* p) { return (uint32_t)__cvta_generic_to_shared(p); }
__device__ __forceinline__ void mbar_init(uint32_t bar, uint32_t cnt) {
  asm volatile("mbarrier.init.shared::cta.b64 [%0], %1;" ::"r"(bar), "r"(cnt) : "memory");
}
__device__ __forceinline__ void mbar_expect_tx(uint32_t bar, uint32_t bytes) {
  asm volatile("mbarrier.arrive.expect_tx.shared::cta.b64 _, [%0], %1;" ::"r"(bar), "r"(bytes) : "memory");
}
__device__ __forceinline__ void mbar_arrive(uint32_t bar) {
  asm volatile("mbarrier.arrive.shared::cta.b64 _, [%0];" ::"r"(bar) : "memory");
}
__device__ __forceinline__ void mbar_arrive_cluster(uint32_t bar_cluster_addr) {
  asm volatile("mbarrier.arrive.shared::cluster.b64 _, [%0];" ::"r"(bar_cluster_addr) : "memory");
}
template <int ID>
__device__ __forceinline__ void mbar_arrive_cluster_now(uint32_t bar_cluster_addr, bool pred) {
  asm volatile("{\n.reg .pred p, q;\nsetp.ne.u32 p, %1, 0;\nsetp.eq.u32 q, %2, %3;\n"
               "ARR_LOOP:\n@p mbarrier.arrive.shared::cluster.b64 _, [%0];\n@q bra.uni ARR_LOOP;\n}"
               ::"r"(bar_cluster_addr), "r"((uint32_t)pred), "r"(blockIdx.y), "n"(ID) : "memory");
}
__device__ __forceinline__ void block_fence(int id) {
  asm volatile("{\n.reg .pred q;\nsetp.eq.u32 q, %0, %1;\nBF_LOOP:\n@q st.volatile.shared.u32 [%0], %0;\n@q bra.uni BF_LOOP;\n}"
               ::"r"(blockIdx.y), "r"(id) : "memory");
}
__device__ __forceinline__ void mbar_wait(uint32_t bar, uint32_t parity) {
  asm volatile("{\n.reg .pred p, q;\n.reg .u32 n;\nmov.u32 n, 0;\n"
               "WAIT_LOOP:\nmbarrier.try_wait.parity.shared::cta.b64 p, [%0], %1;\n"
               "add.u32 n, n, 1;\nsetp.lt.u32 q, n, 4194304;\nand.pred q, q, !p;\n@q bra WAIT_LOOP;\n}"
               ::"r"(bar), "r"(parity) : "memory");
}
__device__ __forceinline__ uint32_t mapa(uint32_t addr, uint32_t rank) {
  uint32_t r;
  asm volatile("mapa.shared::cluster.u32 %0, %1, %2;" : "=r"(r) : "r"(addr), "r"(rank));
  return r;
}
__device__ __forceinline__ void cluster_arrive() { asm volatile("barrier.cluster.arrive.relaxed.aligned;" ::: "memory"); }
__device__ __forceinline__ bool elect_one() {
  uint32_t p;
  asm volatile("{\n.reg .pred p;\nelect.sync _|p, 0xffffffff;\nselp.u32 %0, 1, 0, p;\n}" : "=r"(p));
  return p;
}
__device__ __forceinline__ int read_lane() { return threadIdx.x & 31; }
__device__ __forceinline__ void cluster_wait() { asm volatile("barrier.cluster.wait.acquire.aligned;" ::: "memory"); }
__device__ __forceinline__ void bar_sync(int id, int n) { asm volatile("barrier.cta.sync %0, %1;" ::"r"(id), "r"(n) : "memory"); }
__device__ __forceinline__ void bar_arrive(int id, int n) { asm volatile("barrier.cta.arrive %0, %1;" ::"r"(id), "r"(n) : "memory"); }

__device__ __forceinline__ uint64_t policy_evict_first() {
  uint64_t p;
  asm("createpolicy.fractional.L2::evict_first.b64 %0, 1.0;" : "=l"(p));
  return p;
}
__device__ __forceinline__ void tma2d_mc(uint32_t dst, const CUtensorMap* tm, int c0, int c1, uint32_t bar, uint64_t pol) {
  asm volatile("cp.async.bulk.tensor.2d.shared::cluster.global.mbarrier::complete_tx::bytes.multicast::cluster.L2::cache_hint"
               " [%0], [%1, {%2, %3}], [%4], %5, %6;"
               ::"r"(dst), "l"(tm), "r"(c0), "r"(c1), "r"(bar), "h"((uint16_t)3), "l"(pol) : "memory");
}
__device__ __forceinline__ void tma3d(uint32_t dst, const CUtensorMap* tm, int c1, int c2, uint32_t bar) {
  asm volatile("cp.async.bulk.tensor.3d.shared::cluster.global.mbarrier::complete_tx::bytes [%0], [%1, {%2, %3, %4}], [%5];"
               ::"r"(dst), "l"(tm), "r"(0), "r"(c1), "r"(c2), "r"(bar) : "memory");
}
__device__ __forceinline__ void tma2d_stream(uint32_t dst, const CUtensorMap* tm, int c0, int c1, uint32_t bar) {
  asm volatile("{\n.reg .b64 pol;\ncreatepolicy.fractional.L2::evict_first.b64 pol, 1.0;\n"
               "cp.async.bulk.tensor.2d.shared::cluster.global.mbarrier::complete_tx::bytes.L2::cache_hint [%0], [%1, {%2, %3}], [%4], pol;\n}"
               ::"r"(dst), "l"(tm), "r"(c0), "r"(c1), "r"(bar) : "memory");
}
__device__ __forceinline__ void tma2d_prefetch(const CUtensorMap* tm, int c0, int c1) {
  asm volatile("cp.async.bulk.prefetch.tensor.2d.L2.global [%0, {%1, %2}];" ::"l"(tm), "r"(c0), "r"(c1) : "memory");
}
__device__ __forceinline__ void prefetch_tmap(const CUtensorMap* tm) {
  asm volatile("prefetch.tensormap [%0];" ::"l"(tm) : "memory");
}

__device__ __forceinline__ void wg_fence() { asm volatile("wgmma.fence.sync.aligned;" ::: "memory"); }
__device__ __forceinline__ void wg_commit() { asm volatile("wgmma.commit_group.sync.aligned;" ::: "memory"); }
template <int N> __device__ __forceinline__ void wg_wait() { asm volatile("wgmma.wait_group.sync.aligned %0;" ::"n"(N) : "memory"); }

__device__ __forceinline__ uint64_t mkdesc(uint32_t addr, uint32_t lbo_bytes) {
  return (uint64_t)(((addr & 0x3FFFF) >> 4) | ((lbo_bytes >> 4) << 16)) | ((uint64_t)0x40000040u << 32);
}
__device__ __forceinline__ uint64_t mkdesc_q(uint32_t addr) {
  return (uint64_t)(((addr & 0x3FFFF) >> 4) | (64u << 16)) | ((uint64_t)8 << 32);
}
template <int N> __device__ __forceinline__ void pin(float (&a)[N]) {
#pragma unroll
  for (int i = 0; i < N; i++) asm volatile("" : "+f"(a[i])::"memory");
}
template <int N> __device__ __forceinline__ void kill(float (&a)[N]) {
#pragma unroll
  for (int i = 0; i < N; i++) asm volatile("" : "=f"(a[i]));
}
template <int N> __device__ __forceinline__ void pin(uint32_t (&a)[N]) {
#pragma unroll
  for (int i = 0; i < N; i++) asm volatile("" : "+r"(a[i])::"memory");
}

#define F8(d, o) "+f"(d[o]), "+f"(d[o + 1]), "+f"(d[o + 2]), "+f"(d[o + 3]), "+f"(d[o + 4]), "+f"(d[o + 5]), "+f"(d[o + 6]), "+f"(d[o + 7])
#define R32A "%0, %1, %2, %3, %4, %5, %6, %7, %8, %9, %10, %11, %12, %13, %14, %15, %16, %17, %18, %19, %20, %21, %22, %23, %24, %25, %26, %27, %28, %29, %30, %31"
#define R32B "%32, %33, %34, %35, %36, %37, %38, %39, %40, %41, %42, %43, %44, %45, %46, %47, %48, %49, %50, %51, %52, %53, %54, %55, %56, %57, %58, %59, %60, %61, %62, %63"

template <int TB>
__device__ __forceinline__ void mma_n128(float (&d)[64], uint32_t a0, uint32_t a1, uint32_t a2, uint32_t a3, uint64_t db, int acc) {
  asm volatile("{\n.reg .pred p;\nsetp.ne.b32 p, %69, 0;\n"
               "wgmma.mma_async.sync.aligned.m64n128k16.f32.bf16.bf16 {" R32A ", " R32B "}, {%64, %65, %66, %67}, %68, p, 1, 1, %70;\n}\n"
               : F8(d, 0), F8(d, 8), F8(d, 16), F8(d, 24), F8(d, 32), F8(d, 40), F8(d, 48), F8(d, 56)
               : "r"(a0), "r"(a1), "r"(a2), "r"(a3), "l"(db), "r"(acc), "n"(TB));
}
#define PV1(a0, a1, a2, a3, ob, acc) "add.s64 b, %92, " #ob ";\n" \
  "wgmma.mma_async.sync.aligned.m64n128k16.f32.bf16.bf16 {" R32A ", " R32B "}, {%" #a0 ", %" #a1 ", %" #a2 ", %" #a3 "}, b, " #acc ", 1, 1, 1;\n"
#define PV6 "wgmma.fence.sync.aligned;\n" PV1(64, 65, 66, 67, 0, p) PV1(68, 69, 70, 71, 128, 1) PV1(72, 73, 74, 75, 256, 1) \
  PV1(76, 77, 78, 79, 384, 1) PV1(80, 81, 82, 83, 512, 1) PV1(84, 85, 86, 87, 640, 1)
#define U4(a, o) "r"(a[o]), "r"(a[o + 1]), "r"(a[o + 2]), "r"(a[o + 3])
__device__ __forceinline__ void mma_pv(float (&d)[64], const uint32_t (&a)[28], uint64_t dv, bool acc, bool big) {
  asm volatile("{\n.reg .pred p, q;\n.reg .b64 b;\nsetp.ne.b32 p, %93, 0;\nsetp.eq.b32 q, %94, 0;\n@q bra.uni PV_SMALL;\n"
               PV6 PV1(88, 89, 90, 91, 768, 1) "wgmma.commit_group.sync.aligned;\nbra.uni PV_DONE;\n"
               "PV_SMALL:\n" PV6 "wgmma.commit_group.sync.aligned;\nPV_DONE:\n}\n"
               : F8(d, 0), F8(d, 8), F8(d, 16), F8(d, 24), F8(d, 32), F8(d, 40), F8(d, 48), F8(d, 56)
               : U4(a, 0), U4(a, 4), U4(a, 8), U4(a, 12), U4(a, 16), U4(a, 20), U4(a, 24), "l"(dv), "r"((int)acc), "r"((int)big) : "memory");
}
#define R48 R32A ", %32, %33, %34, %35, %36, %37, %38, %39, %40, %41, %42, %43, %44, %45, %46, %47"
#define R56 R48 ", %48, %49, %50, %51, %52, %53, %54, %55"
#define QK1(N, R, A, B, oa, ob, acc) "add.s64 a, " A ", " #oa ";\nadd.s64 b, " B ", " #ob ";\n" \
  "wgmma.mma_async.sync.aligned.m64n" #N "k16.f32.bf16.bf16 {" R "}, a, b, " #acc ", 1, 1, 0, 0;\n"
#define QK8(N, R, A, B) "{\n.reg .b64 a, b;\nwgmma.fence.sync.aligned;\n" QK1(N, R, A, B, 0, 0, 0) QK1(N, R, A, B, 128, 2, 1) \
  QK1(N, R, A, B, 256, 4, 1) QK1(N, R, A, B, 384, 6, 1) QK1(N, R, A, B, 512, 1024, 1) QK1(N, R, A, B, 640, 1026, 1) \
  QK1(N, R, A, B, 768, 1028, 1) QK1(N, R, A, B, 896, 1030, 1) "wgmma.commit_group.sync.aligned;\n}\n"
#define O8(d, o) "=f"(d[o]), "=f"(d[o + 1]), "=f"(d[o + 2]), "=f"(d[o + 3]), "=f"(d[o + 4]), "=f"(d[o + 5]), "=f"(d[o + 6]), "=f"(d[o + 7])
__device__ __forceinline__ void mma_qk(float (&d)[56], uint64_t dq, uint64_t dk) {
  asm volatile(QK8(112, R56, "%56", "%57")
               : O8(d, 0), O8(d, 8), O8(d, 16), O8(d, 24), O8(d, 32), O8(d, 40), O8(d, 48) : "l"(dq), "l"(dk) : "memory");
}
__device__ __forceinline__ void mma_qk(float (&d)[48], uint64_t dq, uint64_t dk) {
  asm volatile(QK8(96, R48, "%48", "%49")
               : O8(d, 0), O8(d, 8), O8(d, 16), O8(d, 24), O8(d, 32), O8(d, 40) : "l"(dq), "l"(dk) : "memory");
}
__device__ __forceinline__ void mma_n64t(float (&d)[32], uint32_t a0, uint32_t a1, uint32_t a2, uint32_t a3, uint64_t db, int acc) {
  asm volatile("{\n.reg .pred p;\nsetp.ne.b32 p, %37, 0;\n"
               "wgmma.mma_async.sync.aligned.m64n64k16.f32.bf16.bf16 {" R32A "}, {%32, %33, %34, %35}, %36, p, 1, 1, 1;\n}\n"
               : F8(d, 0), F8(d, 8), F8(d, 16), F8(d, 24)
               : "r"(a0), "r"(a1), "r"(a2), "r"(a3), "l"(db), "r"(acc));
}
__device__ __forceinline__ void mma_n8(float (&d)[4], uint64_t da, uint64_t db, int acc) {
  asm volatile("{\n.reg .pred p;\nsetp.ne.b32 p, %6, 0;\n"
               "wgmma.mma_async.sync.aligned.m64n8k16.f32.bf16.bf16 {%0, %1, %2, %3}, %4, %5, p, 1, 1, 1, 0;\n}\n"
               : "+f"(d[0]), "+f"(d[1]), "+f"(d[2]), "+f"(d[3])
               : "l"(da), "l"(db), "r"(acc));
}
__device__ __forceinline__ void hmma_k8(float (&d)[4], uint32_t a0, uint32_t a1, uint32_t b0) {
  asm volatile("mma.sync.aligned.m16n8k8.row.col.f32.bf16.bf16.f32 {%0, %1, %2, %3}, {%4, %5}, {%6}, {%0, %1, %2, %3};"
               : "+f"(d[0]), "+f"(d[1]), "+f"(d[2]), "+f"(d[3]) : "r"(a0), "r"(a1), "r"(b0));
}
__device__ __forceinline__ void hmma_k16(float (&d)[4], uint32_t a0, uint32_t a1, uint32_t a2, uint32_t a3, uint32_t b0, uint32_t b1) {
  asm volatile("mma.sync.aligned.m16n8k16.row.col.f32.bf16.bf16.f32 {%0, %1, %2, %3}, {%4, %5, %6, %7}, {%8, %9}, {%0, %1, %2, %3};"
               : "+f"(d[0]), "+f"(d[1]), "+f"(d[2]), "+f"(d[3]) : "r"(a0), "r"(a1), "r"(a2), "r"(a3), "r"(b0), "r"(b1));
}

__device__ __forceinline__ uint32_t pack2(float lo, float hi) {
  uint32_t r;
  asm("cvt.rn.bf16x2.f32 %0, %1, %2;" : "=r"(r) : "f"(hi), "f"(lo));
  return r;
}
__device__ __forceinline__ float bf_lo(uint32_t w) { return __uint_as_float(w << 16); }
__device__ __forceinline__ float bf_hi(uint32_t w) { return __uint_as_float(w & 0xFFFF0000u); }
__device__ __forceinline__ float bfr(float x) { return __bfloat162float(__float2bfloat16_rn(x)); }
__device__ __forceinline__ uint32_t sub2(uint32_t a, uint32_t b) {
  uint32_t r;
  asm("sub.rn.bf16x2 %0, %1, %2;" : "=r"(r) : "r"(a), "r"(b));
  return r;
}
__device__ __forceinline__ uint32_t add2(uint32_t a, uint32_t b) {
  uint32_t r;
  asm("add.rn.bf16x2 %0, %1, %2;" : "=r"(r) : "r"(a), "r"(b));
  return r;
}
__device__ __forceinline__ float ex2(float x) {
  float r;
  asm("ex2.approx.ftz.f32 %0, %1;" : "=f"(r) : "f"(x));
  return r;
}
__device__ __forceinline__ float rcp(float x) {
  float r;
  asm("rcp.approx.ftz.f32 %0, %1;" : "=f"(r) : "f"(x));
  return r;
}
__device__ __forceinline__ float silu_f(float t) { return t * rcp(1.0f + ex2(-1.4426950408889634f * t)); }
__device__ __forceinline__ void lds128(uint32_t a, uint32_t& x, uint32_t& y, uint32_t& z, uint32_t& w) {
  asm volatile("ld.shared.v4.u32 {%0, %1, %2, %3}, [%4];" : "=r"(x), "=r"(y), "=r"(z), "=r"(w) : "r"(a) : "memory");
}
__device__ __forceinline__ void ldsm4(uint32_t a, uint32_t& x, uint32_t& y, uint32_t& z, uint32_t& w) {
  asm volatile("ldmatrix.sync.aligned.m8n8.x4.shared.b16 {%0, %1, %2, %3}, [%4];" : "=r"(x), "=r"(y), "=r"(z), "=r"(w) : "r"(a) : "memory");
}
__device__ __forceinline__ void st_gran(uint4* p, uint32_t x, uint32_t y, uint32_t z, uint32_t w) {
  asm volatile("st.relaxed.gpu.global.v4.b32 [%0], {%1, %2, %3, %4};" ::"l"(p), "r"(x), "r"(y), "r"(z), "r"(w) : "memory");
}
__device__ __forceinline__ void ld_gran(const uint4* p, uint32_t& x, uint32_t& y, uint32_t& z, uint32_t& w) {
  asm volatile("ld.relaxed.gpu.global.v4.b32 {%0, %1, %2, %3}, [%4];" : "=r"(x), "=r"(y), "=r"(z), "=r"(w) : "l"(p) : "memory");
}
__device__ __forceinline__ void stsm4(uint32_t a, uint32_t x, uint32_t y, uint32_t z, uint32_t w) {
  asm volatile("stmatrix.sync.aligned.m8n8.x4.shared.b16 [%0], {%1, %2, %3, %4};" ::"r"(a), "r"(x), "r"(y), "r"(z), "r"(w) : "memory");
}
__device__ __forceinline__ void cp16(uint32_t dst, const void* src) {
  asm volatile("cp.async.cg.shared.global [%0], [%1], 16;" ::"r"(dst), "l"(src) : "memory");
}
__device__ __forceinline__ void cp_wait_all() { asm volatile("cp.async.wait_all;" ::: "memory"); }
__device__ __forceinline__ void add_granules(float (&red)[32], const uint32_t (&g)[16]) {
#pragma unroll
  for (int i = 0; i < 16; i++) { red[2 * i] += bf_lo((i & 3) ? g[i] : g[i] & ~1u); red[2 * i + 1] += bf_hi(g[i]); }
}
__device__ __forceinline__ bool granules_ok(const uint32_t (&g)[16], uint32_t tag) {
  return __all_sync(0xffffffffu, (((g[0] ^ tag) | (g[4] ^ tag) | (g[8] ^ tag) | (g[12] ^ tag)) & 1) == 0);
}
__device__ __forceinline__ unsigned ld_acquire(const unsigned* p) {
  unsigned v;
  asm volatile("ld.acquire.gpu.global.u32 %0, [%1];" : "=r"(v) : "l"(p) : "memory");
  return v;
}
__device__ __forceinline__ unsigned atom_add_acq_rel(unsigned* p) {
  unsigned v;
  asm volatile("atom.acq_rel.gpu.global.add.u32 %0, [%1], 1;" : "=r"(v) : "l"(p) : "memory");
  return v;
}
__device__ __forceinline__ void st_release(unsigned* p, unsigned v) {
  asm volatile("st.release.gpu.global.u32 [%0], %1;" ::"l"(p), "r"(v) : "memory");
}

struct LnAcc {
  float sm[2][4], sq[8][4];
  __device__ __forceinline__ void clear() {
#pragma unroll
    for (int i = 0; i < 4; i++) {
      sm[0][i] = sm[1][i] = 0.f;
#pragma unroll
      for (int j = 0; j < 8; j++) sq[j][i] = 0.f;
    }
  }
};
template <int K0, int K1>
__device__ __forceinline__ void ln_fetch(uint32_t (&xa)[144], uint32_t boxes, uint32_t lo) {
#pragma unroll
  for (int k = K0; k < K1; k++) ldsm4(boxes + (k >> 2) * 8192 + (lo ^ ((k & 3) << 5)), xa[4 * k], xa[4 * k + 1], xa[4 * k + 2], xa[4 * k + 3]);
}
__device__ __forceinline__ void ln_accum1(LnAcc& a, int h, uint32_t x0, uint32_t x1, uint32_t x2, uint32_t x3) {
  const uint32_t ONES = 0x3F803F80u;
  hmma_k16(a.sm[h], x0, x1, x2, x3, ONES, ONES);
  hmma_k8(a.sq[4 * h], x0, x1, x0);
  hmma_k8(a.sq[4 * h + 1], x0, x1, x1);
  hmma_k8(a.sq[4 * h + 2], x2, x3, x2);
  hmma_k8(a.sq[4 * h + 3], x2, x3, x3);
}
template <int K0, int K1>
__device__ __forceinline__ void ln_accum(const uint32_t (&xa)[144], LnAcc& a) {
#pragma unroll
  for (int k = K0; k < K1; k++) ln_accum1(a, k & 1, xa[4 * k], xa[4 * k + 1], xa[4 * k + 2], xa[4 * k + 3]);
}
__device__ __forceinline__ void ln_row(float sum, float sq, float& mean_b, float& rstd) {
  const float mean = sum * (1.0f / DM);
  const uint32_t mv = pack2(mean, fmaxf(sq * (1.0f / DM) - mean * mean, 0.0f));
  mean_b = bf_lo(mv);
  float sd;
  asm("sqrt.approx.f32 %0, %1;" : "=f"(sd) : "f"(bf_lo(pack2(bf_hi(mv) + 1e-5f, 0.f))));
  rstd = rcp(bf_lo(pack2(sd, 0.f)));
}
__device__ __forceinline__ void ln_diag(const LnAcc& a, int lane, float& t0, float& t1) {
  const bool odd = (lane >> 2) & 1;
  t0 = odd ? (a.sq[0][1] + a.sq[2][1]) + (a.sq[4][1] + a.sq[6][1]) : (a.sq[0][0] + a.sq[2][0]) + (a.sq[4][0] + a.sq[6][0]);
  t1 = odd ? (a.sq[1][3] + a.sq[3][3]) + (a.sq[5][3] + a.sq[7][3]) : (a.sq[1][2] + a.sq[3][2]) + (a.sq[5][2] + a.sq[7][2]);
}
__device__ __forceinline__ void ln_stats(const LnAcc& a, int lane, float& mean0, float& rstd0, float& mean1, float& rstd1) {
  float t0, t1;
  ln_diag(a, lane, t0, t1);
  const int src = (lane & ~3) | (lane >> 3);
  t0 = __shfl_sync(0xffffffffu, t0, src);
  t1 = __shfl_sync(0xffffffffu, t1, src);
  ln_row(a.sm[0][0] + a.sm[1][0], t0, mean0, rstd0);
  ln_row(a.sm[0][2] + a.sm[1][2], t1, mean1, rstd1);
}

template <bool ROUTED>
__device__ __forceinline__ uint32_t gate2(uint32_t x2, float mean_b, float rstd, float2 upd = make_float2(0.f, 0.f)) {
  const uint32_t xc = sub2(x2, pack2(mean_b, mean_b));
  uint32_t t = pack2(bf_lo(xc) * rstd, bf_hi(xc) * rstd);
  if (ROUTED) t = pack2(bf_lo(t) + upd.x, bf_hi(t) + upd.y);
  return pack2(silu_f(bf_lo(t)), silu_f(bf_hi(t)));
}

#define PF_D 4
#define X_SPLIT 38
#define X_SPLITA 36
#define X_SPLITS 32
#define X_SPLITSA 30
#define X_PG 2
#define X_E0 10
#define X_F1 10
#define X_BF2 1
template <int V> struct IC { static constexpr int value = V; };

struct Ctx {
  uint32_t sb;
  uint8_t* sp;
  uint32_t rank;
};

__device__ __forceinline__ void attn_producer(const Ctx& cx, int qb, int hs, const CUtensorMap* tmKV,
                                              const CUtensorMap* tmWq, const CUtensorMap* tmWo) {
  const uint32_t full = cx.sb + SM_FULL, empty = cx.sb + SM_EMPTY, ring = cx.sb + SM_RING + cx.rank * 16384;
  const uint64_t last_use = policy_evict_first();
  auto acquire = [&](uint32_t r, uint32_t n, uint32_t bytes) {
    mbar_wait(empty + 8 * r, (n ^ (r >> 1) ^ 1) & 1);
    mbar_expect_tx(full + 8 * r, bytes);
  };
  int st = 0;
#pragma unroll 1
  for (int p = 0; p < 4; p++) {
    const int n0 = (hs * 4 + (p ^ (p >> 1))) * DH + cx.rank * 64;
#pragma unroll 1
    for (int i = 0; i < 5; i++, st++) {
      const uint32_t r = (st ^ ((st >> 1) & 1)) & 3;
      acquire(r, st >> 2, i == 2 ? 16384 : 32768);
      const int k0 = i < 3 ? 128 * i : 128 * i - 64;
      tma2d_mc(ring + r * STAGE, tmWq, n0, k0, full + 8 * r, last_use);
      if (i != 2) tma2d_mc(ring + r * STAGE + 8192, tmWq, n0, k0 + 64, full + 8 * r, last_use);
      if (st == 1) {
#pragma unroll 1
        for (int b = 8 + qb; b < 72; b += 16) tma2d_prefetch(tmWq, (hs * 4 + ((b / 18) ^ (b / 36))) * DH + (b & 1) * 64, ((b % 18) >> 1) * 64);
      }
      if (st == 8 && qb < 2 * PF_D) tma2d_prefetch(tmKV + ((qb >> 1) & 1), cx.rank * 64, hs * 2 * SEQ + (qb >> 2) * 96);
    }
  }
  uint32_t r = 0, n = 5;
#pragma unroll 1
  for (int u = 0; u < NST_KV; u++) {
    const bool big = blk_big(u >> 1);
    acquire(r, n, big ? 112 * 256 : 96 * 256);
    tma2d_mc(ring + r * STAGE, tmKV + (u & 1) + (big ? 0 : 2), cx.rank * 64, hs * 2 * SEQ + blk_row(u >> 1), full + 8 * r, last_use);
    if (((u ^ (qb >> 1)) & 7) == 0 && u + PF_D < NST_KV)
      tma2d_prefetch(tmKV + ((u + PF_D) & 1), cx.rank * 64, hs * 2 * SEQ + blk_row((u + PF_D) >> 1));
    if ((unsigned)(u - 32) < 36 && (u & 15) == qb) tma2d_prefetch(tmWo, ((u - 32) >> 2) * 64, hs * 512 + (u & 3) * 128);
    if (++r == 3) { r = 0; n++; }
  }
#pragma unroll 1
  for (int u = 0; u < NST_O; u++) {
    const int s = u >> 1;
    const int blk = s == 0 ? 8 : ((hs + s) & 7);
    r = (u + 1) & 3;
    acquire(r, (u >> 2) ^ (u >> 1), 32768);
    tma2d_mc(ring + r * STAGE, tmWo, blk * 64, hs * 512 + ((u & 1) + cx.rank * 2) * 128, full + 8 * r, last_use);
  }
}

__device__ __forceinline__ void attn_gate(const Ctx& cx, int qb, int hs, int t, const __nv_bfloat16* x) {
  uint4 nx = *(const uint4*)(x + (size_t)(qb * 128 + (t >> 3)) * DM + hs * 64 + (t & 7) * 8);
  bar_sync(BAR_GATE, 352);
#pragma unroll 1
  for (int ch = t; ch < 1152; ch += 96) {
    const uint4 v = nx;
    const int n = ch + 96;
    if (n < 1152) nx = *(const uint4*)(x + (size_t)(qb * 128 + (n < 1024 ? n >> 3 : hs * 16 + ((n - 1024) >> 3))) * DM + (n < 1024 ? hs * 64 : 512) + (t & 7) * 8);
    const int lr = ch < 1024 ? ch >> 3 : hs * 16 + ((ch - 1024) >> 3);
    const float2 st = *(const float2*)(cx.sp + SM_STATS + 8 * lr);
    g_gate[((qb * 128 + lr) * DM + (ch < 1024 ? hs * 64 : 512) + (t & 7) * 8) >> 3] =
        make_uint4(gate2<false>(v.x, st.x, st.y), gate2<false>(v.y, st.x, st.y), gate2<false>(v.z, st.x, st.y), gate2<false>(v.w, st.x, st.y));
  }
}

constexpr uint32_t SM_XO = SM_SLOT, SM_GO = SM_SLOT + 128 * 144;
constexpr uint32_t SM_X8 = SM_SLOT + 2 * STAGE + 20480, SM_G8 = SM_X8 + 16 * 144;
__device__ __forceinline__ void attn_stage_xg(const Ctx& cx, int qb, int hs, int t, const __nv_bfloat16* x) {
  bar_sync(BAR_OA, 352);
#pragma unroll 1
  for (int ch = t; ch < 1024; ch += 64) {
    const size_t o = (size_t)(qb * 128 + (ch >> 3)) * DM + hs * 64 + (ch & 7) * 8;
    cp16(cx.sb + SM_XO + (ch >> 3) * 144 + (ch & 7) * 16, x + o);
    cp16(cx.sb + SM_GO + (ch >> 3) * 144 + (ch & 7) * 16, (const __nv_bfloat16*)g_gate + o);
  }
  cp_wait_all();
  mbar_arrive(cx.sb + SM_BAR_XG);
}

__device__ __forceinline__ void attn_helper(const Ctx& cx, int qb, int hs, int lane, const __nv_bfloat16* x) {
  unsigned e = 0;
  if (lane == 0) {
    e = g_launch[blockIdx.x];
    g_launch[blockIdx.x] = e + 1;
  }
  e = __shfl_sync(0xffffffffu, e, 0);
  bar_sync(BAR_HELPER, 128);
#pragma unroll 1
  for (int n = 0; n < (1 << 16) && ld_acquire(&g_ffn_flag) != e + 1; n++) __nanosleep(1000);
  const uint32_t tag = ~e & 1;
  {
#pragma unroll 1
    for (int i = 0; i < 2 * TOPC; i++) {
      const int lr = __ldcg(&g_idx[i >> 1]) - qb * 128, col = ((i & 1) ? 512 : hs * 64) + 2 * lane;
      if ((i & 1) ? (lr >> 4) == hs : (lr >> 7) == 0) {
        const float2 st = *(const float2*)(cx.sp + SM_STATS + 8 * lr);
        const int o = (qb * 128 + lr) * DM + col;
        *(uint32_t*)((__nv_bfloat16*)g_gate + o) =
            gate2<true>(*(const uint32_t*)(x + o), st.x, st.y, __ldcg((const float2*)(g_upd + (i >> 1) * DM + col)));
      }
    }
  }
  if (lane == 0) *(uint32_t*)(cx.sp + SM_TAG) = tag;
  __syncwarp();
  if (lane == 0) mbar_arrive(cx.sb + SM_BAR_MISC);

  const uint4* src = g_part + (size_t)((qb * 64 + 56) * 2 + (hs >> 2)) * 4 * 128 + (hs & 3) * 32 + lane;
  const uint32_t stg = cx.sb + SM_SLOT + 2 * STAGE + lane * 16;
  bar_sync(BAR_OA, 352);

#pragma unroll 1
  for (int i = 0; i < 4; i++) {
    const int ch = i * 32 + lane;
    const size_t o = (size_t)(qb * 128 + hs * 16 + (ch >> 3)) * DM + 512 + (ch & 7) * 8;
    cp16(cx.sb + SM_X8 + (ch >> 3) * 144 + (ch & 7) * 16, x + o);
    cp16(cx.sb + SM_G8 + (ch >> 3) * 144 + (ch & 7) * 16, (const __nv_bfloat16*)g_gate + o);
  }
#pragma unroll 1
  for (int n = 0; n < (1 << 16); n++) {
    __nanosleep(n ? 500 : 2000);
    uint32_t a, b, d, t;
    ld_gran(src - lane + (lane & 7) * (2 * 4 * 128) + 3 * 128 + 31, a, b, d, t);
    if (__all_sync(0xffffffffu, (a & 1) == tag)) break;
  }
#pragma unroll 1
  for (int n = 0; n < (1 << 16); n++) {
#pragma unroll 1
    for (int i = 0; i < 8; i++) {
#pragma unroll
      for (int g = 0; g < 4; g++) cp16(stg + (i * 4 + g) * 512, src + i * (2 * 4 * 128) + g * 128);
    }
    cp_wait_all();
    uint32_t bad = 0;
#pragma unroll 4
    for (int i = 0; i < 32; i++) bad |= *(const volatile uint32_t*)(cx.sp + SM_SLOT + 2 * STAGE + lane * 16 + i * 512) ^ tag;
    if (__all_sync(0xffffffffu, (bad & 1) == 0)) break;
  }

}
__device__ __forceinline__ void attn_finish8(const Ctx& cx, int qb, int hs, int hw, int lane, __nv_bfloat16* out) {
  bar_sync(BAR_GATE, 96);
#pragma unroll 1
  for (int g = hw; g < 4; g += 3) {
    float acc[8] = {0.f, 0.f, 0.f, 0.f, 0.f, 0.f, 0.f, 0.f};
#pragma unroll 2
    for (int sidx = 0; sidx < 8; sidx++) {
      uint32_t a, b, d, t;
      lds128(cx.sb + SM_SLOT + 2 * STAGE + lane * 16 + (sidx * 4 + g) * 512, a, b, d, t);
      acc[0] += bf_lo(a & ~1u); acc[1] += bf_hi(a); acc[2] += bf_lo(b); acc[3] += bf_hi(b);
      acc[4] += bf_lo(d); acc[5] += bf_hi(d); acc[6] += bf_lo(t); acc[7] += bf_hi(t);
    }
#pragma unroll
    for (int j = 0; j < 4; j++) {
      const int o = ((lane >> 2) + (j & 1) * 8) * 144 + (2 * g + (j >> 1)) * 16 + (lane & 3) * 4;
      uint32_t* xp = (uint32_t*)(cx.sp + SM_X8 + o);
      const uint32_t xw = *xp, gw = *(const uint32_t*)(cx.sp + SM_G8 + o);
      *xp = pack2(fmaf(acc[2 * j], bf_lo(gw), bf_lo(xw)), fmaf(acc[2 * j + 1], bf_hi(gw), bf_hi(xw)));
    }
  }
  bar_sync(BAR_GATE, 96);
  for (int ch = hw * 32 + lane; ch < 128; ch += 96)
    *(uint4*)(out + (size_t)(qb * 128 + hs * 16 + (ch >> 3)) * DM + 512 + (ch & 7) * 8) =
        *(const uint4*)(cx.sp + SM_X8 + (ch >> 3) * 144 + (ch & 7) * 16);
}

constexpr float SUM_HI = 1.8446744e19f, SUM_LO = 9.0949470e-13f;

template <int LO, int HI, int N>
__device__ __forceinline__ void softmax_exp(float (&s)[N]) {
#pragma unroll
  for (int i = LO; i < HI; i++) s[i] = ex2(s[i]);
}
__device__ __forceinline__ void sum_tree(const uint32_t (&pf)[28], bool big, uint32_t& h0, uint32_t& h1) {
  uint32_t t0 = add2(add2(pf[16], pf[18]), add2(pf[20], pf[22])), t1 = add2(add2(pf[17], pf[19]), add2(pf[21], pf[23]));
  if (big) { t0 = add2(t0, add2(pf[24], pf[26])); t1 = add2(t1, add2(pf[25], pf[27])); }
  h0 = add2(add2(add2(add2(pf[0], pf[2]), add2(pf[4], pf[6])), add2(add2(pf[8], pf[10]), add2(pf[12], pf[14]))), t0);
  h1 = add2(add2(add2(add2(pf[1], pf[3]), add2(pf[5], pf[7])), add2(add2(pf[9], pf[11]), add2(pf[13], pf[15]))), t1);
}
__device__ __forceinline__ void exact_attention(float (&o)[64], float& l0, float& l1, uint32_t qaddr, const __nv_bfloat16* kh,
                                                const __nv_bfloat16* vh, int lane) {
  const int off = (lane >> 2) * DH + (lane & 3) * 2;
  float m0 = -3.0e38f, m1 = -3.0e38f;
  l0 = l1 = 0.f;
#pragma unroll
  for (int i = 0; i < 64; i++) o[i] = 0.f;
#pragma unroll 1
  for (int key = 0; key < SEQ; key += 16) {
    const __nv_bfloat16 *kp = kh + key * DH + off, *vp = vh + key * DH + off;
    float d0[4] = {0.f, 0.f, 0.f, 0.f}, d1[4] = {0.f, 0.f, 0.f, 0.f};
#pragma unroll 4
    for (int k = 0; k < 8; k++) {
      uint32_t q0, q1, q2, q3;
      ldsm4(qaddr + k * 2048, q0, q1, q2, q3);
      hmma_k16(d0, q0, q1, q2, q3, *(const uint32_t*)(kp + k * 16), *(const uint32_t*)(kp + k * 16 + 8));
      hmma_k16(d1, q0, q1, q2, q3, *(const uint32_t*)(kp + 8 * DH + k * 16), *(const uint32_t*)(kp + 8 * DH + k * 16 + 8));
    }
    float x0 = fmaxf(fmaxf(d0[0], d0[1]), fmaxf(d1[0], d1[1])), x1 = fmaxf(fmaxf(d0[2], d0[3]), fmaxf(d1[2], d1[3]));
    x0 = fmaxf(x0, __shfl_xor_sync(0xffffffffu, x0, 1));
    x1 = fmaxf(x1, __shfl_xor_sync(0xffffffffu, x1, 1));
    x0 = fmaxf(fmaxf(x0, __shfl_xor_sync(0xffffffffu, x0, 2)), m0);
    x1 = fmaxf(fmaxf(x1, __shfl_xor_sync(0xffffffffu, x1, 2)), m1);
    const float sc0 = ex2(m0 - x0), sc1 = ex2(m1 - x1);
    m0 = x0; m1 = x1;
    const uint32_t p0 = pack2(ex2(d0[0] - m0), ex2(d0[1] - m0)), p1 = pack2(ex2(d0[2] - m1), ex2(d0[3] - m1)),
                   p2 = pack2(ex2(d1[0] - m0), ex2(d1[1] - m0)), p3 = pack2(ex2(d1[2] - m1), ex2(d1[3] - m1));
    l0 = fmaf(l0, sc0, (bf_lo(p0) + bf_hi(p0)) + (bf_lo(p2) + bf_hi(p2)));
    l1 = fmaf(l1, sc1, (bf_lo(p1) + bf_hi(p1)) + (bf_lo(p3) + bf_hi(p3)));
#pragma unroll
    for (int nb = 0; nb < 16; nb++) {
      uint32_t b0, b1;
      asm("movmatrix.sync.aligned.m8n8.trans.b16 %0, %1;" : "=r"(b0) : "r"(*(const uint32_t*)(vp + nb * 8)));
      asm("movmatrix.sync.aligned.m8n8.trans.b16 %0, %1;" : "=r"(b1) : "r"(*(const uint32_t*)(vp + 8 * DH + nb * 8)));
      o[4 * nb] *= sc0; o[4 * nb + 1] *= sc0; o[4 * nb + 2] *= sc1; o[4 * nb + 3] *= sc1;
      hmma_k16(*(float (*)[4])&o[4 * nb], p0, p1, p2, p3, b0, b1);
    }
  }
}
__device__ __forceinline__ int fresh_lane() {
  int l;
  asm volatile("mov.u32 %0, %%laneid;" : "=r"(l));
  return l;
}
__device__ __forceinline__ bool inv_sums(float l0, float l1, float& i0, float& i1) {
  l0 += __shfl_xor_sync(0xffffffffu, l0, 1); l1 += __shfl_xor_sync(0xffffffffu, l1, 1);
  l0 += __shfl_xor_sync(0xffffffffu, l0, 2); l1 += __shfl_xor_sync(0xffffffffu, l1, 2);
  i0 = rcp(l0);
  i1 = rcp(l1);
  return !(l0 + l1 <= SUM_HI) | (fminf(l0, l1) < SUM_LO);
}
template <int LO, int HI>
__device__ __forceinline__ void park(uint32_t a, const float (&o)[64], float i0, float i1, bool on = true) {
#pragma unroll
  for (int i = LO; i < HI; i++)
    asm volatile("{\n.reg .pred p;\nsetp.ne.u32 p, %5, 0;\n@p stmatrix.sync.aligned.m8n8.x4.shared.b16 [%0], {%1, %2, %3, %4};\n}"
                 ::"r"(a + i * 2048), "r"(pack2(o[8 * i] * i0, o[8 * i + 1] * i0)), "r"(pack2(o[8 * i + 2] * i1, o[8 * i + 3] * i1)),
                 "r"(pack2(o[8 * i + 4] * i0, o[8 * i + 5] * i0)), "r"(pack2(o[8 * i + 6] * i1, o[8 * i + 7] * i1)), "r"((uint32_t)on) : "memory");
}
template <int I, int E0, int N, int NS>
__device__ __forceinline__ void exp_park(float (&s)[NS], uint32_t a, const float (&o)[64], float i0, float i1, bool on, int id) {
  if constexpr (I < 8) {
    constexpr int E1 = E0 + (N - E0) * X_PG / (8 - I);
    softmax_exp<E0, E1>(s);
    park<I, I + X_PG>(a, o, i0, i1, on);
    if (I + X_PG < 8) {
#pragma unroll
      for (int i = E0; i < E1; i++) asm volatile("" : "+f"(s[i])::"memory");
      block_fence(id + I);
    }
    exp_park<I + X_PG, E1, N>(s, a, o, i0, i1, on, id);
  }
}

__device__ __forceinline__ void attn_consumer(const Ctx& cx, int qb, int hs, int wg, int cw, int lane, const __nv_bfloat16* x,
                                              const __nv_bfloat16* kc, const __nv_bfloat16* vc, __nv_bfloat16* out) {
  const uint32_t full = cx.sb + SM_FULL;
  const uint32_t ring = cx.sb + SM_RING;
  const uint32_t qwg = ring + wg * 16384;
  auto qlane = [&](int l) { return qwg + (cw & 3) * 256 + (l >> 4) * 1024 + (l & 15) * 16; };
  const bool signaller = lane == 0 && (cw & 3) < 2;
  const int my_turn = 1 + wg, other_turn = 2 - wg;

  float oA[64], oB[64], i0, i1;
  uint32_t xl[32];
  uint32_t empty_c;
  {
    const int r = lane >> 2, c = lane & 3;
    const int lr0 = cw * 16 + r;
    uint32_t xa[144];
    float rstd0, rstd1, sq0, sq1;
    {
      const uint32_t xb = cx.sb + SM_X + wg * 73728, xf = cx.sb + SM_XFULL + wg * 24;
      const uint32_t lo = ((cw & 3) * 16 + (lane & 15)) * 128 + (((lane >> 4) ^ (lane & 7)) << 4);
      LnAcc a;
      a.clear();
      prof(wg, 0);
      empty_c = mapa(cx.sb + SM_EMPTY, cw & 1);
      mbar_wait(xf, 0);
      ln_fetch<0, 12>(xa, xb, lo);
      ln_accum<0, 12>(xa, a);
      cluster_wait();
      mbar_wait(xf + 8, 0);
      ln_fetch<12, 24>(xa, xb, lo);
      if (wg == 0) {
        bar_sync(4, 128);
        if (signaller) {
          asm volatile("mbarrier.arrive.shared::cluster.b64 _, [%0], 2;" ::"r"(empty_c + 16) : "memory");
          asm volatile("mbarrier.arrive.shared::cluster.b64 _, [%0], 2;" ::"r"(empty_c + 24) : "memory");
        }
      }
      ln_accum<12, 24>(xa, a);
      mbar_wait(xf + 16, 0);
      prof(wg, 1);
      ln_fetch<24, 36>(xa, xb, lo);
#pragma unroll
      for (int k = 24; k < 36; k++) hmma_k16(a.sm[k & 1], xa[4 * k], xa[4 * k + 1], xa[4 * k + 2], xa[4 * k + 3], 0x3F803F80u, 0x3F803F80u);
      ln_diag(a, lane, sq0, sq1);
      if (c != (r >> 1)) sq0 = sq1 = 0.f;
      rstd0 = a.sm[0][0] + a.sm[1][0];
      rstd1 = a.sm[0][2] + a.sm[1][2];
    }
    const uint32_t mm0 = pack2(rstd0 * (1.0f / DM), rstd0 * (1.0f / DM)), mm1 = pack2(rstd1 * (1.0f / DM), rstd1 * (1.0f / DM));
#pragma unroll
    for (int i = 0; i < 16; i++) { xa[2 * i] = sub2(xa[2 * i], mm0); xa[2 * i + 1] = sub2(xa[2 * i + 1], mm1); }
    pin(xa);
    prof(wg, 2);

    float (&acc)[64] = oB;
#pragma unroll 1
    for (int p = 0; p < 4; p++) {
      const int st0 = p * 5;
#pragma unroll
      for (int i = 0; i < 5; i++) {
        if (i == 4 && p == 3) break;
        const int st = st0 + i;
        const uint32_t sl = (st ^ ((st >> 1) & 1)) & 3, slp = ((st - 1) ^ (((st - 1) >> 1) & 1)) & 3;
        mbar_wait(full + 8 * sl, (st >> 2) & 1);
        const bool join = wg && p == 3;
        if (p && i != (wg ? 4 : 1) && !(join && i == 3)) bar_sync(my_turn, 256);
        wg_fence();
        const uint64_t db = mkdesc(ring + sl * STAGE, 16384);
        const int kb0 = i < 3 ? 8 * i : 8 * i - 4;
#pragma unroll
        for (int k = 0; k < (i == 2 ? 4 : 8); k++) {
          const int kb = kb0 + k;
          mma_n128<1>(acc, xa[4 * kb], xa[4 * kb + 1], xa[4 * kb + 2], xa[4 * kb + 3], db + k * 128, kb > 0);
        }
        wg_commit();
        if (wg ? (i == 4 || (p && (i < 2 || i == (join ? 3 : 2)))) : (p && i)) bar_arrive(other_turn, 256);
        if (p == 0 && i < 4) {
          if (i < 2) {
#pragma unroll
            for (int j = 48 + 12 * i; j < 60 + 12 * i; j++) {
              sq0 = fmaf(bf_lo(xa[2 * j]), bf_lo(xa[2 * j]), fmaf(bf_hi(xa[2 * j]), bf_hi(xa[2 * j]), sq0));
              sq1 = fmaf(bf_lo(xa[2 * j + 1]), bf_lo(xa[2 * j + 1]), fmaf(bf_hi(xa[2 * j + 1]), bf_hi(xa[2 * j + 1]), sq1));
            }
          }
          if (i == 1) {
            sq0 += __shfl_xor_sync(0xffffffffu, sq0, 1); sq1 += __shfl_xor_sync(0xffffffffu, sq1, 1);
            sq0 += __shfl_xor_sync(0xffffffffu, sq0, 2); sq1 += __shfl_xor_sync(0xffffffffu, sq1, 2);
            float mean0, mean1;
            ln_row(rstd0, sq0, mean0, rstd0);
            ln_row(rstd1, sq1, mean1, rstd1);
            if (c == 0) {
              *(float2*)(cx.sp + SM_STATS + 8 * lr0) = make_float2(mean0, rstd0);
              *(float2*)(cx.sp + SM_STATS + 8 * (lr0 + 8)) = make_float2(mean1, rstd1);
            }
            bar_arrive(BAR_GATE, 352);
            bar_sync(4 + wg, 128);
            rstd0 *= SM_SCALE_LOG2;
            rstd1 *= SM_SCALE_LOG2;
          }
#pragma unroll
          for (int j = 0; j < 72; j++)
            if (j >= 2 * (i < 2 ? 8 * i + 8 : 8 * i + 4) && j < 2 * (i == 0 ? 16 : 8 * i + 12)) {
              xa[2 * j] = sub2(xa[2 * j], mm0);
              xa[2 * j + 1] = sub2(xa[2 * j + 1], mm1);
            }
          pin(xa);
        }
        if (i == 0) {
          if (wg) {
            wg_wait<0>();
            if (signaller) mbar_arrive_cluster(empty_c + 8 * sl);
          }
        } else if (i == 2) {
          if (!join) {
            wg_wait<0>();
            if (signaller) mbar_arrive_cluster(empty_c + 8 * sl);
          }
        } else if (i != 3) {
          wg_wait<1>();
          if (signaller && (i == 4 || !wg)) mbar_arrive_cluster(empty_c + 8 * slp);
          wg_wait<0>();
          if (signaller) mbar_arrive_cluster(empty_c + 8 * sl);
        }
      }
      if (p == 3) break;
      pin(acc);
      prof(wg, 3 + p);
      park<0, 8>(qlane(lane) + (4 + p) * STAGE, acc, rstd0, rstd1);
      asm volatile("fence.proxy.async.shared::cta;" ::: "memory");
    }
    wg_wait<1>();
    if (signaller && wg) mbar_arrive_cluster(empty_c + 8 * 1);
    wg_wait<0>();
    pin(acc);
    prof(wg, 6);
#pragma unroll
    for (int i = 0; i < 32; i++) xl[i] = xa[112 + i];
    i0 = rstd0;
    i1 = rstd1;
  }

  uint32_t oa[128];
  float acc[32];
  {
    uint32_t pf[28];
    uint32_t bad = 0;
    float lA0 = 0.f, lA1 = 0.f, lB0 = 0.f, lB1 = 0.f;
    int t = 0;
    uint32_t ra = 0, rb = 2 * 2048, rc = 0, par = 1;
    const uint64_t dk0 = mkdesc(ring, 16), dv0 = mkdesc(ring, 16384);
    uint64_t dqA = mkdesc_q(qwg + 4 * STAGE), dqB = dqA + 2048;
    auto turn = [&](auto kc_, auto bc_) {
      constexpr int KIND = decltype(kc_)::value, BIG = decltype(bc_)::value;
      constexpr int HB = KIND == 1, ID = 10 * KIND + 30 * BIG, T0 = BIG ? 38 : 0;
      constexpr int NS = BIG ? 56 : 48, SPLIT = BIG ? (HB ? X_SPLIT : X_SPLITA) : (HB ? X_SPLITS : X_SPLITSA);
      constexpr bool SPECIAL = KIND && (BIG || HB);
      float s[NS];
      float (&op)[64] = HB ? oA : oB;
      uint32_t h0 = 0, h1 = 0;
      TS2(0)
      bar_sync(my_turn, 256);
      TS2(1)
      if (KIND) { pin(pf); pin(op); }
      mma_qk(s, HB ? dqB : dqA, dk0 + (HB ? ra : rc));
      TS2(2)
      if (KIND) {
        const bool bigp = HB ? BIG : BIG ? t != 10 : t == 66;
        if (X_BF2) block_fence(ID + 9);
        pin(pf);
        sum_tree(pf, bigp, h0, h1);
        asm volatile("" : "+r"(h0), "+r"(h1)::"memory");
        if (HB) mbar_wait(full + (rb >> 8), par);
        mma_pv(op, pf, dv0 + rb, t != T0 + 2 - HB, bigp);
      } else {
        mbar_wait(full + (rb >> 8), (NST_Q - 1) >> 2 & 1);
#pragma unroll
        for (int k = 0; k < 8; k++) mma_n128<1>(op, xl[4 * k], xl[4 * k + 1], xl[4 * k + 2], xl[4 * k + 3], dv0 + rb + k * 128, 1);
        wg_commit();
      }
      TS2(3)
      bar_arrive(other_turn, 256);
      (HB ? lA0 : lB0) += bf_lo(h0) + bf_hi(h0);
      (HB ? lA1 : lB1) += bf_lo(h1) + bf_hi(h1);
      wg_wait<1>();
      pin(s);
      TS1(t)
      TS2(4)
      if (KIND == 1) mbar_arrive_cluster_now<ID + 3>(empty_c + (ra >> 8), signaller);
      if (SPECIAL && t == T0 + HB) {
        constexpr int E0 = BIG ? X_E0 : 0;
        bool ok = true;
        const uint32_t a = qlane(fresh_lane()) + (BIG ? 4 + HB : 3) * STAGE;
        if (BIG) {
          ok = !__any_sync(0xffffffffu, inv_sums(HB ? lB0 : lA0, HB ? lB1 : lA1, i0, i1));
          if (!ok) bad |= 1 << HB;
          (HB ? lB0 : lA0) = 0.f;
          (HB ? lB1 : lA1) = 0.f;
          softmax_exp<0, E0>(s);
#pragma unroll
          for (int i = 0; i < E0; i++) asm volatile("" : "+f"(s[i])::"memory");
          block_fence(ID + 7);
        }
        exp_park<0, E0, SPLIT>(s, a, HB ? oB : oA, i0, i1, ok, 200 + ID);
        if (!BIG) asm volatile("fence.proxy.async.shared::cta;" ::: "memory");
        if (!HB) dqB += 2048;
        prof(wg, BIG ? 8 + HB : 7);
        if (!HB && cw == 0) bar_arrive(BAR_HELPER, 128);
      } else {
        softmax_exp<0, SPLIT>(s);
      }
      pin(s);
      if (!SPECIAL) block_fence(ID + 4);
      TS2(5)
      wg_wait<0>();
      TS2(6)
      pin(op);
      if (KIND) pin(pf); else pin(xl);
      if (HB) {
        par ^= rc == 0;
        if (BIG && t == 37) dqA -= 2048;
      } else {
        mbar_arrive_cluster_now<ID + 5>(empty_c + (rb >> 8), signaller);
        if (KIND) {
          par ^= ra == 0;
          const uint32_t x = ra;
          ra = rc; rc = rb; rb = x;
        }
      }
      softmax_exp<SPLIT, NS>(s);
#pragma unroll
      for (int i = 0; i < NS / 2; i++) pf[i] = pack2(s[2 * i], s[2 * i + 1]);
      pin(pf);
      if (HB) mbar_wait(full + (rc >> 8), par);
      t++;
    };
#pragma unroll
    for (int i = 24; i < 28; i++) asm volatile("" : "=r"(pf[i]));
    mbar_wait(full, (NST_Q >> 2) & 1);
    turn(IC<0>(), IC<0>());
    rb = 2048; rc = 2 * 2048;
    kill(oA);
    const bool never = blockIdx.y == 1;
#pragma unroll 1
    while (true) {
      turn(IC<1>(), IC<0>());
      if (t == 76) break;
      if (t == 10) {
#pragma unroll 1
        do {
#pragma unroll 1
          do turn(IC<2>(), IC<1>()); while (never);
          turn(IC<1>(), IC<1>());
        } while (t != 66);
      }
#pragma unroll 1
      do turn(IC<2>(), IC<0>()); while (never);
    }
    const uint32_t ql = qlane(fresh_lane());
    {
      uint32_t h0, h1;
      sum_tree(pf, false, h0, h1);
      if (inv_sums(lA0, lA1, i0, i1)) bad |= 4;
      if (inv_sums(lB0 + (bf_lo(h0) + bf_hi(h0)), lB1 + (bf_lo(h1) + bf_hi(h1)), lB0, lB1)) bad |= 8;
    }
    volatile uint32_t* const cold = (volatile uint32_t*)(cx.sp + SM_COLD) + wg;
    if (bad) *cold = 1;
    bar_sync(my_turn, 256);
    const uint32_t is_cold = *cold;
    pin(pf); pin(oB);
    mma_pv(oB, pf, dv0, true, false);
    const uint64_t db = mkdesc(ring + STAGE, 16);
    if (__any_sync(0xffffffffu, is_cold)) {
      wg_wait<0>();
      pin(oB); pin(pf);
      bad = __reduce_or_sync(0xffffffffu, bad);
      park<0, 8>(ql + 3 * STAGE, oA, i0, i1, !(bad & 4));
      park<0, 8>(ql + 6 * STAGE, oB, lB0, lB1, !(bad & 8));
#pragma unroll 1
      for (int h = 0; h < 4; h++) {
        if (bad >> h & 1) {
          const uint32_t a = ql + ((0x6354 >> (4 * h)) & 7) * STAGE;
          const size_t o = (size_t)(hs * 2 + (h >> 1)) * SEQ * DH;
          float ox[64], l0, l1;
          exact_attention(ox, l0, l1, a, kc + o, vc + o, fresh_lane());
          inv_sums(l0, l1, l0, l1);
          __syncwarp();
          park<0, 8>(a, ox, l0, l1);
        }
      }
      __syncwarp();
#pragma unroll
      for (int i = 0; i < 32; i++)
        ldsm4(ql + ((0x6534 >> (4 * (i >> 3))) & 7) * STAGE + (i & 7) * 2048, oa[4 * i], oa[4 * i + 1], oa[4 * i + 2], oa[4 * i + 3]);
      pin(oa);
      asm volatile("fence.proxy.async.shared::cta;" ::: "memory");
      bar_sync(4 + wg, 128);
      if (signaller) { mbar_arrive_cluster(empty_c + 8 * 3); mbar_arrive_cluster(empty_c); }
      wg_fence();
#pragma unroll
      for (int k = 0; k < 16; k++) mma_n64t(acc, oa[4 * k], oa[4 * k + 1], oa[4 * k + 2], oa[4 * k + 3], db + k * 128, k > 0);
      wg_commit();
      bar_arrive(other_turn, 256);
      wg_wait<0>();
      pin(acc);
    } else {
      if (signaller) mbar_arrive_cluster(empty_c + 8 * 3);
      auto scale = [&](int i) {
        oa[32 + 2 * i] = pack2(oA[4 * i] * i0, oA[4 * i + 1] * i0);
        oa[32 + 2 * i + 1] = pack2(oA[4 * i + 2] * i1, oA[4 * i + 3] * i1);
      };
#pragma unroll
      for (int i = 0; i < 6; i++) ldsm4(ql + 4 * STAGE + i * 2048, oa[4 * i], oa[4 * i + 1], oa[4 * i + 2], oa[4 * i + 3]);
#pragma unroll
      for (int i = 0; i < X_F1; i++) scale(i);
#pragma unroll
      for (int i = 0; i < 2 * X_F1; i++) asm volatile("" : "+r"(oa[32 + i])::"memory");
      block_fence(93);
#pragma unroll
      for (int i = 6; i < 8; i++) ldsm4(ql + 4 * STAGE + i * 2048, oa[4 * i], oa[4 * i + 1], oa[4 * i + 2], oa[4 * i + 3]);
      wg_fence();
#pragma unroll
      for (int k = 0; k < 6; k++) mma_n64t(acc, oa[4 * k], oa[4 * k + 1], oa[4 * k + 2], oa[4 * k + 3], db + k * 128, k > 0);
      wg_commit();
      block_fence(91);
#pragma unroll
      for (int i = X_F1; i < 16; i++) scale(i);
#pragma unroll
      for (int i = 24; i < 64; i++) asm volatile("" : "+r"(oa[i])::"memory");
      wg_fence();
#pragma unroll
      for (int k = 6; k < 16; k++) mma_n64t(acc, oa[4 * k], oa[4 * k + 1], oa[4 * k + 2], oa[4 * k + 3], db + k * 128, 1);
      wg_commit();
      bar_arrive(other_turn, 256);
      wg_wait<2>();
      pin(oB); pin(pf);
      TS(76)
      if (signaller) mbar_arrive_cluster(empty_c);
#pragma unroll
      for (int i = 16; i < 24; i++) ldsm4(ql + 5 * STAGE + (i & 7) * 2048, oa[4 * i], oa[4 * i + 1], oa[4 * i + 2], oa[4 * i + 3]);
#pragma unroll
      for (int i = 0; i < 16; i++) {
        oa[96 + 2 * i] = pack2(oB[4 * i] * lB0, oB[4 * i + 1] * lB0);
        oa[96 + 2 * i + 1] = pack2(oB[4 * i + 2] * lB1, oB[4 * i + 3] * lB1);
      }
#pragma unroll
      for (int i = 64; i < 128; i++) asm volatile("" : "+r"(oa[i])::"memory");
      block_fence(92);
      wg_wait<0>();
      pin(acc);
    }
    if (signaller) mbar_arrive_cluster(empty_c + 8 * 1);
    mbar_wait(cx.sb + SM_BAR_MISC, 0);
    mbar_wait(full + 8 * 2, 0);
  }

  prof(wg, 10);
  {
    lane = fresh_lane();
    const int c = lane & 3, lr0 = cw * 16 + (lane >> 2), tw = (cw & 3) * 32 + lane;
    float red[32];
#pragma unroll
    for (int i = 0; i < 32; i++) red[i] = 0.f;
    const uint32_t tag = *(const uint32_t*)(cx.sp + SM_TAG);
    uint4* const xch = g_part + (size_t)(qb * 64 * 2 + wg) * 4 * 128 + tw;
    int nrx = 1;
    auto region = [](int s, int h) { return (2 * s + h + 1) & 3; };
    auto half_step = [&](int s, auto hc, bool arrive) {
      constexpr int h = decltype(hc)::value;
      const uint64_t db = mkdesc(ring + region(s, h) * STAGE, 16);
      bar_sync(my_turn, 256);
      pin(oa);
      wg_fence();
#pragma unroll
      for (int k = 0; k < 16; k++) {
        const int kb = h * 16 + k;
        mma_n64t(acc, oa[4 * kb], oa[4 * kb + 1], oa[4 * kb + 2], oa[4 * kb + 3], db + k * 128, kb > 0);
      }
      wg_commit();
      if (arrive) bar_arrive(other_turn, 256);
    };
    auto await = [&](int s, int h) { mbar_wait(full + 8 * region(s, h), ((s >> 1) ^ s) & 1); };
    auto fetch = [&](uint32_t (&g)[16], int n) {
      const uint4* p = xch + (hs * 7 + n - 1) * (2 * 4 * 128);
#pragma unroll
      for (int i = 0; i < 4; i++) ld_gran(p + i * 128, g[4 * i], g[4 * i + 1], g[4 * i + 2], g[4 * i + 3]);
    };
    uint32_t g[16];
#pragma unroll 1
    for (int s = 0; s < 8; s++) {
      const bool pend = nrx < s - 1;
      if (pend) fetch(g, nrx);
      half_step(s, IC<1>(), true);
      if (s == 0) bar_arrive(BAR_OA, 352);
      await(s + 1, 0);
      wg_wait<0>();
      if (signaller && s < 7) mbar_arrive_cluster(empty_c + 8 * region(s, 1));
      pin(acc);
      TS(77 + s)
      prof(wg, 12 + s);
      uint4* p = xch + (s == 0 ? 56 + hs : ((hs + s) & 7) * 7 + s - 1) * (2 * 4 * 128);
#pragma unroll
      for (int i = 0; i < 4; i++)
        st_gran(p + i * 128, (pack2(acc[8 * i], acc[8 * i + 1]) & ~1u) | tag, pack2(acc[8 * i + 2], acc[8 * i + 3]),
                pack2(acc[8 * i + 4], acc[8 * i + 5]), pack2(acc[8 * i + 6], acc[8 * i + 7]));
      half_step(s + 1, IC<0>(), true);
      await(s + 1, 1);
      if (pend && granules_ok(g, tag)) { add_granules(red, g); nrx++; }
      wg_wait<0>();
      if (signaller && s < 6) mbar_arrive_cluster(empty_c + 8 * region(s + 1, 0));
    }
    float gf[32], xf[32];
    {
      uint32_t g2[16], xv[16], gt[16];
      fetch(g, nrx);
      mbar_wait(cx.sb + SM_BAR_XG, 0);
#pragma unroll
      for (int i = 0; i < 16; i++) {
        const uint8_t* p = cx.sp + (lr0 + (i & 1) * 8) * 144 + (i >> 1) * 16 + c * 4;
        xv[i] = *(const uint32_t*)(p + SM_XO);
        gt[i] = *(const uint32_t*)(p + SM_GO);
      }
      {
        const uint64_t db = mkdesc(ring + 2 * STAGE, 16);
        bar_sync(my_turn, 256);
#pragma unroll
        for (int i = 64; i < 128; i++) asm volatile("" : "+r"(oa[i])::"memory");
        wg_fence();
#pragma unroll
        for (int k = 16; k < 32; k++) mma_n64t(acc, oa[4 * k], oa[4 * k + 1], oa[4 * k + 2], oa[4 * k + 3], db + (k - 16) * 128, 1);
        wg_commit();
        if (wg == 0) bar_arrive(other_turn, 256);
      }
      fetch(g2, 7);
      int last = 8;
      const bool two = nrx < 7;
      if (granules_ok(g, tag)) { add_granules(red, g); nrx++; }
#pragma unroll
      for (int i = 0; i < 16; i++) {
        gf[2 * i] = bf_lo(gt[i]); gf[2 * i + 1] = bf_hi(gt[i]);
        xf[2 * i] = bf_lo(xv[i]); xf[2 * i + 1] = bf_hi(xv[i]);
      }
      wg_wait<0>();
      pin(acc);
      TS(85)
#pragma unroll
      for (int i = 0; i < 32; i++) red[i] += acc[i];
      pin(red); pin(gf); pin(xf);
      block_fence(90);
      if (two && granules_ok(g2, tag)) { add_granules(red, g2); last = 7; }
#pragma unroll 1
      for (int spins = 0; nrx < last && spins < (1 << 16); spins++) {
        fetch(g, nrx);
        if (granules_ok(g, tag)) { add_granules(red, g); nrx++; }
      }
    }
    prof(wg, 20);
    TS(86)
    const uint32_t ot = ring + 3 * STAGE + cw * (16 * 144);
    uint32_t ow[16];
#pragma unroll
    for (int i = 0; i < 16; i++) ow[i] = pack2(fmaf(red[2 * i], gf[2 * i], xf[2 * i]), fmaf(red[2 * i + 1], gf[2 * i + 1], xf[2 * i + 1]));
#pragma unroll
    for (int i = 0; i < 4; i++)
      stsm4(ot + (lane & 15) * 144 + (2 * i + (lane >> 4)) * 16, ow[4 * i], ow[4 * i + 1], ow[4 * i + 2], ow[4 * i + 3]);
    __syncwarp();
#pragma unroll
    for (int i = 0; i < 4; i++) {
      uint4 v;
      lds128(ot + (i * 4 + (lane >> 3)) * 144 + (lane & 7) * 16, v.x, v.y, v.z, v.w);
      *(uint4*)(out + (size_t)(qb * 128 + cw * 16 + i * 4 + (lane >> 3)) * DM + hs * 64 + (lane & 7) * 8) = v;
    }
    prof(wg, 22);
    TS(87)
    TS_DUMP()
  }
}

constexpr int FST_X = 24, FST_END = FST_X + 14 * 12;
__device__ __forceinline__ void ffn_producer(const Ctx& cx, int f, const CUtensorMap* tmX, const CUtensorMap* tmG,
                                             const CUtensorMap* tmU, const CUtensorMap* tmD) {
  const uint32_t full = cx.sb + SM_FULL, empty = cx.sb + SM_EMPTY;
  int pair = -2, u = 0;
#pragma unroll 1
  for (int st = 0; st < FST_END; st++) {
    const uint32_t sl = st & 7;
    const int unit = pair * 2 + (u & 1), k = u >> 1, k3 = k >= 3 ? k - 3 : k;
    if (unit < 27) {
      mbar_wait(empty + 8 * sl, ((st >> 3) & 1) ^ 1);
      mbar_expect_tx(full + 8 * sl, FSTAGE);
      if (pair < 0) tma3d(cx.sb + sl * FSTAGE, tmX, f * 512 + ((pair + 2) * 4 + (k >= 3) * 2 + (u & 1)) * 64, k3 * 3, full + 8 * sl);
      else if (pair < 9) tma2d_stream(cx.sb + sl * FSTAGE, k < 3 ? tmG : tmU, f * 1152 + unit * 64, k3 * 192, full + 8 * sl);
      else tma2d_stream(cx.sb + sl * FSTAGE, tmD, (unit - 18) * 64, f * 1152 + k * 192, full + 8 * sl);
    }
    if (++u == 12) { u = 0; pair++; }
  }
}

__device__ __forceinline__ void ffn_consumer(const Ctx& cx, int f, int wg, int cw, int lane, const __nv_bfloat16* x,
                                             const __nv_bfloat16* w_r) {
  const int r = lane >> 2, c = lane & 3, tid = cw * 32 + lane;
  unsigned e = 0;
  if (tid == 0) {
    e = g_launch[blockIdx.x];
    g_launch[blockIdx.x] = e + 1;
    *(unsigned*)(cx.sp + SM_TAG) = e;
  }
  if (tid < 72) *(uint4*)(cx.sp + SM_H + tid * 16) = *(const uint4*)(w_r + tid * 8);
  bar_sync(3, 256);
  prof(wg, 0);
  const uint32_t full = cx.sb + SM_FULL, empty = cx.sb + SM_EMPTY;
  const bool signaller = (tid & 127) == 0;
#pragma unroll 1
  for (int b = wg; b < 8; b += 2) {
    const int row0 = f * 512 + b * 64 + (cw & 3) * 16 + r;
    const uint32_t lo = ((cw & 3) * 16 + (lane & 15)) * 128 + (((lane >> 4) ^ (lane & 7)) << 4);
    LnAcc a;
    a.clear();
#pragma unroll 1
    for (int bx = 0; bx < 9; bx++) {
      const int st = (b >> 1) * 6 + (bx / 3) * 2 + wg;
      if (bx % 3 == 0) mbar_wait(full + 8 * (st & 7), (st >> 3) & 1);
#pragma unroll
      for (int k = 0; k < 4; k++) {
        uint32_t x0, x1, x2, x3;
        ldsm4(cx.sb + (st & 7) * FSTAGE + (bx % 3) * 8192 + (lo ^ (k << 5)), x0, x1, x2, x3);
        ln_accum1(a, k & 1, x0, x1, x2, x3);
      }
    }
    prof(wg, 8 + (b >> 1) * 3);
    float mean0, rstd0, mean1, rstd1;
    ln_stats(a, lane, mean0, rstd0, mean1, rstd1);
    prof(wg, 9 + (b >> 1) * 3);
    const uint32_t mm0 = pack2(mean0, mean0), mm1 = pack2(mean1, mean1);
    float d0[4] = {0, 0, 0, 0}, d1[4] = {0, 0, 0, 0};
#pragma unroll 1
    for (int bx = 0; bx < 9; bx++) {
      const int st = (b >> 1) * 6 + (bx / 3) * 2 + wg;
#pragma unroll
      for (int k = 0; k < 4; k++) {
        uint32_t n[4];
        ldsm4(cx.sb + (st & 7) * FSTAGE + (bx % 3) * 8192 + (lo ^ (k << 5)), n[0], n[1], n[2], n[3]);
        const uint8_t* wp = cx.sp + SM_H + (bx * 4 + k) * 32 + 4 * c;
#pragma unroll
        for (int i = 0; i < 4; i++) {
          const uint32_t t = sub2(n[i], (i & 1) ? mm1 : mm0);
          const float rs = (i & 1) ? rstd1 : rstd0;
          n[i] = pack2(bf_lo(t) * rs, bf_hi(t) * rs);
        }
        if (k & 1) hmma_k16(d1, n[0], n[1], n[2], n[3], *(const uint32_t*)wp, *(const uint32_t*)(wp + 16));
        else hmma_k16(d0, n[0], n[1], n[2], n[3], *(const uint32_t*)wp, *(const uint32_t*)(wp + 16));
      }
    }
    prof(wg, 10 + (b >> 1) * 3);
    bar_sync(4 + wg, 128);
    if (signaller) {
#pragma unroll
      for (int i = 0; i < 3; i++) mbar_arrive(empty + 8 * (((b >> 1) * 6 + i * 2 + wg) & 7));
    }
    if (c == 0) {
      g_r[row0] = bfr(d0[0] + d1[0]);
      g_r[row0 + 8] = bfr(d0[2] + d1[2]);
      g_stats[row0] = make_float2(mean0, rstd0);
      g_stats[row0 + 8] = make_float2(mean1, rstd1);
    }
  }
  prof(wg, 1);
  cluster_wait();
  bar_sync(3, 256);
  e = *(const unsigned*)(cx.sp + SM_TAG);
  if (tid == 0) {
    atom_add_acq_rel(&g_rcnt);
#pragma unroll 1
    for (int n = 0; n < (1 << 16) && (int)(ld_acquire(&g_rcnt) - 4 * (e + 1)) < 0; n++) {}
  }
  bar_sync(3, 256);
  prof(wg, 2);
  uint32_t key[8];
#pragma unroll
  for (int i = 0; i < 8; i++) {
    const int row = i * 256 + tid;
    const uint32_t b = __float_as_uint(__ldcg(&g_r[row])) >> 16;
    key[i] = (((b & 0x8000u) ? (~b & 0xFFFFu) : (b | 0x8000u)) << 16) | (uint32_t)(0xFFFF - row);
  }
  int mysel = 0;
#pragma unroll 1
  for (int k = 0; k < TOPC; k++) {
    uint32_t m = key[0];
#pragma unroll
    for (int i = 1; i < 8; i++) m = max(m, key[i]);
    m = __reduce_max_sync(0xffffffffu, m);
    uint32_t* tk = (uint32_t*)(cx.sp + SM_TOPK) + (k & 1) * 8;
    if (lane == 0) tk[cw] = m;
    bar_sync(3, 256);
    m = __reduce_max_sync(0xffffffffu, tk[lane & 7]);
#pragma unroll
    for (int i = 0; i < 8; i++) if (key[i] == m) key[i] = 0;
    if (k == cw) mysel = 0xFFFF - (int)(m & 0xFFFF);
  }
  {
    const float2 st = __ldcg(&g_stats[mysel]);
    const uint32_t mm = pack2(st.x, st.x);
#pragma unroll 3
    for (int i = 0; i < 9; i++) {
      const uint32_t t = sub2(*(const uint32_t*)(x + (size_t)mysel * DM + i * 64 + 2 * lane), mm);
      *(uint32_t*)(cx.sp + SM_XSEL + i * 1024 + cw * 128 + (((lane >> 2) ^ cw) << 4) + (lane & 3) * 4) =
          pack2(bf_lo(t) * st.y, bf_hi(t) * st.y);
    }
    if (lane == 0) *(int*)(cx.sp + SM_IDX + 4 * cw) = mysel;
  }
  asm volatile("fence.proxy.async.shared::cta;" ::: "memory");
  bar_sync(3, 256);
  prof(wg, 3);
  auto run = [&](float (&acc)[4], int st, int n, uint32_t b) {
#pragma unroll 1
    for (int u = 0; u < n; u++, st += 2, b += 3072) {
      const uint32_t sl = st & 7;
      mbar_wait(full + 8 * sl, (st >> 3) & 1);
      wg_fence();
      const uint64_t da = mkdesc(cx.sb + sl * FSTAGE, 16), db = mkdesc(b, 16);
#pragma unroll
      for (int k = 0; k < 12; k++) mma_n8(acc, da + k * 128, db + (k >> 2) * 64 + (k & 3) * 2, u > 0 || k > 0);
      wg_commit();
      wg_wait<0>();
      if (signaller) mbar_arrive(empty + 8 * sl);
    }
    pin(acc);
  };
#pragma unroll 1
  for (int unit = wg; unit < 27; unit += 2) {
    if (unit >> 1 == 9) {
      asm volatile("fence.proxy.async.shared::cta;" ::: "memory");
      bar_sync(3, 256);
      prof(wg, 4);
    }
    const bool gu = unit < 18;
    float a0[4], a1[4];
#pragma unroll 1
    for (int m = 0; m < (gu ? 2 : 1); m++) {
      run(a1, FST_X + (unit >> 1) * 12 + m * 6 + wg, gu ? 3 : 6, cx.sb + (gu ? SM_XSEL : SM_H));
      if (m == 0) { a0[0] = a1[0]; a0[1] = a1[1]; a0[2] = a1[2]; a0[3] = a1[3]; }
    }
#pragma unroll
    for (int i = 0; i < 4; i++) {
      const int fl = (cw & 3) * 16 + r + (i >> 1) * 8, tok = 2 * c + (i & 1);
      if (gu) {
        const float h = bfr(silu_f(bfr(a0[i]))) * bfr(a1[i]);
        *(__nv_bfloat16*)(cx.sp + SM_H + unit * 1024 + tok * 128 + (((fl >> 3) ^ tok) << 4) + (fl & 7) * 2) = __float2bfloat16_rn(h);
      } else {
        g_ypart[(f * TOPC + tok) * DM + (unit - 18) * 64 + fl] = a1[i];
      }
    }
  }
  prof(wg, 5);
  bar_sync(3, 256);
  if (tid == 0) *(unsigned*)(cx.sp + SM_TOPK) = atom_add_acq_rel(&g_ycnt) == 4 * e + 3;
  bar_sync(3, 256);
  if (*(const unsigned*)(cx.sp + SM_TOPK)) {
    const int row = *(const int*)(cx.sp + SM_IDX + 4 * cw);
    const float rs = bfr(rcp(1.0f + ex2(-1.4426950408889634f * __ldcg(&g_r[row]))));
#pragma unroll 1
    for (int d = lane * 2; d < DM; d += 192) {
#pragma unroll
      for (int i = 0; i < 3; i++) {
        const float* p = g_ypart + cw * DM + d + i * 64;
        const float2 a = __ldcg((const float2*)p), b = __ldcg((const float2*)(p + TOPC * DM)),
                     e2 = __ldcg((const float2*)(p + 2 * TOPC * DM)), h = __ldcg((const float2*)(p + 3 * TOPC * DM));
        const uint32_t y = pack2((a.x + b.x) + (e2.x + h.x), (a.y + b.y) + (e2.y + h.y));
        const uint32_t u = pack2(bf_lo(y) * rs, bf_hi(y) * rs);
        *(float2*)(g_upd + cw * DM + d + i * 64) = make_float2(bf_lo(u), bf_hi(u));
      }
    }
    if (lane == 0) g_idx[cw] = row;
    bar_sync(3, 256);
    if (tid == 0) st_release(&g_ffn_flag, e + 1);
    prof(wg, 6);
  }
}

struct KvMaps { CUtensorMap m[4]; };
__global__ void __cluster_dims__(2, 1, 1) __launch_bounds__(THREADS, 1)
fused_kernel(const __grid_constant__ KvMaps tmKV,
             const __grid_constant__ CUtensorMap tmWq, const __grid_constant__ CUtensorMap tmWo,
             const __grid_constant__ CUtensorMap tmG, const __grid_constant__ CUtensorMap tmU,
             const __grid_constant__ CUtensorMap tmD, const __grid_constant__ CUtensorMap tmX, const __nv_bfloat16* __restrict__ x,
             const __nv_bfloat16* __restrict__ w_r, const __nv_bfloat16* __restrict__ kc,
             const __nv_bfloat16* __restrict__ vc, __nv_bfloat16* __restrict__ out) {
  extern __shared__ __align__(1024) uint8_t smem_raw[];
  prof(0, 23, 511);
  Ctx cx;
  cx.sb = smem_u32(smem_raw);
  cx.sp = smem_raw;
  cx.rank = blockIdx.x & 1;
  const int warp = __shfl_sync(0xffffffffu, threadIdx.x >> 5, 0);
  const int cluster = blockIdx.x >> 1;
  const bool is_ffn = blockIdx.x >= N_ATT_CTA;
  const int hs = cluster < 4 ? 4 + cluster : cluster < 36 ? (cluster - 4) >> 3 : 4 + (cluster - 36) / 7;
  const int qb = (cluster < 4 ? 0 : cluster < 36 ? (cluster - 4) & 7 : 1 + (cluster - 36) % 7) * 2 + cx.rank;

  if (warp == 0 && elect_one()) {
    if (!is_ffn) {
#pragma unroll
      for (int i = 0; i < 6; i++) mbar_init(cx.sb + SM_XFULL + 8 * i, 1);
      asm volatile("fence.proxy.async.shared::cta;" ::: "memory");
#pragma unroll
      for (int i = 0; i < 6; i++) {
        mbar_expect_tx(cx.sb + SM_XFULL + 8 * i, 24576);
        tma3d(cx.sb + SM_X + i * 24576, &tmX, qb * 128 + (i / 3) * 64, (i % 3) * 3, cx.sb + SM_XFULL + 8 * i);
      }
    }
#pragma unroll
    for (int i = 0; i < 8; i++) {
      mbar_init(cx.sb + SM_FULL + 8 * i, 1);
      mbar_init(cx.sb + SM_EMPTY + 8 * i, is_ffn ? 1 : 4);
    }
    mbar_init(cx.sb + SM_BAR_MISC, 1);
    mbar_init(cx.sb + SM_BAR_XG, 64);
    *(uint2*)(cx.sp + SM_COLD) = make_uint2(0, 0);
    asm volatile("fence.mbarrier_init.release.cluster;" ::: "memory");
  } else if (warp == 1 && elect_one()) {
    if (is_ffn) { prefetch_tmap(&tmX); prefetch_tmap(&tmG); prefetch_tmap(&tmU); prefetch_tmap(&tmD); }
    else { prefetch_tmap(&tmWq); prefetch_tmap(&tmKV.m[2]); prefetch_tmap(&tmKV.m[3]); prefetch_tmap(&tmWo); }
  }
  __syncthreads();
  cluster_arrive();

  if (warp < 4) {
    asm volatile("setmaxnreg.dec.sync.aligned.u32 24;");
    cluster_wait();
    prof(0, 24, 511);
    if (warp == 0) {
      if (elect_one()) {
        if (is_ffn) ffn_producer(cx, blockIdx.x - N_ATT_CTA, &tmX, &tmG, &tmU, &tmD);
        else attn_producer(cx, qb, hs, tmKV.m, &tmWq, &tmWo);
        prof(0, 25, 511);
      }
    } else if (!is_ffn) {
      attn_gate(cx, qb, hs, threadIdx.x - 32, x);
      if (warp == 1) attn_helper(cx, qb, hs, read_lane(), x);
      else { bar_arrive(BAR_HELPER, 128); attn_stage_xg(cx, qb, hs, threadIdx.x - 64, x); }
      attn_finish8(cx, qb, hs, warp - 1, read_lane(), out);

    }
    __syncwarp();
    cluster_arrive();
    cluster_wait();
  } else {
    asm volatile("setmaxnreg.inc.sync.aligned.u32 240;");
    const int cw = warp - 4, wg = cw >> 2;
    if (is_ffn) ffn_consumer(cx, blockIdx.x - N_ATT_CTA, wg, cw, read_lane(), x, w_r);
    else attn_consumer(cx, qb, hs, wg, cw, read_lane(), x, kc, vc, out);
  }
}

typedef CUresult (*EncodeFn)(CUtensorMap*, CUtensorMapDataType, cuuint32_t, void*, const cuuint64_t*, const cuuint64_t*,
                             const cuuint32_t*, const cuuint32_t*, CUtensorMapInterleave, CUtensorMapSwizzle,
                             CUtensorMapL2promotion, CUtensorMapFloatOOBfill);

void encode(EncodeFn fn, CUtensorMap* m, const void* p, int rank, const cuuint64_t* dims, const cuuint64_t* strides,
            const cuuint32_t* box) {
  const cuuint32_t es[5] = {1, 1, 1, 1, 1};
  fn(m, CU_TENSOR_MAP_DATA_TYPE_BFLOAT16, rank, const_cast<void*>(p), dims, strides, box, es, CU_TENSOR_MAP_INTERLEAVE_NONE,
     CU_TENSOR_MAP_SWIZZLE_128B, CU_TENSOR_MAP_L2_PROMOTION_L2_128B, CU_TENSOR_MAP_FLOAT_OOB_FILL_NONE);
}
void encode2d(EncodeFn fn, CUtensorMap* m, const void* p, uint64_t rows, uint64_t cols, uint32_t box_rows) {
  const cuuint64_t dims[2] = {cols, rows}, strides[1] = {cols * 2};
  const cuuint32_t box[2] = {64, box_rows};
  encode(fn, m, p, 2, dims, strides, box);
}

}

extern "C" void kernel_launch(void* const* d_in, const int* in_sizes, int n_in, void* d_out, int out_size) {
  (void)in_sizes; (void)n_in; (void)out_size;
  void* fnp = nullptr;
  cudaDriverEntryPointQueryResult qr;
  cudaGetDriverEntryPoint("cuTensorMapEncodeTiled", &fnp, cudaEnableDefault, &qr);
  EncodeFn fn = (EncodeFn)fnp;
  CUtensorMap tmWq, tmWo, tmG, tmU, tmD, tmX;
  KvMaps tmKV;
  for (int i = 0; i < 4; i++) encode2d(fn, &tmKV.m[i], d_in[1 + (i & 1)], 16 * SEQ, DH, i < 2 ? 112 : 96);
  encode2d(fn, &tmWq, d_in[3], DM, 4096, 64);
  {
    const cuuint64_t dims[3] = {64, SEQ, 9}, strides[2] = {DM * 2, 128};
    const cuuint32_t box[3] = {64, 64, 3};
    encode(fn, &tmX, d_in[0], 3, dims, strides, box);
  }
  encode2d(fn, &tmWo, d_in[4], 4096, DM, 128);
  encode2d(fn, &tmG, d_in[7], DM, FF, 192);
  encode2d(fn, &tmU, d_in[8], DM, FF, 192);
  encode2d(fn, &tmD, d_in[9], FF, DM, 192);
  cudaFuncSetAttribute(fused_kernel, cudaFuncAttributeMaxDynamicSharedMemorySize, SM_TOTAL);
  fused_kernel<<<N_CTA, THREADS, SM_TOTAL>>>(tmKV, tmWq, tmWo, tmG, tmU, tmD, tmX, (const __nv_bfloat16*)d_in[0],
                                            (const __nv_bfloat16*)d_in[6], (const __nv_bfloat16*)d_in[1],
                                            (const __nv_bfloat16*)d_in[2], (__nv_bfloat16*)d_out);
}
```

```cpp
#include <cuda_runtime.h>
#include <cuda_bf16.h>
#include <cuda.h>
#include <stdint.h>

namespace {

constexpr int SEQ = 2048, DM = 576, DH = 128, FF = 4608, TOPC = 8;
constexpr int N_ATT_CTA = 128, N_CTA = 132;
constexpr int THREADS = 384;

constexpr uint32_t SM_RING = 0;
constexpr uint32_t STAGE = 32768;
constexpr uint32_t SM_SLOT = 131072;
constexpr uint32_t FSTAGE = 24576;
constexpr uint32_t SM_XSEL = 196608;
constexpr uint32_t SM_H = 205824;
constexpr uint32_t SM_MISC = 229376;
constexpr uint32_t SM_FULL = SM_MISC, SM_EMPTY = SM_MISC + 64, SM_BAR_MISC = SM_MISC + 128,
                   SM_COLD = SM_MISC + 136, SM_TAG = SM_MISC + 144, SM_IDX = SM_MISC + 160,
                   SM_TOPK = SM_MISC + 192, SM_XFULL = SM_MISC + 256, SM_BAR_XG = SM_MISC + 304, SM_STATS = SM_MISC + 320;
constexpr uint32_t SM_TOTAL = SM_MISC + 1344;
constexpr uint32_t SM_X = SM_MISC - 147456;

constexpr int BAR_GATE = 6, BAR_HELPER = 7, BAR_OA = 8;
constexpr int NST_Q = 20, NST_KV = 76, NST_O = 18;
__device__ __forceinline__ bool blk_big(int j) { return (unsigned)(j - 5) < 28; }
__device__ __forceinline__ int blk_row(int j) { return 112 * j - 16 * (min(j, 5) + max(j - 33, 0)); }
constexpr float SM_SCALE_LOG2 = 0.08838834764831845f * 1.4426950408889634f;

__device__ __align__(1024) uint4 g_part[16 * 64 * 2 * 4 * 128];
__device__ __align__(1024) uint4 g_gate[SEQ * DM / 8];
__device__ __align__(128) float g_r[SEQ];
__device__ __align__(128) float2 g_stats[SEQ];
__device__ __align__(128) float g_ypart[4 * TOPC * DM];
__device__ __align__(128) float g_upd[TOPC * DM];
__device__ __align__(128) int g_idx[TOPC];
__device__ __align__(128) unsigned g_launch[N_CTA];
__device__ unsigned g_rcnt, g_ycnt, g_ffn_flag;

__device__ __forceinline__ void prof(int, int, int = 0) {}

#define TS(id) {}
#define TS_DUMP() {}
#define TS1(id) TS(id)
#define TS2(k) {}
#define TS3(k) {}

__device__ __forceinline__ uint32_t smem_u32(const void* p) { return (uint32_t)__cvta_generic_to_shared(p); }
__device__ __forceinline__ void mbar_init(uint32_t bar, uint32_t cnt) {
  asm volatile("mbarrier.init.shared::cta.b64 [%0], %1;" ::"r"(bar), "r"(cnt) : "memory");
}
__device__ __forceinline__ void mbar_expect_tx(uint32_t bar, uint32_t bytes) {
  asm volatile("mbarrier.arrive.expect_tx.shared::cta.b64 _, [%0], %1;" ::"r"(bar), "r"(bytes) : "memory");
}
__device__ __forceinline__ void mbar_arrive(uint32_t bar) {
  asm volatile("mbarrier.arrive.shared::cta.b64 _, [%0];" ::"r"(bar) : "memory");
}
__device__ __forceinline__ void mbar_arrive_cluster(uint32_t bar_cluster_addr) {
  asm volatile("mbarrier.arrive.shared::cluster.b64 _, [%0];" ::"r"(bar_cluster_addr) : "memory");
}
template <int ID>
__device__ __forceinline__ void mbar_arrive_cluster_now(uint32_t bar_cluster_addr, bool pred) {
  asm volatile("{\n.reg .pred p, q;\nsetp.ne.u32 p, %1, 0;\nsetp.eq.u32 q, %2, %3;\n"
               "ARR_LOOP:\n@p mbarrier.arrive.shared::cluster.b64 _, [%0];\n@q bra.uni ARR_LOOP;\n}"
               ::"r"(bar_cluster_addr), "r"((uint32_t)pred), "r"(blockIdx.y), "n"(ID) : "memory");
}
__device__ __forceinline__ void block_fence(int id) {
  asm volatile("{\n.reg .pred q;\nsetp.eq.u32 q, %0, %1;\nBF_LOOP:\n@q st.volatile.shared.u32 [%0], %0;\n@q bra.uni BF_LOOP;\n}"
               ::"r"(blockIdx.y), "r"(id) : "memory");
}
__device__ __forceinline__ void mbar_wait(uint32_t bar, uint32_t parity) {
  asm volatile("{\n.reg .pred p, q;\n.reg .u32 n;\nmov.u32 n, 0;\n"
               "WAIT_LOOP:\nmbarrier.try_wait.parity.shared::cta.b64 p, [%0], %1;\n"
               "add.u32 n, n, 1;\nsetp.lt.u32 q, n, 4194304;\nand.pred q, q, !p;\n@q bra WAIT_LOOP;\n}"
               ::"r"(bar), "r"(parity) : "memory");
}
__device__ __forceinline__ uint32_t mapa(uint32_t addr, uint32_t rank) {
  uint32_t r;
  asm volatile("mapa.shared::cluster.u32 %0, %1, %2;" : "=r"(r) : "r"(addr), "r"(rank));
  return r;
}
__device__ __forceinline__ void cluster_arrive() { asm volatile("barrier.cluster.arrive.relaxed.aligned;" ::: "memory"); }
__device__ __forceinline__ bool elect_one() {
  uint32_t p;
  asm volatile("{\n.reg .pred p;\nelect.sync _|p, 0xffffffff;\nselp.u32 %0, 1, 0, p;\n}" : "=r"(p));
  return p;
}
__device__ __forceinline__ int read_lane() { return threadIdx.x & 31; }
__device__ __forceinline__ void cluster_wait() { asm volatile("barrier.cluster.wait.acquire.aligned;" ::: "memory"); }
__device__ __forceinline__ void bar_sync(int id, int n) { asm volatile("barrier.cta.sync %0, %1;" ::"r"(id), "r"(n) : "memory"); }
__device__ __forceinline__ void bar_arrive(int id, int n) { asm volatile("barrier.cta.arrive %0, %1;" ::"r"(id), "r"(n) : "memory"); }

__device__ __forceinline__ uint64_t policy_evict_first() {
  uint64_t p;
  asm("createpolicy.fractional.L2::evict_first.b64 %0, 1.0;" : "=l"(p));
  return p;
}
__device__ __forceinline__ void tma2d_mc(uint32_t dst, const CUtensorMap* tm, int c0, int c1, uint32_t bar, uint64_t pol) {
  asm volatile("cp.async.bulk.tensor.2d.shared::cluster.global.mbarrier::complete_tx::bytes.multicast::cluster.L2::cache_hint"
               " [%0], [%1, {%2, %3}], [%4], %5, %6;"
               ::"r"(dst), "l"(tm), "r"(c0), "r"(c1), "r"(bar), "h"((uint16_t)3), "l"(pol) : "memory");
}
__device__ __forceinline__ void tma3d(uint32_t dst, const CUtensorMap* tm, int c1, int c2, uint32_t bar) {
  asm volatile("cp.async.bulk.tensor.3d.shared::cluster.global.mbarrier::complete_tx::bytes [%0], [%1, {%2, %3, %4}], [%5];"
               ::"r"(dst), "l"(tm), "r"(0), "r"(c1), "r"(c2), "r"(bar) : "memory");
}
__device__ __forceinline__ void tma2d_stream(uint32_t dst, const CUtensorMap* tm, int c0, int c1, uint32_t bar) {
  asm volatile("{\n.reg .b64 pol;\ncreatepolicy.fractional.L2::evict_first.b64 pol, 1.0;\n"
               "cp.async.bulk.tensor.2d.shared::cluster.global.mbarrier::complete_tx::bytes.L2::cache_hint [%0], [%1, {%2, %3}], [%4], pol;\n}"
               ::"r"(dst), "l"(tm), "r"(c0), "r"(c1), "r"(bar) : "memory");
}
__device__ __forceinline__ void tma2d_prefetch(const CUtensorMap* tm, int c0, int c1) {
  asm volatile("cp.async.bulk.prefetch.tensor.2d.L2.global [%0, {%1, %2}];" ::"l"(tm), "r"(c0), "r"(c1) : "memory");
}
__device__ __forceinline__ void prefetch_tmap(const CUtensorMap* tm) {
  asm volatile("prefetch.tensormap [%0];" ::"l"(tm) : "memory");
}

__device__ __forceinline__ void wg_fence() { asm volatile("wgmma.fence.sync.aligned;" ::: "memory"); }
__device__ __forceinline__ void wg_commit() { asm volatile("wgmma.commit_group.sync.aligned;" ::: "memory"); }
template <int N> __device__ __forceinline__ void wg_wait() { asm volatile("wgmma.wait_group.sync.aligned %0;" ::"n"(N) : "memory"); }

__device__ __forceinline__ uint64_t mkdesc(uint32_t addr, uint32_t lbo_bytes) {
  return (uint64_t)(((addr & 0x3FFFF) >> 4) | ((lbo_bytes >> 4) << 16)) | ((uint64_t)0x40000040u << 32);
}
__device__ __forceinline__ uint64_t mkdesc_q(uint32_t addr) {
  return (uint64_t)(((addr & 0x3FFFF) >> 4) | (64u << 16)) | ((uint64_t)8 << 32);
}
template <int N> __device__ __forceinline__ void pin(float (&a)[N]) {
#pragma unroll
  for (int i = 0; i < N; i++) asm volatile("" : "+f"(a[i])::"memory");
}
template <int N> __device__ __forceinline__ void kill(float (&a)[N]) {
#pragma unroll
  for (int i = 0; i < N; i++) asm volatile("" : "=f"(a[i]));
}
template <int N> __device__ __forceinline__ void pin(uint32_t (&a)[N]) {
#pragma unroll
  for (int i = 0; i < N; i++) asm volatile("" : "+r"(a[i])::"memory");
}

#define F8(d, o) "+f"(d[o]), "+f"(d[o + 1]), "+f"(d[o + 2]), "+f"(d[o + 3]), "+f"(d[o + 4]), "+f"(d[o + 5]), "+f"(d[o + 6]), "+f"(d[o + 7])
#define R32A "%0, %1, %2, %3, %4, %5, %6, %7, %8, %9, %10, %11, %12, %13, %14, %15, %16, %17, %18, %19, %20, %21, %22, %23, %24, %25, %26, %27, %28, %29, %30, %31"
#define R32B "%32, %33, %34, %35, %36, %37, %38, %39, %40, %41, %42, %43, %44, %45, %46, %47, %48, %49, %50, %51, %52, %53, %54, %55, %56, %57, %58, %59, %60, %61, %62, %63"

template <int TB>
__device__ __forceinline__ void mma_n128(float (&d)[64], uint32_t a0, uint32_t a1, uint32_t a2, uint32_t a3, uint64_t db, int acc) {
  asm volatile("{\n.reg .pred p;\nsetp.ne.b32 p, %69, 0;\n"
               "wgmma.mma_async.sync.aligned.m64n128k16.f32.bf16.bf16 {" R32A ", " R32B "}, {%64, %65, %66, %67}, %68, p, 1, 1, %70;\n}\n"
               : F8(d, 0), F8(d, 8), F8(d, 16), F8(d, 24), F8(d, 32), F8(d, 40), F8(d, 48), F8(d, 56)
               : "r"(a0), "r"(a1), "r"(a2), "r"(a3), "l"(db), "r"(acc), "n"(TB));
}
#define PV1(a0, a1, a2, a3, ob, acc) "add.s64 b, %92, " #ob ";\n" \
  "wgmma.mma_async.sync.aligned.m64n128k16.f32.bf16.bf16 {" R32A ", " R32B "}, {%" #a0 ", %" #a1 ", %" #a2 ", %" #a3 "}, b, " #acc ", 1, 1, 1;\n"
#define PV6 "wgmma.fence.sync.aligned;\n" PV1(64, 65, 66, 67, 0, p) PV1(68, 69, 70, 71, 128, 1) PV1(72, 73, 74, 75, 256, 1) \
  PV1(76, 77, 78, 79, 384, 1) PV1(80, 81, 82, 83, 512, 1) PV1(84, 85, 86, 87, 640, 1)
#define U4(a, o) "r"(a[o]), "r"(a[o + 1]), "r"(a[o + 2]), "r"(a[o + 3])
__device__ __forceinline__ void mma_pv(float (&d)[64], const uint32_t (&a)[28], uint64_t dv, bool acc, bool big) {
  asm volatile("{\n.reg .pred p, q;\n.reg .b64 b;\nsetp.ne.b32 p, %93, 0;\nsetp.eq.b32 q, %94, 0;\n@q bra.uni PV_SMALL;\n"
               PV6 PV1(88, 89, 90, 91, 768, 1) "wgmma.commit_group.sync.aligned;\nbra.uni PV_DONE;\n"
               "PV_SMALL:\n" PV6 "wgmma.commit_group.sync.aligned;\nPV_DONE:\n}\n"
               : F8(d, 0), F8(d, 8), F8(d, 16), F8(d, 24), F8(d, 32), F8(d, 40), F8(d, 48), F8(d, 56)
               : U4(a, 0), U4(a, 4), U4(a, 8), U4(a, 12), U4(a, 16), U4(a, 20), U4(a, 24), "l"(dv), "r"((int)acc), "r"((int)big) : "memory");
}
#define R48 R32A ", %32, %33, %34, %35, %36, %37, %38, %39, %40, %41, %42, %43, %44, %45, %46, %47"
#define R56 R48 ", %48, %49, %50, %51, %52, %53, %54, %55"
#define QK1(N, R, A, B, oa, ob, acc) "add.s64 a, " A ", " #oa ";\nadd.s64 b, " B ", " #ob ";\n" \
  "wgmma.mma_async.sync.aligned.m64n" #N "k16.f32.bf16.bf16 {" R "}, a, b, " #acc ", 1, 1, 0, 0;\n"
#define QK8(N, R, A, B) "{\n.reg .b64 a, b;\nwgmma.fence.sync.aligned;\n" QK1(N, R, A, B, 0, 0, 0) QK1(N, R, A, B, 128, 2, 1) \
  QK1(N, R, A, B, 256, 4, 1) QK1(N, R, A, B, 384, 6, 1) QK1(N, R, A, B, 512, 1024, 1) QK1(N, R, A, B, 640, 1026, 1) \
  QK1(N, R, A, B, 768, 1028, 1) QK1(N, R, A, B, 896, 1030, 1) "wgmma.commit_group.sync.aligned;\n}\n"
#define O8(d, o) "=f"(d[o]), "=f"(d[o + 1]), "=f"(d[o + 2]), "=f"(d[o + 3]), "=f"(d[o + 4]), "=f"(d[o + 5]), "=f"(d[o + 6]), "=f"(d[o + 7])
__device__ __forceinline__ void mma_qk(float (&d)[56], uint64_t dq, uint64_t dk) {
  asm volatile(QK8(112, R56, "%56", "%57")
               : O8(d, 0), O8(d, 8), O8(d, 16), O8(d, 24), O8(d, 32), O8(d, 40), O8(d, 48) : "l"(dq), "l"(dk) : "memory");
}
__device__ __forceinline__ void mma_qk(float (&d)[48], uint64_t dq, uint64_t dk) {
  asm volatile(QK8(96, R48, "%48", "%49")
               : O8(d, 0), O8(d, 8), O8(d, 16), O8(d, 24), O8(d, 32), O8(d, 40) : "l"(dq), "l"(dk) : "memory");
}
__device__ __forceinline__ void mma_n64t(float (&d)[32], uint32_t a0, uint32_t a1, uint32_t a2, uint32_t a3, uint64_t db, int acc) {
  asm volatile("{\n.reg .pred p;\nsetp.ne.b32 p, %37, 0;\n"
               "wgmma.mma_async.sync.aligned.m64n64k16.f32.bf16.bf16 {" R32A "}, {%32, %33, %34, %35}, %36, p, 1, 1, 1;\n}\n"
               : F8(d, 0), F8(d, 8), F8(d, 16), F8(d, 24)
               : "r"(a0), "r"(a1), "r"(a2), "r"(a3), "l"(db), "r"(acc));
}
__device__ __forceinline__ void mma_n8(float (&d)[4], uint64_t da, uint64_t db, int acc) {
  asm volatile("{\n.reg .pred p;\nsetp.ne.b32 p, %6, 0;\n"
               "wgmma.mma_async.sync.aligned.m64n8k16.f32.bf16.bf16 {%0, %1, %2, %3}, %4, %5, p, 1, 1, 1, 0;\n}\n"
               : "+f"(d[0]), "+f"(d[1]), "+f"(d[2]), "+f"(d[3])
               : "l"(da), "l"(db), "r"(acc));
}
__device__ __forceinline__ void hmma_k8(float (&d)[4], uint32_t a0, uint32_t a1, uint32_t b0) {
  asm volatile("mma.sync.aligned.m16n8k8.row.col.f32.bf16.bf16.f32 {%0, %1, %2, %3}, {%4, %5}, {%6}, {%0, %1, %2, %3};"
               : "+f"(d[0]), "+f"(d[1]), "+f"(d[2]), "+f"(d[3]) : "r"(a0), "r"(a1), "r"(b0));
}
__device__ __forceinline__ void hmma_k16(float (&d)[4], uint32_t a0, uint32_t a1, uint32_t a2, uint32_t a3, uint32_t b0, uint32_t b1) {
  asm volatile("mma.sync.aligned.m16n8k16.row.col.f32.bf16.bf16.f32 {%0, %1, %2, %3}, {%4, %5, %6, %7}, {%8, %9}, {%0, %1, %2, %3};"
               : "+f"(d[0]), "+f"(d[1]), "+f"(d[2]), "+f"(d[3]) : "r"(a0), "r"(a1), "r"(a2), "r"(a3), "r"(b0), "r"(b1));
}

__device__ __forceinline__ uint32_t pack2(float lo, float hi) {
  uint32_t r;
  asm("cvt.rn.bf16x2.f32 %0, %1, %2;" : "=r"(r) : "f"(hi), "f"(lo));
  return r;
}
__device__ __forceinline__ float bf_lo(uint32_t w) { return __uint_as_float(w << 16); }
__device__ __forceinline__ float bf_hi(uint32_t w) { return __uint_as_float(w & 0xFFFF0000u); }
__device__ __forceinline__ float bfr(float x) { return __bfloat162float(__float2bfloat16_rn(x)); }
__device__ __forceinline__ uint32_t sub2(uint32_t a, uint32_t b) {
  uint32_t r;
  asm("sub.rn.bf16x2 %0, %1, %2;" : "=r"(r) : "r"(a), "r"(b));
  return r;
}
__device__ __forceinline__ uint32_t add2(uint32_t a, uint32_t b) {
  uint32_t r;
  asm("add.rn.bf16x2 %0, %1, %2;" : "=r"(r) : "r"(a), "r"(b));
  return r;
}
__device__ __forceinline__ uint32_t fma2(uint32_t a, uint32_t b, uint32_t c) {
  uint32_t r;
  asm("fma.rn.bf16x2 %0, %1, %2, %3;" : "=r"(r) : "r"(a), "r"(b), "r"(c));
  return r;
}
__device__ __forceinline__ float ex2(float x) {
  float r;
  asm("ex2.approx.ftz.f32 %0, %1;" : "=f"(r) : "f"(x));
  return r;
}
__device__ __forceinline__ float rcp(float x) {
  float r;
  asm("rcp.approx.ftz.f32 %0, %1;" : "=f"(r) : "f"(x));
  return r;
}
__device__ __forceinline__ float silu_f(float t) { return t * rcp(1.0f + ex2(-1.4426950408889634f * t)); }
__device__ __forceinline__ void lds128(uint32_t a, uint32_t& x, uint32_t& y, uint32_t& z, uint32_t& w) {
  asm volatile("ld.shared.v4.u32 {%0, %1, %2, %3}, [%4];" : "=r"(x), "=r"(y), "=r"(z), "=r"(w) : "r"(a) : "memory");
}
__device__ __forceinline__ void ldsm4(uint32_t a, uint32_t& x, uint32_t& y, uint32_t& z, uint32_t& w) {
  asm volatile("ldmatrix.sync.aligned.m8n8.x4.shared.b16 {%0, %1, %2, %3}, [%4];" : "=r"(x), "=r"(y), "=r"(z), "=r"(w) : "r"(a) : "memory");
}
constexpr uint32_t TAG = 0x10000;
__device__ __forceinline__ void st_gran(uint4* p, uint32_t x, uint32_t y, uint32_t z, uint32_t w) {
  asm volatile("st.relaxed.gpu.global.v4.b32 [%0], {%1, %2, %3, %4};" ::"l"(p), "r"(x), "r"(y), "r"(z), "r"(w) : "memory");
}
__device__ __forceinline__ void ld_gran(const uint4* p, uint32_t& x, uint32_t& y, uint32_t& z, uint32_t& w) {
  asm volatile("ld.relaxed.gpu.global.v4.b32 {%0, %1, %2, %3}, [%4];" : "=r"(x), "=r"(y), "=r"(z), "=r"(w) : "l"(p) : "memory");
}
__device__ __forceinline__ void stsm4(uint32_t a, uint32_t x, uint32_t y, uint32_t z, uint32_t w) {
  asm volatile("stmatrix.sync.aligned.m8n8.x4.shared.b16 [%0], {%1, %2, %3, %4};" ::"r"(a), "r"(x), "r"(y), "r"(z), "r"(w) : "memory");
}
__device__ __forceinline__ void cp16(uint32_t dst, const void* src) {
  asm volatile("cp.async.cg.shared.global [%0], [%1], 16;" ::"r"(dst), "l"(src) : "memory");
}
__device__ __forceinline__ void cp_wait_all() { asm volatile("cp.async.wait_all;" ::: "memory"); }
__device__ __forceinline__ void add_granules(float (&red)[32], const uint32_t (&g)[16]) {
#pragma unroll
  for (int i = 0; i < 16; i++) { red[2 * i] += bf_lo(g[i]); red[2 * i + 1] += bf_hi((i & 3) ? g[i] : g[i] & ~TAG); }
}
__device__ __forceinline__ bool granules_ok(const uint32_t (&g)[16], uint32_t tag) {
  uint32_t a, b;
  asm("lop3.b32 %0, %1, %2, %3, 0x7E;" : "=r"(a) : "r"(g[0]), "r"(g[4]), "r"(tag));
  asm("lop3.b32 %0, %1, %2, %3, 0x7E;" : "=r"(b) : "r"(g[8]), "r"(g[12]), "r"(tag));
  return __all_sync(0xffffffffu, ((a | b) & TAG) == 0);
}
__device__ __forceinline__ unsigned ld_acquire(const unsigned* p) {
  unsigned v;
  asm volatile("ld.acquire.gpu.global.u32 %0, [%1];" : "=r"(v) : "l"(p) : "memory");
  return v;
}
__device__ __forceinline__ unsigned atom_add_acq_rel(unsigned* p) {
  unsigned v;
  asm volatile("atom.acq_rel.gpu.global.add.u32 %0, [%1], 1;" : "=r"(v) : "l"(p) : "memory");
  return v;
}
__device__ __forceinline__ void st_release(unsigned* p, unsigned v) {
  asm volatile("st.release.gpu.global.u32 [%0], %1;" ::"l"(p), "r"(v) : "memory");
}

struct LnAcc {
  float sm[2][4], sq[8][4];
  __device__ __forceinline__ void clear() {
#pragma unroll
    for (int i = 0; i < 4; i++) {
      sm[0][i] = sm[1][i] = 0.f;
#pragma unroll
      for (int j = 0; j < 8; j++) sq[j][i] = 0.f;
    }
  }
};
template <int K0, int K1>
__device__ __forceinline__ void ln_fetch(uint32_t (&xa)[144], uint32_t boxes, uint32_t lo) {
#pragma unroll
  for (int k = K0; k < K1; k++) ldsm4(boxes + (k >> 2) * 8192 + (lo ^ ((k & 3) << 5)), xa[4 * k], xa[4 * k + 1], xa[4 * k + 2], xa[4 * k + 3]);
}
__device__ __forceinline__ void ln_accum1(LnAcc& a, int h, uint32_t x0, uint32_t x1, uint32_t x2, uint32_t x3) {
  const uint32_t ONES = 0x3F803F80u;
  hmma_k16(a.sm[h], x0, x1, x2, x3, ONES, ONES);
  hmma_k8(a.sq[4 * h], x0, x1, x0);
  hmma_k8(a.sq[4 * h + 1], x0, x1, x1);
  hmma_k8(a.sq[4 * h + 2], x2, x3, x2);
  hmma_k8(a.sq[4 * h + 3], x2, x3, x3);
}
template <int K0, int K1>
__device__ __forceinline__ void ln_accum(const uint32_t (&xa)[144], LnAcc& a) {
#pragma unroll
  for (int k = K0; k < K1; k++) ln_accum1(a, k & 1, xa[4 * k], xa[4 * k + 1], xa[4 * k + 2], xa[4 * k + 3]);
}
__device__ __forceinline__ void ln_row(float sum, float sq, float& mean_b, float& rstd) {
  const float mean = sum * (1.0f / DM);
  const uint32_t mv = pack2(mean, fmaxf(sq * (1.0f / DM) - mean * mean, 0.0f));
  mean_b = bf_lo(mv);
  float sd;
  asm("sqrt.approx.f32 %0, %1;" : "=f"(sd) : "f"(bf_lo(pack2(bf_hi(mv) + 1e-5f, 0.f))));
  rstd = rcp(bf_lo(pack2(sd, 0.f)));
}
__device__ __forceinline__ void ln_diag(const LnAcc& a, int lane, float& t0, float& t1) {
  const bool odd = (lane >> 2) & 1;
  t0 = odd ? (a.sq[0][1] + a.sq[2][1]) + (a.sq[4][1] + a.sq[6][1]) : (a.sq[0][0] + a.sq[2][0]) + (a.sq[4][0] + a.sq[6][0]);
  t1 = odd ? (a.sq[1][3] + a.sq[3][3]) + (a.sq[5][3] + a.sq[7][3]) : (a.sq[1][2] + a.sq[3][2]) + (a.sq[5][2] + a.sq[7][2]);
}
__device__ __forceinline__ void ln_stats(const LnAcc& a, int lane, float& mean0, float& rstd0, float& mean1, float& rstd1) {
  float t0, t1;
  ln_diag(a, lane, t0, t1);
  const int src = (lane & ~3) | (lane >> 3);
  t0 = __shfl_sync(0xffffffffu, t0, src);
  t1 = __shfl_sync(0xffffffffu, t1, src);
  ln_row(a.sm[0][0] + a.sm[1][0], t0, mean0, rstd0);
  ln_row(a.sm[0][2] + a.sm[1][2], t1, mean1, rstd1);
}

template <bool ROUTED>
__device__ __forceinline__ uint32_t gate2(uint32_t x2, float mean_b, float rstd, float2 upd = make_float2(0.f, 0.f)) {
  const uint32_t xc = sub2(x2, pack2(mean_b, mean_b));
  uint32_t t = pack2(bf_lo(xc) * rstd, bf_hi(xc) * rstd);
  if (ROUTED) t = pack2(bf_lo(t) + upd.x, bf_hi(t) + upd.y);
  return pack2(silu_f(bf_lo(t)), silu_f(bf_hi(t)));
}

#define PF_D 4
#define X_SPLIT 38
#define X_SPLITA 36
#define X_SPLITS 32
#define X_SPLITSA 30
#define X_PA 8
#define X_PG 2
#define X_E0 10
#define X_F2 12
#define X_F1 8
#define X_BF2 1
#define X_EARLY 1
template <int V> struct IC { static constexpr int value = V; };

struct Ctx {
  uint32_t sb;
  uint8_t* sp;
  uint32_t rank;
};

__device__ __forceinline__ void attn_producer(const Ctx& cx, int qb, int hs, const CUtensorMap* tmKV,
                                              const CUtensorMap* tmWq, const CUtensorMap* tmWo) {
  const uint32_t full = cx.sb + SM_FULL, empty = cx.sb + SM_EMPTY, ring = cx.sb + SM_RING + cx.rank * 16384;
  const uint64_t last_use = policy_evict_first();
  auto acquire = [&](uint32_t r, uint32_t n, uint32_t bytes) {
    mbar_wait(empty + 8 * r, (n ^ (r >> 1) ^ 1) & 1);
    mbar_expect_tx(full + 8 * r, bytes);
  };
  int st = 0;
#pragma unroll 1
  for (int p = 0; p < 4; p++) {
    const int n0 = (hs * 4 + (p ^ (p >> 1))) * DH + cx.rank * 64;
#pragma unroll 1
    for (int i = 0; i < 5; i++, st++) {
      const uint32_t r = (st ^ ((st >> 1) & 1)) & 3;
      acquire(r, st >> 2, i == 2 ? 16384 : 32768);
      const int k0 = i < 3 ? 128 * i : 128 * i - 64;
      tma2d_mc(ring + r * STAGE, tmWq, n0, k0, full + 8 * r, last_use);
      if (i != 2) tma2d_mc(ring + r * STAGE + 8192, tmWq, n0, k0 + 64, full + 8 * r, last_use);
      if (st == 1) {
#pragma unroll 1
        for (int b = 8 + qb; b < 72; b += 16) tma2d_prefetch(tmWq, (hs * 4 + ((b / 18) ^ (b / 36))) * DH + (b & 1) * 64, ((b % 18) >> 1) * 64);
      }
      if (st == 8 && qb < 2 * PF_D) tma2d_prefetch(tmKV + ((qb >> 1) & 1), cx.rank * 64, hs * 2 * SEQ + (qb >> 2) * 96);
    }
  }
  uint32_t r = 0, n = 5;
#pragma unroll 1
  for (int u = 0; u < NST_KV; u++) {
    const bool big = blk_big(u >> 1);
    acquire(r, n, big ? 112 * 256 : 96 * 256);
    tma2d_mc(ring + r * STAGE, tmKV + (u & 1) + (big ? 0 : 2), cx.rank * 64, hs * 2 * SEQ + blk_row(u >> 1), full + 8 * r, last_use);
    if (((u ^ (qb >> 1)) & 7) == 0 && u + PF_D < NST_KV)
      tma2d_prefetch(tmKV + ((u + PF_D) & 1), cx.rank * 64, hs * 2 * SEQ + blk_row((u + PF_D) >> 1));
    if ((unsigned)(u - 32) < 36 && (u & 15) == qb) tma2d_prefetch(tmWo, ((u - 32) >> 2) * 64, hs * 512 + (u & 3) * 128);
    if (++r == 3) { r = 0; n++; }
  }
#pragma unroll 1
  for (int u = 0; u < NST_O; u++) {
    const int s = u >> 1;
    const int blk = s == 0 ? 8 : ((hs + s) & 7);
    r = (u + 1) & 3;
    acquire(r, (u >> 2) ^ (u >> 1), 32768);
    tma2d_mc(ring + r * STAGE, tmWo, blk * 64, hs * 512 + ((u & 1) + cx.rank * 2) * 128, full + 8 * r, last_use);
  }
}

__device__ __forceinline__ void attn_gate(const Ctx& cx, int qb, int hs, int t, const __nv_bfloat16* x) {
  uint4 nx = *(const uint4*)(x + (size_t)(qb * 128 + (t >> 3)) * DM + hs * 64 + (t & 7) * 8);
  bar_sync(BAR_GATE, 352);
#pragma unroll 1
  for (int ch = t; ch < 1152; ch += 96) {
    const uint4 v = nx;
    const int n = ch + 96;
    if (n < 1152) nx = *(const uint4*)(x + (size_t)(qb * 128 + (n < 1024 ? n >> 3 : hs * 16 + ((n - 1024) >> 3))) * DM + (n < 1024 ? hs * 64 : 512) + (t & 7) * 8);
    const int lr = ch < 1024 ? ch >> 3 : hs * 16 + ((ch - 1024) >> 3);
    const float2 st = *(const float2*)(cx.sp + SM_STATS + 8 * lr);
    g_gate[((qb * 128 + lr) * DM + (ch < 1024 ? hs * 64 : 512) + (t & 7) * 8) >> 3] =
        make_uint4(gate2<false>(v.x, st.x, st.y), gate2<false>(v.y, st.x, st.y), gate2<false>(v.z, st.x, st.y), gate2<false>(v.w, st.x, st.y));
  }
}

constexpr uint32_t SM_XO = SM_SLOT, SM_GO = SM_SLOT + 128 * 144;
constexpr uint32_t SM_X8 = SM_SLOT + 2 * STAGE + 20480, SM_G8 = SM_X8 + 16 * 144;
__device__ __forceinline__ void attn_stage_xg(const Ctx& cx, int qb, int hs, int t, const __nv_bfloat16* x) {
  bar_sync(BAR_OA, 352);
#pragma unroll 1
  for (int ch = t; ch < 1024; ch += 64) {
    const size_t o = (size_t)(qb * 128 + (ch >> 3)) * DM + hs * 64 + (ch & 7) * 8;
    cp16(cx.sb + SM_XO + (ch >> 3) * 144 + (ch & 7) * 16, x + o);
    cp16(cx.sb + SM_GO + (ch >> 3) * 144 + (ch & 7) * 16, (const __nv_bfloat16*)g_gate + o);
  }
  cp_wait_all();
  mbar_arrive(cx.sb + SM_BAR_XG);
}

__device__ __forceinline__ void attn_helper(const Ctx& cx, int qb, int hs, int lane, const __nv_bfloat16* x) {
  unsigned e = 0;
  if (lane == 0) {
    e = g_launch[blockIdx.x];
    g_launch[blockIdx.x] = e + 1;
  }
  e = __shfl_sync(0xffffffffu, e, 0);
  bar_sync(BAR_HELPER, 128);
#pragma unroll 1
  for (int n = 0; n < (1 << 16) && ld_acquire(&g_ffn_flag) != e + 1; n++) __nanosleep(1000);
  const uint32_t tag = (~e & 1) * TAG;
  {
#pragma unroll 1
    for (int i = 0; i < 2 * TOPC; i++) {
      const int lr = __ldcg(&g_idx[i >> 1]) - qb * 128, col = ((i & 1) ? 512 : hs * 64) + 2 * lane;
      if ((i & 1) ? (lr >> 4) == hs : (lr >> 7) == 0) {
        const float2 st = *(const float2*)(cx.sp + SM_STATS + 8 * lr);
        const int o = (qb * 128 + lr) * DM + col;
        *(uint32_t*)((__nv_bfloat16*)g_gate + o) =
            gate2<true>(*(const uint32_t*)(x + o), st.x, st.y, __ldcg((const float2*)(g_upd + (i >> 1) * DM + col)));
      }
    }
  }
  if (lane == 0) *(uint32_t*)(cx.sp + SM_TAG) = tag;
  __syncwarp();
  if (lane == 0) mbar_arrive(cx.sb + SM_BAR_MISC);

  const uint4* src = g_part + (size_t)((qb * 64 + 56) * 2 + (hs >> 2)) * 4 * 128 + (hs & 3) * 32 + lane;
  const uint32_t stg = cx.sb + SM_SLOT + 2 * STAGE + lane * 16;
  bar_sync(BAR_OA, 352);

#pragma unroll 1
  for (int i = 0; i < 4; i++) {
    const int ch = i * 32 + lane;
    const size_t o = (size_t)(qb * 128 + hs * 16 + (ch >> 3)) * DM + 512 + (ch & 7) * 8;
    cp16(cx.sb + SM_X8 + (ch >> 3) * 144 + (ch & 7) * 16, x + o);
    cp16(cx.sb + SM_G8 + (ch >> 3) * 144 + (ch & 7) * 16, (const __nv_bfloat16*)g_gate + o);
  }
#pragma unroll 1
  for (int n = 0; n < (1 << 16); n++) {
    __nanosleep(n ? 500 : 2000);
    uint32_t a, b, d, t;
    ld_gran(src - lane + (lane & 7) * (2 * 4 * 128) + 3 * 128 + 31, a, b, d, t);
    if (__all_sync(0xffffffffu, (a & TAG) == tag)) break;
  }
#pragma unroll 1
  for (int n = 0; n < (1 << 16); n++) {
#pragma unroll 1
    for (int i = 0; i < 8; i++) {
#pragma unroll
      for (int g = 0; g < 4; g++) cp16(stg + (i * 4 + g) * 512, src + i * (2 * 4 * 128) + g * 128);
    }
    cp_wait_all();
    uint32_t bad = 0;
#pragma unroll 4
    for (int i = 0; i < 32; i++) bad |= *(const volatile uint32_t*)(cx.sp + SM_SLOT + 2 * STAGE + lane * 16 + i * 512) ^ tag;
    if (__all_sync(0xffffffffu, (bad & TAG) == 0)) break;
  }

}
__device__ __forceinline__ void attn_finish8(const Ctx& cx, int qb, int hs, int hw, int lane, __nv_bfloat16* out) {
  bar_sync(BAR_GATE, 96);
#pragma unroll 1
  for (int g = hw; g < 4; g += 3) {
    float acc[8] = {0.f, 0.f, 0.f, 0.f, 0.f, 0.f, 0.f, 0.f};
#pragma unroll 2
    for (int sidx = 0; sidx < 8; sidx++) {
      uint32_t a, b, d, t;
      lds128(cx.sb + SM_SLOT + 2 * STAGE + lane * 16 + (sidx * 4 + g) * 512, a, b, d, t);
      acc[0] += bf_lo(a); acc[1] += bf_hi(a & ~TAG); acc[2] += bf_lo(b); acc[3] += bf_hi(b);
      acc[4] += bf_lo(d); acc[5] += bf_hi(d); acc[6] += bf_lo(t); acc[7] += bf_hi(t);
    }
#pragma unroll
    for (int j = 0; j < 4; j++) {
      const int o = ((lane >> 2) + (j & 1) * 8) * 144 + (2 * g + (j >> 1)) * 16 + (lane & 3) * 4;
      uint32_t* xp = (uint32_t*)(cx.sp + SM_X8 + o);
      const uint32_t xw = *xp, gw = *(const uint32_t*)(cx.sp + SM_G8 + o);
      *xp = fma2(pack2(acc[2 * j], acc[2 * j + 1]), gw, xw);
    }
  }
  bar_sync(BAR_GATE, 96);
  for (int ch = hw * 32 + lane; ch < 128; ch += 96)
    *(uint4*)(out + (size_t)(qb * 128 + hs * 16 + (ch >> 3)) * DM + 512 + (ch & 7) * 8) =
        *(const uint4*)(cx.sp + SM_X8 + (ch >> 3) * 144 + (ch & 7) * 16);
}

constexpr float SUM_HI = 1.8446744e19f, SUM_LO = 9.0949470e-13f;

template <int LO, int HI, int N>
__device__ __forceinline__ void softmax_exp(float (&s)[N]) {
#pragma unroll
  for (int i = LO; i < HI; i++) s[i] = ex2(s[i]);
}
__device__ __forceinline__ void sum_tree(const uint32_t (&pf)[28], bool big, uint32_t& h0, uint32_t& h1) {
  uint32_t t0 = add2(add2(pf[16], pf[18]), add2(pf[20], pf[22])), t1 = add2(add2(pf[17], pf[19]), add2(pf[21], pf[23]));
  if (big) { t0 = add2(t0, add2(pf[24], pf[26])); t1 = add2(t1, add2(pf[25], pf[27])); }
  h0 = add2(add2(add2(add2(pf[0], pf[2]), add2(pf[4], pf[6])), add2(add2(pf[8], pf[10]), add2(pf[12], pf[14]))), t0);
  h1 = add2(add2(add2(add2(pf[1], pf[3]), add2(pf[5], pf[7])), add2(add2(pf[9], pf[11]), add2(pf[13], pf[15]))), t1);
}
__device__ __forceinline__ void exact_attention(float (&o)[64], float& l0, float& l1, uint32_t qaddr, const __nv_bfloat16* kh,
                                                const __nv_bfloat16* vh, int lane) {
  const int off = (lane >> 2) * DH + (lane & 3) * 2;
  float m0 = -3.0e38f, m1 = -3.0e38f;
  l0 = l1 = 0.f;
#pragma unroll
  for (int i = 0; i < 64; i++) o[i] = 0.f;
#pragma unroll 1
  for (int key = 0; key < SEQ; key += 16) {
    const __nv_bfloat16 *kp = kh + key * DH + off, *vp = vh + key * DH + off;
    float d0[4] = {0.f, 0.f, 0.f, 0.f}, d1[4] = {0.f, 0.f, 0.f, 0.f};
#pragma unroll 4
    for (int k = 0; k < 8; k++) {
      uint32_t q0, q1, q2, q3;
      ldsm4(qaddr + k * 2048, q0, q1, q2, q3);
      hmma_k16(d0, q0, q1, q2, q3, *(const uint32_t*)(kp + k * 16), *(const uint32_t*)(kp + k * 16 + 8));
      hmma_k16(d1, q0, q1, q2, q3, *(const uint32_t*)(kp + 8 * DH + k * 16), *(const uint32_t*)(kp + 8 * DH + k * 16 + 8));
    }
    float x0 = fmaxf(fmaxf(d0[0], d0[1]), fmaxf(d1[0], d1[1])), x1 = fmaxf(fmaxf(d0[2], d0[3]), fmaxf(d1[2], d1[3]));
    x0 = fmaxf(x0, __shfl_xor_sync(0xffffffffu, x0, 1));
    x1 = fmaxf(x1, __shfl_xor_sync(0xffffffffu, x1, 1));
    x0 = fmaxf(fmaxf(x0, __shfl_xor_sync(0xffffffffu, x0, 2)), m0);
    x1 = fmaxf(fmaxf(x1, __shfl_xor_sync(0xffffffffu, x1, 2)), m1);
    const float sc0 = ex2(m0 - x0), sc1 = ex2(m1 - x1);
    m0 = x0; m1 = x1;
    const uint32_t p0 = pack2(ex2(d0[0] - m0), ex2(d0[1] - m0)), p1 = pack2(ex2(d0[2] - m1), ex2(d0[3] - m1)),
                   p2 = pack2(ex2(d1[0] - m0), ex2(d1[1] - m0)), p3 = pack2(ex2(d1[2] - m1), ex2(d1[3] - m1));
    l0 = fmaf(l0, sc0, (bf_lo(p0) + bf_hi(p0)) + (bf_lo(p2) + bf_hi(p2)));
    l1 = fmaf(l1, sc1, (bf_lo(p1) + bf_hi(p1)) + (bf_lo(p3) + bf_hi(p3)));
#pragma unroll
    for (int nb = 0; nb < 16; nb++) {
      uint32_t b0, b1;
      asm("movmatrix.sync.aligned.m8n8.trans.b16 %0, %1;" : "=r"(b0) : "r"(*(const uint32_t*)(vp + nb * 8)));
      asm("movmatrix.sync.aligned.m8n8.trans.b16 %0, %1;" : "=r"(b1) : "r"(*(const uint32_t*)(vp + 8 * DH + nb * 8)));
      o[4 * nb] *= sc0; o[4 * nb + 1] *= sc0; o[4 * nb + 2] *= sc1; o[4 * nb + 3] *= sc1;
      hmma_k16(*(float (*)[4])&o[4 * nb], p0, p1, p2, p3, b0, b1);
    }
  }
}
__device__ __forceinline__ int fresh_lane() {
  int l;
  asm volatile("mov.u32 %0, %%laneid;" : "=r"(l));
  return l;
}
__device__ __forceinline__ bool inv_sums(float l0, float l1, float& i0, float& i1) {
  l0 += __shfl_xor_sync(0xffffffffu, l0, 1); l1 += __shfl_xor_sync(0xffffffffu, l1, 1);
  l0 += __shfl_xor_sync(0xffffffffu, l0, 2); l1 += __shfl_xor_sync(0xffffffffu, l1, 2);
  i0 = rcp(l0);
  i1 = rcp(l1);
  return !(l0 + l1 <= SUM_HI) | (fminf(l0, l1) < SUM_LO);
}
template <int LO, int HI>
__device__ __forceinline__ void park(uint32_t a, const float (&o)[64], float i0, float i1, bool on = true) {
#pragma unroll
  for (int i = LO; i < HI; i++)
    asm volatile("{\n.reg .pred p;\nsetp.ne.u32 p, %5, 0;\n@p stmatrix.sync.aligned.m8n8.x4.shared.b16 [%0], {%1, %2, %3, %4};\n}"
                 ::"r"(a + i * 2048), "r"(pack2(o[8 * i] * i0, o[8 * i + 1] * i0)), "r"(pack2(o[8 * i + 2] * i1, o[8 * i + 3] * i1)),
                 "r"(pack2(o[8 * i + 4] * i0, o[8 * i + 5] * i0)), "r"(pack2(o[8 * i + 6] * i1, o[8 * i + 7] * i1)), "r"((uint32_t)on) : "memory");
}

template <int I, int NP, int E0, int N, int NS>
__device__ __forceinline__ void exp_park(float (&s)[NS], uint32_t a, const float (&o)[64], float i0, float i1, bool on, int id) {
  if constexpr (I < NP) {
    constexpr int E1 = E0 + (N - E0) * X_PG / (NP - I);
    softmax_exp<E0, E1>(s);
    park<I, I + X_PG>(a, o, i0, i1, on);
    if (I + X_PG < NP) {
#pragma unroll
      for (int i = E0; i < E1; i++) asm volatile("" : "+f"(s[i])::"memory");
      block_fence(id + I);
    }
    exp_park<I + X_PG, NP, E1, N>(s, a, o, i0, i1, on, id);
  }
}

__device__ __forceinline__ void attn_consumer(const Ctx& cx, int qb, int hs, int wg, int cw, int lane, const __nv_bfloat16* x,
                                              const __nv_bfloat16* kc, const __nv_bfloat16* vc, __nv_bfloat16* out) {
  const uint32_t full = cx.sb + SM_FULL;
  const uint32_t ring = cx.sb + SM_RING;
  const uint32_t qwg = ring + wg * 16384;
  auto qlane = [&](int l) { return qwg + (cw & 3) * 256 + (l >> 4) * 1024 + (l & 15) * 16; };
  const bool signaller = lane == 0 && (cw & 3) < 2;
  const int my_turn = 1 + wg, other_turn = 2 - wg;

  float oA[64], oB[64], i0, i1;
  uint32_t xl[32];
  uint32_t empty_c;
  {
    const int r = lane >> 2, c = lane & 3;
    const int lr0 = cw * 16 + r;
    uint32_t xa[144];
    float rstd0, rstd1, sq0, sq1;
    {
      const uint32_t xb = cx.sb + SM_X + wg * 73728, xf = cx.sb + SM_XFULL + wg * 24;
      const uint32_t lo = ((cw & 3) * 16 + (lane & 15)) * 128 + (((lane >> 4) ^ (lane & 7)) << 4);
      LnAcc a;
      a.clear();
      prof(wg, 0);
      empty_c = mapa(cx.sb + SM_EMPTY, cw & 1);
      mbar_wait(xf, 0);
      ln_fetch<0, 12>(xa, xb, lo);
      ln_accum<0, 12>(xa, a);
      cluster_wait();
      mbar_wait(xf + 8, 0);
      ln_fetch<12, 24>(xa, xb, lo);
      if (wg == 0) {
        bar_sync(4, 128);
        if (signaller) {
          asm volatile("mbarrier.arrive.shared::cluster.b64 _, [%0], 2;" ::"r"(empty_c + 16) : "memory");
          asm volatile("mbarrier.arrive.shared::cluster.b64 _, [%0], 2;" ::"r"(empty_c + 24) : "memory");
        }
      }
      ln_accum<12, 24>(xa, a);
      mbar_wait(xf + 16, 0);
      prof(wg, 1);
      ln_fetch<24, 36>(xa, xb, lo);
#pragma unroll
      for (int k = 24; k < 36; k++) hmma_k16(a.sm[k & 1], xa[4 * k], xa[4 * k + 1], xa[4 * k + 2], xa[4 * k + 3], 0x3F803F80u, 0x3F803F80u);
      ln_diag(a, lane, sq0, sq1);
      if (c != (r >> 1)) sq0 = sq1 = 0.f;
      rstd0 = a.sm[0][0] + a.sm[1][0];
      rstd1 = a.sm[0][2] + a.sm[1][2];
    }
    const uint32_t mm0 = pack2(rstd0 * (1.0f / DM), rstd0 * (1.0f / DM)), mm1 = pack2(rstd1 * (1.0f / DM), rstd1 * (1.0f / DM));
#pragma unroll
    for (int i = 0; i < 16; i++) { xa[2 * i] = sub2(xa[2 * i], mm0); xa[2 * i + 1] = sub2(xa[2 * i + 1], mm1); }
    pin(xa);
    prof(wg, 2);

    float (&acc)[64] = oB;
#pragma unroll 1
    for (int p = 0; p < 4; p++) {
      const int st0 = p * 5;
#pragma unroll
      for (int i = 0; i < 5; i++) {
        if (i == 4 && p == 3) break;
        const int st = st0 + i;
        const uint32_t sl = (st ^ ((st >> 1) & 1)) & 3, slp = ((st - 1) ^ (((st - 1) >> 1) & 1)) & 3;
        mbar_wait(full + 8 * sl, (st >> 2) & 1);
        const bool join = wg && p == 3;
        if (p && i != (wg ? 4 : 1) && !(join && i == 3)) bar_sync(my_turn, 256);
        wg_fence();
        const uint64_t db = mkdesc(ring + sl * STAGE, 16384);
        const int kb0 = i < 3 ? 8 * i : 8 * i - 4;
#pragma unroll
        for (int k = 0; k < (i == 2 ? 4 : 8); k++) {
          const int kb = kb0 + k;
          mma_n128<1>(acc, xa[4 * kb], xa[4 * kb + 1], xa[4 * kb + 2], xa[4 * kb + 3], db + k * 128, kb > 0);
        }
        wg_commit();
        if (wg ? (i == 4 || (p && (i < 2 || i == (join ? 3 : 2)))) : (p && i)) bar_arrive(other_turn, 256);
        if (p == 0 && i < 4) {
          if (i < 2) {
#pragma unroll
            for (int j = 48 + 12 * i; j < 60 + 12 * i; j++) {
              sq0 = fmaf(bf_lo(xa[2 * j]), bf_lo(xa[2 * j]), fmaf(bf_hi(xa[2 * j]), bf_hi(xa[2 * j]), sq0));
              sq1 = fmaf(bf_lo(xa[2 * j + 1]), bf_lo(xa[2 * j + 1]), fmaf(bf_hi(xa[2 * j + 1]), bf_hi(xa[2 * j + 1]), sq1));
            }
          }
          if (i == 1) {
            sq0 += __shfl_xor_sync(0xffffffffu, sq0, 1); sq1 += __shfl_xor_sync(0xffffffffu, sq1, 1);
            sq0 += __shfl_xor_sync(0xffffffffu, sq0, 2); sq1 += __shfl_xor_sync(0xffffffffu, sq1, 2);
            float mean0, mean1;
            ln_row(rstd0, sq0, mean0, rstd0);
            ln_row(rstd1, sq1, mean1, rstd1);
            if (c == 0) {
              *(float2*)(cx.sp + SM_STATS + 8 * lr0) = make_float2(mean0, rstd0);
              *(float2*)(cx.sp + SM_STATS + 8 * (lr0 + 8)) = make_float2(mean1, rstd1);
            }
            bar_arrive(BAR_GATE, 352);
            bar_sync(4 + wg, 128);
            rstd0 *= SM_SCALE_LOG2;
            rstd1 *= SM_SCALE_LOG2;
          }
#pragma unroll
          for (int j = 0; j < 72; j++)
            if (j >= 2 * (i < 2 ? 8 * i + 8 : 8 * i + 4) && j < 2 * (i == 0 ? 16 : 8 * i + 12)) {
              xa[2 * j] = sub2(xa[2 * j], mm0);
              xa[2 * j + 1] = sub2(xa[2 * j + 1], mm1);
            }
          pin(xa);
        }
        if (i == 0) {
          if (wg) {
            wg_wait<0>();
            if (signaller) mbar_arrive_cluster(empty_c + 8 * sl);
          }
        } else if (i == 2) {
          if (!join) {
            wg_wait<0>();
            if (signaller) mbar_arrive_cluster(empty_c + 8 * sl);
          }
        } else if (i != 3) {
          wg_wait<1>();
          if (signaller && (i == 4 || !wg)) mbar_arrive_cluster(empty_c + 8 * slp);
          wg_wait<0>();
          if (signaller) mbar_arrive_cluster(empty_c + 8 * sl);
        }
      }
      if (p == 3) break;
      pin(acc);
      prof(wg, 3 + p);
      park<0, 8>(qlane(lane) + (4 + p) * STAGE, acc, rstd0, rstd1);
      asm volatile("fence.proxy.async.shared::cta;" ::: "memory");
    }
    wg_wait<1>();
    if (signaller && wg) mbar_arrive_cluster(empty_c + 8 * 1);
    wg_wait<0>();
    pin(acc);
    prof(wg, 6);
#pragma unroll
    for (int i = 0; i < 32; i++) xl[i] = xa[112 + i];
    i0 = rstd0;
    i1 = rstd1;
  }

  uint32_t oa[128];
  float acc[32];
  {
    uint32_t pf[28];
    uint32_t bad = 0;
    float lA0 = 0.f, lA1 = 0.f, lB0 = 0.f, lB1 = 0.f;
    int t = 0;
    uint32_t ra = 0, rb = 2 * 2048, rc = 0, par = 1;
    const uint64_t dk0 = mkdesc(ring, 16), dv0 = mkdesc(ring, 16384);
    uint64_t dqA = mkdesc_q(qwg + 4 * STAGE), dqB = dqA + 2048;
    auto turn = [&](auto kc_, auto bc_) {
      constexpr int KIND = decltype(kc_)::value, BIG = decltype(bc_)::value;
      constexpr int HB = KIND == 1, ID = 10 * KIND + 30 * BIG, T0 = BIG ? 38 : 0;
      constexpr int NS = BIG ? 56 : 48, SPLIT = BIG ? (HB ? X_SPLIT : X_SPLITA) : (HB ? X_SPLITS : X_SPLITSA);
      float s[NS];
      float (&op)[64] = HB ? oA : oB;
      uint32_t h0 = 0, h1 = 0;
      TS2(0)
      bar_sync(my_turn, 256);
      TS2(1)
      if (KIND) { pin(pf); pin(op); }
      mma_qk(s, HB ? dqB : dqA, dk0 + (HB ? ra : rc));
      TS2(2)
      if (KIND) {
        const bool bigp = HB ? BIG : BIG ? t != 10 : t == 66;
        if (X_BF2) block_fence(ID + 9);
        pin(pf);
        sum_tree(pf, bigp, h0, h1);
        asm volatile("" : "+r"(h0), "+r"(h1)::"memory");
        if (HB) mbar_wait(full + (rb >> 8), par);
        mma_pv(op, pf, dv0 + rb, t != T0 + 2 - HB, bigp);
      } else {
        mbar_wait(full + (rb >> 8), (NST_Q - 1) >> 2 & 1);
#pragma unroll
        for (int k = 0; k < 8; k++) mma_n128<1>(op, xl[4 * k], xl[4 * k + 1], xl[4 * k + 2], xl[4 * k + 3], dv0 + rb + k * 128, 1);
        wg_commit();
      }
      TS2(3)
      bar_arrive(other_turn, 256);
      (HB ? lA0 : lB0) += bf_lo(h0) + bf_hi(h0);
      (HB ? lA1 : lB1) += bf_lo(h1) + bf_hi(h1);
      wg_wait<1>();
      pin(s);
      TS1(t)
      TS2(4)
      if (KIND == 1) mbar_arrive_cluster_now<ID + 3>(empty_c + (ra >> 8), signaller);
      if (BIG && t == T0 + HB) {
        const uint32_t a = qlane(fresh_lane()) + (4 + HB) * STAGE;
        const bool ok = !__any_sync(0xffffffffu, inv_sums(HB ? lB0 : lA0, HB ? lB1 : lA1, i0, i1));
        bad = (HB ? bad : 0) | (ok ? 0 : 1 << HB);
        (HB ? lB0 : lA0) = 0.f;
        (HB ? lB1 : lA1) = 0.f;
        softmax_exp<0, X_E0>(s);
#pragma unroll
        for (int i = 0; i < X_E0; i++) asm volatile("" : "+f"(s[i])::"memory");
        block_fence(ID + 7);
        exp_park<0, X_PA, X_E0, SPLIT>(s, a, HB ? oB : oA, i0, i1, ok, 200 + ID);
        if (!HB) dqB += 2048;
        prof(wg, 8 + HB);
        if (!HB && cw == 0) bar_arrive(BAR_HELPER, 128);
      } else {
        if (HB && !BIG) bad = (bad & 3) | (inv_sums(lA0, lA1, i0, i1) ? 4 : 0);
        softmax_exp<0, SPLIT>(s);
      }
      pin(s);
      if (!BIG) block_fence(ID + 4);
      TS2(5)
      wg_wait<0>();
      TS2(6)
      pin(op);
      if (KIND) pin(pf); else pin(xl);
      if (HB) {
        par ^= rc == 0;
        if (BIG && t == 37) dqA -= 2048;
      } else {
        mbar_arrive_cluster_now<ID + 5>(empty_c + (rb >> 8), signaller);
        if (KIND) {
          par ^= ra == 0;
          const uint32_t x = ra;
          ra = rc; rc = rb; rb = x;
        }
      }
      softmax_exp<SPLIT, NS>(s);
#pragma unroll
      for (int i = 0; i < NS / 2; i++) pf[i] = pack2(s[2 * i], s[2 * i + 1]);
      pin(pf);
      if (KIND == 0) {
        block_fence(ID + 6);
        park<0, 8>(qlane(fresh_lane()) + 3 * STAGE, oB, i0, i1);
        asm volatile("fence.proxy.async.shared::cta;" ::: "memory");
        prof(wg, 7);
      }
      if (BIG && X_PA < 8 && t == T0 + HB) park<X_PA, 8>(qlane(fresh_lane()) + (4 + HB) * STAGE, HB ? oB : oA, i0, i1, !(bad >> HB));
      if (HB) mbar_wait(full + (rc >> 8), par);
      t++;
    };
#pragma unroll
    for (int i = 24; i < 28; i++) asm volatile("" : "=r"(pf[i]));
    mbar_wait(full, (NST_Q >> 2) & 1);
    turn(IC<0>(), IC<0>());
    rb = 2048; rc = 2 * 2048;
    kill(oA);
    const bool never = blockIdx.y == 1;
#pragma unroll 1
    while (true) {
      turn(IC<1>(), IC<0>());
      if (t == 76) break;
      if (t == 10) {
#pragma unroll 1
        do {
#pragma unroll 1
          do turn(IC<2>(), IC<1>()); while (never);
          turn(IC<1>(), IC<1>());
        } while (t != 66);
      }
#pragma unroll 1
      do turn(IC<2>(), IC<0>()); while (never);
    }
    const uint32_t ql = qlane(fresh_lane());
    auto scale = [&](auto lo, auto hi) {
#pragma unroll
      for (int i = decltype(lo)::value; i < decltype(hi)::value; i++) {
        oa[32 + 2 * i] = pack2(oA[4 * i] * i0, oA[4 * i + 1] * i0);
        oa[32 + 2 * i + 1] = pack2(oA[4 * i + 2] * i1, oA[4 * i + 3] * i1);
        asm volatile("" : "+r"(oa[32 + 2 * i]), "+r"(oa[32 + 2 * i + 1])::"memory");
      }
    };
    TS3(1)
    volatile uint32_t* const cold = (volatile uint32_t*)(cx.sp + SM_COLD) + wg;
    if (bad) *cold = 1;
#pragma unroll
    for (int i = 0; i < 8; i++) ldsm4(ql + 4 * STAGE + i * 2048, oa[4 * i], oa[4 * i + 1], oa[4 * i + 2], oa[4 * i + 3]);
    scale(IC<0>(), IC<X_F1>());
    block_fence(93);
    TS3(2)
    bar_sync(my_turn, 256);
    const uint32_t held = *cold;
    TS3(3)
    pin(pf); pin(oB);
    mma_pv(oB, pf, dv0, true, false);
    mbar_arrive_cluster_now<91>(empty_c + 8 * 3, signaller && !held);
    TS3(4)
    const uint64_t db = mkdesc(ring + STAGE, 16);
    scale(IC<X_F1>(), IC<X_F2>());
    block_fence(94);
#pragma unroll
    for (int i = 0; i < 32; i++) asm volatile("" : "+r"(oa[i])::"memory");
    wg_fence();
#pragma unroll
    for (int k = 0; k < 8; k++) mma_n64t(acc, oa[4 * k], oa[4 * k + 1], oa[4 * k + 2], oa[4 * k + 3], db + k * 128, k > 0);
    if (X_F2 < 16) {
      wg_commit();
      block_fence(95);
      scale(IC<X_F2>(), IC<16>());
      TS3(5)
      wg_fence();
    }
#pragma unroll
    for (int k = 8; k < 16; k++) mma_n64t(acc, oa[4 * k], oa[4 * k + 1], oa[4 * k + 2], oa[4 * k + 3], db + k * 128, 1);
    wg_commit();
    bar_arrive(other_turn, 256);
    wg_wait<(X_F2 < 16 ? 2 : 1)>();
    pin(oB); pin(pf);
    TS(76)
    TS3(6)
    if (signaller) mbar_arrive_cluster(empty_c);
    {
      uint32_t h0, h1;
      sum_tree(pf, false, h0, h1);
      if (inv_sums(lB0 + (bf_lo(h0) + bf_hi(h0)), lB1 + (bf_lo(h1) + bf_hi(h1)), i0, i1)) {
        bad |= 8;
        *cold = 1;
      }
    }
    bar_sync(4 + wg, 128);
    const uint32_t is_cold = *cold;
#pragma unroll
    for (int i = 16; i < 24; i++) ldsm4(ql + 5 * STAGE + (i & 7) * 2048, oa[4 * i], oa[4 * i + 1], oa[4 * i + 2], oa[4 * i + 3]);
#pragma unroll
    for (int i = 0; i < 16; i++) {
      oa[96 + 2 * i] = pack2(oB[4 * i] * i0, oB[4 * i + 1] * i0);
      oa[96 + 2 * i + 1] = pack2(oB[4 * i + 2] * i1, oB[4 * i + 3] * i1);
    }
    TS3(7)
    mbar_wait(full + 8 * 2, 0);
    TS3(8)
    wg_wait<0>();
    pin(acc); pin(oa);
    if (__any_sync(0xffffffffu, is_cold)) {
      bad = __reduce_or_sync(0xffffffffu, bad);
      if (!(bad & 8)) {
#pragma unroll
        for (int i = 24; i < 32; i++) stsm4(ql + 6 * STAGE + (i & 7) * 2048, oa[4 * i], oa[4 * i + 1], oa[4 * i + 2], oa[4 * i + 3]);
      }
#pragma unroll 1
      for (int h = 0; h < 4; h++) {
        if (bad >> h & 1) {
          const uint32_t a = ql + ((0x6354 >> (4 * h)) & 7) * STAGE;
          const size_t o = (size_t)(hs * 2 + (h >> 1)) * SEQ * DH;
          float ox[64], l0, l1;
          exact_attention(ox, l0, l1, a, kc + o, vc + o, fresh_lane());
          inv_sums(l0, l1, l0, l1);
          __syncwarp();
          park<0, 8>(a, ox, l0, l1);
        }
      }
      __syncwarp();
#pragma unroll
      for (int i = 0; i < 32; i++)
        if ((i >> 3) != 1 || (bad & 4))
          ldsm4(ql + ((0x6534 >> (4 * (i >> 3))) & 7) * STAGE + (i & 7) * 2048, oa[4 * i], oa[4 * i + 1], oa[4 * i + 2], oa[4 * i + 3]);
      pin(oa);
      asm volatile("fence.proxy.async.shared::cta;" ::: "memory");
      bar_sync(4 + wg, 128);
      if (signaller && held) mbar_arrive_cluster(empty_c + 8 * 3);
      wg_fence();
#pragma unroll
      for (int k = 0; k < 16; k++) mma_n64t(acc, oa[4 * k], oa[4 * k + 1], oa[4 * k + 2], oa[4 * k + 3], db + k * 128, k > 0);
      wg_commit();
      wg_wait<0>();
      pin(acc);
    }
    if (signaller) mbar_arrive_cluster(empty_c + 8 * 1);
  }

  prof(wg, 10);
  TS3(9)
  {
    lane = fresh_lane();
    const int tw = (cw & 3) * 32 + lane;
    float red[32];
#pragma unroll
    for (int i = 0; i < 32; i++) red[i] = 0.f;
    uint32_t tag = 0;
    uint4* const xch = g_part + (size_t)(qb * 64 * 2 + wg) * 4 * 128 + tw;
    int nrx = 1;
    auto region = [](int s, int h) { return (2 * s + h + 1) & 3; };
    auto half_step = [&](int s, auto hc, bool arrive) {
      constexpr int h = decltype(hc)::value;
      const uint64_t db = mkdesc(ring + region(s, h) * STAGE, 16);
      bar_sync(my_turn, 256);
      pin(oa);
      wg_fence();
#pragma unroll
      for (int k = 0; k < 16; k++) {
        const int kb = h * 16 + k;
        mma_n64t(acc, oa[4 * kb], oa[4 * kb + 1], oa[4 * kb + 2], oa[4 * kb + 3], db + k * 128, kb > 0);
      }
      wg_commit();
      if (arrive) bar_arrive(other_turn, 256);
    };
    auto await = [&](int s, int h) { mbar_wait(full + 8 * region(s, h), ((s >> 1) ^ s) & 1); };
    auto fetch = [&](uint32_t (&g)[16], int n) {
      const uint4* p = xch + (hs * 7 + n - 1) * (2 * 4 * 128);
#pragma unroll
      for (int i = 0; i < 4; i++) ld_gran(p + i * 128, g[4 * i], g[4 * i + 1], g[4 * i + 2], g[4 * i + 3]);
    };
    uint32_t g[16];
#pragma unroll 1
    for (int s = 0; s < 8; s++) {
      const bool pend = nrx < s - 1;
      if (pend) fetch(g, nrx);
      half_step(s, IC<1>(), true);
      TS3(s < 3 ? 16 + 8 * s : 75)
      if (s == 0) {
        mbar_wait(cx.sb + SM_BAR_MISC, 0);
        tag = *(const volatile uint32_t*)(cx.sp + SM_TAG);
        bar_arrive(BAR_OA, 352);
      }
      await(s + 1, 0);
      TS3(s < 3 ? 17 + 8 * s : 75)
      wg_wait<0>();
      TS3(s < 3 ? 18 + 8 * s : 75)
      if (signaller && s < 7) mbar_arrive_cluster(empty_c + 8 * region(s, 1));
      pin(acc);
      TS(77 + s)
      prof(wg, 12 + s);
      uint4* p = xch + (s == 0 ? 56 + hs : ((hs + s) & 7) * 7 + s - 1) * (2 * 4 * 128);
#pragma unroll
      for (int i = 0; i < 4; i++)
        st_gran(p + i * 128, (pack2(acc[8 * i], acc[8 * i + 1]) & ~TAG) | tag, pack2(acc[8 * i + 2], acc[8 * i + 3]),
                pack2(acc[8 * i + 4], acc[8 * i + 5]), pack2(acc[8 * i + 6], acc[8 * i + 7]));
      TS3(s < 3 ? 19 + 8 * s : 75)
      half_step(s + 1, IC<0>(), true);
      TS3(s < 3 ? 20 + 8 * s : 75)
      await(s + 1, 1);
      TS3(s < 3 ? 21 + 8 * s : 75)
      if (pend && granules_ok(g, tag)) { add_granules(red, g); nrx++; }
      if (X_EARLY == 2 && s == 7) fetch(g, nrx);
      wg_wait<0>();
      TS3(s < 3 ? 22 + 8 * s : 75)
      if (signaller && s < 6) mbar_arrive_cluster(empty_c + 8 * region(s + 1, 0));
    }
    uint32_t xv[16], gt[16], g2[16];
    if (X_EARLY < 2) fetch(g, nrx);
    mbar_wait(cx.sb + SM_BAR_XG, 0);
    const bool two = nrx < 7;
    bool ok;
    {
      const uint64_t db = mkdesc(ring + 2 * STAGE, 16);
      if (X_EARLY == 2) ok = granules_ok(g, tag);
      bar_sync(my_turn, 256);
      if (X_EARLY == 2) fetch(g2, 7);
#pragma unroll
      for (int i = 64; i < 128; i++) asm volatile("" : "+r"(oa[i])::"memory");
      wg_fence();
#pragma unroll
      for (int k = 16; k < 32; k++) mma_n64t(acc, oa[4 * k], oa[4 * k + 1], oa[4 * k + 2], oa[4 * k + 3], db + (k - 16) * 128, 1);
      wg_commit();
      if (wg == 0) bar_arrive(other_turn, 256);
    }
    if (X_EARLY < 2) {
      ok = granules_ok(g, tag);
      fetch(g2, 7);
    }
    const uint32_t frag = (cw * 16 + (lane & 15)) * 144 + (lane >> 4) * 16;
#pragma unroll
    for (int i = 0; i < 4; i++) {
      ldsm4(cx.sb + SM_XO + frag + i * 32, xv[4 * i], xv[4 * i + 1], xv[4 * i + 2], xv[4 * i + 3]);
      ldsm4(cx.sb + SM_GO + frag + i * 32, gt[4 * i], gt[4 * i + 1], gt[4 * i + 2], gt[4 * i + 3]);
    }
    if (ok) { add_granules(red, g); nrx++; }
    wg_wait<0>();
    pin(acc);
    TS(85)
#pragma unroll
    for (int i = 0; i < 32; i++) red[i] += acc[i];
    pin(red);
    block_fence(90);
    int last = 8;
    if (two && granules_ok(g2, tag)) { add_granules(red, g2); last = 7; }
#pragma unroll 1
    for (int spins = 0; nrx < last && spins < (1 << 16); spins++) {
      fetch(g, nrx);
      if (granules_ok(g, tag)) { add_granules(red, g); nrx++; }
    }
    prof(wg, 20);
    TS(86)
    const uint32_t ot = ring + 3 * STAGE + cw * (16 * 144);
    uint32_t ow[16];
#pragma unroll
    for (int i = 0; i < 16; i++) ow[i] = fma2(pack2(red[2 * i], red[2 * i + 1]), gt[i], xv[i]);
#pragma unroll
    for (int i = 0; i < 4; i++)
      stsm4(ot + (lane & 15) * 144 + (2 * i + (lane >> 4)) * 16, ow[4 * i], ow[4 * i + 1], ow[4 * i + 2], ow[4 * i + 3]);
    __syncwarp();
#pragma unroll
    for (int i = 0; i < 4; i++) {
      uint4 v;
      lds128(ot + (i * 4 + (lane >> 3)) * 144 + (lane & 7) * 16, v.x, v.y, v.z, v.w);
      *(uint4*)(out + (size_t)(qb * 128 + cw * 16 + i * 4 + (lane >> 3)) * DM + hs * 64 + (lane & 7) * 8) = v;
    }
    prof(wg, 22);
    TS(87)
    TS_DUMP()
  }
}

constexpr int FST_X = 24, FST_END = FST_X + 14 * 12;
__device__ __forceinline__ void ffn_producer(const Ctx& cx, int f, const CUtensorMap* tmX, const CUtensorMap* tmG,
                                             const CUtensorMap* tmU, const CUtensorMap* tmD) {
  const uint32_t full = cx.sb + SM_FULL, empty = cx.sb + SM_EMPTY;
  int pair = -2, u = 0;
#pragma unroll 1
  for (int st = 0; st < FST_END; st++) {
    const uint32_t sl = st & 7;
    const int unit = pair * 2 + (u & 1), k = u >> 1, k3 = k >= 3 ? k - 3 : k;
    if (unit < 27) {
      mbar_wait(empty + 8 * sl, ((st >> 3) & 1) ^ 1);
      mbar_expect_tx(full + 8 * sl, FSTAGE);
      if (pair < 0) tma3d(cx.sb + sl * FSTAGE, tmX, f * 512 + ((pair + 2) * 4 + (k >= 3) * 2 + (u & 1)) * 64, k3 * 3, full + 8 * sl);
      else if (pair < 9) tma2d_stream(cx.sb + sl * FSTAGE, k < 3 ? tmG : tmU, f * 1152 + unit * 64, k3 * 192, full + 8 * sl);
      else tma2d_stream(cx.sb + sl * FSTAGE, tmD, (unit - 18) * 64, f * 1152 + k * 192, full + 8 * sl);
    }
    if (++u == 12) { u = 0; pair++; }
  }
}

__device__ __forceinline__ void ffn_consumer(const Ctx& cx, int f, int wg, int cw, int lane, const __nv_bfloat16* x,
                                             const __nv_bfloat16* w_r) {
  const int r = lane >> 2, c = lane & 3, tid = cw * 32 + lane;
  unsigned e = 0;
  if (tid == 0) {
    e = g_launch[blockIdx.x];
    g_launch[blockIdx.x] = e + 1;
    *(unsigned*)(cx.sp + SM_TAG) = e;
  }
  if (tid < 72) *(uint4*)(cx.sp + SM_H + tid * 16) = *(const uint4*)(w_r + tid * 8);
  bar_sync(3, 256);
  prof(wg, 0);
  const uint32_t full = cx.sb + SM_FULL, empty = cx.sb + SM_EMPTY;
  const bool signaller = (tid & 127) == 0;
#pragma unroll 1
  for (int b = wg; b < 8; b += 2) {
    const int row0 = f * 512 + b * 64 + (cw & 3) * 16 + r;
    const uint32_t lo = ((cw & 3) * 16 + (lane & 15)) * 128 + (((lane >> 4) ^ (lane & 7)) << 4);
    LnAcc a;
    a.clear();
#pragma unroll 1
    for (int bx = 0; bx < 9; bx++) {
      const int st = (b >> 1) * 6 + (bx / 3) * 2 + wg;
      if (bx % 3 == 0) mbar_wait(full + 8 * (st & 7), (st >> 3) & 1);
#pragma unroll
      for (int k = 0; k < 4; k++) {
        uint32_t x0, x1, x2, x3;
        ldsm4(cx.sb + (st & 7) * FSTAGE + (bx % 3) * 8192 + (lo ^ (k << 5)), x0, x1, x2, x3);
        ln_accum1(a, k & 1, x0, x1, x2, x3);
      }
    }
    prof(wg, 8 + (b >> 1) * 3);
    float mean0, rstd0, mean1, rstd1;
    ln_stats(a, lane, mean0, rstd0, mean1, rstd1);
    prof(wg, 9 + (b >> 1) * 3);
    const uint32_t mm0 = pack2(mean0, mean0), mm1 = pack2(mean1, mean1);
    float d0[4] = {0, 0, 0, 0}, d1[4] = {0, 0, 0, 0};
#pragma unroll 1
    for (int bx = 0; bx < 9; bx++) {
      const int st = (b >> 1) * 6 + (bx / 3) * 2 + wg;
#pragma unroll
      for (int k = 0; k < 4; k++) {
        uint32_t n[4];
        ldsm4(cx.sb + (st & 7) * FSTAGE + (bx % 3) * 8192 + (lo ^ (k << 5)), n[0], n[1], n[2], n[3]);
        const uint8_t* wp = cx.sp + SM_H + (bx * 4 + k) * 32 + 4 * c;
#pragma unroll
        for (int i = 0; i < 4; i++) {
          const uint32_t t = sub2(n[i], (i & 1) ? mm1 : mm0);
          const float rs = (i & 1) ? rstd1 : rstd0;
          n[i] = pack2(bf_lo(t) * rs, bf_hi(t) * rs);
        }
        if (k & 1) hmma_k16(d1, n[0], n[1], n[2], n[3], *(const uint32_t*)wp, *(const uint32_t*)(wp + 16));
        else hmma_k16(d0, n[0], n[1], n[2], n[3], *(const uint32_t*)wp, *(const uint32_t*)(wp + 16));
      }
    }
    prof(wg, 10 + (b >> 1) * 3);
    bar_sync(4 + wg, 128);
    if (signaller) {
#pragma unroll
      for (int i = 0; i < 3; i++) mbar_arrive(empty + 8 * (((b >> 1) * 6 + i * 2 + wg) & 7));
    }
    if (c == 0) {
      g_r[row0] = bfr(d0[0] + d1[0]);
      g_r[row0 + 8] = bfr(d0[2] + d1[2]);
      g_stats[row0] = make_float2(mean0, rstd0);
      g_stats[row0 + 8] = make_float2(mean1, rstd1);
    }
  }
  prof(wg, 1);
  cluster_wait();
  bar_sync(3, 256);
  e = *(const unsigned*)(cx.sp + SM_TAG);
  if (tid == 0) {
    atom_add_acq_rel(&g_rcnt);
#pragma unroll 1
    for (int n = 0; n < (1 << 16) && (int)(ld_acquire(&g_rcnt) - 4 * (e + 1)) < 0; n++) {}
  }
  bar_sync(3, 256);
  prof(wg, 2);
  uint32_t key[8];
#pragma unroll
  for (int i = 0; i < 8; i++) {
    const int row = i * 256 + tid;
    const uint32_t b = __float_as_uint(__ldcg(&g_r[row])) >> 16;
    key[i] = (((b & 0x8000u) ? (~b & 0xFFFFu) : (b | 0x8000u)) << 16) | (uint32_t)(0xFFFF - row);
  }
  int mysel = 0;
#pragma unroll 1
  for (int k = 0; k < TOPC; k++) {
    uint32_t m = key[0];
#pragma unroll
    for (int i = 1; i < 8; i++) m = max(m, key[i]);
    m = __reduce_max_sync(0xffffffffu, m);
    uint32_t* tk = (uint32_t*)(cx.sp + SM_TOPK) + (k & 1) * 8;
    if (lane == 0) tk[cw] = m;
    bar_sync(3, 256);
    m = __reduce_max_sync(0xffffffffu, tk[lane & 7]);
#pragma unroll
    for (int i = 0; i < 8; i++) if (key[i] == m) key[i] = 0;
    if (k == cw) mysel = 0xFFFF - (int)(m & 0xFFFF);
  }
  {
    const float2 st = __ldcg(&g_stats[mysel]);
    const uint32_t mm = pack2(st.x, st.x);
#pragma unroll 3
    for (int i = 0; i < 9; i++) {
      const uint32_t t = sub2(*(const uint32_t*)(x + (size_t)mysel * DM + i * 64 + 2 * lane), mm);
      *(uint32_t*)(cx.sp + SM_XSEL + i * 1024 + cw * 128 + (((lane >> 2) ^ cw) << 4) + (lane & 3) * 4) =
          pack2(bf_lo(t) * st.y, bf_hi(t) * st.y);
    }
    if (lane == 0) *(int*)(cx.sp + SM_IDX + 4 * cw) = mysel;
  }
  asm volatile("fence.proxy.async.shared::cta;" ::: "memory");
  bar_sync(3, 256);
  prof(wg, 3);
  auto run = [&](float (&acc)[4], int st, int n, uint32_t b) {
#pragma unroll 1
    for (int u = 0; u < n; u++, st += 2, b += 3072) {
      const uint32_t sl = st & 7;
      mbar_wait(full + 8 * sl, (st >> 3) & 1);
      wg_fence();
      const uint64_t da = mkdesc(cx.sb + sl * FSTAGE, 16), db = mkdesc(b, 16);
#pragma unroll
      for (int k = 0; k < 12; k++) mma_n8(acc, da + k * 128, db + (k >> 2) * 64 + (k & 3) * 2, u > 0 || k > 0);
      wg_commit();
      wg_wait<0>();
      if (signaller) mbar_arrive(empty + 8 * sl);
    }
    pin(acc);
  };
#pragma unroll 1
  for (int unit = wg; unit < 27; unit += 2) {
    if (unit >> 1 == 9) {
      asm volatile("fence.proxy.async.shared::cta;" ::: "memory");
      bar_sync(3, 256);
      prof(wg, 4);
    }
    const bool gu = unit < 18;
    float a0[4], a1[4];
#pragma unroll 1
    for (int m = 0; m < (gu ? 2 : 1); m++) {
      run(a1, FST_X + (unit >> 1) * 12 + m * 6 + wg, gu ? 3 : 6, cx.sb + (gu ? SM_XSEL : SM_H));
      if (m == 0) { a0[0] = a1[0]; a0[1] = a1[1]; a0[2] = a1[2]; a0[3] = a1[3]; }
    }
#pragma unroll
    for (int i = 0; i < 4; i++) {
      const int fl = (cw & 3) * 16 + r + (i >> 1) * 8, tok = 2 * c + (i & 1);
      if (gu) {
        const float h = bfr(silu_f(bfr(a0[i]))) * bfr(a1[i]);
        *(__nv_bfloat16*)(cx.sp + SM_H + unit * 1024 + tok * 128 + (((fl >> 3) ^ tok) << 4) + (fl & 7) * 2) = __float2bfloat16_rn(h);
      } else {
        g_ypart[(f * TOPC + tok) * DM + (unit - 18) * 64 + fl] = a1[i];
      }
    }
  }
  prof(wg, 5);
  bar_sync(3, 256);
  if (tid == 0) *(unsigned*)(cx.sp + SM_TOPK) = atom_add_acq_rel(&g_ycnt) == 4 * e + 3;
  bar_sync(3, 256);
  if (*(const unsigned*)(cx.sp + SM_TOPK)) {
    const int row = *(const int*)(cx.sp + SM_IDX + 4 * cw);
    const float rs = bfr(rcp(1.0f + ex2(-1.4426950408889634f * __ldcg(&g_r[row]))));
#pragma unroll 1
    for (int d = lane * 2; d < DM; d += 192) {
#pragma unroll
      for (int i = 0; i < 3; i++) {
        const float* p = g_ypart + cw * DM + d + i * 64;
        const float2 a = __ldcg((const float2*)p), b = __ldcg((const float2*)(p + TOPC * DM)),
                     e2 = __ldcg((const float2*)(p + 2 * TOPC * DM)), h = __ldcg((const float2*)(p + 3 * TOPC * DM));
        const uint32_t y = pack2((a.x + b.x) + (e2.x + h.x), (a.y + b.y) + (e2.y + h.y));
        const uint32_t u = pack2(bf_lo(y) * rs, bf_hi(y) * rs);
        *(float2*)(g_upd + cw * DM + d + i * 64) = make_float2(bf_lo(u), bf_hi(u));
      }
    }
    if (lane == 0) g_idx[cw] = row;
    bar_sync(3, 256);
    if (tid == 0) st_release(&g_ffn_flag, e + 1);
    prof(wg, 6);
  }
}

struct KvMaps { CUtensorMap m[4]; };
__global__ void __cluster_dims__(2, 1, 1) __launch_bounds__(THREADS, 1)
fused_kernel(const __grid_constant__ KvMaps tmKV,
             const __grid_constant__ CUtensorMap tmWq, const __grid_constant__ CUtensorMap tmWo,
             const __grid_constant__ CUtensorMap tmG, const __grid_constant__ CUtensorMap tmU,
             const __grid_constant__ CUtensorMap tmD, const __grid_constant__ CUtensorMap tmX, const __nv_bfloat16* __restrict__ x,
             const __nv_bfloat16* __restrict__ w_r, const __nv_bfloat16* __restrict__ kc,
             const __nv_bfloat16* __restrict__ vc, __nv_bfloat16* __restrict__ out) {
  extern __shared__ __align__(1024) uint8_t smem_raw[];
  prof(0, 23, 511);
  Ctx cx;
  cx.sb = smem_u32(smem_raw);
  cx.sp = smem_raw;
  cx.rank = blockIdx.x & 1;
  const int warp = __shfl_sync(0xffffffffu, threadIdx.x >> 5, 0);
  const int cluster = blockIdx.x >> 1;
  const bool is_ffn = blockIdx.x >= N_ATT_CTA;
  const int hs = cluster < 4 ? 4 + cluster : cluster < 36 ? (cluster - 4) >> 3 : 4 + (cluster - 36) / 7;
  const int qb = (cluster < 4 ? 0 : cluster < 36 ? (cluster - 4) & 7 : 1 + (cluster - 36) % 7) * 2 + cx.rank;

  if (warp == 0 && elect_one()) {
    if (!is_ffn) {
#pragma unroll
      for (int i = 0; i < 6; i++) mbar_init(cx.sb + SM_XFULL + 8 * i, 1);
      asm volatile("fence.proxy.async.shared::cta;" ::: "memory");
#pragma unroll
      for (int i = 0; i < 6; i++) {
        mbar_expect_tx(cx.sb + SM_XFULL + 8 * i, 24576);
        tma3d(cx.sb + SM_X + i * 24576, &tmX, qb * 128 + (i / 3) * 64, (i % 3) * 3, cx.sb + SM_XFULL + 8 * i);
      }
    }
#pragma unroll
    for (int i = 0; i < 8; i++) {
      mbar_init(cx.sb + SM_FULL + 8 * i, 1);
      mbar_init(cx.sb + SM_EMPTY + 8 * i, is_ffn ? 1 : 4);
    }
    mbar_init(cx.sb + SM_BAR_MISC, 1);
    mbar_init(cx.sb + SM_BAR_XG, 64);
    *(uint2*)(cx.sp + SM_COLD) = make_uint2(0, 0);
    asm volatile("fence.mbarrier_init.release.cluster;" ::: "memory");
  } else if (warp == 1 && elect_one()) {
    if (is_ffn) { prefetch_tmap(&tmX); prefetch_tmap(&tmG); prefetch_tmap(&tmU); prefetch_tmap(&tmD); }
    else { prefetch_tmap(&tmWq); prefetch_tmap(&tmKV.m[2]); prefetch_tmap(&tmKV.m[3]); prefetch_tmap(&tmWo); }
  }
  __syncthreads();
  cluster_arrive();

  if (warp < 4) {
    asm volatile("setmaxnreg.dec.sync.aligned.u32 24;");
    cluster_wait();
    prof(0, 24, 511);
    if (warp == 0) {
      if (elect_one()) {
        if (is_ffn) ffn_producer(cx, blockIdx.x - N_ATT_CTA, &tmX, &tmG, &tmU, &tmD);
        else attn_producer(cx, qb, hs, tmKV.m, &tmWq, &tmWo);
        prof(0, 25, 511);
      }
    } else if (!is_ffn) {
      attn_gate(cx, qb, hs, threadIdx.x - 32, x);
      if (warp == 1) attn_helper(cx, qb, hs, read_lane(), x);
      else { bar_arrive(BAR_HELPER, 128); attn_stage_xg(cx, qb, hs, threadIdx.x - 64, x); }
      attn_finish8(cx, qb, hs, warp - 1, read_lane(), out);

    }
    __syncwarp();
    cluster_arrive();
    cluster_wait();
  } else {
    asm volatile("setmaxnreg.inc.sync.aligned.u32 240;");
    const int cw = warp - 4, wg = cw >> 2;
    if (is_ffn) ffn_consumer(cx, blockIdx.x - N_ATT_CTA, wg, cw, read_lane(), x, w_r);
    else attn_consumer(cx, qb, hs, wg, cw, read_lane(), x, kc, vc, out);
  }
}

typedef CUresult (*EncodeFn)(CUtensorMap*, CUtensorMapDataType, cuuint32_t, void*, const cuuint64_t*, const cuuint64_t*,
                             const cuuint32_t*, const cuuint32_t*, CUtensorMapInterleave, CUtensorMapSwizzle,
                             CUtensorMapL2promotion, CUtensorMapFloatOOBfill);

void encode(EncodeFn fn, CUtensorMap* m, const void* p, int rank, const cuuint64_t* dims, const cuuint64_t* strides,
            const cuuint32_t* box) {
  const cuuint32_t es[5] = {1, 1, 1, 1, 1};
  fn(m, CU_TENSOR_MAP_DATA_TYPE_BFLOAT16, rank, const_cast<void*>(p), dims, strides, box, es, CU_TENSOR_MAP_INTERLEAVE_NONE,
     CU_TENSOR_MAP_SWIZZLE_128B, CU_TENSOR_MAP_L2_PROMOTION_L2_128B, CU_TENSOR_MAP_FLOAT_OOB_FILL_NONE);
}
void encode2d(EncodeFn fn, CUtensorMap* m, const void* p, uint64_t rows, uint64_t cols, uint32_t box_rows) {
  const cuuint64_t dims[2] = {cols, rows}, strides[1] = {cols * 2};
  const cuuint32_t box[2] = {64, box_rows};
  encode(fn, m, p, 2, dims, strides, box);
}

}

extern "C" void kernel_launch(void* const* d_in, const int* in_sizes, int n_in, void* d_out, int out_size) {
  (void)in_sizes; (void)n_in; (void)out_size;
  void* fnp = nullptr;
  cudaDriverEntryPointQueryResult qr;
  cudaGetDriverEntryPoint("cuTensorMapEncodeTiled", &fnp, cudaEnableDefault, &qr);
  EncodeFn fn = (EncodeFn)fnp;
  CUtensorMap tmWq, tmWo, tmG, tmU, tmD, tmX;
  KvMaps tmKV;
  for (int i = 0; i < 4; i++) encode2d(fn, &tmKV.m[i], d_in[1 + (i & 1)], 16 * SEQ, DH, i < 2 ? 112 : 96);
  encode2d(fn, &tmWq, d_in[3], DM, 4096, 64);
  {
    const cuuint64_t dims[3] = {64, SEQ, 9}, strides[2] = {DM * 2, 128};
    const cuuint32_t box[3] = {64, 64, 3};
    encode(fn, &tmX, d_in[0], 3, dims, strides, box);
  }
  encode2d(fn, &tmWo, d_in[4], 4096, DM, 128);
  encode2d(fn, &tmG, d_in[7], DM, FF, 192);
  encode2d(fn, &tmU, d_in[8], DM, FF, 192);
  encode2d(fn, &tmD, d_in[9], FF, DM, 192);
  cudaFuncSetAttribute(fused_kernel, cudaFuncAttributeMaxDynamicSharedMemorySize, SM_TOTAL);
  fused_kernel<<<N_CTA, THREADS, SM_TOTAL>>>(tmKV, tmWq, tmWo, tmG, tmU, tmD, tmX, (const __nv_bfloat16*)d_in[0],
                                            (const __nv_bfloat16*)d_in[6], (const __nv_bfloat16*)d_in[1],
                                            (const __nv_bfloat16*)d_in[2], (__nv_bfloat16*)d_out);
}
```

```cpp
#include <cuda_runtime.h>
#include <cuda_bf16.h>
#include <cuda.h>
#include <stdint.h>

namespace {

constexpr int SEQ = 2048, DM = 576, DH = 128, FF = 4608, TOPC = 8;
constexpr int N_ATT_CTA = 128, N_CTA = 132;
constexpr int THREADS = 384;

constexpr uint32_t SM_RING = 0;
constexpr uint32_t STAGE = 32768;
constexpr uint32_t SM_SLOT = 131072;
constexpr uint32_t FSTAGE = 24576;
constexpr uint32_t SM_XSEL = 196608;
constexpr uint32_t SM_H = 205824;
constexpr uint32_t SM_MISC = 229376;
constexpr uint32_t SM_FULL = SM_MISC, SM_EMPTY = SM_MISC + 64, SM_BAR_MISC = SM_MISC + 128,
                   SM_COLD = SM_MISC + 136, SM_TAG = SM_MISC + 144, SM_IDX = SM_MISC + 160,
                   SM_TOPK = SM_MISC + 192, SM_XFULL = SM_MISC + 256, SM_BAR_XG = SM_MISC + 304, SM_STATS = SM_MISC + 320;
constexpr uint32_t SM_TOTAL = SM_MISC + 1344;
constexpr uint32_t SM_X = SM_MISC - 147456;

constexpr int BAR_GATE = 6, BAR_HELPER = 7, BAR_OA = 8;
constexpr int NST_Q = 20, NST_KV = 76, NST_O = 18;
__device__ __forceinline__ bool blk_big(int j) { return (unsigned)(j - 5) < 28; }
__device__ __forceinline__ int blk_row(int j) { return 112 * j - 16 * (min(j, 5) + max(j - 33, 0)); }
constexpr float SM_SCALE_LOG2 = 0.08838834764831845f * 1.4426950408889634f;

__device__ __align__(1024) uint4 g_part[16 * 64 * 2 * 4 * 128];
__device__ __align__(1024) uint4 g_gate[SEQ * DM / 8];
__device__ __align__(128) float g_r[SEQ];
__device__ __align__(128) float2 g_stats[SEQ];
__device__ __align__(128) float g_ypart[4 * TOPC * DM];
__device__ __align__(128) float g_upd[TOPC * DM];
__device__ __align__(128) int g_idx[TOPC];
__device__ __align__(128) unsigned g_launch[N_CTA];
__device__ unsigned g_rcnt, g_ycnt, g_ffn_flag;

__device__ __forceinline__ void prof(int, int, int = 0) {}

#define TS(id) {}
#define TS_DUMP() {}
#define TS4(k) {}
#define TS1(id) TS(id)
#define TS2(k) {}
#define TS3(k) {}

__device__ __forceinline__ uint32_t smem_u32(const void* p) { return (uint32_t)__cvta_generic_to_shared(p); }
__device__ __forceinline__ void mbar_init(uint32_t bar, uint32_t cnt) {
  asm volatile("mbarrier.init.shared::cta.b64 [%0], %1;" ::"r"(bar), "r"(cnt) : "memory");
}
__device__ __forceinline__ void mbar_expect_tx(uint32_t bar, uint32_t bytes) {
  asm volatile("mbarrier.arrive.expect_tx.shared::cta.b64 _, [%0], %1;" ::"r"(bar), "r"(bytes) : "memory");
}
__device__ __forceinline__ void mbar_arrive(uint32_t bar) {
  asm volatile("mbarrier.arrive.shared::cta.b64 _, [%0];" ::"r"(bar) : "memory");
}
__device__ __forceinline__ void mbar_arrive_cluster(uint32_t bar_cluster_addr) {
  asm volatile("mbarrier.arrive.shared::cluster.b64 _, [%0];" ::"r"(bar_cluster_addr) : "memory");
}
template <int ID>
__device__ __forceinline__ void mbar_arrive_cluster_now(uint32_t bar_cluster_addr, bool pred) {
  asm volatile("{\n.reg .pred p, q;\nsetp.ne.u32 p, %1, 0;\nsetp.eq.u32 q, %2, %3;\n"
               "ARR_LOOP:\n@p mbarrier.arrive.shared::cluster.b64 _, [%0];\n@q bra.uni ARR_LOOP;\n}"
               ::"r"(bar_cluster_addr), "r"((uint32_t)pred), "r"(blockIdx.y), "n"(ID) : "memory");
}
__device__ __forceinline__ void block_fence(int id) {
  asm volatile("{\n.reg .pred q;\nsetp.eq.u32 q, %0, %1;\nBF_LOOP:\n@q st.volatile.shared.u32 [%0], %0;\n@q bra.uni BF_LOOP;\n}"
               ::"r"(blockIdx.y), "r"(id) : "memory");
}
__device__ __forceinline__ void mbar_wait(uint32_t bar, uint32_t parity) {
  asm volatile("{\n.reg .pred p, q;\n.reg .u32 n;\nmov.u32 n, 0;\n"
               "WAIT_LOOP:\nmbarrier.try_wait.parity.shared::cta.b64 p, [%0], %1;\n"
               "add.u32 n, n, 1;\nsetp.lt.u32 q, n, 4194304;\nand.pred q, q, !p;\n@q bra WAIT_LOOP;\n}"
               ::"r"(bar), "r"(parity) : "memory");
}
__device__ __forceinline__ uint32_t mapa(uint32_t addr, uint32_t rank) {
  uint32_t r;
  asm volatile("mapa.shared::cluster.u32 %0, %1, %2;" : "=r"(r) : "r"(addr), "r"(rank));
  return r;
}
__device__ __forceinline__ void cluster_arrive() { asm volatile("barrier.cluster.arrive.relaxed.aligned;" ::: "memory"); }
__device__ __forceinline__ bool elect_one() {
  uint32_t p;
  asm volatile("{\n.reg .pred p;\nelect.sync _|p, 0xffffffff;\nselp.u32 %0, 1, 0, p;\n}" : "=r"(p));
  return p;
}
__device__ __forceinline__ int read_lane() { return threadIdx.x & 31; }
__device__ __forceinline__ void cluster_wait() { asm volatile("barrier.cluster.wait.acquire.aligned;" ::: "memory"); }
__device__ __forceinline__ void bar_sync(int id, int n) { asm volatile("barrier.cta.sync %0, %1;" ::"r"(id), "r"(n) : "memory"); }
__device__ __forceinline__ void bar_arrive(int id, int n) { asm volatile("barrier.cta.arrive %0, %1;" ::"r"(id), "r"(n) : "memory"); }

__device__ __forceinline__ uint64_t policy_evict_first() {
  uint64_t p;
  asm("createpolicy.fractional.L2::evict_first.b64 %0, 1.0;" : "=l"(p));
  return p;
}
__device__ __forceinline__ void tma2d_mc(uint32_t dst, const CUtensorMap* tm, int c0, int c1, uint32_t bar, uint64_t pol) {
  asm volatile("cp.async.bulk.tensor.2d.shared::cluster.global.mbarrier::complete_tx::bytes.multicast::cluster.L2::cache_hint"
               " [%0], [%1, {%2, %3}], [%4], %5, %6;"
               ::"r"(dst), "l"(tm), "r"(c0), "r"(c1), "r"(bar), "h"((uint16_t)3), "l"(pol) : "memory");
}
__device__ __forceinline__ void tma3d(uint32_t dst, const CUtensorMap* tm, int c1, int c2, uint32_t bar) {
  asm volatile("cp.async.bulk.tensor.3d.shared::cluster.global.mbarrier::complete_tx::bytes [%0], [%1, {%2, %3, %4}], [%5];"
               ::"r"(dst), "l"(tm), "r"(0), "r"(c1), "r"(c2), "r"(bar) : "memory");
}
__device__ __forceinline__ void tma2d_stream(uint32_t dst, const CUtensorMap* tm, int c0, int c1, uint32_t bar) {
  asm volatile("{\n.reg .b64 pol;\ncreatepolicy.fractional.L2::evict_first.b64 pol, 1.0;\n"
               "cp.async.bulk.tensor.2d.shared::cluster.global.mbarrier::complete_tx::bytes.L2::cache_hint [%0], [%1, {%2, %3}], [%4], pol;\n}"
               ::"r"(dst), "l"(tm), "r"(c0), "r"(c1), "r"(bar) : "memory");
}
__device__ __forceinline__ void tma2d_prefetch(const CUtensorMap* tm, int c0, int c1) {
  asm volatile("cp.async.bulk.prefetch.tensor.2d.L2.global [%0, {%1, %2}];" ::"l"(tm), "r"(c0), "r"(c1) : "memory");
}
__device__ __forceinline__ void prefetch_tmap(const CUtensorMap* tm) {
  asm volatile("prefetch.tensormap [%0];" ::"l"(tm) : "memory");
}

__device__ __forceinline__ void wg_fence() { asm volatile("wgmma.fence.sync.aligned;" ::: "memory"); }
__device__ __forceinline__ void wg_commit() { asm volatile("wgmma.commit_group.sync.aligned;" ::: "memory"); }
template <int N> __device__ __forceinline__ void wg_wait() { asm volatile("wgmma.wait_group.sync.aligned %0;" ::"n"(N) : "memory"); }

__device__ __forceinline__ uint64_t mkdesc(uint32_t addr, uint32_t lbo_bytes) {
  return (uint64_t)(((addr & 0x3FFFF) >> 4) | ((lbo_bytes >> 4) << 16)) | ((uint64_t)0x40000040u << 32);
}
__device__ __forceinline__ uint64_t mkdesc_q(uint32_t addr) {
  return (uint64_t)(((addr & 0x3FFFF) >> 4) | (64u << 16)) | ((uint64_t)8 << 32);
}
template <int N> __device__ __forceinline__ void pin(float (&a)[N]) {
#pragma unroll
  for (int i = 0; i < N; i++) asm volatile("" : "+f"(a[i])::"memory");
}
template <int N> __device__ __forceinline__ void kill(float (&a)[N]) {
#pragma unroll
  for (int i = 0; i < N; i++) asm volatile("" : "=f"(a[i]));
}
template <int N> __device__ __forceinline__ void pin(uint32_t (&a)[N]) {
#pragma unroll
  for (int i = 0; i < N; i++) asm volatile("" : "+r"(a[i])::"memory");
}

#define F8(d, o) "+f"(d[o]), "+f"(d[o + 1]), "+f"(d[o + 2]), "+f"(d[o + 3]), "+f"(d[o + 4]), "+f"(d[o + 5]), "+f"(d[o + 6]), "+f"(d[o + 7])
#define R32A "%0, %1, %2, %3, %4, %5, %6, %7, %8, %9, %10, %11, %12, %13, %14, %15, %16, %17, %18, %19, %20, %21, %22, %23, %24, %25, %26, %27, %28, %29, %30, %31"
#define R32B "%32, %33, %34, %35, %36, %37, %38, %39, %40, %41, %42, %43, %44, %45, %46, %47, %48, %49, %50, %51, %52, %53, %54, %55, %56, %57, %58, %59, %60, %61, %62, %63"

template <int TB>
__device__ __forceinline__ void mma_n128(float (&d)[64], uint32_t a0, uint32_t a1, uint32_t a2, uint32_t a3, uint64_t db, int acc) {
  asm volatile("{\n.reg .pred p;\nsetp.ne.b32 p, %69, 0;\n"
               "wgmma.mma_async.sync.aligned.m64n128k16.f32.bf16.bf16 {" R32A ", " R32B "}, {%64, %65, %66, %67}, %68, p, 1, 1, %70;\n}\n"
               : F8(d, 0), F8(d, 8), F8(d, 16), F8(d, 24), F8(d, 32), F8(d, 40), F8(d, 48), F8(d, 56)
               : "r"(a0), "r"(a1), "r"(a2), "r"(a3), "l"(db), "r"(acc), "n"(TB));
}
#define PV1(a0, a1, a2, a3, ob, acc) "add.s64 b, %92, " #ob ";\n" \
  "wgmma.mma_async.sync.aligned.m64n128k16.f32.bf16.bf16 {" R32A ", " R32B "}, {%" #a0 ", %" #a1 ", %" #a2 ", %" #a3 "}, b, " #acc ", 1, 1, 1;\n"
#define PV6 "wgmma.fence.sync.aligned;\n" PV1(64, 65, 66, 67, 0, p) PV1(68, 69, 70, 71, 128, 1) PV1(72, 73, 74, 75, 256, 1) \
  PV1(76, 77, 78, 79, 384, 1) PV1(80, 81, 82, 83, 512, 1) PV1(84, 85, 86, 87, 640, 1)
#define U4(a, o) "r"(a[o]), "r"(a[o + 1]), "r"(a[o + 2]), "r"(a[o + 3])
__device__ __forceinline__ void mma_pv(float (&d)[64], const uint32_t (&a)[28], uint64_t dv, bool acc, bool big) {
  asm volatile("{\n.reg .pred p, q;\n.reg .b64 b;\nsetp.ne.b32 p, %93, 0;\nsetp.eq.b32 q, %94, 0;\n@q bra.uni PV_SMALL;\n"
               PV6 PV1(88, 89, 90, 91, 768, 1) "wgmma.commit_group.sync.aligned;\nbra.uni PV_DONE;\n"
               "PV_SMALL:\n" PV6 "wgmma.commit_group.sync.aligned;\nPV_DONE:\n}\n"
               : F8(d, 0), F8(d, 8), F8(d, 16), F8(d, 24), F8(d, 32), F8(d, 40), F8(d, 48), F8(d, 56)
               : U4(a, 0), U4(a, 4), U4(a, 8), U4(a, 12), U4(a, 16), U4(a, 20), U4(a, 24), "l"(dv), "r"((int)acc), "r"((int)big) : "memory");
}
#define R48 R32A ", %32, %33, %34, %35, %36, %37, %38, %39, %40, %41, %42, %43, %44, %45, %46, %47"
#define R56 R48 ", %48, %49, %50, %51, %52, %53, %54, %55"
#define QK1(N, R, A, B, oa, ob, acc) "add.s64 a, " A ", " #oa ";\nadd.s64 b, " B ", " #ob ";\n" \
  "wgmma.mma_async.sync.aligned.m64n" #N "k16.f32.bf16.bf16 {" R "}, a, b, " #acc ", 1, 1, 0, 0;\n"
#define QK8(N, R, A, B) "{\n.reg .b64 a, b;\nwgmma.fence.sync.aligned;\n" QK1(N, R, A, B, 0, 0, 0) QK1(N, R, A, B, 128, 2, 1) \
  QK1(N, R, A, B, 256, 4, 1) QK1(N, R, A, B, 384, 6, 1) QK1(N, R, A, B, 512, 1024, 1) QK1(N, R, A, B, 640, 1026, 1) \
  QK1(N, R, A, B, 768, 1028, 1) QK1(N, R, A, B, 896, 1030, 1) "wgmma.commit_group.sync.aligned;\n}\n"
#define O8(d, o) "=f"(d[o]), "=f"(d[o + 1]), "=f"(d[o + 2]), "=f"(d[o + 3]), "=f"(d[o + 4]), "=f"(d[o + 5]), "=f"(d[o + 6]), "=f"(d[o + 7])
__device__ __forceinline__ void mma_qk(float (&d)[56], uint64_t dq, uint64_t dk) {
  asm volatile(QK8(112, R56, "%56", "%57")
               : O8(d, 0), O8(d, 8), O8(d, 16), O8(d, 24), O8(d, 32), O8(d, 40), O8(d, 48) : "l"(dq), "l"(dk) : "memory");
}
__device__ __forceinline__ void mma_qk(float (&d)[48], uint64_t dq, uint64_t dk) {
  asm volatile(QK8(96, R48, "%48", "%49")
               : O8(d, 0), O8(d, 8), O8(d, 16), O8(d, 24), O8(d, 32), O8(d, 40) : "l"(dq), "l"(dk) : "memory");
}
__device__ __forceinline__ void mma_n64t(float (&d)[32], uint32_t a0, uint32_t a1, uint32_t a2, uint32_t a3, uint64_t db, int acc) {
  asm volatile("{\n.reg .pred p;\nsetp.ne.b32 p, %37, 0;\n"
               "wgmma.mma_async.sync.aligned.m64n64k16.f32.bf16.bf16 {" R32A "}, {%32, %33, %34, %35}, %36, p, 1, 1, 1;\n}\n"
               : F8(d, 0), F8(d, 8), F8(d, 16), F8(d, 24)
               : "r"(a0), "r"(a1), "r"(a2), "r"(a3), "l"(db), "r"(acc));
}
__device__ __forceinline__ void mma_n8(float (&d)[4], uint64_t da, uint64_t db, int acc) {
  asm volatile("{\n.reg .pred p;\nsetp.ne.b32 p, %6, 0;\n"
               "wgmma.mma_async.sync.aligned.m64n8k16.f32.bf16.bf16 {%0, %1, %2, %3}, %4, %5, p, 1, 1, 1, 0;\n}\n"
               : "+f"(d[0]), "+f"(d[1]), "+f"(d[2]), "+f"(d[3])
               : "l"(da), "l"(db), "r"(acc));
}
__device__ __forceinline__ void hmma_k8(float (&d)[4], uint32_t a0, uint32_t a1, uint32_t b0) {
  asm volatile("mma.sync.aligned.m16n8k8.row.col.f32.bf16.bf16.f32 {%0, %1, %2, %3}, {%4, %5}, {%6}, {%0, %1, %2, %3};"
               : "+f"(d[0]), "+f"(d[1]), "+f"(d[2]), "+f"(d[3]) : "r"(a0), "r"(a1), "r"(b0));
}
__device__ __forceinline__ void hmma_k16(float (&d)[4], uint32_t a0, uint32_t a1, uint32_t a2, uint32_t a3, uint32_t b0, uint32_t b1) {
  asm volatile("mma.sync.aligned.m16n8k16.row.col.f32.bf16.bf16.f32 {%0, %1, %2, %3}, {%4, %5, %6, %7}, {%8, %9}, {%0, %1, %2, %3};"
               : "+f"(d[0]), "+f"(d[1]), "+f"(d[2]), "+f"(d[3]) : "r"(a0), "r"(a1), "r"(a2), "r"(a3), "r"(b0), "r"(b1));
}

__device__ __forceinline__ uint32_t pack2(float lo, float hi) {
  uint32_t r;
  asm("cvt.rn.bf16x2.f32 %0, %1, %2;" : "=r"(r) : "f"(hi), "f"(lo));
  return r;
}
__device__ __forceinline__ float bf_lo(uint32_t w) { return __uint_as_float(w << 16); }
__device__ __forceinline__ float bf_hi(uint32_t w) { return __uint_as_float(w & 0xFFFF0000u); }
__device__ __forceinline__ float bfr(float x) { return __bfloat162float(__float2bfloat16_rn(x)); }
__device__ __forceinline__ uint32_t sub2(uint32_t a, uint32_t b) {
  uint32_t r;
  asm("sub.rn.bf16x2 %0, %1, %2;" : "=r"(r) : "r"(a), "r"(b));
  return r;
}
__device__ __forceinline__ uint32_t add2(uint32_t a, uint32_t b) {
  uint32_t r;
  asm("add.rn.bf16x2 %0, %1, %2;" : "=r"(r) : "r"(a), "r"(b));
  return r;
}
__device__ __forceinline__ uint32_t fma2(uint32_t a, uint32_t b, uint32_t c) {
  uint32_t r;
  asm("fma.rn.bf16x2 %0, %1, %2, %3;" : "=r"(r) : "r"(a), "r"(b), "r"(c));
  return r;
}
__device__ __forceinline__ float ex2(float x) {
  float r;
  asm("ex2.approx.ftz.f32 %0, %1;" : "=f"(r) : "f"(x));
  return r;
}
__device__ __forceinline__ float rcp(float x) {
  float r;
  asm("rcp.approx.ftz.f32 %0, %1;" : "=f"(r) : "f"(x));
  return r;
}
__device__ __forceinline__ float silu_f(float t) { return t * rcp(1.0f + ex2(-1.4426950408889634f * t)); }
__device__ __forceinline__ void lds128(uint32_t a, uint32_t& x, uint32_t& y, uint32_t& z, uint32_t& w) {
  asm volatile("ld.shared.v4.u32 {%0, %1, %2, %3}, [%4];" : "=r"(x), "=r"(y), "=r"(z), "=r"(w) : "r"(a) : "memory");
}
__device__ __forceinline__ void ldsm4(uint32_t a, uint32_t& x, uint32_t& y, uint32_t& z, uint32_t& w) {
  asm volatile("ldmatrix.sync.aligned.m8n8.x4.shared.b16 {%0, %1, %2, %3}, [%4];" : "=r"(x), "=r"(y), "=r"(z), "=r"(w) : "r"(a) : "memory");
}
constexpr uint32_t TAG = 0x10000;
__device__ __forceinline__ void st_gran(uint4* p, uint32_t x, uint32_t y, uint32_t z, uint32_t w) {
  asm volatile("st.relaxed.gpu.global.v4.b32 [%0], {%1, %2, %3, %4};" ::"l"(p), "r"(x), "r"(y), "r"(z), "r"(w) : "memory");
}
__device__ __forceinline__ void ld_gran(const uint4* p, uint32_t& x, uint32_t& y, uint32_t& z, uint32_t& w) {
  asm volatile("ld.relaxed.gpu.global.v4.b32 {%0, %1, %2, %3}, [%4];" : "=r"(x), "=r"(y), "=r"(z), "=r"(w) : "l"(p) : "memory");
}
__device__ __forceinline__ void stsm4(uint32_t a, uint32_t x, uint32_t y, uint32_t z, uint32_t w) {
  asm volatile("stmatrix.sync.aligned.m8n8.x4.shared.b16 [%0], {%1, %2, %3, %4};" ::"r"(a), "r"(x), "r"(y), "r"(z), "r"(w) : "memory");
}
__device__ __forceinline__ void cp16(uint32_t dst, const void* src) {
  asm volatile("cp.async.cg.shared.global [%0], [%1], 16;" ::"r"(dst), "l"(src) : "memory");
}
__device__ __forceinline__ void cp_wait_all() { asm volatile("cp.async.wait_all;" ::: "memory"); }
__device__ __forceinline__ void add_granules(float (&red)[32], const uint32_t (&g)[16]) {
#pragma unroll
  for (int i = 0; i < 16; i++) { red[2 * i] += bf_lo(g[i]); red[2 * i + 1] += bf_hi((i & 3) ? g[i] : g[i] & ~TAG); }
}
__device__ __forceinline__ bool granules_ok(const uint32_t (&g)[16], uint32_t tag) {
  uint32_t a, b;
  asm("lop3.b32 %0, %1, %2, %3, 0x7E;" : "=r"(a) : "r"(g[0]), "r"(g[4]), "r"(tag));
  asm("lop3.b32 %0, %1, %2, %3, 0x7E;" : "=r"(b) : "r"(g[8]), "r"(g[12]), "r"(tag));
  return __all_sync(0xffffffffu, ((a | b) & TAG) == 0);
}
__device__ __forceinline__ unsigned ld_acquire(const unsigned* p) {
  unsigned v;
  asm volatile("ld.acquire.gpu.global.u32 %0, [%1];" : "=r"(v) : "l"(p) : "memory");
  return v;
}
__device__ __forceinline__ unsigned atom_add_acq_rel(unsigned* p) {
  unsigned v;
  asm volatile("atom.acq_rel.gpu.global.add.u32 %0, [%1], 1;" : "=r"(v) : "l"(p) : "memory");
  return v;
}
__device__ __forceinline__ void st_release(unsigned* p, unsigned v) {
  asm volatile("st.release.gpu.global.u32 [%0], %1;" ::"l"(p), "r"(v) : "memory");
}

struct LnAcc {
  float sm[2][4], sq[8][4];
  __device__ __forceinline__ void clear() {
#pragma unroll
    for (int i = 0; i < 4; i++) {
      sm[0][i] = sm[1][i] = 0.f;
#pragma unroll
      for (int j = 0; j < 8; j++) sq[j][i] = 0.f;
    }
  }
};
template <int K0, int K1>
__device__ __forceinline__ void ln_fetch(uint32_t (&xa)[144], uint32_t boxes, uint32_t lo) {
#pragma unroll
  for (int k = K0; k < K1; k++) ldsm4(boxes + (k >> 2) * 8192 + (lo ^ ((k & 3) << 5)), xa[4 * k], xa[4 * k + 1], xa[4 * k + 2], xa[4 * k + 3]);
}
__device__ __forceinline__ void ln_accum1(LnAcc& a, int h, uint32_t x0, uint32_t x1, uint32_t x2, uint32_t x3) {
  const uint32_t ONES = 0x3F803F80u;
  hmma_k16(a.sm[h], x0, x1, x2, x3, ONES, ONES);
  hmma_k8(a.sq[4 * h], x0, x1, x0);
  hmma_k8(a.sq[4 * h + 1], x0, x1, x1);
  hmma_k8(a.sq[4 * h + 2], x2, x3, x2);
  hmma_k8(a.sq[4 * h + 3], x2, x3, x3);
}
template <int K0, int K1>
__device__ __forceinline__ void ln_accum(const uint32_t (&xa)[144], LnAcc& a) {
#pragma unroll
  for (int k = K0; k < K1; k++) ln_accum1(a, k & 1, xa[4 * k], xa[4 * k + 1], xa[4 * k + 2], xa[4 * k + 3]);
}
__device__ __forceinline__ void ln_row(float sum, float sq, float& mean_b, float& rstd) {
  const float mean = sum * (1.0f / DM);
  const uint32_t mv = pack2(mean, fmaxf(sq * (1.0f / DM) - mean * mean, 0.0f));
  mean_b = bf_lo(mv);
  float sd;
  asm("sqrt.approx.f32 %0, %1;" : "=f"(sd) : "f"(bf_lo(pack2(bf_hi(mv) + 1e-5f, 0.f))));
  rstd = rcp(bf_lo(pack2(sd, 0.f)));
}
__device__ __forceinline__ void ln_diag(const LnAcc& a, int lane, float& t0, float& t1) {
  const bool odd = (lane >> 2) & 1;
  t0 = odd ? (a.sq[0][1] + a.sq[2][1]) + (a.sq[4][1] + a.sq[6][1]) : (a.sq[0][0] + a.sq[2][0]) + (a.sq[4][0] + a.sq[6][0]);
  t1 = odd ? (a.sq[1][3] + a.sq[3][3]) + (a.sq[5][3] + a.sq[7][3]) : (a.sq[1][2] + a.sq[3][2]) + (a.sq[5][2] + a.sq[7][2]);
}
__device__ __forceinline__ void ln_stats(const LnAcc& a, int lane, float& mean0, float& rstd0, float& mean1, float& rstd1) {
  float t0, t1;
  ln_diag(a, lane, t0, t1);
  const int src = (lane & ~3) | (lane >> 3);
  t0 = __shfl_sync(0xffffffffu, t0, src);
  t1 = __shfl_sync(0xffffffffu, t1, src);
  ln_row(a.sm[0][0] + a.sm[1][0], t0, mean0, rstd0);
  ln_row(a.sm[0][2] + a.sm[1][2], t1, mean1, rstd1);
}

template <bool ROUTED>
__device__ __forceinline__ uint32_t gate2(uint32_t x2, float mean_b, float rstd, float2 upd = make_float2(0.f, 0.f)) {
  const uint32_t xc = sub2(x2, pack2(mean_b, mean_b));
  uint32_t t = pack2(bf_lo(xc) * rstd, bf_hi(xc) * rstd);
  if (ROUTED) t = pack2(bf_lo(t) + upd.x, bf_hi(t) + upd.y);
  return pack2(silu_f(bf_lo(t)), silu_f(bf_hi(t)));
}

#define PF_D 4
#define X_SPLIT 38
#define X_SPLITA 36
#define X_SPLITS 32
#define X_SPLITSA 30
#define X_PA 8
#define X_PG 2
#define X_E0 10
#define X_F2 10
#define X_LD 0
#define X_F1 0
#define X_BF2 1
#define X_EARLY 1
template <int V> struct IC { static constexpr int value = V; };

struct Ctx {
  uint32_t sb;
  uint8_t* sp;
  uint32_t rank;
};

__device__ __forceinline__ void attn_producer(const Ctx& cx, int qb, int hs, const CUtensorMap* tmKV,
                                              const CUtensorMap* tmWq, const CUtensorMap* tmWo) {
  const uint32_t full = cx.sb + SM_FULL, empty = cx.sb + SM_EMPTY, ring = cx.sb + SM_RING + cx.rank * 16384;
  const uint64_t last_use = policy_evict_first();
  auto acquire = [&](uint32_t r, uint32_t n, uint32_t bytes) {
    mbar_wait(empty + 8 * r, (n ^ (r >> 1) ^ 1) & 1);
    mbar_expect_tx(full + 8 * r, bytes);
  };
  int st = 0;
#pragma unroll 1
  for (int p = 0; p < 4; p++) {
    const int n0 = (hs * 4 + (p ^ (p >> 1))) * DH + cx.rank * 64;
#pragma unroll 1
    for (int i = 0; i < 5; i++, st++) {
      const uint32_t r = (st ^ ((st >> 1) & 1)) & 3;
      acquire(r, st >> 2, i == 2 ? 16384 : 32768);
      const int k0 = i < 3 ? 128 * i : 128 * i - 64;
      tma2d_mc(ring + r * STAGE, tmWq, n0, k0, full + 8 * r, last_use);
      if (i != 2) tma2d_mc(ring + r * STAGE + 8192, tmWq, n0, k0 + 64, full + 8 * r, last_use);
      if (st == 1) {
#pragma unroll 1
        for (int b = 8 + qb; b < 72; b += 16) tma2d_prefetch(tmWq, (hs * 4 + ((b / 18) ^ (b / 36))) * DH + (b & 1) * 64, ((b % 18) >> 1) * 64);
      }
      if (st == 8 && qb < 2 * PF_D) tma2d_prefetch(tmKV + ((qb >> 1) & 1), cx.rank * 64, hs * 2 * SEQ + (qb >> 2) * 96);
    }
  }
  uint32_t r = 0, n = 5;
#pragma unroll 1
  for (int u = 0; u < NST_KV; u++) {
    const bool big = blk_big(u >> 1);
    acquire(r, n, big ? 112 * 256 : 96 * 256);
    tma2d_mc(ring + r * STAGE, tmKV + (u & 1) + (big ? 0 : 2), cx.rank * 64, hs * 2 * SEQ + blk_row(u >> 1), full + 8 * r, last_use);
    if (((u ^ (qb >> 1)) & 7) == 0 && u + PF_D < NST_KV)
      tma2d_prefetch(tmKV + ((u + PF_D) & 1), cx.rank * 64, hs * 2 * SEQ + blk_row((u + PF_D) >> 1));
    if ((unsigned)(u - 32) < 36 && (u & 15) == qb) tma2d_prefetch(tmWo, ((u - 32) >> 2) * 64, hs * 512 + (u & 3) * 128);
    if (++r == 3) { r = 0; n++; }
  }
#pragma unroll 1
  for (int u = 0; u < NST_O; u++) {
    const int s = u >> 1;
    const int blk = s == 0 ? 8 : ((hs + s) & 7);
    r = (u + 1) & 3;
    acquire(r, (u >> 2) ^ (u >> 1), 32768);
    tma2d_mc(ring + r * STAGE, tmWo, blk * 64, hs * 512 + ((u & 1) + cx.rank * 2) * 128, full + 8 * r, last_use);
  }
}

__device__ __forceinline__ void attn_gate(const Ctx& cx, int qb, int hs, int t, const __nv_bfloat16* x) {
  uint4 nx = *(const uint4*)(x + (size_t)(qb * 128 + (t >> 3)) * DM + hs * 64 + (t & 7) * 8);
  bar_sync(BAR_GATE, 352);
#pragma unroll 1
  for (int ch = t; ch < 1152; ch += 96) {
    const uint4 v = nx;
    const int n = ch + 96;
    if (n < 1152) nx = *(const uint4*)(x + (size_t)(qb * 128 + (n < 1024 ? n >> 3 : hs * 16 + ((n - 1024) >> 3))) * DM + (n < 1024 ? hs * 64 : 512) + (t & 7) * 8);
    const int lr = ch < 1024 ? ch >> 3 : hs * 16 + ((ch - 1024) >> 3);
    const float2 st = *(const float2*)(cx.sp + SM_STATS + 8 * lr);
    g_gate[((qb * 128 + lr) * DM + (ch < 1024 ? hs * 64 : 512) + (t & 7) * 8) >> 3] =
        make_uint4(gate2<false>(v.x, st.x, st.y), gate2<false>(v.y, st.x, st.y), gate2<false>(v.z, st.x, st.y), gate2<false>(v.w, st.x, st.y));
  }
}

constexpr uint32_t SM_XO = SM_SLOT, SM_GO = SM_SLOT + 128 * 144;
constexpr uint32_t SM_X8 = SM_SLOT + 2 * STAGE + 20480, SM_G8 = SM_X8 + 16 * 144;
__device__ __forceinline__ void attn_stage_xg(const Ctx& cx, int qb, int hs, int t, const __nv_bfloat16* x) {
  bar_sync(BAR_OA, 352);
#pragma unroll 1
  for (int ch = t; ch < 1024; ch += 64) {
    const size_t o = (size_t)(qb * 128 + (ch >> 3)) * DM + hs * 64 + (ch & 7) * 8;
    cp16(cx.sb + SM_XO + (ch >> 3) * 144 + (ch & 7) * 16, x + o);
    cp16(cx.sb + SM_GO + (ch >> 3) * 144 + (ch & 7) * 16, (const __nv_bfloat16*)g_gate + o);
  }
  cp_wait_all();
  mbar_arrive(cx.sb + SM_BAR_XG);
}

__device__ __forceinline__ void attn_helper(const Ctx& cx, int qb, int hs, int lane, const __nv_bfloat16* x) {
  unsigned e = 0;
  if (lane == 0) {
    e = g_launch[blockIdx.x];
    g_launch[blockIdx.x] = e + 1;
  }
  e = __shfl_sync(0xffffffffu, e, 0);
  bar_sync(BAR_HELPER, 128);
#pragma unroll 1
  for (int n = 0; n < (1 << 16) && ld_acquire(&g_ffn_flag) != e + 1; n++) __nanosleep(1000);
  const uint32_t tag = (~e & 1) * TAG;
  {
#pragma unroll 1
    for (int i = 0; i < 2 * TOPC; i++) {
      const int lr = __ldcg(&g_idx[i >> 1]) - qb * 128, col = ((i & 1) ? 512 : hs * 64) + 2 * lane;
      if ((i & 1) ? (lr >> 4) == hs : (lr >> 7) == 0) {
        const float2 st = *(const float2*)(cx.sp + SM_STATS + 8 * lr);
        const int o = (qb * 128 + lr) * DM + col;
        *(uint32_t*)((__nv_bfloat16*)g_gate + o) =
            gate2<true>(*(const uint32_t*)(x + o), st.x, st.y, __ldcg((const float2*)(g_upd + (i >> 1) * DM + col)));
      }
    }
  }
  if (lane == 0) *(uint32_t*)(cx.sp + SM_TAG) = tag;
  __syncwarp();
  if (lane == 0) mbar_arrive(cx.sb + SM_BAR_MISC);

  const uint4* src = g_part + (size_t)((qb * 64 + 56) * 2 + (hs >> 2)) * 4 * 128 + (hs & 3) * 32 + lane;
  const uint32_t stg = cx.sb + SM_SLOT + 2 * STAGE + lane * 16;
  bar_sync(BAR_OA, 352);

#pragma unroll 1
  for (int i = 0; i < 4; i++) {
    const int ch = i * 32 + lane;
    const size_t o = (size_t)(qb * 128 + hs * 16 + (ch >> 3)) * DM + 512 + (ch & 7) * 8;
    cp16(cx.sb + SM_X8 + (ch >> 3) * 144 + (ch & 7) * 16, x + o);
    cp16(cx.sb + SM_G8 + (ch >> 3) * 144 + (ch & 7) * 16, (const __nv_bfloat16*)g_gate + o);
  }
#pragma unroll 1
  for (int n = 0; n < (1 << 16); n++) {
    __nanosleep(n ? 500 : 2000);
    uint32_t a, b, d, t;
    ld_gran(src - lane + (lane & 7) * (2 * 4 * 128) + 3 * 128 + 31, a, b, d, t);
    if (__all_sync(0xffffffffu, (a & TAG) == tag)) break;
  }
#pragma unroll 1
  for (int n = 0; n < (1 << 16); n++) {
#pragma unroll 1
    for (int i = 0; i < 8; i++) {
#pragma unroll
      for (int g = 0; g < 4; g++) cp16(stg + (i * 4 + g) * 512, src + i * (2 * 4 * 128) + g * 128);
    }
    cp_wait_all();
    uint32_t bad = 0;
#pragma unroll 4
    for (int i = 0; i < 32; i++) bad |= *(const volatile uint32_t*)(cx.sp + SM_SLOT + 2 * STAGE + lane * 16 + i * 512) ^ tag;
    if (__all_sync(0xffffffffu, (bad & TAG) == 0)) break;
  }

}
__device__ __forceinline__ void attn_finish8(const Ctx& cx, int qb, int hs, int hw, int lane, __nv_bfloat16* out) {
  bar_sync(BAR_GATE, 96);
#pragma unroll 1
  for (int g = hw; g < 4; g += 3) {
    float acc[8] = {0.f, 0.f, 0.f, 0.f, 0.f, 0.f, 0.f, 0.f};
#pragma unroll 2
    for (int sidx = 0; sidx < 8; sidx++) {
      uint32_t a, b, d, t;
      lds128(cx.sb + SM_SLOT + 2 * STAGE + lane * 16 + (sidx * 4 + g) * 512, a, b, d, t);
      acc[0] += bf_lo(a); acc[1] += bf_hi(a & ~TAG); acc[2] += bf_lo(b); acc[3] += bf_hi(b);
      acc[4] += bf_lo(d); acc[5] += bf_hi(d); acc[6] += bf_lo(t); acc[7] += bf_hi(t);
    }
#pragma unroll
    for (int j = 0; j < 4; j++) {
      const int o = ((lane >> 2) + (j & 1) * 8) * 144 + (2 * g + (j >> 1)) * 16 + (lane & 3) * 4;
      uint32_t* xp = (uint32_t*)(cx.sp + SM_X8 + o);
      const uint32_t xw = *xp, gw = *(const uint32_t*)(cx.sp + SM_G8 + o);
      *xp = fma2(pack2(acc[2 * j], acc[2 * j + 1]), gw, xw);
    }
  }
  bar_sync(BAR_GATE, 96);
  for (int ch = hw * 32 + lane; ch < 128; ch += 96)
    *(uint4*)(out + (size_t)(qb * 128 + hs * 16 + (ch >> 3)) * DM + 512 + (ch & 7) * 8) =
        *(const uint4*)(cx.sp + SM_X8 + (ch >> 3) * 144 + (ch & 7) * 16);
}

constexpr float SUM_HI = 1.8446744e19f, SUM_LO = 9.0949470e-13f;

template <int LO, int HI, int N>
__device__ __forceinline__ void softmax_exp(float (&s)[N]) {
#pragma unroll
  for (int i = LO; i < HI; i++) s[i] = ex2(s[i]);
}
__device__ __forceinline__ void sum_tree(const uint32_t (&pf)[28], bool big, uint32_t& h0, uint32_t& h1) {
  uint32_t t0 = add2(add2(pf[16], pf[18]), add2(pf[20], pf[22])), t1 = add2(add2(pf[17], pf[19]), add2(pf[21], pf[23]));
  if (big) { t0 = add2(t0, add2(pf[24], pf[26])); t1 = add2(t1, add2(pf[25], pf[27])); }
  h0 = add2(add2(add2(add2(pf[0], pf[2]), add2(pf[4], pf[6])), add2(add2(pf[8], pf[10]), add2(pf[12], pf[14]))), t0);
  h1 = add2(add2(add2(add2(pf[1], pf[3]), add2(pf[5], pf[7])), add2(add2(pf[9], pf[11]), add2(pf[13], pf[15]))), t1);
}
__device__ __forceinline__ void exact_attention(float (&o)[64], float& l0, float& l1, uint32_t qaddr, const __nv_bfloat16* kh,
                                                const __nv_bfloat16* vh, int lane) {
  const int off = (lane >> 2) * DH + (lane & 3) * 2;
  float m0 = -3.0e38f, m1 = -3.0e38f;
  l0 = l1 = 0.f;
#pragma unroll
  for (int i = 0; i < 64; i++) o[i] = 0.f;
#pragma unroll 1
  for (int key = 0; key < SEQ; key += 16) {
    const __nv_bfloat16 *kp = kh + key * DH + off, *vp = vh + key * DH + off;
    float d0[4] = {0.f, 0.f, 0.f, 0.f}, d1[4] = {0.f, 0.f, 0.f, 0.f};
#pragma unroll 4
    for (int k = 0; k < 8; k++) {
      uint32_t q0, q1, q2, q3;
      ldsm4(qaddr + k * 2048, q0, q1, q2, q3);
      hmma_k16(d0, q0, q1, q2, q3, *(const uint32_t*)(kp + k * 16), *(const uint32_t*)(kp + k * 16 + 8));
      hmma_k16(d1, q0, q1, q2, q3, *(const uint32_t*)(kp + 8 * DH + k * 16), *(const uint32_t*)(kp + 8 * DH + k * 16 + 8));
    }
    float x0 = fmaxf(fmaxf(d0[0], d0[1]), fmaxf(d1[0], d1[1])), x1 = fmaxf(fmaxf(d0[2], d0[3]), fmaxf(d1[2], d1[3]));
    x0 = fmaxf(x0, __shfl_xor_sync(0xffffffffu, x0, 1));
    x1 = fmaxf(x1, __shfl_xor_sync(0xffffffffu, x1, 1));
    x0 = fmaxf(fmaxf(x0, __shfl_xor_sync(0xffffffffu, x0, 2)), m0);
    x1 = fmaxf(fmaxf(x1, __shfl_xor_sync(0xffffffffu, x1, 2)), m1);
    const float sc0 = ex2(m0 - x0), sc1 = ex2(m1 - x1);
    m0 = x0; m1 = x1;
    const uint32_t p0 = pack2(ex2(d0[0] - m0), ex2(d0[1] - m0)), p1 = pack2(ex2(d0[2] - m1), ex2(d0[3] - m1)),
                   p2 = pack2(ex2(d1[0] - m0), ex2(d1[1] - m0)), p3 = pack2(ex2(d1[2] - m1), ex2(d1[3] - m1));
    l0 = fmaf(l0, sc0, (bf_lo(p0) + bf_hi(p0)) + (bf_lo(p2) + bf_hi(p2)));
    l1 = fmaf(l1, sc1, (bf_lo(p1) + bf_hi(p1)) + (bf_lo(p3) + bf_hi(p3)));
#pragma unroll
    for (int nb = 0; nb < 16; nb++) {
      uint32_t b0, b1;
      asm("movmatrix.sync.aligned.m8n8.trans.b16 %0, %1;" : "=r"(b0) : "r"(*(const uint32_t*)(vp + nb * 8)));
      asm("movmatrix.sync.aligned.m8n8.trans.b16 %0, %1;" : "=r"(b1) : "r"(*(const uint32_t*)(vp + 8 * DH + nb * 8)));
      o[4 * nb] *= sc0; o[4 * nb + 1] *= sc0; o[4 * nb + 2] *= sc1; o[4 * nb + 3] *= sc1;
      hmma_k16(*(float (*)[4])&o[4 * nb], p0, p1, p2, p3, b0, b1);
    }
  }
}
__device__ __forceinline__ int fresh_lane() {
  int l;
  asm volatile("mov.u32 %0, %%laneid;" : "=r"(l));
  return l;
}
__device__ __forceinline__ bool inv_sums(float l0, float l1, float& i0, float& i1) {
  l0 += __shfl_xor_sync(0xffffffffu, l0, 1); l1 += __shfl_xor_sync(0xffffffffu, l1, 1);
  l0 += __shfl_xor_sync(0xffffffffu, l0, 2); l1 += __shfl_xor_sync(0xffffffffu, l1, 2);
  i0 = rcp(l0);
  i1 = rcp(l1);
  return !(l0 + l1 <= SUM_HI) | (fminf(l0, l1) < SUM_LO);
}
template <int LO, int HI>
__device__ __forceinline__ void park(uint32_t a, const float (&o)[64], float i0, float i1, bool on = true) {
#pragma unroll
  for (int i = LO; i < HI; i++)
    asm volatile("{\n.reg .pred p;\nsetp.ne.u32 p, %5, 0;\n@p stmatrix.sync.aligned.m8n8.x4.shared.b16 [%0], {%1, %2, %3, %4};\n}"
                 ::"r"(a + i * 2048), "r"(pack2(o[8 * i] * i0, o[8 * i + 1] * i0)), "r"(pack2(o[8 * i + 2] * i1, o[8 * i + 3] * i1)),
                 "r"(pack2(o[8 * i + 4] * i0, o[8 * i + 5] * i0)), "r"(pack2(o[8 * i + 6] * i1, o[8 * i + 7] * i1)), "r"((uint32_t)on) : "memory");
}

template <int I, int NP, int E0, int N, int NS>
__device__ __forceinline__ void exp_park(float (&s)[NS], uint32_t a, const float (&o)[64], float i0, float i1, bool on, int id) {
  if constexpr (I < NP) {
    constexpr int E1 = E0 + (N - E0) * X_PG / (NP - I);
    softmax_exp<E0, E1>(s);
    park<I, I + X_PG>(a, o, i0, i1, on);
    if (I + X_PG < NP) {
#pragma unroll
      for (int i = E0; i < E1; i++) asm volatile("" : "+f"(s[i])::"memory");
      block_fence(id + I);
    }
    exp_park<I + X_PG, NP, E1, N>(s, a, o, i0, i1, on, id);
  }
}

__device__ __forceinline__ void attn_consumer(const Ctx& cx, int qb, int hs, int wg, int cw, int lane, const __nv_bfloat16* x,
                                              const __nv_bfloat16* kc, const __nv_bfloat16* vc, __nv_bfloat16* out) {
  const uint32_t full = cx.sb + SM_FULL;
  const uint32_t ring = cx.sb + SM_RING;
  const uint32_t qwg = ring + wg * 16384;
  auto qlane = [&](int l) { return qwg + (cw & 3) * 256 + (l >> 4) * 1024 + (l & 15) * 16; };
  const bool signaller = lane == 0 && (cw & 3) < 2;
  const int my_turn = 1 + wg, other_turn = 2 - wg;

  float oA[64], oB[64], i0, i1;
  uint32_t xl[32];
  uint32_t empty_c;
  {
    const int r = lane >> 2, c = lane & 3;
    const int lr0 = cw * 16 + r;
    uint32_t xa[144];
    float rstd0, rstd1, sq0, sq1;
    {
      const uint32_t xb = cx.sb + SM_X + wg * 73728, xf = cx.sb + SM_XFULL + wg * 24;
      const uint32_t lo = ((cw & 3) * 16 + (lane & 15)) * 128 + (((lane >> 4) ^ (lane & 7)) << 4);
      LnAcc a;
      a.clear();
      prof(wg, 0);
      empty_c = mapa(cx.sb + SM_EMPTY, cw & 1);
      TS4(1)
      mbar_wait(xf, 0);
      TS4(2)
      ln_fetch<0, 12>(xa, xb, lo);
      ln_accum<0, 12>(xa, a);
      cluster_wait();
      mbar_wait(xf + 8, 0);
      TS4(3)
      ln_fetch<12, 24>(xa, xb, lo);
      if (wg == 0) {
        bar_sync(4, 128);
        if (signaller) {
          asm volatile("mbarrier.arrive.shared::cluster.b64 _, [%0], 2;" ::"r"(empty_c + 16) : "memory");
          asm volatile("mbarrier.arrive.shared::cluster.b64 _, [%0], 2;" ::"r"(empty_c + 24) : "memory");
        }
      }
      ln_accum<12, 24>(xa, a);
      mbar_wait(xf + 16, 0);
      TS4(4)
      prof(wg, 1);
      ln_fetch<24, 36>(xa, xb, lo);
#pragma unroll
      for (int k = 24; k < 36; k++) hmma_k16(a.sm[k & 1], xa[4 * k], xa[4 * k + 1], xa[4 * k + 2], xa[4 * k + 3], 0x3F803F80u, 0x3F803F80u);
      ln_diag(a, lane, sq0, sq1);
      if (c != (r >> 1)) sq0 = sq1 = 0.f;
      rstd0 = a.sm[0][0] + a.sm[1][0];
      rstd1 = a.sm[0][2] + a.sm[1][2];
    }
    const uint32_t mm0 = pack2(rstd0 * (1.0f / DM), rstd0 * (1.0f / DM)), mm1 = pack2(rstd1 * (1.0f / DM), rstd1 * (1.0f / DM));
#pragma unroll
    for (int i = 0; i < 16; i++) { xa[2 * i] = sub2(xa[2 * i], mm0); xa[2 * i + 1] = sub2(xa[2 * i + 1], mm1); }
    pin(xa);
    prof(wg, 2);
    TS4(5)

    float (&acc)[64] = oB;
#pragma unroll 1
    for (int p = 0; p < 4; p++) {
      const int st0 = p * 5;
#pragma unroll
      for (int i = 0; i < 5; i++) {
        if (i == 4 && p == 3) break;
        const int st = st0 + i;
        const uint32_t sl = (st ^ ((st >> 1) & 1)) & 3, slp = ((st - 1) ^ (((st - 1) >> 1) & 1)) & 3;
        mbar_wait(full + 8 * sl, (st >> 2) & 1);
        TS4(8 + 2 * st)
        const bool join = wg && p == 3;
        if (p && i != (wg ? 4 : 1) && !(join && i == 3)) bar_sync(my_turn, 256);
        wg_fence();
        const uint64_t db = mkdesc(ring + sl * STAGE, 16384);
        const int kb0 = i < 3 ? 8 * i : 8 * i - 4;
#pragma unroll
        for (int k = 0; k < (i == 2 ? 4 : 8); k++) {
          const int kb = kb0 + k;
          mma_n128<1>(acc, xa[4 * kb], xa[4 * kb + 1], xa[4 * kb + 2], xa[4 * kb + 3], db + k * 128, kb > 0);
        }
        wg_commit();
        TS4(9 + 2 * st)
        if (wg ? (i == 4 || (p && (i < 2 || i == (join ? 3 : 2)))) : (p && i)) bar_arrive(other_turn, 256);
        if (p == 0 && i < 4) {
          if (i < 2) {
#pragma unroll
            for (int j = 48 + 12 * i; j < 60 + 12 * i; j++) {
              sq0 = fmaf(bf_lo(xa[2 * j]), bf_lo(xa[2 * j]), fmaf(bf_hi(xa[2 * j]), bf_hi(xa[2 * j]), sq0));
              sq1 = fmaf(bf_lo(xa[2 * j + 1]), bf_lo(xa[2 * j + 1]), fmaf(bf_hi(xa[2 * j + 1]), bf_hi(xa[2 * j + 1]), sq1));
            }
          }
          if (i == 1) {
            sq0 += __shfl_xor_sync(0xffffffffu, sq0, 1); sq1 += __shfl_xor_sync(0xffffffffu, sq1, 1);
            sq0 += __shfl_xor_sync(0xffffffffu, sq0, 2); sq1 += __shfl_xor_sync(0xffffffffu, sq1, 2);
            float mean0, mean1;
            ln_row(rstd0, sq0, mean0, rstd0);
            ln_row(rstd1, sq1, mean1, rstd1);
            if (c == 0) {
              *(float2*)(cx.sp + SM_STATS + 8 * lr0) = make_float2(mean0, rstd0);
              *(float2*)(cx.sp + SM_STATS + 8 * (lr0 + 8)) = make_float2(mean1, rstd1);
            }
            bar_arrive(BAR_GATE, 352);
            bar_sync(4 + wg, 128);
            rstd0 *= SM_SCALE_LOG2;
            rstd1 *= SM_SCALE_LOG2;
          }
#pragma unroll
          for (int j = 0; j < 72; j++)
            if (j >= 2 * (i < 2 ? 8 * i + 8 : 8 * i + 4) && j < 2 * (i == 0 ? 16 : 8 * i + 12)) {
              xa[2 * j] = sub2(xa[2 * j], mm0);
              xa[2 * j + 1] = sub2(xa[2 * j + 1], mm1);
            }
          pin(xa);
        }
        if (i == 0) {
          if (wg) {
            wg_wait<0>();
            if (signaller) mbar_arrive_cluster(empty_c + 8 * sl);
          }
        } else if (i == 2) {
          if (!join) {
            wg_wait<0>();
            if (signaller) mbar_arrive_cluster(empty_c + 8 * sl);
          }
        } else if (i != 3) {
          wg_wait<1>();
          if (signaller && (i == 4 || !wg)) mbar_arrive_cluster(empty_c + 8 * slp);
          wg_wait<0>();
          if (signaller) mbar_arrive_cluster(empty_c + 8 * sl);
        }
      }
      if (p == 3) break;
      pin(acc);
      prof(wg, 3 + p);
      TS4(50 + 2 * p)
      park<0, 8>(qlane(lane) + (4 + p) * STAGE, acc, rstd0, rstd1);
      asm volatile("fence.proxy.async.shared::cta;" ::: "memory");
      TS4(51 + 2 * p)
    }
    wg_wait<1>();
    if (signaller && wg) mbar_arrive_cluster(empty_c + 8 * 1);
    wg_wait<0>();
    pin(acc);
    prof(wg, 6);
#pragma unroll
    for (int i = 0; i < 32; i++) xl[i] = xa[112 + i];
    i0 = rstd0;
    i1 = rstd1;
  }

  uint32_t oa[128];
  float acc[32];
  {
    uint32_t pf[28];
    uint32_t bad = 0;
    float lA0 = 0.f, lA1 = 0.f, lB0 = 0.f, lB1 = 0.f;
    int t = 0;
    uint32_t ra = 0, rb = 2 * 2048, rc = 0, par = 1;
    const uint64_t dk0 = mkdesc(ring, 16), dv0 = mkdesc(ring, 16384);
    uint64_t dqA = mkdesc_q(qwg + 4 * STAGE), dqB = dqA + 2048;
    auto turn = [&](auto kc_, auto bc_) {
      constexpr int KIND = decltype(kc_)::value, BIG = decltype(bc_)::value;
      constexpr int HB = KIND == 1, ID = 10 * KIND + 30 * BIG, T0 = BIG ? 38 : 0;
      constexpr int NS = BIG ? 56 : 48, SPLIT = BIG ? (HB ? X_SPLIT : X_SPLITA) : (HB ? X_SPLITS : X_SPLITSA);
      float s[NS];
      float (&op)[64] = HB ? oA : oB;
      uint32_t h0 = 0, h1 = 0;
      TS2(0)
      bar_sync(my_turn, 256);
      TS2(1)
      if (KIND) { pin(pf); pin(op); }
      mma_qk(s, HB ? dqB : dqA, dk0 + (HB ? ra : rc));
      TS2(2)
      if (KIND) {
        const bool bigp = HB ? BIG : BIG ? t != 10 : t == 66;
        if (X_BF2) block_fence(ID + 9);
        pin(pf);
        sum_tree(pf, bigp, h0, h1);
        asm volatile("" : "+r"(h0), "+r"(h1)::"memory");
        if (HB) mbar_wait(full + (rb >> 8), par);
        mma_pv(op, pf, dv0 + rb, t != T0 + 2 - HB, bigp);
      } else {
        mbar_wait(full + (rb >> 8), (NST_Q - 1) >> 2 & 1);
#pragma unroll
        for (int k = 0; k < 8; k++) mma_n128<1>(op, xl[4 * k], xl[4 * k + 1], xl[4 * k + 2], xl[4 * k + 3], dv0 + rb + k * 128, 1);
        wg_commit();
      }
      TS2(3)
      bar_arrive(other_turn, 256);
      (HB ? lA0 : lB0) += bf_lo(h0) + bf_hi(h0);
      (HB ? lA1 : lB1) += bf_lo(h1) + bf_hi(h1);
      wg_wait<1>();
      pin(s);
      TS1(t)
      TS2(4)
      if (KIND == 1) mbar_arrive_cluster_now<ID + 3>(empty_c + (ra >> 8), signaller);
      if (BIG && t == T0 + HB) {
        const uint32_t a = qlane(fresh_lane()) + (4 + HB) * STAGE;
        const bool ok = !__any_sync(0xffffffffu, inv_sums(HB ? lB0 : lA0, HB ? lB1 : lA1, i0, i1));
        bad = (HB ? bad : 0) | (ok ? 0 : 1 << HB);
        (HB ? lB0 : lA0) = 0.f;
        (HB ? lB1 : lA1) = 0.f;
        softmax_exp<0, X_E0>(s);
#pragma unroll
        for (int i = 0; i < X_E0; i++) asm volatile("" : "+f"(s[i])::"memory");
        block_fence(ID + 7);
        exp_park<0, X_PA, X_E0, SPLIT>(s, a, HB ? oB : oA, i0, i1, ok, 200 + ID);
        if (!HB) dqB += 2048;
        prof(wg, 8 + HB);
        if (!HB && cw == 0) bar_arrive(BAR_HELPER, 128);
      } else {
        if (HB && !BIG) bad = (bad & 3) | (inv_sums(lA0, lA1, i0, i1) ? 4 : 0);
        softmax_exp<0, SPLIT>(s);
      }
      pin(s);
      if (!BIG) block_fence(ID + 4);
      TS2(5)
      wg_wait<0>();
      TS2(6)
      pin(op);
      if (KIND) pin(pf); else pin(xl);
      if (HB) {
        par ^= rc == 0;
        if (BIG && t == 37) dqA -= 2048;
      } else {
        mbar_arrive_cluster_now<ID + 5>(empty_c + (rb >> 8), signaller);
        if (KIND) {
          par ^= ra == 0;
          const uint32_t x = ra;
          ra = rc; rc = rb; rb = x;
        }
      }
      softmax_exp<SPLIT, NS>(s);
#pragma unroll
      for (int i = 0; i < NS / 2; i++) pf[i] = pack2(s[2 * i], s[2 * i + 1]);
      pin(pf);
      if (KIND == 0) {
        block_fence(ID + 6);
        park<0, 8>(qlane(fresh_lane()) + 3 * STAGE, oB, i0, i1);
        asm volatile("fence.proxy.async.shared::cta;" ::: "memory");
        prof(wg, 7);
      }
      if (BIG && X_PA < 8 && t == T0 + HB) park<X_PA, 8>(qlane(fresh_lane()) + (4 + HB) * STAGE, HB ? oB : oA, i0, i1, !(bad >> HB));
      if (HB) mbar_wait(full + (rc >> 8), par);
      t++;
    };
#pragma unroll
    for (int i = 24; i < 28; i++) asm volatile("" : "=r"(pf[i]));
    mbar_wait(full, (NST_Q >> 2) & 1);
    turn(IC<0>(), IC<0>());
    rb = 2048; rc = 2 * 2048;
    kill(oA);
    const bool never = blockIdx.y == 1;
#pragma unroll 1
    while (true) {
      turn(IC<1>(), IC<0>());
      if (t == 76) break;
      if (t == 10) {
#pragma unroll 1
        do {
#pragma unroll 1
          do turn(IC<2>(), IC<1>()); while (never);
          turn(IC<1>(), IC<1>());
        } while (t != 66);
      }
#pragma unroll 1
      do turn(IC<2>(), IC<0>()); while (never);
    }
    const uint32_t ql = qlane(fresh_lane());
    auto scale = [&](auto lo, auto hi) {
#pragma unroll
      for (int i = decltype(lo)::value; i < decltype(hi)::value; i++) {
        oa[32 + 2 * i] = pack2(oA[4 * i] * i0, oA[4 * i + 1] * i0);
        oa[32 + 2 * i + 1] = pack2(oA[4 * i + 2] * i1, oA[4 * i + 3] * i1);
        asm volatile("" : "+r"(oa[32 + 2 * i]), "+r"(oa[32 + 2 * i + 1])::"memory");
      }
    };
    TS3(1)
    if (X_LD == 0) {
#pragma unroll
      for (int i = 0; i < 8; i++) ldsm4(ql + 4 * STAGE + i * 2048, oa[4 * i], oa[4 * i + 1], oa[4 * i + 2], oa[4 * i + 3]);
    }
    {
      uint32_t h0, h1;
      sum_tree(pf, false, h0, h1);
      if (inv_sums(lB0 + (bf_lo(h0) + bf_hi(h0)), lB1 + (bf_lo(h1) + bf_hi(h1)), lB0, lB1)) bad |= 8;
    }
    scale(IC<0>(), IC<X_F1>());
    volatile uint32_t* const cold = (volatile uint32_t*)(cx.sp + SM_COLD) + wg;
    if (bad) *cold = 1;
    block_fence(93);
    TS3(2)
    bar_sync(my_turn, 256);
    const uint32_t is_cold = *cold;
    TS3(3)
    pin(pf); pin(oB);
    mma_pv(oB, pf, dv0, true, false);
    mbar_arrive_cluster_now<91>(empty_c + 8 * 3, signaller && !is_cold);
    TS3(4)
    if (X_LD == 1) {
#pragma unroll
      for (int i = 0; i < 8; i++) ldsm4(ql + 4 * STAGE + i * 2048, oa[4 * i], oa[4 * i + 1], oa[4 * i + 2], oa[4 * i + 3]);
    }
    const uint64_t db = mkdesc(ring + STAGE, 16);
    scale(IC<X_F1>(), IC<X_F2>());
    block_fence(94);
#pragma unroll
    for (int i = 0; i < 32; i++) asm volatile("" : "+r"(oa[i])::"memory");
    wg_fence();
#pragma unroll
    for (int k = 0; k < 8; k++) mma_n64t(acc, oa[4 * k], oa[4 * k + 1], oa[4 * k + 2], oa[4 * k + 3], db + k * 128, k > 0);
    if (X_F2 < 16) {
      wg_commit();
      block_fence(95);
      scale(IC<X_F2>(), IC<16>());
      TS3(5)
      wg_fence();
    }
#pragma unroll
    for (int k = 8; k < 16; k++) mma_n64t(acc, oa[4 * k], oa[4 * k + 1], oa[4 * k + 2], oa[4 * k + 3], db + k * 128, 1);
    wg_commit();
    bar_arrive(other_turn, 256);
    wg_wait<(X_F2 < 16 ? 2 : 1)>();
    pin(oB); pin(pf);
    TS(76)
    TS3(6)
    if (signaller) mbar_arrive_cluster(empty_c);
#pragma unroll
    for (int i = 16; i < 24; i++) ldsm4(ql + 5 * STAGE + (i & 7) * 2048, oa[4 * i], oa[4 * i + 1], oa[4 * i + 2], oa[4 * i + 3]);
#pragma unroll
    for (int i = 0; i < 16; i++) {
      oa[96 + 2 * i] = pack2(oB[4 * i] * lB0, oB[4 * i + 1] * lB0);
      oa[96 + 2 * i + 1] = pack2(oB[4 * i + 2] * lB1, oB[4 * i + 3] * lB1);
    }
    TS3(7)
    mbar_wait(full + 8 * 2, 0);
    TS3(8)
    wg_wait<0>();
    pin(acc); pin(oa);
    if (__any_sync(0xffffffffu, is_cold)) {
      bad = __reduce_or_sync(0xffffffffu, bad);
      if (!(bad & 8)) {
#pragma unroll
        for (int i = 24; i < 32; i++) stsm4(ql + 6 * STAGE + (i & 7) * 2048, oa[4 * i], oa[4 * i + 1], oa[4 * i + 2], oa[4 * i + 3]);
      }
#pragma unroll 1
      for (int h = 0; h < 4; h++) {
        if (bad >> h & 1) {
          const uint32_t a = ql + ((0x6354 >> (4 * h)) & 7) * STAGE;
          const size_t o = (size_t)(hs * 2 + (h >> 1)) * SEQ * DH;
          float ox[64], l0, l1;
          exact_attention(ox, l0, l1, a, kc + o, vc + o, fresh_lane());
          inv_sums(l0, l1, l0, l1);
          __syncwarp();
          park<0, 8>(a, ox, l0, l1);
        }
      }
      __syncwarp();
#pragma unroll
      for (int i = 0; i < 32; i++)
        if ((i >> 3) != 1 || (bad & 4))
          ldsm4(ql + ((0x6534 >> (4 * (i >> 3))) & 7) * STAGE + (i & 7) * 2048, oa[4 * i], oa[4 * i + 1], oa[4 * i + 2], oa[4 * i + 3]);
      pin(oa);
      asm volatile("fence.proxy.async.shared::cta;" ::: "memory");
      bar_sync(4 + wg, 128);
      if (signaller) mbar_arrive_cluster(empty_c + 8 * 3);
      wg_fence();
#pragma unroll
      for (int k = 0; k < 16; k++) mma_n64t(acc, oa[4 * k], oa[4 * k + 1], oa[4 * k + 2], oa[4 * k + 3], db + k * 128, k > 0);
      wg_commit();
      wg_wait<0>();
      pin(acc);
    }
    if (signaller) mbar_arrive_cluster(empty_c + 8 * 1);
  }

  prof(wg, 10);
  TS3(9)
  {
    lane = fresh_lane();
    const int tw = (cw & 3) * 32 + lane;
    float red[32];
    kill(red);
    uint32_t tag = 0;
    uint4* const xch = g_part + (size_t)(qb * 64 * 2 + wg) * 4 * 128 + tw;
    int nrx = 1;
    auto region = [](int s, int h) { return (2 * s + h + 1) & 3; };
    auto half_step = [&](int s, auto hc, bool arrive) {
      constexpr int h = decltype(hc)::value;
      const uint64_t db = mkdesc(ring + region(s, h) * STAGE, 16);
      bar_sync(my_turn, 256);
      pin(oa);
      wg_fence();
#pragma unroll
      for (int k = 0; k < 16; k++) {
        const int kb = h * 16 + k;
        mma_n64t(acc, oa[4 * kb], oa[4 * kb + 1], oa[4 * kb + 2], oa[4 * kb + 3], db + k * 128, kb > 0);
      }
      wg_commit();
      if (arrive) bar_arrive(other_turn, 256);
    };
    auto await = [&](int s, int h) { mbar_wait(full + 8 * region(s, h), ((s >> 1) ^ s) & 1); };
    auto fetch = [&](uint32_t (&g)[16], int n) {
      const uint4* p = xch + (hs * 7 + n - 1) * (2 * 4 * 128);
#pragma unroll
      for (int i = 0; i < 4; i++) ld_gran(p + i * 128, g[4 * i], g[4 * i + 1], g[4 * i + 2], g[4 * i + 3]);
    };
    uint32_t g[16];
#pragma unroll 1
    for (int s = 0; s < 8; s++) {
      const bool pend = nrx < s - 1;
      if (pend) fetch(g, nrx);
      half_step(s, IC<1>(), true);
      TS3(s < 3 ? 16 + 8 * s : 75)
      if (s == 0) {
        mbar_wait(cx.sb + SM_BAR_MISC, 0);
        tag = *(const volatile uint32_t*)(cx.sp + SM_TAG);
        bar_arrive(BAR_OA, 352);
#pragma unroll
        for (int i = 0; i < 32; i++) red[i] = 0.f;
      }
      await(s + 1, 0);
      TS3(s < 3 ? 17 + 8 * s : 75)
      wg_wait<0>();
      TS3(s < 3 ? 18 + 8 * s : 75)
      if (signaller && s < 7) mbar_arrive_cluster(empty_c + 8 * region(s, 1));
      pin(acc);
      TS(77 + s)
      prof(wg, 12 + s);
      uint4* p = xch + (s == 0 ? 56 + hs : ((hs + s) & 7) * 7 + s - 1) * (2 * 4 * 128);
#pragma unroll
      for (int i = 0; i < 4; i++)
        st_gran(p + i * 128, (pack2(acc[8 * i], acc[8 * i + 1]) & ~TAG) | tag, pack2(acc[8 * i + 2], acc[8 * i + 3]),
                pack2(acc[8 * i + 4], acc[8 * i + 5]), pack2(acc[8 * i + 6], acc[8 * i + 7]));
      TS3(s < 3 ? 19 + 8 * s : 75)
      half_step(s + 1, IC<0>(), true);
      TS3(s < 3 ? 20 + 8 * s : 75)
      await(s + 1, 1);
      TS3(s < 3 ? 21 + 8 * s : 75)
      if (pend && granules_ok(g, tag)) { add_granules(red, g); nrx++; }
      if (X_EARLY == 2 && s == 7) fetch(g, nrx);
      wg_wait<0>();
      TS3(s < 3 ? 22 + 8 * s : 75)
      if (signaller && s < 6) mbar_arrive_cluster(empty_c + 8 * region(s + 1, 0));
    }
    uint32_t xv[16], gt[16], g2[16];
    if (X_EARLY < 2) fetch(g, nrx);
    mbar_wait(cx.sb + SM_BAR_XG, 0);
    const bool two = nrx < 7;
    bool ok;
    {
      const uint64_t db = mkdesc(ring + 2 * STAGE, 16);
      if (X_EARLY == 2) ok = granules_ok(g, tag);
      bar_sync(my_turn, 256);
      if (X_EARLY == 2) fetch(g2, 7);
#pragma unroll
      for (int i = 64; i < 128; i++) asm volatile("" : "+r"(oa[i])::"memory");
      wg_fence();
#pragma unroll
      for (int k = 16; k < 32; k++) mma_n64t(acc, oa[4 * k], oa[4 * k + 1], oa[4 * k + 2], oa[4 * k + 3], db + (k - 16) * 128, 1);
      wg_commit();
      if (wg == 0) bar_arrive(other_turn, 256);
    }
    if (X_EARLY < 2) {
      ok = granules_ok(g, tag);
      fetch(g2, 7);
    }
    const uint32_t frag = (cw * 16 + (lane & 15)) * 144 + (lane >> 4) * 16;
#pragma unroll
    for (int i = 0; i < 4; i++) {
      ldsm4(cx.sb + SM_XO + frag + i * 32, xv[4 * i], xv[4 * i + 1], xv[4 * i + 2], xv[4 * i + 3]);
      ldsm4(cx.sb + SM_GO + frag + i * 32, gt[4 * i], gt[4 * i + 1], gt[4 * i + 2], gt[4 * i + 3]);
    }
    if (ok) { add_granules(red, g); nrx++; }
    wg_wait<0>();
    pin(acc);
    TS(85)
#pragma unroll
    for (int i = 0; i < 32; i++) red[i] += acc[i];
    pin(red);
    block_fence(90);
    int last = 8;
    if (two && granules_ok(g2, tag)) { add_granules(red, g2); last = 7; }
#pragma unroll 1
    for (int spins = 0; nrx < last && spins < (1 << 16); spins++) {
      fetch(g, nrx);
      if (granules_ok(g, tag)) { add_granules(red, g); nrx++; }
    }
    prof(wg, 20);
    TS(86)
    const uint32_t ot = ring + 3 * STAGE + cw * (16 * 144);
    uint32_t ow[16];
#pragma unroll
    for (int i = 0; i < 16; i++) ow[i] = fma2(pack2(red[2 * i], red[2 * i + 1]), gt[i], xv[i]);
#pragma unroll
    for (int i = 0; i < 4; i++)
      stsm4(ot + (lane & 15) * 144 + (2 * i + (lane >> 4)) * 16, ow[4 * i], ow[4 * i + 1], ow[4 * i + 2], ow[4 * i + 3]);
    __syncwarp();
#pragma unroll
    for (int i = 0; i < 4; i++) {
      uint4 v;
      lds128(ot + (i * 4 + (lane >> 3)) * 144 + (lane & 7) * 16, v.x, v.y, v.z, v.w);
      *(uint4*)(out + (size_t)(qb * 128 + cw * 16 + i * 4 + (lane >> 3)) * DM + hs * 64 + (lane & 7) * 8) = v;
    }
    prof(wg, 22);
    TS(87)
    TS_DUMP()
  }
}

constexpr int FST_X = 24, FST_END = FST_X + 14 * 12;
__device__ __forceinline__ void ffn_producer(const Ctx& cx, int f, const CUtensorMap* tmX, const CUtensorMap* tmG,
                                             const CUtensorMap* tmU, const CUtensorMap* tmD) {
  const uint32_t full = cx.sb + SM_FULL, empty = cx.sb + SM_EMPTY;
  int pair = -2, u = 0;
#pragma unroll 1
  for (int st = 0; st < FST_END; st++) {
    const uint32_t sl = st & 7;
    const int unit = pair * 2 + (u & 1), k = u >> 1, k3 = k >= 3 ? k - 3 : k;
    if (unit < 27) {
      mbar_wait(empty + 8 * sl, ((st >> 3) & 1) ^ 1);
      mbar_expect_tx(full + 8 * sl, FSTAGE);
      if (pair < 0) tma3d(cx.sb + sl * FSTAGE, tmX, f * 512 + ((pair + 2) * 4 + (k >= 3) * 2 + (u & 1)) * 64, k3 * 3, full + 8 * sl);
      else if (pair < 9) tma2d_stream(cx.sb + sl * FSTAGE, k < 3 ? tmG : tmU, f * 1152 + unit * 64, k3 * 192, full + 8 * sl);
      else tma2d_stream(cx.sb + sl * FSTAGE, tmD, (unit - 18) * 64, f * 1152 + k * 192, full + 8 * sl);
    }
    if (++u == 12) { u = 0; pair++; }
  }
}

__device__ __forceinline__ void ffn_consumer(const Ctx& cx, int f, int wg, int cw, int lane, const __nv_bfloat16* x,
                                             const __nv_bfloat16* w_r) {
  const int r = lane >> 2, c = lane & 3, tid = cw * 32 + lane;
  unsigned e = 0;
  if (tid == 0) {
    e = g_launch[blockIdx.x];
    g_launch[blockIdx.x] = e + 1;
    *(unsigned*)(cx.sp + SM_TAG) = e;
  }
  if (tid < 72) *(uint4*)(cx.sp + SM_H + tid * 16) = *(const uint4*)(w_r + tid * 8);
  bar_sync(3, 256);
  prof(wg, 0);
  const uint32_t full = cx.sb + SM_FULL, empty = cx.sb + SM_EMPTY;
  const bool signaller = (tid & 127) == 0;
#pragma unroll 1
  for (int b = wg; b < 8; b += 2) {
    const int row0 = f * 512 + b * 64 + (cw & 3) * 16 + r;
    const uint32_t lo = ((cw & 3) * 16 + (lane & 15)) * 128 + (((lane >> 4) ^ (lane & 7)) << 4);
    LnAcc a;
    a.clear();
#pragma unroll 1
    for (int bx = 0; bx < 9; bx++) {
      const int st = (b >> 1) * 6 + (bx / 3) * 2 + wg;
      if (bx % 3 == 0) mbar_wait(full + 8 * (st & 7), (st >> 3) & 1);
#pragma unroll
      for (int k = 0; k < 4; k++) {
        uint32_t x0, x1, x2, x3;
        ldsm4(cx.sb + (st & 7) * FSTAGE + (bx % 3) * 8192 + (lo ^ (k << 5)), x0, x1, x2, x3);
        ln_accum1(a, k & 1, x0, x1, x2, x3);
      }
    }
    prof(wg, 8 + (b >> 1) * 3);
    float mean0, rstd0, mean1, rstd1;
    ln_stats(a, lane, mean0, rstd0, mean1, rstd1);
    prof(wg, 9 + (b >> 1) * 3);
    const uint32_t mm0 = pack2(mean0, mean0), mm1 = pack2(mean1, mean1);
    float d0[4] = {0, 0, 0, 0}, d1[4] = {0, 0, 0, 0};
#pragma unroll 1
    for (int bx = 0; bx < 9; bx++) {
      const int st = (b >> 1) * 6 + (bx / 3) * 2 + wg;
#pragma unroll
      for (int k = 0; k < 4; k++) {
        uint32_t n[4];
        ldsm4(cx.sb + (st & 7) * FSTAGE + (bx % 3) * 8192 + (lo ^ (k << 5)), n[0], n[1], n[2], n[3]);
        const uint8_t* wp = cx.sp + SM_H + (bx * 4 + k) * 32 + 4 * c;
#pragma unroll
        for (int i = 0; i < 4; i++) {
          const uint32_t t = sub2(n[i], (i & 1) ? mm1 : mm0);
          const float rs = (i & 1) ? rstd1 : rstd0;
          n[i] = pack2(bf_lo(t) * rs, bf_hi(t) * rs);
        }
        if (k & 1) hmma_k16(d1, n[0], n[1], n[2], n[3], *(const uint32_t*)wp, *(const uint32_t*)(wp + 16));
        else hmma_k16(d0, n[0], n[1], n[2], n[3], *(const uint32_t*)wp, *(const uint32_t*)(wp + 16));
      }
    }
    prof(wg, 10 + (b >> 1) * 3);
    bar_sync(4 + wg, 128);
    if (signaller) {
#pragma unroll
      for (int i = 0; i < 3; i++) mbar_arrive(empty + 8 * (((b >> 1) * 6 + i * 2 + wg) & 7));
    }
    if (c == 0) {
      g_r[row0] = bfr(d0[0] + d1[0]);
      g_r[row0 + 8] = bfr(d0[2] + d1[2]);
      g_stats[row0] = make_float2(mean0, rstd0);
      g_stats[row0 + 8] = make_float2(mean1, rstd1);
    }
  }
  prof(wg, 1);
  cluster_wait();
  bar_sync(3, 256);
  e = *(const unsigned*)(cx.sp + SM_TAG);
  if (tid == 0) {
    atom_add_acq_rel(&g_rcnt);
#pragma unroll 1
    for (int n = 0; n < (1 << 16) && (int)(ld_acquire(&g_rcnt) - 4 * (e + 1)) < 0; n++) {}
  }
  bar_sync(3, 256);
  prof(wg, 2);
  uint32_t key[8];
#pragma unroll
  for (int i = 0; i < 8; i++) {
    const int row = i * 256 + tid;
    const uint32_t b = __float_as_uint(__ldcg(&g_r[row])) >> 16;
    key[i] = (((b & 0x8000u) ? (~b & 0xFFFFu) : (b | 0x8000u)) << 16) | (uint32_t)(0xFFFF - row);
  }
  int mysel = 0;
#pragma unroll 1
  for (int k = 0; k < TOPC; k++) {
    uint32_t m = key[0];
#pragma unroll
    for (int i = 1; i < 8; i++) m = max(m, key[i]);
    m = __reduce_max_sync(0xffffffffu, m);
    uint32_t* tk = (uint32_t*)(cx.sp + SM_TOPK) + (k & 1) * 8;
    if (lane == 0) tk[cw] = m;
    bar_sync(3, 256);
    m = __reduce_max_sync(0xffffffffu, tk[lane & 7]);
#pragma unroll
    for (int i = 0; i < 8; i++) if (key[i] == m) key[i] = 0;
    if (k == cw) mysel = 0xFFFF - (int)(m & 0xFFFF);
  }
  {
    const float2 st = __ldcg(&g_stats[mysel]);
    const uint32_t mm = pack2(st.x, st.x);
#pragma unroll 3
    for (int i = 0; i < 9; i++) {
      const uint32_t t = sub2(*(const uint32_t*)(x + (size_t)mysel * DM + i * 64 + 2 * lane), mm);
      *(uint32_t*)(cx.sp + SM_XSEL + i * 1024 + cw * 128 + (((lane >> 2) ^ cw) << 4) + (lane & 3) * 4) =
          pack2(bf_lo(t) * st.y, bf_hi(t) * st.y);
    }
    if (lane == 0) *(int*)(cx.sp + SM_IDX + 4 * cw) = mysel;
  }
  asm volatile("fence.proxy.async.shared::cta;" ::: "memory");
  bar_sync(3, 256);
  prof(wg, 3);
  auto run = [&](float (&acc)[4], int st, int n, uint32_t b) {
#pragma unroll 1
    for (int u = 0; u < n; u++, st += 2, b += 3072) {
      const uint32_t sl = st & 7;
      mbar_wait(full + 8 * sl, (st >> 3) & 1);
      wg_fence();
      const uint64_t da = mkdesc(cx.sb + sl * FSTAGE, 16), db = mkdesc(b, 16);
#pragma unroll
      for (int k = 0; k < 12; k++) mma_n8(acc, da + k * 128, db + (k >> 2) * 64 + (k & 3) * 2, u > 0 || k > 0);
      wg_commit();
      wg_wait<0>();
      if (signaller) mbar_arrive(empty + 8 * sl);
    }
    pin(acc);
  };
#pragma unroll 1
  for (int unit = wg; unit < 27; unit += 2) {
    if (unit >> 1 == 9) {
      asm volatile("fence.proxy.async.shared::cta;" ::: "memory");
      bar_sync(3, 256);
      prof(wg, 4);
    }
    const bool gu = unit < 18;
    float a0[4], a1[4];
#pragma unroll 1
    for (int m = 0; m < (gu ? 2 : 1); m++) {
      run(a1, FST_X + (unit >> 1) * 12 + m * 6 + wg, gu ? 3 : 6, cx.sb + (gu ? SM_XSEL : SM_H));
      if (m == 0) { a0[0] = a1[0]; a0[1] = a1[1]; a0[2] = a1[2]; a0[3] = a1[3]; }
    }
#pragma unroll
    for (int i = 0; i < 4; i++) {
      const int fl = (cw & 3) * 16 + r + (i >> 1) * 8, tok = 2 * c + (i & 1);
      if (gu) {
        const float h = bfr(silu_f(bfr(a0[i]))) * bfr(a1[i]);
        *(__nv_bfloat16*)(cx.sp + SM_H + unit * 1024 + tok * 128 + (((fl >> 3) ^ tok) << 4) + (fl & 7) * 2) = __float2bfloat16_rn(h);
      } else {
        g_ypart[(f * TOPC + tok) * DM + (unit - 18) * 64 + fl] = a1[i];
      }
    }
  }
  prof(wg, 5);
  bar_sync(3, 256);
  if (tid == 0) *(unsigned*)(cx.sp + SM_TOPK) = atom_add_acq_rel(&g_ycnt) == 4 * e + 3;
  bar_sync(3, 256);
  if (*(const unsigned*)(cx.sp + SM_TOPK)) {
    const int row = *(const int*)(cx.sp + SM_IDX + 4 * cw);
    const float rs = bfr(rcp(1.0f + ex2(-1.4426950408889634f * __ldcg(&g_r[row]))));
#pragma unroll 1
    for (int d = lane * 2; d < DM; d += 192) {
#pragma unroll
      for (int i = 0; i < 3; i++) {
        const float* p = g_ypart + cw * DM + d + i * 64;
        const float2 a = __ldcg((const float2*)p), b = __ldcg((const float2*)(p + TOPC * DM)),
                     e2 = __ldcg((const float2*)(p + 2 * TOPC * DM)), h = __ldcg((const float2*)(p + 3 * TOPC * DM));
        const uint32_t y = pack2((a.x + b.x) + (e2.x + h.x), (a.y + b.y) + (e2.y + h.y));
        const uint32_t u = pack2(bf_lo(y) * rs, bf_hi(y) * rs);
        *(float2*)(g_upd + cw * DM + d + i * 64) = make_float2(bf_lo(u), bf_hi(u));
      }
    }
    if (lane == 0) g_idx[cw] = row;
    bar_sync(3, 256);
    if (tid == 0) st_release(&g_ffn_flag, e + 1);
    prof(wg, 6);
  }
}

struct KvMaps { CUtensorMap m[4]; };
__global__ void __cluster_dims__(2, 1, 1) __launch_bounds__(THREADS, 1)
fused_kernel(const __grid_constant__ KvMaps tmKV,
             const __grid_constant__ CUtensorMap tmWq, const __grid_constant__ CUtensorMap tmWo,
             const __grid_constant__ CUtensorMap tmG, const __grid_constant__ CUtensorMap tmU,
             const __grid_constant__ CUtensorMap tmD, const __grid_constant__ CUtensorMap tmX, const __nv_bfloat16* __restrict__ x,
             const __nv_bfloat16* __restrict__ w_r, const __nv_bfloat16* __restrict__ kc,
             const __nv_bfloat16* __restrict__ vc, __nv_bfloat16* __restrict__ out) {
  extern __shared__ __align__(1024) uint8_t smem_raw[];
  prof(0, 23, 511);
  Ctx cx;
  cx.sb = smem_u32(smem_raw);
  cx.sp = smem_raw;
  cx.rank = blockIdx.x & 1;
  const int warp = __shfl_sync(0xffffffffu, threadIdx.x >> 5, 0);
  const int cluster = blockIdx.x >> 1;
  const bool is_ffn = blockIdx.x >= N_ATT_CTA;
  const int hs = cluster < 4 ? 4 + cluster : cluster < 36 ? (cluster - 4) >> 3 : 4 + (cluster - 36) / 7;
  const int qb = (cluster < 4 ? 0 : cluster < 36 ? (cluster - 4) & 7 : 1 + (cluster - 36) % 7) * 2 + cx.rank;

  if (warp == 0 && elect_one()) {
    if (!is_ffn) {
#pragma unroll
      for (int i = 0; i < 6; i++) mbar_init(cx.sb + SM_XFULL + 8 * i, 1);
      asm volatile("fence.proxy.async.shared::cta;" ::: "memory");
#pragma unroll
      for (int i = 0; i < 6; i++) {
        mbar_expect_tx(cx.sb + SM_XFULL + 8 * i, 24576);
        tma3d(cx.sb + SM_X + i * 24576, &tmX, qb * 128 + (i / 3) * 64, (i % 3) * 3, cx.sb + SM_XFULL + 8 * i);
      }
    }
#pragma unroll
    for (int i = 0; i < 8; i++) {
      mbar_init(cx.sb + SM_FULL + 8 * i, 1);
      mbar_init(cx.sb + SM_EMPTY + 8 * i, is_ffn ? 1 : 4);
    }
    mbar_init(cx.sb + SM_BAR_MISC, 1);
    mbar_init(cx.sb + SM_BAR_XG, 64);
    *(uint2*)(cx.sp + SM_COLD) = make_uint2(0, 0);
    asm volatile("fence.mbarrier_init.release.cluster;" ::: "memory");
  } else if (warp == 1 && elect_one()) {
    if (is_ffn) { prefetch_tmap(&tmX); prefetch_tmap(&tmG); prefetch_tmap(&tmU); prefetch_tmap(&tmD); }
    else { prefetch_tmap(&tmWq); prefetch_tmap(&tmKV.m[2]); prefetch_tmap(&tmKV.m[3]); prefetch_tmap(&tmWo); }
  }
  __syncthreads();
  cluster_arrive();

  if (warp < 4) {
    asm volatile("setmaxnreg.dec.sync.aligned.u32 24;");
    cluster_wait();
    prof(0, 24, 511);
    if (warp == 0) {
      if (elect_one()) {
        if (is_ffn) ffn_producer(cx, blockIdx.x - N_ATT_CTA, &tmX, &tmG, &tmU, &tmD);
        else attn_producer(cx, qb, hs, tmKV.m, &tmWq, &tmWo);
        prof(0, 25, 511);
      }
    } else if (!is_ffn) {
      attn_gate(cx, qb, hs, threadIdx.x - 32, x);
      if (warp == 1) attn_helper(cx, qb, hs, read_lane(), x);
      else { bar_arrive(BAR_HELPER, 128); attn_stage_xg(cx, qb, hs, threadIdx.x - 64, x); }
      attn_finish8(cx, qb, hs, warp - 1, read_lane(), out);

    }
    __syncwarp();
    cluster_arrive();
    cluster_wait();
  } else {
    asm volatile("setmaxnreg.inc.sync.aligned.u32 240;");
    const int cw = warp - 4, wg = cw >> 2;
    if (is_ffn) ffn_consumer(cx, blockIdx.x - N_ATT_CTA, wg, cw, read_lane(), x, w_r);
    else attn_consumer(cx, qb, hs, wg, cw, read_lane(), x, kc, vc, out);
  }
}

typedef CUresult (*EncodeFn)(CUtensorMap*, CUtensorMapDataType, cuuint32_t, void*, const cuuint64_t*, const cuuint64_t*,
                             const cuuint32_t*, const cuuint32_t*, CUtensorMapInterleave, CUtensorMapSwizzle,
                             CUtensorMapL2promotion, CUtensorMapFloatOOBfill);

void encode(EncodeFn fn, CUtensorMap* m, const void* p, int rank, const cuuint64_t* dims, const cuuint64_t* strides,
            const cuuint32_t* box) {
  const cuuint32_t es[5] = {1, 1, 1, 1, 1};
  fn(m, CU_TENSOR_MAP_DATA_TYPE_BFLOAT16, rank, const_cast<void*>(p), dims, strides, box, es, CU_TENSOR_MAP_INTERLEAVE_NONE,
     CU_TENSOR_MAP_SWIZZLE_128B, CU_TENSOR_MAP_L2_PROMOTION_L2_128B, CU_TENSOR_MAP_FLOAT_OOB_FILL_NONE);
}
void encode2d(EncodeFn fn, CUtensorMap* m, const void* p, uint64_t rows, uint64_t cols, uint32_t box_rows) {
  const cuuint64_t dims[2] = {cols, rows}, strides[1] = {cols * 2};
  const cuuint32_t box[2] = {64, box_rows};
  encode(fn, m, p, 2, dims, strides, box);
}

}

extern "C" void kernel_launch(void* const* d_in, const int* in_sizes, int n_in, void* d_out, int out_size) {
  (void)in_sizes; (void)n_in; (void)out_size;
  void* fnp = nullptr;
  cudaDriverEntryPointQueryResult qr;
  cudaGetDriverEntryPoint("cuTensorMapEncodeTiled", &fnp, cudaEnableDefault, &qr);
  EncodeFn fn = (EncodeFn)fnp;
  CUtensorMap tmWq, tmWo, tmG, tmU, tmD, tmX;
  KvMaps tmKV;
  for (int i = 0; i < 4; i++) encode2d(fn, &tmKV.m[i], d_in[1 + (i & 1)], 16 * SEQ, DH, i < 2 ? 112 : 96);
  encode2d(fn, &tmWq, d_in[3], DM, 4096, 64);
  {
    const cuuint64_t dims[3] = {64, SEQ, 9}, strides[2] = {DM * 2, 128};
    const cuuint32_t box[3] = {64, 64, 3};
    encode(fn, &tmX, d_in[0], 3, dims, strides, box);
  }
  encode2d(fn, &tmWo, d_in[4], 4096, DM, 128);
  encode2d(fn, &tmG, d_in[7], DM, FF, 192);
  encode2d(fn, &tmU, d_in[8], DM, FF, 192);
  encode2d(fn, &tmD, d_in[9], FF, DM, 192);
  cudaFuncSetAttribute(fused_kernel, cudaFuncAttributeMaxDynamicSharedMemorySize, SM_TOTAL);
  fused_kernel<<<N_CTA, THREADS, SM_TOTAL>>>(tmKV, tmWq, tmWo, tmG, tmU, tmD, tmX, (const __nv_bfloat16*)d_in[0],
                                            (const __nv_bfloat16*)d_in[6], (const __nv_bfloat16*)d_in[1],
                                            (const __nv_bfloat16*)d_in[2], (__nv_bfloat16*)d_out);
}
```

```cpp
#include <cuda_runtime.h>
#include <cuda_bf16.h>
#include <cuda.h>
#include <stdint.h>

namespace {

constexpr int SEQ = 2048, DM = 576, DH = 128, FF = 4608, TOPC = 8;
constexpr int N_ATT_CTA = 128, N_CTA = 132;
constexpr int THREADS = 384;

constexpr uint32_t SM_RING = 0;
constexpr uint32_t STAGE = 32768;
constexpr uint32_t SM_SLOT = 131072;
constexpr uint32_t FSTAGE = 24576;
constexpr uint32_t SM_XSEL = 196608;
constexpr uint32_t SM_H = 205824;
constexpr uint32_t SM_MISC = 229376;
constexpr uint32_t SM_FULL = SM_MISC, SM_EMPTY = SM_MISC + 64, SM_BAR_MISC = SM_MISC + 128,
                   SM_COLD = SM_MISC + 136, SM_TAG = SM_MISC + 144, SM_IDX = SM_MISC + 160,
                   SM_TOPK = SM_MISC + 192, SM_XFULL = SM_MISC + 256, SM_BAR_XG = SM_MISC + 304, SM_STATS = SM_MISC + 320;
constexpr uint32_t SM_TOTAL = SM_MISC + 1344;
constexpr uint32_t SM_X = SM_MISC - 147456;

constexpr int BAR_GATE = 6, BAR_HELPER = 7, BAR_OA = 8;
constexpr int NST_Q = 20, NST_KV = 76, NST_O = 18;
__device__ __forceinline__ bool blk_big(int j) { return (unsigned)(j - 5) < 28; }
__device__ __forceinline__ int blk_row(int j) { return 112 * j - 16 * (min(j, 5) + max(j - 33, 0)); }
constexpr float SM_SCALE_LOG2 = 0.08838834764831845f * 1.4426950408889634f;

struct Scratch {
  uint4 part[16 * 64 * 2 * 4 * 128];
  uint4 gate[SEQ * DM / 8];
  float r[SEQ];
  float2 stats[SEQ];
  float ypart[4 * TOPC * DM];
  float upd[TOPC * DM];
  int idx[32];
  unsigned launch[160];
  unsigned rcnt, ycnt, ffn_flag;
};
__device__ __align__(1024) Scratch g_scratch;

__device__ __forceinline__ void prof(int, int, int = 0) {}

#define TS(id) {}
#define TS_DUMP() {}
#define TS4(k) {}
#define TSP(k) {}
#define TS1(id) TS(id)
#define TS2(k) {}
#define TS3(k) {}

__device__ __forceinline__ uint32_t smem_u32(const void* p) { return (uint32_t)__cvta_generic_to_shared(p); }
__device__ __forceinline__ void mbar_init(uint32_t bar, uint32_t cnt) {
  asm volatile("mbarrier.init.shared::cta.b64 [%0], %1;" ::"r"(bar), "r"(cnt) : "memory");
}
__device__ __forceinline__ void mbar_expect_tx(uint32_t bar, uint32_t bytes) {
  asm volatile("mbarrier.arrive.expect_tx.shared::cta.b64 _, [%0], %1;" ::"r"(bar), "r"(bytes) : "memory");
}
__device__ __forceinline__ void mbar_arrive(uint32_t bar) {
  asm volatile("mbarrier.arrive.shared::cta.b64 _, [%0];" ::"r"(bar) : "memory");
}
__device__ __forceinline__ void mbar_arrive_cluster(uint32_t bar_cluster_addr) {
  asm volatile("mbarrier.arrive.shared::cluster.b64 _, [%0];" ::"r"(bar_cluster_addr) : "memory");
}
template <int ID>
__device__ __forceinline__ void mbar_arrive_cluster_now(uint32_t bar_cluster_addr, bool pred) {
  asm volatile("{\n.reg .pred p, q;\nsetp.ne.u32 p, %1, 0;\nsetp.eq.u32 q, %2, %3;\n"
               "ARR_LOOP:\n@p mbarrier.arrive.shared::cluster.b64 _, [%0];\n@q bra.uni ARR_LOOP;\n}"
               ::"r"(bar_cluster_addr), "r"((uint32_t)pred), "r"(blockIdx.y), "n"(ID) : "memory");
}
__device__ __forceinline__ void block_fence(int id) {
  asm volatile("{\n.reg .pred q;\nsetp.eq.u32 q, %0, %1;\nBF_LOOP:\n@q st.volatile.shared.u32 [%0], %0;\n@q bra.uni BF_LOOP;\n}"
               ::"r"(blockIdx.y), "r"(id) : "memory");
}
__device__ __forceinline__ void mbar_wait(uint32_t bar, uint32_t parity) {
  asm volatile("{\n.reg .pred p, q;\n.reg .u32 n;\nmov.u32 n, 0;\n"
               "WAIT_LOOP:\nmbarrier.try_wait.parity.shared::cta.b64 p, [%0], %1;\n"
               "add.u32 n, n, 1;\nsetp.lt.u32 q, n, 4194304;\nand.pred q, q, !p;\n@q bra WAIT_LOOP;\n}"
               ::"r"(bar), "r"(parity) : "memory");
}
__device__ __forceinline__ uint32_t mapa(uint32_t addr, uint32_t rank) {
  uint32_t r;
  asm volatile("mapa.shared::cluster.u32 %0, %1, %2;" : "=r"(r) : "r"(addr), "r"(rank));
  return r;
}
__device__ __forceinline__ void cluster_arrive() { asm volatile("barrier.cluster.arrive.relaxed.aligned;" ::: "memory"); }
__device__ __forceinline__ bool elect_one() {
  uint32_t p;
  asm volatile("{\n.reg .pred p;\nelect.sync _|p, 0xffffffff;\nselp.u32 %0, 1, 0, p;\n}" : "=r"(p));
  return p;
}
__device__ __forceinline__ int read_lane() { return threadIdx.x & 31; }
__device__ __forceinline__ void cluster_wait() { asm volatile("barrier.cluster.wait.acquire.aligned;" ::: "memory"); }
__device__ __forceinline__ void bar_sync(int id, int n) { asm volatile("barrier.cta.sync %0, %1;" ::"r"(id), "r"(n) : "memory"); }
__device__ __forceinline__ void bar_arrive(int id, int n) { asm volatile("barrier.cta.arrive %0, %1;" ::"r"(id), "r"(n) : "memory"); }

__device__ __forceinline__ uint64_t policy_evict_first() {
  uint64_t p;
  asm("createpolicy.fractional.L2::evict_first.b64 %0, 1.0;" : "=l"(p));
  return p;
}
__device__ __forceinline__ void tma2d_mc(uint32_t dst, const CUtensorMap* tm, int c0, int c1, uint32_t bar, uint64_t pol) {
  asm volatile("cp.async.bulk.tensor.2d.shared::cluster.global.mbarrier::complete_tx::bytes.multicast::cluster.L2::cache_hint"
               " [%0], [%1, {%2, %3}], [%4], %5, %6;"
               ::"r"(dst), "l"(tm), "r"(c0), "r"(c1), "r"(bar), "h"((uint16_t)3), "l"(pol) : "memory");
}
__device__ __forceinline__ void tma3d(uint32_t dst, const CUtensorMap* tm, int c1, int c2, uint32_t bar) {
  asm volatile("cp.async.bulk.tensor.3d.shared::cluster.global.mbarrier::complete_tx::bytes [%0], [%1, {%2, %3, %4}], [%5];"
               ::"r"(dst), "l"(tm), "r"(0), "r"(c1), "r"(c2), "r"(bar) : "memory");
}
__device__ __forceinline__ void tma2d_stream(uint32_t dst, const CUtensorMap* tm, int c0, int c1, uint32_t bar) {
  asm volatile("{\n.reg .b64 pol;\ncreatepolicy.fractional.L2::evict_first.b64 pol, 1.0;\n"
               "cp.async.bulk.tensor.2d.shared::cluster.global.mbarrier::complete_tx::bytes.L2::cache_hint [%0], [%1, {%2, %3}], [%4], pol;\n}"
               ::"r"(dst), "l"(tm), "r"(c0), "r"(c1), "r"(bar) : "memory");
}
__device__ __forceinline__ void tma2d_prefetch(const CUtensorMap* tm, int c0, int c1) {
  asm volatile("cp.async.bulk.prefetch.tensor.2d.L2.global [%0, {%1, %2}];" ::"l"(tm), "r"(c0), "r"(c1) : "memory");
}
__device__ __forceinline__ void prefetch_tmap(const CUtensorMap* tm) {
  asm volatile("prefetch.tensormap [%0];" ::"l"(tm) : "memory");
}

__device__ __forceinline__ void wg_fence() { asm volatile("wgmma.fence.sync.aligned;" ::: "memory"); }
__device__ __forceinline__ void wg_commit() { asm volatile("wgmma.commit_group.sync.aligned;" ::: "memory"); }
template <int N> __device__ __forceinline__ void wg_wait() { asm volatile("wgmma.wait_group.sync.aligned %0;" ::"n"(N) : "memory"); }

__device__ __forceinline__ uint64_t mkdesc(uint32_t addr, uint32_t lbo_bytes) {
  return (uint64_t)(((addr & 0x3FFFF) >> 4) | ((lbo_bytes >> 4) << 16)) | ((uint64_t)0x40000040u << 32);
}
__device__ __forceinline__ uint64_t mkdesc_q(uint32_t addr) {
  return (uint64_t)(((addr & 0x3FFFF) >> 4) | (64u << 16)) | ((uint64_t)8 << 32);
}
template <int N> __device__ __forceinline__ void pin(float (&a)[N]) {
#pragma unroll
  for (int i = 0; i < N; i++) asm volatile("" : "+f"(a[i])::"memory");
}
template <int N> __device__ __forceinline__ void kill(float (&a)[N]) {
#pragma unroll
  for (int i = 0; i < N; i++) asm volatile("" : "=f"(a[i]));
}
template <int N> __device__ __forceinline__ void pin(uint32_t (&a)[N]) {
#pragma unroll
  for (int i = 0; i < N; i++) asm volatile("" : "+r"(a[i])::"memory");
}

#define F8(d, o) "+f"(d[o]), "+f"(d[o + 1]), "+f"(d[o + 2]), "+f"(d[o + 3]), "+f"(d[o + 4]), "+f"(d[o + 5]), "+f"(d[o + 6]), "+f"(d[o + 7])
#define R32A "%0, %1, %2, %3, %4, %5, %6, %7, %8, %9, %10, %11, %12, %13, %14, %15, %16, %17, %18, %19, %20, %21, %22, %23, %24, %25, %26, %27, %28, %29, %30, %31"
#define R32B "%32, %33, %34, %35, %36, %37, %38, %39, %40, %41, %42, %43, %44, %45, %46, %47, %48, %49, %50, %51, %52, %53, %54, %55, %56, %57, %58, %59, %60, %61, %62, %63"

template <int TB>
__device__ __forceinline__ void mma_n128(float (&d)[64], uint32_t a0, uint32_t a1, uint32_t a2, uint32_t a3, uint64_t db, int acc) {
  asm volatile("{\n.reg .pred p;\nsetp.ne.b32 p, %69, 0;\n"
               "wgmma.mma_async.sync.aligned.m64n128k16.f32.bf16.bf16 {" R32A ", " R32B "}, {%64, %65, %66, %67}, %68, p, 1, 1, %70;\n}\n"
               : F8(d, 0), F8(d, 8), F8(d, 16), F8(d, 24), F8(d, 32), F8(d, 40), F8(d, 48), F8(d, 56)
               : "r"(a0), "r"(a1), "r"(a2), "r"(a3), "l"(db), "r"(acc), "n"(TB));
}
#define PV1(a0, a1, a2, a3, ob, acc) "add.s64 b, %92, " #ob ";\n" \
  "wgmma.mma_async.sync.aligned.m64n128k16.f32.bf16.bf16 {" R32A ", " R32B "}, {%" #a0 ", %" #a1 ", %" #a2 ", %" #a3 "}, b, " #acc ", 1, 1, 1;\n"
#define PV6 "wgmma.fence.sync.aligned;\n" PV1(64, 65, 66, 67, 0, p) PV1(68, 69, 70, 71, 128, 1) PV1(72, 73, 74, 75, 256, 1) \
  PV1(76, 77, 78, 79, 384, 1) PV1(80, 81, 82, 83, 512, 1) PV1(84, 85, 86, 87, 640, 1)
#define U4(a, o) "r"(a[o]), "r"(a[o + 1]), "r"(a[o + 2]), "r"(a[o + 3])
__device__ __forceinline__ void mma_pv(float (&d)[64], const uint32_t (&a)[28], uint64_t dv, bool acc, bool big) {
  asm volatile("{\n.reg .pred p, q;\n.reg .b64 b;\nsetp.ne.b32 p, %93, 0;\nsetp.eq.b32 q, %94, 0;\n@q bra.uni PV_SMALL;\n"
               PV6 PV1(88, 89, 90, 91, 768, 1) "wgmma.commit_group.sync.aligned;\nbra.uni PV_DONE;\n"
               "PV_SMALL:\n" PV6 "wgmma.commit_group.sync.aligned;\nPV_DONE:\n}\n"
               : F8(d, 0), F8(d, 8), F8(d, 16), F8(d, 24), F8(d, 32), F8(d, 40), F8(d, 48), F8(d, 56)
               : U4(a, 0), U4(a, 4), U4(a, 8), U4(a, 12), U4(a, 16), U4(a, 20), U4(a, 24), "l"(dv), "r"((int)acc), "r"((int)big) : "memory");
}
#define R48 R32A ", %32, %33, %34, %35, %36, %37, %38, %39, %40, %41, %42, %43, %44, %45, %46, %47"
#define R56 R48 ", %48, %49, %50, %51, %52, %53, %54, %55"
#define QK1(N, R, A, B, oa, ob, acc) "add.s64 a, " A ", " #oa ";\nadd.s64 b, " B ", " #ob ";\n" \
  "wgmma.mma_async.sync.aligned.m64n" #N "k16.f32.bf16.bf16 {" R "}, a, b, " #acc ", 1, 1, 0, 0;\n"
#define QK8(N, R, A, B) "{\n.reg .b64 a, b;\nwgmma.fence.sync.aligned;\n" QK1(N, R, A, B, 0, 0, 0) QK1(N, R, A, B, 128, 2, 1) \
  QK1(N, R, A, B, 256, 4, 1) QK1(N, R, A, B, 384, 6, 1) QK1(N, R, A, B, 512, 1024, 1) QK1(N, R, A, B, 640, 1026, 1) \
  QK1(N, R, A, B, 768, 1028, 1) QK1(N, R, A, B, 896, 1030, 1) "wgmma.commit_group.sync.aligned;\n}\n"
#define O8(d, o) "=f"(d[o]), "=f"(d[o + 1]), "=f"(d[o + 2]), "=f"(d[o + 3]), "=f"(d[o + 4]), "=f"(d[o + 5]), "=f"(d[o + 6]), "=f"(d[o + 7])
__device__ __forceinline__ void mma_qk(float (&d)[56], uint64_t dq, uint64_t dk) {
  asm volatile(QK8(112, R56, "%56", "%57")
               : O8(d, 0), O8(d, 8), O8(d, 16), O8(d, 24), O8(d, 32), O8(d, 40), O8(d, 48) : "l"(dq), "l"(dk) : "memory");
}
__device__ __forceinline__ void mma_qk(float (&d)[48], uint64_t dq, uint64_t dk) {
  asm volatile(QK8(96, R48, "%48", "%49")
               : O8(d, 0), O8(d, 8), O8(d, 16), O8(d, 24), O8(d, 32), O8(d, 40) : "l"(dq), "l"(dk) : "memory");
}
__device__ __forceinline__ void mma_n64t(float (&d)[32], uint32_t a0, uint32_t a1, uint32_t a2, uint32_t a3, uint64_t db, int acc) {
  asm volatile("{\n.reg .pred p;\nsetp.ne.b32 p, %37, 0;\n"
               "wgmma.mma_async.sync.aligned.m64n64k16.f32.bf16.bf16 {" R32A "}, {%32, %33, %34, %35}, %36, p, 1, 1, 1;\n}\n"
               : F8(d, 0), F8(d, 8), F8(d, 16), F8(d, 24)
               : "r"(a0), "r"(a1), "r"(a2), "r"(a3), "l"(db), "r"(acc));
}
__device__ __forceinline__ void mma_n8(float (&d)[4], uint64_t da, uint64_t db, int acc) {
  asm volatile("{\n.reg .pred p;\nsetp.ne.b32 p, %6, 0;\n"
               "wgmma.mma_async.sync.aligned.m64n8k16.f32.bf16.bf16 {%0, %1, %2, %3}, %4, %5, p, 1, 1, 1, 0;\n}\n"
               : "+f"(d[0]), "+f"(d[1]), "+f"(d[2]), "+f"(d[3])
               : "l"(da), "l"(db), "r"(acc));
}
__device__ __forceinline__ void hmma_k8(float (&d)[4], uint32_t a0, uint32_t a1, uint32_t b0) {
  asm volatile("mma.sync.aligned.m16n8k8.row.col.f32.bf16.bf16.f32 {%0, %1, %2, %3}, {%4, %5}, {%6}, {%0, %1, %2, %3};"
               : "+f"(d[0]), "+f"(d[1]), "+f"(d[2]), "+f"(d[3]) : "r"(a0), "r"(a1), "r"(b0));
}
__device__ __forceinline__ void hmma_k16(float (&d)[4], uint32_t a0, uint32_t a1, uint32_t a2, uint32_t a3, uint32_t b0, uint32_t b1) {
  asm volatile("mma.sync.aligned.m16n8k16.row.col.f32.bf16.bf16.f32 {%0, %1, %2, %3}, {%4, %5, %6, %7}, {%8, %9}, {%0, %1, %2, %3};"
               : "+f"(d[0]), "+f"(d[1]), "+f"(d[2]), "+f"(d[3]) : "r"(a0), "r"(a1), "r"(a2), "r"(a3), "r"(b0), "r"(b1));
}

__device__ __forceinline__ uint32_t pack2(float lo, float hi) {
  uint32_t r;
  asm("cvt.rn.bf16x2.f32 %0, %1, %2;" : "=r"(r) : "f"(hi), "f"(lo));
  return r;
}
__device__ __forceinline__ float bf_lo(uint32_t w) { return __uint_as_float(w << 16); }
__device__ __forceinline__ float bf_hi(uint32_t w) { return __uint_as_float(w & 0xFFFF0000u); }
__device__ __forceinline__ float bfr(float x) { return __bfloat162float(__float2bfloat16_rn(x)); }
__device__ __forceinline__ uint32_t sub2(uint32_t a, uint32_t b) {
  uint32_t r;
  asm("sub.rn.bf16x2 %0, %1, %2;" : "=r"(r) : "r"(a), "r"(b));
  return r;
}
__device__ __forceinline__ uint32_t add2(uint32_t a, uint32_t b) {
  uint32_t r;
  asm("add.rn.bf16x2 %0, %1, %2;" : "=r"(r) : "r"(a), "r"(b));
  return r;
}
__device__ __forceinline__ uint32_t fma2(uint32_t a, uint32_t b, uint32_t c) {
  uint32_t r;
  asm("fma.rn.bf16x2 %0, %1, %2, %3;" : "=r"(r) : "r"(a), "r"(b), "r"(c));
  return r;
}
__device__ __forceinline__ float ex2(float x) {
  float r;
  asm("ex2.approx.ftz.f32 %0, %1;" : "=f"(r) : "f"(x));
  return r;
}
__device__ __forceinline__ float rcp(float x) {
  float r;
  asm("rcp.approx.ftz.f32 %0, %1;" : "=f"(r) : "f"(x));
  return r;
}
__device__ __forceinline__ float silu_f(float t) { return t * rcp(1.0f + ex2(-1.4426950408889634f * t)); }
__device__ __forceinline__ void lds128(uint32_t a, uint32_t& x, uint32_t& y, uint32_t& z, uint32_t& w) {
  asm volatile("ld.shared.v4.u32 {%0, %1, %2, %3}, [%4];" : "=r"(x), "=r"(y), "=r"(z), "=r"(w) : "r"(a) : "memory");
}
__device__ __forceinline__ void ldsm4(uint32_t a, uint32_t& x, uint32_t& y, uint32_t& z, uint32_t& w) {
  asm volatile("ldmatrix.sync.aligned.m8n8.x4.shared.b16 {%0, %1, %2, %3}, [%4];" : "=r"(x), "=r"(y), "=r"(z), "=r"(w) : "r"(a) : "memory");
}
constexpr uint32_t TAG = 0x10000;
__device__ __forceinline__ void st_gran(uint4* p, uint32_t x, uint32_t y, uint32_t z, uint32_t w) {
  asm volatile("st.relaxed.gpu.global.v4.b32 [%0], {%1, %2, %3, %4};" ::"l"(p), "r"(x), "r"(y), "r"(z), "r"(w) : "memory");
}
__device__ __forceinline__ void ld_gran(const uint4* p, uint32_t& x, uint32_t& y, uint32_t& z, uint32_t& w) {
  asm volatile("ld.relaxed.gpu.global.v4.b32 {%0, %1, %2, %3}, [%4];" : "=r"(x), "=r"(y), "=r"(z), "=r"(w) : "l"(p) : "memory");
}
__device__ __forceinline__ void stsm4(uint32_t a, uint32_t x, uint32_t y, uint32_t z, uint32_t w) {
  asm volatile("stmatrix.sync.aligned.m8n8.x4.shared.b16 [%0], {%1, %2, %3, %4};" ::"r"(a), "r"(x), "r"(y), "r"(z), "r"(w) : "memory");
}
__device__ __forceinline__ void cp16(uint32_t dst, const void* src) {
  asm volatile("cp.async.cg.shared.global [%0], [%1], 16;" ::"r"(dst), "l"(src) : "memory");
}
__device__ __forceinline__ void cp_wait_all() { asm volatile("cp.async.wait_all;" ::: "memory"); }
__device__ __forceinline__ void add_granules(float (&red)[32], const uint32_t (&g)[16]) {
#pragma unroll
  for (int i = 0; i < 16; i++) { red[2 * i] += bf_lo(g[i]); red[2 * i + 1] += bf_hi((i & 3) ? g[i] : g[i] & ~TAG); }
}
__device__ __forceinline__ bool granules_ok(const uint32_t (&g)[16], uint32_t tag) {
  uint32_t a, b;
  asm("lop3.b32 %0, %1, %2, %3, 0x7E;" : "=r"(a) : "r"(g[0]), "r"(g[4]), "r"(tag));
  asm("lop3.b32 %0, %1, %2, %3, 0x7E;" : "=r"(b) : "r"(g[8]), "r"(g[12]), "r"(tag));
  return __all_sync(0xffffffffu, ((a | b) & TAG) == 0);
}
__device__ __forceinline__ unsigned ld_acquire(const unsigned* p) {
  unsigned v;
  asm volatile("ld.acquire.gpu.global.u32 %0, [%1];" : "=r"(v) : "l"(p) : "memory");
  return v;
}
__device__ __forceinline__ unsigned atom_add_acq_rel(unsigned* p) {
  unsigned v;
  asm volatile("atom.acq_rel.gpu.global.add.u32 %0, [%1], 1;" : "=r"(v) : "l"(p) : "memory");
  return v;
}
__device__ __forceinline__ void st_release(unsigned* p, unsigned v) {
  asm volatile("st.release.gpu.global.u32 [%0], %1;" ::"l"(p), "r"(v) : "memory");
}

struct LnAcc {
  float sm[2][4], sq[8][4];
  __device__ __forceinline__ void clear() {
#pragma unroll
    for (int i = 0; i < 4; i++) {
      sm[0][i] = sm[1][i] = 0.f;
#pragma unroll
      for (int j = 0; j < 8; j++) sq[j][i] = 0.f;
    }
  }
};
template <int K0, int K1>
__device__ __forceinline__ void ln_fetch(uint32_t (&xa)[144], uint32_t boxes, uint32_t lo) {
#pragma unroll
  for (int k = K0; k < K1; k++) ldsm4(boxes + (k >> 2) * 8192 + (lo ^ ((k & 3) << 5)), xa[4 * k], xa[4 * k + 1], xa[4 * k + 2], xa[4 * k + 3]);
}
__device__ __forceinline__ void ln_accum1(LnAcc& a, int h, uint32_t x0, uint32_t x1, uint32_t x2, uint32_t x3) {
  const uint32_t ONES = 0x3F803F80u;
  hmma_k16(a.sm[h], x0, x1, x2, x3, ONES, ONES);
  hmma_k8(a.sq[4 * h], x0, x1, x0);
  hmma_k8(a.sq[4 * h + 1], x0, x1, x1);
  hmma_k8(a.sq[4 * h + 2], x2, x3, x2);
  hmma_k8(a.sq[4 * h + 3], x2, x3, x3);
}
template <int K0, int K1>
__device__ __forceinline__ void ln_accum(const uint32_t (&xa)[144], LnAcc& a) {
#pragma unroll
  for (int k = K0; k < K1; k++) ln_accum1(a, k & 1, xa[4 * k], xa[4 * k + 1], xa[4 * k + 2], xa[4 * k + 3]);
}
__device__ __forceinline__ void ln_row(float sum, float sq, float& mean_b, float& rstd) {
  const float mean = sum * (1.0f / DM);
  const uint32_t mv = pack2(mean, fmaxf(sq * (1.0f / DM) - mean * mean, 0.0f));
  mean_b = bf_lo(mv);
  float sd;
  asm("sqrt.approx.f32 %0, %1;" : "=f"(sd) : "f"(bf_lo(pack2(bf_hi(mv) + 1e-5f, 0.f))));
  rstd = rcp(bf_lo(pack2(sd, 0.f)));
}
__device__ __forceinline__ void ln_diag(const LnAcc& a, int lane, float& t0, float& t1) {
  const bool odd = (lane >> 2) & 1;
  t0 = odd ? (a.sq[0][1] + a.sq[2][1]) + (a.sq[4][1] + a.sq[6][1]) : (a.sq[0][0] + a.sq[2][0]) + (a.sq[4][0] + a.sq[6][0]);
  t1 = odd ? (a.sq[1][3] + a.sq[3][3]) + (a.sq[5][3] + a.sq[7][3]) : (a.sq[1][2] + a.sq[3][2]) + (a.sq[5][2] + a.sq[7][2]);
}
__device__ __forceinline__ void ln_stats(const LnAcc& a, int lane, float& mean0, float& rstd0, float& mean1, float& rstd1) {
  float t0, t1;
  ln_diag(a, lane, t0, t1);
  const int src = (lane & ~3) | (lane >> 3);
  t0 = __shfl_sync(0xffffffffu, t0, src);
  t1 = __shfl_sync(0xffffffffu, t1, src);
  ln_row(a.sm[0][0] + a.sm[1][0], t0, mean0, rstd0);
  ln_row(a.sm[0][2] + a.sm[1][2], t1, mean1, rstd1);
}

template <bool ROUTED>
__device__ __forceinline__ uint32_t gate2(uint32_t x2, float mean_b, float rstd, float2 upd = make_float2(0.f, 0.f)) {
  const uint32_t xc = sub2(x2, pack2(mean_b, mean_b));
  uint32_t t = pack2(bf_lo(xc) * rstd, bf_hi(xc) * rstd);
  if (ROUTED) t = pack2(bf_lo(t) + upd.x, bf_hi(t) + upd.y);
  return pack2(silu_f(bf_lo(t)), silu_f(bf_hi(t)));
}

#define PF_D 4
#define X_SPLIT 38
#define X_SPLITA 36
#define X_SPLITS 32
#define X_SPLITSA 30
#define X_PA 8
#define X_PG 2
#define X_E0 10
#define X_F2 10
#define X_LD 0
#define X_ORDER 0
#define X_PFX 1
#define X_F1 0
#define X_BF2 1
#define X_EARLY 1
template <int V> struct IC { static constexpr int value = V; };

struct Ctx {
  uint32_t sb;
  uint8_t* sp;
  uint32_t rank;
  Scratch* g;
};

template <class LoadX>
__device__ __forceinline__ void attn_producer(const Ctx& cx, int qb, int hs, const CUtensorMap* tmKV,
                                              const CUtensorMap* tmWq, const CUtensorMap* tmWo, LoadX load_x) {
  const uint32_t full = cx.sb + SM_FULL, empty = cx.sb + SM_EMPTY, ring = cx.sb + SM_RING + cx.rank * 16384;
  const uint64_t last_use = policy_evict_first();
  auto acquire = [&](uint32_t r, uint32_t n, uint32_t bytes) {
    mbar_wait(empty + 8 * r, (n ^ (r >> 1) ^ 1) & 1);
    mbar_expect_tx(full + 8 * r, bytes);
  };
  int st = 0;
#pragma unroll 1
  for (int p = 0; p < 4; p++) {
    const int n0 = (hs * 4 + (p ^ (p >> 1))) * DH + cx.rank * 64;
#pragma unroll 1
    for (int i = 0; i < 5; i++, st++) {
      const uint32_t r = (st ^ ((st >> 1) & 1)) & 3;
      acquire(r, st >> 2, i == 2 ? 16384 : 32768);
      const int k0 = i < 3 ? 128 * i : 128 * i - 64;
      tma2d_mc(ring + r * STAGE, tmWq, n0, k0, full + 8 * r, last_use);
      if (i != 2) tma2d_mc(ring + r * STAGE + 8192, tmWq, n0, k0 + 64, full + 8 * r, last_use);
      if (st < 3) TSP(72 + st)
      if (X_ORDER && X_ORDER < 3 && st == X_ORDER - 1) load_x(1);
      if (st == 1) {
#pragma unroll 1
        for (int b = 8 + qb; b < 72; b += 16) tma2d_prefetch(tmWq, (hs * 4 + ((b / 18) ^ (b / 36))) * DH + (b & 1) * 64, ((b % 18) >> 1) * 64);
      }
      if (st == 8 && qb < 2 * PF_D) tma2d_prefetch(tmKV + ((qb >> 1) & 1), cx.rank * 64, hs * 2 * SEQ + (qb >> 2) * 96);
    }
  }
  uint32_t r = 0, n = 5;
#pragma unroll 1
  for (int u = 0; u < NST_KV; u++) {
    const bool big = blk_big(u >> 1);
    acquire(r, n, big ? 112 * 256 : 96 * 256);
    tma2d_mc(ring + r * STAGE, tmKV + (u & 1) + (big ? 0 : 2), cx.rank * 64, hs * 2 * SEQ + blk_row(u >> 1), full + 8 * r, last_use);
    if (((u ^ (qb >> 1)) & 7) == 0 && u + PF_D < NST_KV)
      tma2d_prefetch(tmKV + ((u + PF_D) & 1), cx.rank * 64, hs * 2 * SEQ + blk_row((u + PF_D) >> 1));
    if ((unsigned)(u - 32) < 36 && (u & 15) == qb) tma2d_prefetch(tmWo, ((u - 32) >> 2) * 64, hs * 512 + (u & 3) * 128);
    if (++r == 3) { r = 0; n++; }
  }
#pragma unroll 1
  for (int u = 0; u < NST_O; u++) {
    const int s = u >> 1;
    const int blk = s == 0 ? 8 : ((hs + s) & 7);
    r = (u + 1) & 3;
    acquire(r, (u >> 2) ^ (u >> 1), 32768);
    tma2d_mc(ring + r * STAGE, tmWo, blk * 64, hs * 512 + ((u & 1) + cx.rank * 2) * 128, full + 8 * r, last_use);
  }
}

__device__ __forceinline__ void attn_gate(const Ctx& cx, int qb, int hs, int t, const __nv_bfloat16* x) {
  uint4 nx = *(const uint4*)(x + (size_t)(qb * 128 + (t >> 3)) * DM + hs * 64 + (t & 7) * 8);
  bar_sync(BAR_GATE, 352);
#pragma unroll 1
  for (int ch = t; ch < 1152; ch += 96) {
    const uint4 v = nx;
    const int n = ch + 96;
    if (n < 1152) nx = *(const uint4*)(x + (size_t)(qb * 128 + (n < 1024 ? n >> 3 : hs * 16 + ((n - 1024) >> 3))) * DM + (n < 1024 ? hs * 64 : 512) + (t & 7) * 8);
    const int lr = ch < 1024 ? ch >> 3 : hs * 16 + ((ch - 1024) >> 3);
    const float2 st = *(const float2*)(cx.sp + SM_STATS + 8 * lr);
    cx.g->gate[((qb * 128 + lr) * DM + (ch < 1024 ? hs * 64 : 512) + (t & 7) * 8) >> 3] =
        make_uint4(gate2<false>(v.x, st.x, st.y), gate2<false>(v.y, st.x, st.y), gate2<false>(v.z, st.x, st.y), gate2<false>(v.w, st.x, st.y));
  }
}

constexpr uint32_t SM_XO = SM_SLOT, SM_GO = SM_SLOT + 128 * 144;
constexpr uint32_t SM_X8 = SM_SLOT + 2 * STAGE + 20480, SM_G8 = SM_X8 + 16 * 144;
__device__ __forceinline__ void attn_stage_xg(const Ctx& cx, int qb, int hs, int t, const __nv_bfloat16* x) {
  bar_sync(BAR_OA, 352);
#pragma unroll 1
  for (int ch = t; ch < 1024; ch += 64) {
    const size_t o = (size_t)(qb * 128 + (ch >> 3)) * DM + hs * 64 + (ch & 7) * 8;
    cp16(cx.sb + SM_XO + (ch >> 3) * 144 + (ch & 7) * 16, x + o);
    cp16(cx.sb + SM_GO + (ch >> 3) * 144 + (ch & 7) * 16, (const __nv_bfloat16*)cx.g->gate + o);
  }
  cp_wait_all();
  mbar_arrive(cx.sb + SM_BAR_XG);
}

__device__ __forceinline__ void attn_helper(const Ctx& cx, int qb, int hs, int lane, const __nv_bfloat16* x) {
  unsigned e = 0;
  if (lane == 0) {
    e = cx.g->launch[blockIdx.x];
    cx.g->launch[blockIdx.x] = e + 1;
  }
  e = __shfl_sync(0xffffffffu, e, 0);
  bar_sync(BAR_HELPER, 128);
#pragma unroll 1
  for (int n = 0; n < (1 << 16) && ld_acquire(&cx.g->ffn_flag) != e + 1; n++) __nanosleep(1000);
  const uint32_t tag = (~e & 1) * TAG;
  {
#pragma unroll 1
    for (int i = 0; i < 2 * TOPC; i++) {
      const int lr = __ldcg(&cx.g->idx[i >> 1]) - qb * 128, col = ((i & 1) ? 512 : hs * 64) + 2 * lane;
      if ((i & 1) ? (lr >> 4) == hs : (lr >> 7) == 0) {
        const float2 st = *(const float2*)(cx.sp + SM_STATS + 8 * lr);
        const int o = (qb * 128 + lr) * DM + col;
        *(uint32_t*)((__nv_bfloat16*)cx.g->gate + o) =
            gate2<true>(*(const uint32_t*)(x + o), st.x, st.y, __ldcg((const float2*)(cx.g->upd + (i >> 1) * DM + col)));
      }
    }
  }
  if (lane == 0) *(uint32_t*)(cx.sp + SM_TAG) = tag;
  __syncwarp();
  if (lane == 0) mbar_arrive(cx.sb + SM_BAR_MISC);

  const uint4* src = cx.g->part + (size_t)((qb * 64 + 56) * 2 + (hs >> 2)) * 4 * 128 + (hs & 3) * 32 + lane;
  const uint32_t stg = cx.sb + SM_SLOT + 2 * STAGE + lane * 16;
  bar_sync(BAR_OA, 352);

#pragma unroll 1
  for (int i = 0; i < 4; i++) {
    const int ch = i * 32 + lane;
    const size_t o = (size_t)(qb * 128 + hs * 16 + (ch >> 3)) * DM + 512 + (ch & 7) * 8;
    cp16(cx.sb + SM_X8 + (ch >> 3) * 144 + (ch & 7) * 16, x + o);
    cp16(cx.sb + SM_G8 + (ch >> 3) * 144 + (ch & 7) * 16, (const __nv_bfloat16*)cx.g->gate + o);
  }
#pragma unroll 1
  for (int n = 0; n < (1 << 16); n++) {
    __nanosleep(n ? 500 : 2000);
    uint32_t a, b, d, t;
    ld_gran(src - lane + (lane & 7) * (2 * 4 * 128) + 3 * 128 + 31, a, b, d, t);
    if (__all_sync(0xffffffffu, (a & TAG) == tag)) break;
  }
#pragma unroll 1
  for (int n = 0; n < (1 << 16); n++) {
#pragma unroll 1
    for (int i = 0; i < 8; i++) {
#pragma unroll
      for (int g = 0; g < 4; g++) cp16(stg + (i * 4 + g) * 512, src + i * (2 * 4 * 128) + g * 128);
    }
    cp_wait_all();
    uint32_t bad = 0;
#pragma unroll 4
    for (int i = 0; i < 32; i++) bad |= *(const volatile uint32_t*)(cx.sp + SM_SLOT + 2 * STAGE + lane * 16 + i * 512) ^ tag;
    if (__all_sync(0xffffffffu, (bad & TAG) == 0)) break;
  }

}
__device__ __forceinline__ void attn_finish8(const Ctx& cx, int qb, int hs, int hw, int lane, __nv_bfloat16* out) {
  bar_sync(BAR_GATE, 96);
#pragma unroll 1
  for (int g = hw; g < 4; g += 3) {
    float acc[8] = {0.f, 0.f, 0.f, 0.f, 0.f, 0.f, 0.f, 0.f};
#pragma unroll 2
    for (int sidx = 0; sidx < 8; sidx++) {
      uint32_t a, b, d, t;
      lds128(cx.sb + SM_SLOT + 2 * STAGE + lane * 16 + (sidx * 4 + g) * 512, a, b, d, t);
      acc[0] += bf_lo(a); acc[1] += bf_hi(a & ~TAG); acc[2] += bf_lo(b); acc[3] += bf_hi(b);
      acc[4] += bf_lo(d); acc[5] += bf_hi(d); acc[6] += bf_lo(t); acc[7] += bf_hi(t);
    }
#pragma unroll
    for (int j = 0; j < 4; j++) {
      const int o = ((lane >> 2) + (j & 1) * 8) * 144 + (2 * g + (j >> 1)) * 16 + (lane & 3) * 4;
      uint32_t* xp = (uint32_t*)(cx.sp + SM_X8 + o);
      const uint32_t xw = *xp, gw = *(const uint32_t*)(cx.sp + SM_G8 + o);
      *xp = fma2(pack2(acc[2 * j], acc[2 * j + 1]), gw, xw);
    }
  }
  bar_sync(BAR_GATE, 96);
  for (int ch = hw * 32 + lane; ch < 128; ch += 96)
    *(uint4*)(out + (size_t)(qb * 128 + hs * 16 + (ch >> 3)) * DM + 512 + (ch & 7) * 8) =
        *(const uint4*)(cx.sp + SM_X8 + (ch >> 3) * 144 + (ch & 7) * 16);
}

constexpr float SUM_HI = 1.8446744e19f, SUM_LO = 9.0949470e-13f;

template <int LO, int HI, int N>
__device__ __forceinline__ void softmax_exp(float (&s)[N]) {
#pragma unroll
  for (int i = LO; i < HI; i++) s[i] = ex2(s[i]);
}
__device__ __forceinline__ void sum_tree(const uint32_t (&pf)[28], bool big, uint32_t& h0, uint32_t& h1) {
  uint32_t t0 = add2(add2(pf[16], pf[18]), add2(pf[20], pf[22])), t1 = add2(add2(pf[17], pf[19]), add2(pf[21], pf[23]));
  if (big) { t0 = add2(t0, add2(pf[24], pf[26])); t1 = add2(t1, add2(pf[25], pf[27])); }
  h0 = add2(add2(add2(add2(pf[0], pf[2]), add2(pf[4], pf[6])), add2(add2(pf[8], pf[10]), add2(pf[12], pf[14]))), t0);
  h1 = add2(add2(add2(add2(pf[1], pf[3]), add2(pf[5], pf[7])), add2(add2(pf[9], pf[11]), add2(pf[13], pf[15]))), t1);
}
__device__ __forceinline__ void exact_attention(float (&o)[64], float& l0, float& l1, uint32_t qaddr, const __nv_bfloat16* kh,
                                                const __nv_bfloat16* vh, int lane) {
  const int off = (lane >> 2) * DH + (lane & 3) * 2;
  float m0 = -3.0e38f, m1 = -3.0e38f;
  l0 = l1 = 0.f;
#pragma unroll
  for (int i = 0; i < 64; i++) o[i] = 0.f;
#pragma unroll 1
  for (int key = 0; key < SEQ; key += 16) {
    const __nv_bfloat16 *kp = kh + key * DH + off, *vp = vh + key * DH + off;
    float d0[4] = {0.f, 0.f, 0.f, 0.f}, d1[4] = {0.f, 0.f, 0.f, 0.f};
#pragma unroll 4
    for (int k = 0; k < 8; k++) {
      uint32_t q0, q1, q2, q3;
      ldsm4(qaddr + k * 2048, q0, q1, q2, q3);
      hmma_k16(d0, q0, q1, q2, q3, *(const uint32_t*)(kp + k * 16), *(const uint32_t*)(kp + k * 16 + 8));
      hmma_k16(d1, q0, q1, q2, q3, *(const uint32_t*)(kp + 8 * DH + k * 16), *(const uint32_t*)(kp + 8 * DH + k * 16 + 8));
    }
    float x0 = fmaxf(fmaxf(d0[0], d0[1]), fmaxf(d1[0], d1[1])), x1 = fmaxf(fmaxf(d0[2], d0[3]), fmaxf(d1[2], d1[3]));
    x0 = fmaxf(x0, __shfl_xor_sync(0xffffffffu, x0, 1));
    x1 = fmaxf(x1, __shfl_xor_sync(0xffffffffu, x1, 1));
    x0 = fmaxf(fmaxf(x0, __shfl_xor_sync(0xffffffffu, x0, 2)), m0);
    x1 = fmaxf(fmaxf(x1, __shfl_xor_sync(0xffffffffu, x1, 2)), m1);
    const float sc0 = ex2(m0 - x0), sc1 = ex2(m1 - x1);
    m0 = x0; m1 = x1;
    const uint32_t p0 = pack2(ex2(d0[0] - m0), ex2(d0[1] - m0)), p1 = pack2(ex2(d0[2] - m1), ex2(d0[3] - m1)),
                   p2 = pack2(ex2(d1[0] - m0), ex2(d1[1] - m0)), p3 = pack2(ex2(d1[2] - m1), ex2(d1[3] - m1));
    l0 = fmaf(l0, sc0, (bf_lo(p0) + bf_hi(p0)) + (bf_lo(p2) + bf_hi(p2)));
    l1 = fmaf(l1, sc1, (bf_lo(p1) + bf_hi(p1)) + (bf_lo(p3) + bf_hi(p3)));
#pragma unroll
    for (int nb = 0; nb < 16; nb++) {
      uint32_t b0, b1;
      asm("movmatrix.sync.aligned.m8n8.trans.b16 %0, %1;" : "=r"(b0) : "r"(*(const uint32_t*)(vp + nb * 8)));
      asm("movmatrix.sync.aligned.m8n8.trans.b16 %0, %1;" : "=r"(b1) : "r"(*(const uint32_t*)(vp + 8 * DH + nb * 8)));
      o[4 * nb] *= sc0; o[4 * nb + 1] *= sc0; o[4 * nb + 2] *= sc1; o[4 * nb + 3] *= sc1;
      hmma_k16(*(float (*)[4])&o[4 * nb], p0, p1, p2, p3, b0, b1);
    }
  }
}
__device__ __forceinline__ int fresh_lane() {
  int l;
  asm volatile("mov.u32 %0, %%laneid;" : "=r"(l));
  return l;
}
__device__ __forceinline__ bool inv_sums(float l0, float l1, float& i0, float& i1) {
  l0 += __shfl_xor_sync(0xffffffffu, l0, 1); l1 += __shfl_xor_sync(0xffffffffu, l1, 1);
  l0 += __shfl_xor_sync(0xffffffffu, l0, 2); l1 += __shfl_xor_sync(0xffffffffu, l1, 2);
  i0 = rcp(l0);
  i1 = rcp(l1);
  return !(l0 + l1 <= SUM_HI) | (fminf(l0, l1) < SUM_LO);
}
template <int LO, int HI>
__device__ __forceinline__ void park(uint32_t a, const float (&o)[64], float i0, float i1, bool on = true) {
#pragma unroll
  for (int i = LO; i < HI; i++)
    asm volatile("{\n.reg .pred p;\nsetp.ne.u32 p, %5, 0;\n@p stmatrix.sync.aligned.m8n8.x4.shared.b16 [%0], {%1, %2, %3, %4};\n}"
                 ::"r"(a + i * 2048), "r"(pack2(o[8 * i] * i0, o[8 * i + 1] * i0)), "r"(pack2(o[8 * i + 2] * i1, o[8 * i + 3] * i1)),
                 "r"(pack2(o[8 * i + 4] * i0, o[8 * i + 5] * i0)), "r"(pack2(o[8 * i + 6] * i1, o[8 * i + 7] * i1)), "r"((uint32_t)on) : "memory");
}

template <int I, int NP, int E0, int N, int NS>
__device__ __forceinline__ void exp_park(float (&s)[NS], uint32_t a, const float (&o)[64], float i0, float i1, bool on, int id) {
  if constexpr (I < NP) {
    constexpr int E1 = E0 + (N - E0) * X_PG / (NP - I);
    softmax_exp<E0, E1>(s);
    park<I, I + X_PG>(a, o, i0, i1, on);
    if (I + X_PG < NP) {
#pragma unroll
      for (int i = E0; i < E1; i++) asm volatile("" : "+f"(s[i])::"memory");
      block_fence(id + I);
    }
    exp_park<I + X_PG, NP, E1, N>(s, a, o, i0, i1, on, id);
  }
}

__device__ __forceinline__ void attn_consumer(const Ctx& cx, int qb, int hs, int wg, int cw, int lane, const __nv_bfloat16* x,
                                              const __nv_bfloat16* kc, const __nv_bfloat16* vc, __nv_bfloat16* out) {
  const uint32_t full = cx.sb + SM_FULL;
  const uint32_t ring = cx.sb + SM_RING;
  const uint32_t qwg = ring + wg * 16384;
  auto qlane = [&](int l) { return qwg + (cw & 3) * 256 + (l >> 4) * 1024 + (l & 15) * 16; };
  const bool signaller = lane == 0 && (cw & 3) < 2;
  const int my_turn = 1 + wg, other_turn = 2 - wg;

  float oA[64], oB[64], i0, i1;
  uint32_t xl[32];
  uint32_t empty_c;
  {
    const int r = lane >> 2, c = lane & 3;
    const int lr0 = cw * 16 + r;
    uint32_t xa[144];
    float rstd0, rstd1, sq0, sq1;
    {
      const uint32_t xb = cx.sb + SM_X + wg * 73728, xf = cx.sb + SM_XFULL + wg * 24;
      const uint32_t lo = ((cw & 3) * 16 + (lane & 15)) * 128 + (((lane >> 4) ^ (lane & 7)) << 4);
      LnAcc a;
      a.clear();
      prof(wg, 0);
      empty_c = mapa(cx.sb + SM_EMPTY, cw & 1);
      TS4(1)
      mbar_wait(xf, 0);
      TS4(2)
      ln_fetch<0, 12>(xa, xb, lo);
      ln_accum<0, 12>(xa, a);
      mbar_wait(xf + 8, 0);
      TS4(3)
      ln_fetch<12, 24>(xa, xb, lo);
      if (wg == 0) {
        bar_sync(4, 128);
        if (signaller) {
          asm volatile("mbarrier.arrive.shared::cluster.b64 _, [%0], 2;" ::"r"(empty_c + 16) : "memory");
          asm volatile("mbarrier.arrive.shared::cluster.b64 _, [%0], 2;" ::"r"(empty_c + 24) : "memory");
        }
      }
      ln_accum<12, 24>(xa, a);
      mbar_wait(xf + 16, 0);
      TS4(4)
      prof(wg, 1);
      ln_fetch<24, 36>(xa, xb, lo);
#pragma unroll
      for (int k = 24; k < 36; k++) hmma_k16(a.sm[k & 1], xa[4 * k], xa[4 * k + 1], xa[4 * k + 2], xa[4 * k + 3], 0x3F803F80u, 0x3F803F80u);
      ln_diag(a, lane, sq0, sq1);
      if (c != (r >> 1)) sq0 = sq1 = 0.f;
      rstd0 = a.sm[0][0] + a.sm[1][0];
      rstd1 = a.sm[0][2] + a.sm[1][2];
    }
    const uint32_t mm0 = pack2(rstd0 * (1.0f / DM), rstd0 * (1.0f / DM)), mm1 = pack2(rstd1 * (1.0f / DM), rstd1 * (1.0f / DM));
#pragma unroll
    for (int i = 0; i < 16; i++) { xa[2 * i] = sub2(xa[2 * i], mm0); xa[2 * i + 1] = sub2(xa[2 * i + 1], mm1); }
    pin(xa);
    prof(wg, 2);
    TS4(5)

    float (&acc)[64] = oB;
#pragma unroll 1
    for (int p = 0; p < 4; p++) {
      const int st0 = p * 5;
#pragma unroll
      for (int i = 0; i < 5; i++) {
        if (i == 4 && p == 3) break;
        const int st = st0 + i;
        const uint32_t sl = (st ^ ((st >> 1) & 1)) & 3, slp = ((st - 1) ^ (((st - 1) >> 1) & 1)) & 3;
        mbar_wait(full + 8 * sl, (st >> 2) & 1);
        TS4(8 + 2 * st)
        const bool join = wg && p == 3;
        if (p && i != (wg ? 4 : 1) && !(join && i == 3)) bar_sync(my_turn, 256);
        wg_fence();
        const uint64_t db = mkdesc(ring + sl * STAGE, 16384);
        const int kb0 = i < 3 ? 8 * i : 8 * i - 4;
#pragma unroll
        for (int k = 0; k < (i == 2 ? 4 : 8); k++) {
          const int kb = kb0 + k;
          mma_n128<1>(acc, xa[4 * kb], xa[4 * kb + 1], xa[4 * kb + 2], xa[4 * kb + 3], db + k * 128, kb > 0);
        }
        wg_commit();
        TS4(9 + 2 * st)
        if (wg ? (i == 4 || (p && (i < 2 || i == (join ? 3 : 2)))) : (p && i)) bar_arrive(other_turn, 256);
        if (p == 0 && i < 4) {
          if (i < 2) {
#pragma unroll
            for (int j = 48 + 12 * i; j < 60 + 12 * i; j++) {
              sq0 = fmaf(bf_lo(xa[2 * j]), bf_lo(xa[2 * j]), fmaf(bf_hi(xa[2 * j]), bf_hi(xa[2 * j]), sq0));
              sq1 = fmaf(bf_lo(xa[2 * j + 1]), bf_lo(xa[2 * j + 1]), fmaf(bf_hi(xa[2 * j + 1]), bf_hi(xa[2 * j + 1]), sq1));
            }
          }
          if (i == 1) {
            sq0 += __shfl_xor_sync(0xffffffffu, sq0, 1); sq1 += __shfl_xor_sync(0xffffffffu, sq1, 1);
            sq0 += __shfl_xor_sync(0xffffffffu, sq0, 2); sq1 += __shfl_xor_sync(0xffffffffu, sq1, 2);
            float mean0, mean1;
            ln_row(rstd0, sq0, mean0, rstd0);
            ln_row(rstd1, sq1, mean1, rstd1);
            if (c == 0) {
              *(float2*)(cx.sp + SM_STATS + 8 * lr0) = make_float2(mean0, rstd0);
              *(float2*)(cx.sp + SM_STATS + 8 * (lr0 + 8)) = make_float2(mean1, rstd1);
            }
            *((uint32_t*)(cx.sp + SM_COLD) + wg) = 0;
            bar_arrive(BAR_GATE, 352);
            bar_sync(4 + wg, 128);
            rstd0 *= SM_SCALE_LOG2;
            rstd1 *= SM_SCALE_LOG2;
          }
#pragma unroll
          for (int j = 0; j < 72; j++)
            if (j >= 2 * (i < 2 ? 8 * i + 8 : 8 * i + 4) && j < 2 * (i == 0 ? 16 : 8 * i + 12)) {
              xa[2 * j] = sub2(xa[2 * j], mm0);
              xa[2 * j + 1] = sub2(xa[2 * j + 1], mm1);
            }
          pin(xa);
        }
        if (i == 0) {
          if (wg) {
            wg_wait<0>();
            if (signaller) mbar_arrive_cluster(empty_c + 8 * sl);
          }
        } else if (i == 2) {
          if (!join) {
            wg_wait<0>();
            if (signaller) mbar_arrive_cluster(empty_c + 8 * sl);
          }
        } else if (i != 3) {
          wg_wait<1>();
          if (signaller && (i == 4 || !wg)) mbar_arrive_cluster(empty_c + 8 * slp);
          wg_wait<0>();
          if (signaller) mbar_arrive_cluster(empty_c + 8 * sl);
        }
      }
      if (p == 3) break;
      pin(acc);
      prof(wg, 3 + p);
      TS4(50 + 2 * p)
      park<0, 8>(qlane(lane) + (4 + p) * STAGE, acc, rstd0, rstd1);
      asm volatile("fence.proxy.async.shared::cta;" ::: "memory");
      TS4(51 + 2 * p)
    }
    wg_wait<1>();
    if (signaller && wg) mbar_arrive_cluster(empty_c + 8 * 1);
    wg_wait<0>();
    pin(acc);
    prof(wg, 6);
#pragma unroll
    for (int i = 0; i < 32; i++) xl[i] = xa[112 + i];
    i0 = rstd0;
    i1 = rstd1;
  }

  uint32_t oa[128];
  float acc[32];
  {
    uint32_t pf[28];
    uint32_t bad = 0;
    float lA0 = 0.f, lA1 = 0.f, lB0 = 0.f, lB1 = 0.f;
    int t = 0;
    uint32_t ra = 0, rb = 2 * 2048, rc = 0, par = 1;
    const uint64_t dk0 = mkdesc(ring, 16), dv0 = mkdesc(ring, 16384);
    uint64_t dqA = mkdesc_q(qwg + 4 * STAGE), dqB = dqA + 2048;
    auto turn = [&](auto kc_, auto bc_) {
      constexpr int KIND = decltype(kc_)::value, BIG = decltype(bc_)::value;
      constexpr int HB = KIND == 1, ID = 10 * KIND + 30 * BIG, T0 = BIG ? 38 : 0;
      constexpr int NS = BIG ? 56 : 48, SPLIT = BIG ? (HB ? X_SPLIT : X_SPLITA) : (HB ? X_SPLITS : X_SPLITSA);
      float s[NS];
      float (&op)[64] = HB ? oA : oB;
      uint32_t h0 = 0, h1 = 0;
      TS2(0)
      bar_sync(my_turn, 256);
      TS2(1)
      if (KIND) { pin(pf); pin(op); }
      mma_qk(s, HB ? dqB : dqA, dk0 + (HB ? ra : rc));
      TS2(2)
      if (KIND) {
        const bool bigp = HB ? BIG : BIG ? t != 10 : t == 66;
        if (X_BF2) block_fence(ID + 9);
        pin(pf);
        sum_tree(pf, bigp, h0, h1);
        asm volatile("" : "+r"(h0), "+r"(h1)::"memory");
        if (HB) mbar_wait(full + (rb >> 8), par);
        mma_pv(op, pf, dv0 + rb, t != T0 + 2 - HB, bigp);
      } else {
        mbar_wait(full + (rb >> 8), (NST_Q - 1) >> 2 & 1);
#pragma unroll
        for (int k = 0; k < 8; k++) mma_n128<1>(op, xl[4 * k], xl[4 * k + 1], xl[4 * k + 2], xl[4 * k + 3], dv0 + rb + k * 128, 1);
        wg_commit();
      }
      TS2(3)
      bar_arrive(other_turn, 256);
      (HB ? lA0 : lB0) += bf_lo(h0) + bf_hi(h0);
      (HB ? lA1 : lB1) += bf_lo(h1) + bf_hi(h1);
      wg_wait<1>();
      pin(s);
      TS1(t)
      TS2(4)
      if (KIND == 1) mbar_arrive_cluster_now<ID + 3>(empty_c + (ra >> 8), signaller);
      if (BIG && t == T0 + HB) {
        const uint32_t a = qlane(fresh_lane()) + (4 + HB) * STAGE;
        const bool ok = !__any_sync(0xffffffffu, inv_sums(HB ? lB0 : lA0, HB ? lB1 : lA1, i0, i1));
        bad = (HB ? bad : 0) | (ok ? 0 : 1 << HB);
        (HB ? lB0 : lA0) = 0.f;
        (HB ? lB1 : lA1) = 0.f;
        softmax_exp<0, X_E0>(s);
#pragma unroll
        for (int i = 0; i < X_E0; i++) asm volatile("" : "+f"(s[i])::"memory");
        block_fence(ID + 7);
        exp_park<0, X_PA, X_E0, SPLIT>(s, a, HB ? oB : oA, i0, i1, ok, 200 + ID);
        if (!HB) dqB += 2048;
        prof(wg, 8 + HB);
        if (!HB && cw == 0) bar_arrive(BAR_HELPER, 128);
      } else {
        if (HB && !BIG) bad = (bad & 3) | (inv_sums(lA0, lA1, i0, i1) ? 4 : 0);
        softmax_exp<0, SPLIT>(s);
      }
      pin(s);
      if (!BIG) block_fence(ID + 4);
      TS2(5)
      wg_wait<0>();
      TS2(6)
      pin(op);
      if (KIND) pin(pf); else pin(xl);
      if (HB) {
        par ^= rc == 0;
        if (BIG && t == 37) dqA -= 2048;
      } else {
        mbar_arrive_cluster_now<ID + 5>(empty_c + (rb >> 8), signaller);
        if (KIND) {
          par ^= ra == 0;
          const uint32_t x = ra;
          ra = rc; rc = rb; rb = x;
        }
      }
      softmax_exp<SPLIT, NS>(s);
#pragma unroll
      for (int i = 0; i < NS / 2; i++) pf[i] = pack2(s[2 * i], s[2 * i + 1]);
      pin(pf);
      if (KIND == 0) {
        block_fence(ID + 6);
        park<0, 8>(qlane(fresh_lane()) + 3 * STAGE, oB, i0, i1);
        asm volatile("fence.proxy.async.shared::cta;" ::: "memory");
        prof(wg, 7);
      }
      if (BIG && X_PA < 8 && t == T0 + HB) park<X_PA, 8>(qlane(fresh_lane()) + (4 + HB) * STAGE, HB ? oB : oA, i0, i1, !(bad >> HB));
      if (HB) mbar_wait(full + (rc >> 8), par);
      t++;
    };
#pragma unroll
    for (int i = 24; i < 28; i++) asm volatile("" : "=r"(pf[i]));
    mbar_wait(full, (NST_Q >> 2) & 1);
    turn(IC<0>(), IC<0>());
    rb = 2048; rc = 2 * 2048;
    kill(oA);
    const bool never = blockIdx.y == 1;
#pragma unroll 1
    while (true) {
      turn(IC<1>(), IC<0>());
      if (t == 76) break;
      if (t == 10) {
#pragma unroll 1
        do {
#pragma unroll 1
          do turn(IC<2>(), IC<1>()); while (never);
          turn(IC<1>(), IC<1>());
        } while (t != 66);
      }
#pragma unroll 1
      do turn(IC<2>(), IC<0>()); while (never);
    }
    const uint32_t ql = qlane(fresh_lane());
    auto scale = [&](auto lo, auto hi) {
#pragma unroll
      for (int i = decltype(lo)::value; i < decltype(hi)::value; i++) {
        oa[32 + 2 * i] = pack2(oA[4 * i] * i0, oA[4 * i + 1] * i0);
        oa[32 + 2 * i + 1] = pack2(oA[4 * i + 2] * i1, oA[4 * i + 3] * i1);
        asm volatile("" : "+r"(oa[32 + 2 * i]), "+r"(oa[32 + 2 * i + 1])::"memory");
      }
    };
    TS3(1)
    if (X_LD == 0) {
#pragma unroll
      for (int i = 0; i < 8; i++) ldsm4(ql + 4 * STAGE + i * 2048, oa[4 * i], oa[4 * i + 1], oa[4 * i + 2], oa[4 * i + 3]);
    }
    {
      uint32_t h0, h1;
      sum_tree(pf, false, h0, h1);
      if (inv_sums(lB0 + (bf_lo(h0) + bf_hi(h0)), lB1 + (bf_lo(h1) + bf_hi(h1)), lB0, lB1)) bad |= 8;
    }
    scale(IC<0>(), IC<X_F1>());
    volatile uint32_t* const cold = (volatile uint32_t*)(cx.sp + SM_COLD) + wg;
    if (bad) *cold = 1;
    block_fence(93);
    TS3(2)
    bar_sync(my_turn, 256);
    const uint32_t is_cold = *cold;
    TS3(3)
    pin(pf); pin(oB);
    mma_pv(oB, pf, dv0, true, false);
    mbar_arrive_cluster_now<91>(empty_c + 8 * 3, signaller && !is_cold);
    TS3(4)
    if (X_LD == 1) {
#pragma unroll
      for (int i = 0; i < 8; i++) ldsm4(ql + 4 * STAGE + i * 2048, oa[4 * i], oa[4 * i + 1], oa[4 * i + 2], oa[4 * i + 3]);
    }
    const uint64_t db = mkdesc(ring + STAGE, 16);
    scale(IC<X_F1>(), IC<X_F2>());
    block_fence(94);
#pragma unroll
    for (int i = 0; i < 32; i++) asm volatile("" : "+r"(oa[i])::"memory");
    wg_fence();
#pragma unroll
    for (int k = 0; k < 8; k++) mma_n64t(acc, oa[4 * k], oa[4 * k + 1], oa[4 * k + 2], oa[4 * k + 3], db + k * 128, k > 0);
    if (X_F2 < 16) {
      wg_commit();
      block_fence(95);
      scale(IC<X_F2>(), IC<16>());
      TS3(5)
      wg_fence();
    }
#pragma unroll
    for (int k = 8; k < 16; k++) mma_n64t(acc, oa[4 * k], oa[4 * k + 1], oa[4 * k + 2], oa[4 * k + 3], db + k * 128, 1);
    wg_commit();
    bar_arrive(other_turn, 256);
    wg_wait<(X_F2 < 16 ? 2 : 1)>();
    pin(oB); pin(pf);
    TS(76)
    TS3(6)
    if (signaller) mbar_arrive_cluster(empty_c);
#pragma unroll
    for (int i = 16; i < 24; i++) ldsm4(ql + 5 * STAGE + (i & 7) * 2048, oa[4 * i], oa[4 * i + 1], oa[4 * i + 2], oa[4 * i + 3]);
#pragma unroll
    for (int i = 0; i < 16; i++) {
      oa[96 + 2 * i] = pack2(oB[4 * i] * lB0, oB[4 * i + 1] * lB0);
      oa[96 + 2 * i + 1] = pack2(oB[4 * i + 2] * lB1, oB[4 * i + 3] * lB1);
    }
    TS3(7)
    mbar_wait(full + 8 * 2, 0);
    TS3(8)
    wg_wait<0>();
    pin(acc); pin(oa);
    if (__any_sync(0xffffffffu, is_cold)) {
      bad = __reduce_or_sync(0xffffffffu, bad);
      if (!(bad & 8)) {
#pragma unroll
        for (int i = 24; i < 32; i++) stsm4(ql + 6 * STAGE + (i & 7) * 2048, oa[4 * i], oa[4 * i + 1], oa[4 * i + 2], oa[4 * i + 3]);
      }
#pragma unroll 1
      for (int h = 0; h < 4; h++) {
        if (bad >> h & 1) {
          const uint32_t a = ql + ((0x6354 >> (4 * h)) & 7) * STAGE;
          const size_t o = (size_t)(hs * 2 + (h >> 1)) * SEQ * DH;
          float ox[64], l0, l1;
          exact_attention(ox, l0, l1, a, kc + o, vc + o, fresh_lane());
          inv_sums(l0, l1, l0, l1);
          __syncwarp();
          park<0, 8>(a, ox, l0, l1);
        }
      }
      __syncwarp();
#pragma unroll
      for (int i = 0; i < 32; i++)
        if ((i >> 3) != 1 || (bad & 4))
          ldsm4(ql + ((0x6534 >> (4 * (i >> 3))) & 7) * STAGE + (i & 7) * 2048, oa[4 * i], oa[4 * i + 1], oa[4 * i + 2], oa[4 * i + 3]);
      pin(oa);
      asm volatile("fence.proxy.async.shared::cta;" ::: "memory");
      bar_sync(4 + wg, 128);
      if (signaller) mbar_arrive_cluster(empty_c + 8 * 3);
      wg_fence();
#pragma unroll
      for (int k = 0; k < 16; k++) mma_n64t(acc, oa[4 * k], oa[4 * k + 1], oa[4 * k + 2], oa[4 * k + 3], db + k * 128, k > 0);
      wg_commit();
      wg_wait<0>();
      pin(acc);
    }
    if (signaller) mbar_arrive_cluster(empty_c + 8 * 1);
  }

  prof(wg, 10);
  TS3(9)
  {
    lane = fresh_lane();
    const int tw = (cw & 3) * 32 + lane;
    float red[32];
    kill(red);
    uint32_t tag = 0;
    uint4* const xch = cx.g->part + (size_t)(qb * 64 * 2 + wg) * 4 * 128 + tw;
    int nrx = 1;
    auto region = [](int s, int h) { return (2 * s + h + 1) & 3; };
    auto half_step = [&](int s, auto hc, bool arrive) {
      constexpr int h = decltype(hc)::value;
      const uint64_t db = mkdesc(ring + region(s, h) * STAGE, 16);
      bar_sync(my_turn, 256);
      pin(oa);
      wg_fence();
#pragma unroll
      for (int k = 0; k < 16; k++) {
        const int kb = h * 16 + k;
        mma_n64t(acc, oa[4 * kb], oa[4 * kb + 1], oa[4 * kb + 2], oa[4 * kb + 3], db + k * 128, kb > 0);
      }
      wg_commit();
      if (arrive) bar_arrive(other_turn, 256);
    };
    auto await = [&](int s, int h) { mbar_wait(full + 8 * region(s, h), ((s >> 1) ^ s) & 1); };
    auto fetch = [&](uint32_t (&g)[16], int n) {
      const uint4* p = xch + (hs * 7 + n - 1) * (2 * 4 * 128);
#pragma unroll
      for (int i = 0; i < 4; i++) ld_gran(p + i * 128, g[4 * i], g[4 * i + 1], g[4 * i + 2], g[4 * i + 3]);
    };
    uint32_t g[16];
#pragma unroll 1
    for (int s = 0; s < 8; s++) {
      const bool pend = nrx < s - 1;
      if (pend) fetch(g, nrx);
      half_step(s, IC<1>(), true);
      TS3(s < 3 ? 16 + 8 * s : 75)
      if (s == 0) {
        mbar_wait(cx.sb + SM_BAR_MISC, 0);
        tag = *(const volatile uint32_t*)(cx.sp + SM_TAG);
        bar_arrive(BAR_OA, 352);
#pragma unroll
        for (int i = 0; i < 32; i++) red[i] = 0.f;
      }
      await(s + 1, 0);
      TS3(s < 3 ? 17 + 8 * s : 75)
      wg_wait<0>();
      TS3(s < 3 ? 18 + 8 * s : 75)
      if (signaller && s < 7) mbar_arrive_cluster(empty_c + 8 * region(s, 1));
      pin(acc);
      TS(77 + s)
      prof(wg, 12 + s);
      uint4* p = xch + (s == 0 ? 56 + hs : ((hs + s) & 7) * 7 + s - 1) * (2 * 4 * 128);
#pragma unroll
      for (int i = 0; i < 4; i++)
        st_gran(p + i * 128, (pack2(acc[8 * i], acc[8 * i + 1]) & ~TAG) | tag, pack2(acc[8 * i + 2], acc[8 * i + 3]),
                pack2(acc[8 * i + 4], acc[8 * i + 5]), pack2(acc[8 * i + 6], acc[8 * i + 7]));
      TS3(s < 3 ? 19 + 8 * s : 75)
      half_step(s + 1, IC<0>(), true);
      TS3(s < 3 ? 20 + 8 * s : 75)
      await(s + 1, 1);
      TS3(s < 3 ? 21 + 8 * s : 75)
      if (pend && granules_ok(g, tag)) { add_granules(red, g); nrx++; }
      if (X_EARLY == 2 && s == 7) fetch(g, nrx);
      wg_wait<0>();
      TS3(s < 3 ? 22 + 8 * s : 75)
      if (signaller && s < 6) mbar_arrive_cluster(empty_c + 8 * region(s + 1, 0));
    }
    uint32_t xv[16], gt[16], g2[16];
    if (X_EARLY < 2) fetch(g, nrx);
    mbar_wait(cx.sb + SM_BAR_XG, 0);
    const bool two = nrx < 7;
    bool ok;
    {
      const uint64_t db = mkdesc(ring + 2 * STAGE, 16);
      if (X_EARLY == 2) ok = granules_ok(g, tag);
      bar_sync(my_turn, 256);
      if (X_EARLY == 2) fetch(g2, 7);
#pragma unroll
      for (int i = 64; i < 128; i++) asm volatile("" : "+r"(oa[i])::"memory");
      wg_fence();
#pragma unroll
      for (int k = 16; k < 32; k++) mma_n64t(acc, oa[4 * k], oa[4 * k + 1], oa[4 * k + 2], oa[4 * k + 3], db + (k - 16) * 128, 1);
      wg_commit();
      if (wg == 0) bar_arrive(other_turn, 256);
    }
    if (X_EARLY < 2) {
      ok = granules_ok(g, tag);
      fetch(g2, 7);
    }
    const uint32_t frag = (cw * 16 + (lane & 15)) * 144 + (lane >> 4) * 16;
#pragma unroll
    for (int i = 0; i < 4; i++) {
      ldsm4(cx.sb + SM_XO + frag + i * 32, xv[4 * i], xv[4 * i + 1], xv[4 * i + 2], xv[4 * i + 3]);
      ldsm4(cx.sb + SM_GO + frag + i * 32, gt[4 * i], gt[4 * i + 1], gt[4 * i + 2], gt[4 * i + 3]);
    }
    if (ok) { add_granules(red, g); nrx++; }
    wg_wait<0>();
    pin(acc);
    TS(85)
#pragma unroll
    for (int i = 0; i < 32; i++) red[i] += acc[i];
    pin(red);
    block_fence(90);
    int last = 8;
    if (two && granules_ok(g2, tag)) { add_granules(red, g2); last = 7; }
#pragma unroll 1
    for (int spins = 0; nrx < last && spins < (1 << 16); spins++) {
      fetch(g, nrx);
      if (granules_ok(g, tag)) { add_granules(red, g); nrx++; }
    }
    prof(wg, 20);
    TS(86)
    const uint32_t ot = ring + 3 * STAGE + cw * (16 * 144);
    uint32_t ow[16];
#pragma unroll
    for (int i = 0; i < 16; i++) ow[i] = fma2(pack2(red[2 * i], red[2 * i + 1]), gt[i], xv[i]);
#pragma unroll
    for (int i = 0; i < 4; i++)
      stsm4(ot + (lane & 15) * 144 + (2 * i + (lane >> 4)) * 16, ow[4 * i], ow[4 * i + 1], ow[4 * i + 2], ow[4 * i + 3]);
    __syncwarp();
#pragma unroll
    for (int i = 0; i < 4; i++) {
      uint4 v;
      lds128(ot + (i * 4 + (lane >> 3)) * 144 + (lane & 7) * 16, v.x, v.y, v.z, v.w);
      *(uint4*)(out + (size_t)(qb * 128 + cw * 16 + i * 4 + (lane >> 3)) * DM + hs * 64 + (lane & 7) * 8) = v;
    }
    prof(wg, 22);
    TS(87)
    TS_DUMP()
  }
}

constexpr int FST_X = 24, FST_END = FST_X + 14 * 12;
__device__ __forceinline__ void ffn_producer(const Ctx& cx, int f, const CUtensorMap* tmX, const CUtensorMap* tmG,
                                             const CUtensorMap* tmU, const CUtensorMap* tmD) {
  const uint32_t full = cx.sb + SM_FULL, empty = cx.sb + SM_EMPTY;
  int pair = -2, u = 0;
#pragma unroll 1
  for (int st = 0; st < FST_END; st++) {
    const uint32_t sl = st & 7;
    const int unit = pair * 2 + (u & 1), k = u >> 1, k3 = k >= 3 ? k - 3 : k;
    if (unit < 27) {
      mbar_wait(empty + 8 * sl, ((st >> 3) & 1) ^ 1);
      mbar_expect_tx(full + 8 * sl, FSTAGE);
      if (pair < 0) tma3d(cx.sb + sl * FSTAGE, tmX, f * 512 + ((pair + 2) * 4 + (k >= 3) * 2 + (u & 1)) * 64, k3 * 3, full + 8 * sl);
      else if (pair < 9) tma2d_stream(cx.sb + sl * FSTAGE, k < 3 ? tmG : tmU, f * 1152 + unit * 64, k3 * 192, full + 8 * sl);
      else tma2d_stream(cx.sb + sl * FSTAGE, tmD, (unit - 18) * 64, f * 1152 + k * 192, full + 8 * sl);
    }
    if (++u == 12) { u = 0; pair++; }
  }
}

__device__ __forceinline__ void ffn_consumer(const Ctx& cx, int f, int wg, int cw, int lane, const __nv_bfloat16* x,
                                             const __nv_bfloat16* w_r) {
  const int r = lane >> 2, c = lane & 3, tid = cw * 32 + lane;
  unsigned e = 0;
  if (tid == 0) {
    e = cx.g->launch[blockIdx.x];
    cx.g->launch[blockIdx.x] = e + 1;
    *(unsigned*)(cx.sp + SM_TAG) = e;
  }
  if (tid < 72) *(uint4*)(cx.sp + SM_H + tid * 16) = *(const uint4*)(w_r + tid * 8);
  bar_sync(3, 256);
  prof(wg, 0);
  const uint32_t full = cx.sb + SM_FULL, empty = cx.sb + SM_EMPTY;
  const bool signaller = (tid & 127) == 0;
#pragma unroll 1
  for (int b = wg; b < 8; b += 2) {
    const int row0 = f * 512 + b * 64 + (cw & 3) * 16 + r;
    const uint32_t lo = ((cw & 3) * 16 + (lane & 15)) * 128 + (((lane >> 4) ^ (lane & 7)) << 4);
    LnAcc a;
    a.clear();
#pragma unroll 1
    for (int bx = 0; bx < 9; bx++) {
      const int st = (b >> 1) * 6 + (bx / 3) * 2 + wg;
      if (bx % 3 == 0) mbar_wait(full + 8 * (st & 7), (st >> 3) & 1);
#pragma unroll
      for (int k = 0; k < 4; k++) {
        uint32_t x0, x1, x2, x3;
        ldsm4(cx.sb + (st & 7) * FSTAGE + (bx % 3) * 8192 + (lo ^ (k << 5)), x0, x1, x2, x3);
        ln_accum1(a, k & 1, x0, x1, x2, x3);
      }
    }
    prof(wg, 8 + (b >> 1) * 3);
    float mean0, rstd0, mean1, rstd1;
    ln_stats(a, lane, mean0, rstd0, mean1, rstd1);
    prof(wg, 9 + (b >> 1) * 3);
    const uint32_t mm0 = pack2(mean0, mean0), mm1 = pack2(mean1, mean1);
    float d0[4] = {0, 0, 0, 0}, d1[4] = {0, 0, 0, 0};
#pragma unroll 1
    for (int bx = 0; bx < 9; bx++) {
      const int st = (b >> 1) * 6 + (bx / 3) * 2 + wg;
#pragma unroll
      for (int k = 0; k < 4; k++) {
        uint32_t n[4];
        ldsm4(cx.sb + (st & 7) * FSTAGE + (bx % 3) * 8192 + (lo ^ (k << 5)), n[0], n[1], n[2], n[3]);
        const uint8_t* wp = cx.sp + SM_H + (bx * 4 + k) * 32 + 4 * c;
#pragma unroll
        for (int i = 0; i < 4; i++) {
          const uint32_t t = sub2(n[i], (i & 1) ? mm1 : mm0);
          const float rs = (i & 1) ? rstd1 : rstd0;
          n[i] = pack2(bf_lo(t) * rs, bf_hi(t) * rs);
        }
        if (k & 1) hmma_k16(d1, n[0], n[1], n[2], n[3], *(const uint32_t*)wp, *(const uint32_t*)(wp + 16));
        else hmma_k16(d0, n[0], n[1], n[2], n[3], *(const uint32_t*)wp, *(const uint32_t*)(wp + 16));
      }
    }
    prof(wg, 10 + (b >> 1) * 3);
    bar_sync(4 + wg, 128);
    if (signaller) {
#pragma unroll
      for (int i = 0; i < 3; i++) mbar_arrive(empty + 8 * (((b >> 1) * 6 + i * 2 + wg) & 7));
    }
    if (c == 0) {
      cx.g->r[row0] = bfr(d0[0] + d1[0]);
      cx.g->r[row0 + 8] = bfr(d0[2] + d1[2]);
      cx.g->stats[row0] = make_float2(mean0, rstd0);
      cx.g->stats[row0 + 8] = make_float2(mean1, rstd1);
    }
  }
  prof(wg, 1);
  bar_sync(3, 256);
  e = *(const unsigned*)(cx.sp + SM_TAG);
  if (tid == 0) {
    atom_add_acq_rel(&cx.g->rcnt);
#pragma unroll 1
    for (int n = 0; n < (1 << 16) && (int)(ld_acquire(&cx.g->rcnt) - 4 * (e + 1)) < 0; n++) {}
  }
  bar_sync(3, 256);
  prof(wg, 2);
  uint32_t key[8];
#pragma unroll
  for (int i = 0; i < 8; i++) {
    const int row = i * 256 + tid;
    const uint32_t b = __float_as_uint(__ldcg(&cx.g->r[row])) >> 16;
    key[i] = (((b & 0x8000u) ? (~b & 0xFFFFu) : (b | 0x8000u)) << 16) | (uint32_t)(0xFFFF - row);
  }
  int mysel = 0;
#pragma unroll 1
  for (int k = 0; k < TOPC; k++) {
    uint32_t m = key[0];
#pragma unroll
    for (int i = 1; i < 8; i++) m = max(m, key[i]);
    m = __reduce_max_sync(0xffffffffu, m);
    uint32_t* tk = (uint32_t*)(cx.sp + SM_TOPK) + (k & 1) * 8;
    if (lane == 0) tk[cw] = m;
    bar_sync(3, 256);
    m = __reduce_max_sync(0xffffffffu, tk[lane & 7]);
#pragma unroll
    for (int i = 0; i < 8; i++) if (key[i] == m) key[i] = 0;
    if (k == cw) mysel = 0xFFFF - (int)(m & 0xFFFF);
  }
  {
    const float2 st = __ldcg(&cx.g->stats[mysel]);
    const uint32_t mm = pack2(st.x, st.x);
#pragma unroll 3
    for (int i = 0; i < 9; i++) {
      const uint32_t t = sub2(*(const uint32_t*)(x + (size_t)mysel * DM + i * 64 + 2 * lane), mm);
      *(uint32_t*)(cx.sp + SM_XSEL + i * 1024 + cw * 128 + (((lane >> 2) ^ cw) << 4) + (lane & 3) * 4) =
          pack2(bf_lo(t) * st.y, bf_hi(t) * st.y);
    }
    if (lane == 0) *(int*)(cx.sp + SM_IDX + 4 * cw) = mysel;
  }
  asm volatile("fence.proxy.async.shared::cta;" ::: "memory");
  bar_sync(3, 256);
  prof(wg, 3);
  auto run = [&](float (&acc)[4], int st, int n, uint32_t b) {
#pragma unroll 1
    for (int u = 0; u < n; u++, st += 2, b += 3072) {
      const uint32_t sl = st & 7;
      mbar_wait(full + 8 * sl, (st >> 3) & 1);
      wg_fence();
      const uint64_t da = mkdesc(cx.sb + sl * FSTAGE, 16), db = mkdesc(b, 16);
#pragma unroll
      for (int k = 0; k < 12; k++) mma_n8(acc, da + k * 128, db + (k >> 2) * 64 + (k & 3) * 2, u > 0 || k > 0);
      wg_commit();
      wg_wait<0>();
      if (signaller) mbar_arrive(empty + 8 * sl);
    }
    pin(acc);
  };
#pragma unroll 1
  for (int unit = wg; unit < 27; unit += 2) {
    if (unit >> 1 == 9) {
      asm volatile("fence.proxy.async.shared::cta;" ::: "memory");
      bar_sync(3, 256);
      prof(wg, 4);
    }
    const bool gu = unit < 18;
    float a0[4], a1[4];
#pragma unroll 1
    for (int m = 0; m < (gu ? 2 : 1); m++) {
      run(a1, FST_X + (unit >> 1) * 12 + m * 6 + wg, gu ? 3 : 6, cx.sb + (gu ? SM_XSEL : SM_H));
      if (m == 0) { a0[0] = a1[0]; a0[1] = a1[1]; a0[2] = a1[2]; a0[3] = a1[3]; }
    }
#pragma unroll
    for (int i = 0; i < 4; i++) {
      const int fl = (cw & 3) * 16 + r + (i >> 1) * 8, tok = 2 * c + (i & 1);
      if (gu) {
        const float h = bfr(silu_f(bfr(a0[i]))) * bfr(a1[i]);
        *(__nv_bfloat16*)(cx.sp + SM_H + unit * 1024 + tok * 128 + (((fl >> 3) ^ tok) << 4) + (fl & 7) * 2) = __float2bfloat16_rn(h);
      } else {
        cx.g->ypart[(f * TOPC + tok) * DM + (unit - 18) * 64 + fl] = a1[i];
      }
    }
  }
  prof(wg, 5);
  bar_sync(3, 256);
  if (tid == 0) *(unsigned*)(cx.sp + SM_TOPK) = atom_add_acq_rel(&cx.g->ycnt) == 4 * e + 3;
  bar_sync(3, 256);
  if (*(const unsigned*)(cx.sp + SM_TOPK)) {
    const int row = *(const int*)(cx.sp + SM_IDX + 4 * cw);
    const float rs = bfr(rcp(1.0f + ex2(-1.4426950408889634f * __ldcg(&cx.g->r[row]))));
#pragma unroll 1
    for (int d = lane * 2; d < DM; d += 192) {
#pragma unroll
      for (int i = 0; i < 3; i++) {
        const float* p = cx.g->ypart + cw * DM + d + i * 64;
        const float2 a = __ldcg((const float2*)p), b = __ldcg((const float2*)(p + TOPC * DM)),
                     e2 = __ldcg((const float2*)(p + 2 * TOPC * DM)), h = __ldcg((const float2*)(p + 3 * TOPC * DM));
        const uint32_t y = pack2((a.x + b.x) + (e2.x + h.x), (a.y + b.y) + (e2.y + h.y));
        const uint32_t u = pack2(bf_lo(y) * rs, bf_hi(y) * rs);
        *(float2*)(cx.g->upd + cw * DM + d + i * 64) = make_float2(bf_lo(u), bf_hi(u));
      }
    }
    if (lane == 0) cx.g->idx[cw] = row;
    bar_sync(3, 256);
    if (tid == 0) st_release(&cx.g->ffn_flag, e + 1);
    prof(wg, 6);
  }
}

struct KvMaps { CUtensorMap m[4]; };
__global__ void __cluster_dims__(2, 1, 1) __launch_bounds__(THREADS, 1)
fused_kernel(const __nv_bfloat16* __restrict__ x, const __nv_bfloat16* __restrict__ w_r, const __nv_bfloat16* __restrict__ kc,
             const __nv_bfloat16* __restrict__ vc, __nv_bfloat16* __restrict__ out, Scratch* scratch,
             const __grid_constant__ CUtensorMap tmX, const __grid_constant__ CUtensorMap tmWq,
             const __grid_constant__ KvMaps tmKV, const __grid_constant__ CUtensorMap tmWo,
             const __grid_constant__ CUtensorMap tmG, const __grid_constant__ CUtensorMap tmU,
             const __grid_constant__ CUtensorMap tmD) {
  extern __shared__ __align__(1024) uint8_t smem_raw[];
  prof(0, 23, 511);
  if (X_PFX && threadIdx.x == 160) { prefetch_tmap(&tmX); prefetch_tmap(&tmWq); }
  Ctx cx;
  cx.sb = smem_u32(smem_raw);
  cx.sp = smem_raw;
  cx.g = scratch;
  cx.rank = blockIdx.x & 1;
  const int warp = __shfl_sync(0xffffffffu, threadIdx.x >> 5, 0);
  const int cluster = blockIdx.x >> 1;
  const bool is_ffn = blockIdx.x >= N_ATT_CTA;
  const int c7 = ((cluster - 36) * 37) >> 8;
  const int hs = cluster < 4 ? 4 + cluster : cluster < 36 ? (cluster - 4) >> 3 : 4 + c7;
  const int qb = (cluster < 4 ? 0 : cluster < 36 ? (cluster - 4) & 7 : cluster - 35 - 7 * c7) * 2 + cx.rank;

  auto load_x = [&](int w) {
#pragma unroll
    for (int i = 0; i < 3; i++) {
      mbar_expect_tx(cx.sb + SM_XFULL + 24 * w + 8 * i, 24576);
      tma3d(cx.sb + SM_X + (3 * w + i) * 24576, &tmX, qb * 128 + w * 64, i * 3, cx.sb + SM_XFULL + 24 * w + 8 * i);
    }
  };
  if (warp < 4) {
    asm volatile("setmaxnreg.dec.sync.aligned.u32 24;");
    if (elect_one()) {
      if (warp == 0) {
        TSP(64)
#pragma unroll
        for (int i = 0; i < 4; i++) mbar_init(cx.sb + SM_FULL + 8 * i, 1);
#pragma unroll
        for (int i = 3; i < 6; i++) if (X_ORDER != 3) mbar_init(cx.sb + SM_XFULL + 8 * i, 1);
        TSP(65)
      } else if (warp == 1) {
#pragma unroll
        for (int i = 0; i < 4; i++) mbar_init(cx.sb + SM_EMPTY + 8 * i, is_ffn ? 1 : 4);
        mbar_init(cx.sb + SM_BAR_MISC, 1);
        mbar_init(cx.sb + SM_BAR_XG, 64);
      } else if (warp == 2) {
        if (is_ffn) { prefetch_tmap(&tmG); prefetch_tmap(&tmU); prefetch_tmap(&tmD); }
        else if (!X_PFX) prefetch_tmap(&tmWq);
      } else if (is_ffn) {
#pragma unroll
        for (int i = 4; i < 8; i++) { mbar_init(cx.sb + SM_FULL + 8 * i, 1); mbar_init(cx.sb + SM_EMPTY + 8 * i, 1); }
      }
      asm volatile("fence.mbarrier_init.release.cluster;" ::: "memory");
    }
    __syncwarp();
    cluster_arrive();
    if (X_ORDER == 0 && warp == 0 && !is_ffn && elect_one()) {
      load_x(1);
    }
    __syncwarp();
    if (warp == 0) TSP(70)
    cluster_wait();
    if (warp == 0) TSP(71)
    prof(0, 24, 511);
    if (warp == 0) {
      if (elect_one()) {
        if (is_ffn) ffn_producer(cx, blockIdx.x - N_ATT_CTA, &tmX, &tmG, &tmU, &tmD);
        else attn_producer(cx, qb, hs, tmKV.m, &tmWq, &tmWo, load_x);
        prof(0, 25, 511);
      }
    } else if (!is_ffn) {
      attn_gate(cx, qb, hs, threadIdx.x - 32, x);
      if (warp == 1) attn_helper(cx, qb, hs, read_lane(), x);
      else { bar_arrive(BAR_HELPER, 128); attn_stage_xg(cx, qb, hs, threadIdx.x - 64, x); }
      attn_finish8(cx, qb, hs, warp - 1, read_lane(), out);
    }
    __syncwarp();
    cluster_arrive();
    cluster_wait();
  } else {
    if ((warp == 4 || (X_ORDER == 3 && warp == 8)) && !is_ffn && elect_one()) {
      const int w = X_ORDER == 3 ? warp >> 3 : 0;
#pragma unroll
      for (int i = 0; i < 3; i++) mbar_init(cx.sb + SM_XFULL + 24 * w + 8 * i, 1);
      asm volatile("fence.mbarrier_init.release.cluster;" ::: "memory");
      if (!w) TSP(66)
      load_x(w);
      if (!w) TSP(67)
    }
    __syncwarp();
    cluster_arrive();
    asm volatile("setmaxnreg.inc.sync.aligned.u32 240;");
    cluster_wait();
    const int cw = warp - 4, wg = cw >> 2;
    if (is_ffn) ffn_consumer(cx, blockIdx.x - N_ATT_CTA, wg, cw, read_lane(), x, w_r);
    else attn_consumer(cx, qb, hs, wg, cw, read_lane(), x, kc, vc, out);
  }
}

typedef CUresult (*EncodeFn)(CUtensorMap*, CUtensorMapDataType, cuuint32_t, void*, const cuuint64_t*, const cuuint64_t*,
                             const cuuint32_t*, const cuuint32_t*, CUtensorMapInterleave, CUtensorMapSwizzle,
                             CUtensorMapL2promotion, CUtensorMapFloatOOBfill);

void encode(EncodeFn fn, CUtensorMap* m, const void* p, int rank, const cuuint64_t* dims, const cuuint64_t* strides,
            const cuuint32_t* box) {
  const cuuint32_t es[5] = {1, 1, 1, 1, 1};
  fn(m, CU_TENSOR_MAP_DATA_TYPE_BFLOAT16, rank, const_cast<void*>(p), dims, strides, box, es, CU_TENSOR_MAP_INTERLEAVE_NONE,
     CU_TENSOR_MAP_SWIZZLE_128B, CU_TENSOR_MAP_L2_PROMOTION_L2_128B, CU_TENSOR_MAP_FLOAT_OOB_FILL_NONE);
}
void encode2d(EncodeFn fn, CUtensorMap* m, const void* p, uint64_t rows, uint64_t cols, uint32_t box_rows) {
  const cuuint64_t dims[2] = {cols, rows}, strides[1] = {cols * 2};
  const cuuint32_t box[2] = {64, box_rows};
  encode(fn, m, p, 2, dims, strides, box);
}

}

extern "C" void kernel_launch(void* const* d_in, const int* in_sizes, int n_in, void* d_out, int out_size) {
  (void)in_sizes; (void)n_in; (void)out_size;
  void* fnp = nullptr;
  cudaDriverEntryPointQueryResult qr;
  cudaGetDriverEntryPoint("cuTensorMapEncodeTiled", &fnp, cudaEnableDefault, &qr);
  EncodeFn fn = (EncodeFn)fnp;
  CUtensorMap tmWq, tmWo, tmG, tmU, tmD, tmX;
  KvMaps tmKV;
  for (int i = 0; i < 4; i++) encode2d(fn, &tmKV.m[i], d_in[1 + (i & 1)], 16 * SEQ, DH, i < 2 ? 112 : 96);
  encode2d(fn, &tmWq, d_in[3], DM, 4096, 64);
  {
    const cuuint64_t dims[3] = {64, SEQ, 9}, strides[2] = {DM * 2, 128};
    const cuuint32_t box[3] = {64, 64, 3};
    encode(fn, &tmX, d_in[0], 3, dims, strides, box);
  }
  encode2d(fn, &tmWo, d_in[4], 4096, DM, 128);
  encode2d(fn, &tmG, d_in[7], DM, FF, 192);
  encode2d(fn, &tmU, d_in[8], DM, FF, 192);
  encode2d(fn, &tmD, d_in[9], FF, DM, 192);
  cudaFuncSetAttribute(fused_kernel, cudaFuncAttributeMaxDynamicSharedMemorySize, SM_TOTAL);
  void* scratch = nullptr;
  cudaGetSymbolAddress(&scratch, g_scratch);
  fused_kernel<<<N_CTA, THREADS, SM_TOTAL>>>((const __nv_bfloat16*)d_in[0], (const __nv_bfloat16*)d_in[6], (const __nv_bfloat16*)d_in[1],
                                            (const __nv_bfloat16*)d_in[2], (__nv_bfloat16*)d_out, (Scratch*)scratch, tmX, tmWq, tmKV,
                                            tmWo, tmG, tmU, tmD);
}
```

```cpp
#include <cuda_runtime.h>
#include <cuda_bf16.h>
#include <cuda.h>
#include <stdint.h>

namespace {

constexpr int SEQ = 2048, DM = 576, DH = 128, FF = 4608, TOPC = 8;
constexpr int N_ATT_CTA = 128, N_CTA = 132;
constexpr int THREADS = 384;

constexpr uint32_t SM_RING = 0;
constexpr uint32_t STAGE = 32768;
constexpr uint32_t SM_SLOT = 131072;
constexpr uint32_t FSTAGE = 24576;
constexpr uint32_t SM_XSEL = 196608;
constexpr uint32_t SM_H = 205824;
constexpr uint32_t SM_MISC = 229376;
constexpr uint32_t SM_FULL = SM_MISC, SM_EMPTY = SM_MISC + 64, SM_BAR_MISC = SM_MISC + 128,
                   SM_COLD = SM_MISC + 136, SM_TAG = SM_MISC + 144,
                   SM_TOPK = SM_MISC + 192, SM_XFULL = SM_MISC + 256, SM_BAR_XG = SM_MISC + 304, SM_STATS = SM_MISC + 320;
constexpr uint32_t SM_TOTAL = SM_MISC + 1344;
constexpr uint32_t SM_X = SM_MISC - 147456;

constexpr int BAR_GATE = 6, BAR_OA = 8;
constexpr int NST_Q = 20, NST_KV = 76, NST_O = 18;
__device__ __forceinline__ bool blk_big(int j) { return (unsigned)(j - 5) < 28; }
__device__ __forceinline__ int blk_row(int j) { return 112 * j - 16 * (min(j, 5) + max(j - 33, 0)); }
constexpr float SM_SCALE_LOG2 = 0.08838834764831845f * 1.4426950408889634f;

struct Scratch {
  uint4 part[16 * 64 * 2 * 4 * 128];
  uint4 gate[N_ATT_CTA * 1152];
  float r[SEQ];
  float2 stats[SEQ];
  float ypart[4 * TOPC * DM];
  int2 sel[16];
  unsigned launch[160];
  unsigned rcnt, ycnt;
};
__device__ __align__(1024) Scratch g_scratch;

__device__ __forceinline__ void prof(int, int, int = 0) {}

#define TS(id) {}
#define TS_DUMP() {}
#define TS4(k) {}
#define TSP(k) {}
#define TS1(id) TS(id)
#define TS2(k) {}
#define TS3(k) {}

__device__ __forceinline__ uint32_t smem_u32(const void* p) { return (uint32_t)__cvta_generic_to_shared(p); }
__device__ __forceinline__ void mbar_init(uint32_t bar, uint32_t cnt) {
  asm volatile("mbarrier.init.shared::cta.b64 [%0], %1;" ::"r"(bar), "r"(cnt) : "memory");
}
__device__ __forceinline__ void mbar_expect_tx(uint32_t bar, uint32_t bytes) {
  asm volatile("mbarrier.arrive.expect_tx.shared::cta.b64 _, [%0], %1;" ::"r"(bar), "r"(bytes) : "memory");
}
__device__ __forceinline__ void mbar_arrive(uint32_t bar) {
  asm volatile("mbarrier.arrive.shared::cta.b64 _, [%0];" ::"r"(bar) : "memory");
}
__device__ __forceinline__ void mbar_arrive_cluster(uint32_t bar_cluster_addr) {
  asm volatile("mbarrier.arrive.shared::cluster.b64 _, [%0];" ::"r"(bar_cluster_addr) : "memory");
}
template <int ID>
__device__ __forceinline__ void mbar_arrive_cluster_now(uint32_t bar_cluster_addr, bool pred) {
  asm volatile("{\n.reg .pred p, q;\nsetp.ne.u32 p, %1, 0;\nsetp.eq.u32 q, %2, %3;\n"
               "ARR_LOOP:\n@p mbarrier.arrive.shared::cluster.b64 _, [%0];\n@q bra.uni ARR_LOOP;\n}"
               ::"r"(bar_cluster_addr), "r"((uint32_t)pred), "r"(blockIdx.y), "n"(ID) : "memory");
}
__device__ __forceinline__ void block_fence(int id) {
  asm volatile("{\n.reg .pred q;\nsetp.eq.u32 q, %0, %1;\nBF_LOOP:\n@q st.volatile.shared.u32 [%0], %0;\n@q bra.uni BF_LOOP;\n}"
               ::"r"(blockIdx.y), "r"(id) : "memory");
}
__device__ __forceinline__ void mbar_wait(uint32_t bar, uint32_t parity) {
  asm volatile("{\n.reg .pred p, q;\n.reg .u32 n;\nmov.u32 n, 0;\n"
               "WAIT_LOOP:\nmbarrier.try_wait.parity.shared::cta.b64 p, [%0], %1;\n"
               "add.u32 n, n, 1;\nsetp.lt.u32 q, n, 4194304;\nand.pred q, q, !p;\n@q bra WAIT_LOOP;\n}"
               ::"r"(bar), "r"(parity) : "memory");
}
__device__ __forceinline__ uint32_t mapa(uint32_t addr, uint32_t rank) {
  uint32_t r;
  asm volatile("mapa.shared::cluster.u32 %0, %1, %2;" : "=r"(r) : "r"(addr), "r"(rank));
  return r;
}
__device__ __forceinline__ void cluster_arrive() { asm volatile("barrier.cluster.arrive.relaxed.aligned;" ::: "memory"); }
__device__ __forceinline__ bool elect_one() {
  uint32_t p;
  asm volatile("{\n.reg .pred p;\nelect.sync _|p, 0xffffffff;\nselp.u32 %0, 1, 0, p;\n}" : "=r"(p));
  return p;
}
__device__ __forceinline__ int read_lane() { return threadIdx.x & 31; }
__device__ __forceinline__ void cluster_wait() { asm volatile("barrier.cluster.wait.acquire.aligned;" ::: "memory"); }
__device__ __forceinline__ void bar_sync(int id, int n) { asm volatile("barrier.cta.sync %0, %1;" ::"r"(id), "r"(n) : "memory"); }
__device__ __forceinline__ void bar_arrive(int id, int n) { asm volatile("barrier.cta.arrive %0, %1;" ::"r"(id), "r"(n) : "memory"); }

__device__ __forceinline__ uint64_t policy_evict_first() {
  uint64_t p;
  asm("createpolicy.fractional.L2::evict_first.b64 %0, 1.0;" : "=l"(p));
  return p;
}
__device__ __forceinline__ void tma2d_mc(uint32_t dst, const CUtensorMap* tm, int c0, int c1, uint32_t bar, uint64_t pol) {
  asm volatile("cp.async.bulk.tensor.2d.shared::cluster.global.mbarrier::complete_tx::bytes.multicast::cluster.L2::cache_hint"
               " [%0], [%1, {%2, %3}], [%4], %5, %6;"
               ::"r"(dst), "l"(tm), "r"(c0), "r"(c1), "r"(bar), "h"((uint16_t)3), "l"(pol) : "memory");
}
__device__ __forceinline__ void tma3d(uint32_t dst, const CUtensorMap* tm, int c1, int c2, uint32_t bar) {
  asm volatile("cp.async.bulk.tensor.3d.shared::cluster.global.mbarrier::complete_tx::bytes [%0], [%1, {%2, %3, %4}], [%5];"
               ::"r"(dst), "l"(tm), "r"(0), "r"(c1), "r"(c2), "r"(bar) : "memory");
}
__device__ __forceinline__ void tma2d_stream(uint32_t dst, const CUtensorMap* tm, int c0, int c1, uint32_t bar) {
  asm volatile("{\n.reg .b64 pol;\ncreatepolicy.fractional.L2::evict_first.b64 pol, 1.0;\n"
               "cp.async.bulk.tensor.2d.shared::cluster.global.mbarrier::complete_tx::bytes.L2::cache_hint [%0], [%1, {%2, %3}], [%4], pol;\n}"
               ::"r"(dst), "l"(tm), "r"(c0), "r"(c1), "r"(bar) : "memory");
}
__device__ __forceinline__ void bulk_load(uint32_t dst, const void* src, uint32_t bytes, uint32_t bar) {
  asm volatile("cp.async.bulk.shared::cluster.global.mbarrier::complete_tx::bytes [%0], [%1], %2, [%3];"
               ::"r"(dst), "l"(src), "r"(bytes), "r"(bar) : "memory");
}
__device__ __forceinline__ void tma2d_prefetch(const CUtensorMap* tm, int c0, int c1) {
  asm volatile("cp.async.bulk.prefetch.tensor.2d.L2.global [%0, {%1, %2}];" ::"l"(tm), "r"(c0), "r"(c1) : "memory");
}
__device__ __forceinline__ void prefetch_tmap(const CUtensorMap* tm) {
  asm volatile("prefetch.tensormap [%0];" ::"l"(tm) : "memory");
}

__device__ __forceinline__ void wg_fence() { asm volatile("wgmma.fence.sync.aligned;" ::: "memory"); }
__device__ __forceinline__ void wg_commit() { asm volatile("wgmma.commit_group.sync.aligned;" ::: "memory"); }
template <int N> __device__ __forceinline__ void wg_wait() { asm volatile("wgmma.wait_group.sync.aligned %0;" ::"n"(N) : "memory"); }

__device__ __forceinline__ uint64_t mkdesc(uint32_t addr, uint32_t lbo_bytes) {
  return (uint64_t)(((addr & 0x3FFFF) >> 4) | ((lbo_bytes >> 4) << 16)) | ((uint64_t)0x40000040u << 32);
}
__device__ __forceinline__ uint64_t mkdesc_q(uint32_t addr) {
  return (uint64_t)(((addr & 0x3FFFF) >> 4) | (64u << 16)) | ((uint64_t)8 << 32);
}
template <int N> __device__ __forceinline__ void pin(float (&a)[N]) {
#pragma unroll
  for (int i = 0; i < N; i++) asm volatile("" : "+f"(a[i])::"memory");
}
template <int N> __device__ __forceinline__ void kill(float (&a)[N]) {
#pragma unroll
  for (int i = 0; i < N; i++) asm volatile("" : "=f"(a[i]));
}
template <int N> __device__ __forceinline__ void pin(uint32_t (&a)[N]) {
#pragma unroll
  for (int i = 0; i < N; i++) asm volatile("" : "+r"(a[i])::"memory");
}

#define F8(d, o) "+f"(d[o]), "+f"(d[o + 1]), "+f"(d[o + 2]), "+f"(d[o + 3]), "+f"(d[o + 4]), "+f"(d[o + 5]), "+f"(d[o + 6]), "+f"(d[o + 7])
#define R32A "%0, %1, %2, %3, %4, %5, %6, %7, %8, %9, %10, %11, %12, %13, %14, %15, %16, %17, %18, %19, %20, %21, %22, %23, %24, %25, %26, %27, %28, %29, %30, %31"
#define R32B "%32, %33, %34, %35, %36, %37, %38, %39, %40, %41, %42, %43, %44, %45, %46, %47, %48, %49, %50, %51, %52, %53, %54, %55, %56, %57, %58, %59, %60, %61, %62, %63"

template <int TB>
__device__ __forceinline__ void mma_n128(float (&d)[64], uint32_t a0, uint32_t a1, uint32_t a2, uint32_t a3, uint64_t db, int acc) {
  asm volatile("{\n.reg .pred p;\nsetp.ne.b32 p, %69, 0;\n"
               "wgmma.mma_async.sync.aligned.m64n128k16.f32.bf16.bf16 {" R32A ", " R32B "}, {%64, %65, %66, %67}, %68, p, 1, 1, %70;\n}\n"
               : F8(d, 0), F8(d, 8), F8(d, 16), F8(d, 24), F8(d, 32), F8(d, 40), F8(d, 48), F8(d, 56)
               : "r"(a0), "r"(a1), "r"(a2), "r"(a3), "l"(db), "r"(acc), "n"(TB));
}
#define PV1(a0, a1, a2, a3, ob, acc) "add.s64 b, %92, " #ob ";\n" \
  "wgmma.mma_async.sync.aligned.m64n128k16.f32.bf16.bf16 {" R32A ", " R32B "}, {%" #a0 ", %" #a1 ", %" #a2 ", %" #a3 "}, b, " #acc ", 1, 1, 1;\n"
#define PV6 "wgmma.fence.sync.aligned;\n" PV1(64, 65, 66, 67, 0, p) PV1(68, 69, 70, 71, 128, 1) PV1(72, 73, 74, 75, 256, 1) \
  PV1(76, 77, 78, 79, 384, 1) PV1(80, 81, 82, 83, 512, 1) PV1(84, 85, 86, 87, 640, 1)
#define U4(a, o) "r"(a[o]), "r"(a[o + 1]), "r"(a[o + 2]), "r"(a[o + 3])
__device__ __forceinline__ void mma_pv(float (&d)[64], const uint32_t (&a)[28], uint64_t dv, bool acc, bool big) {
  asm volatile("{\n.reg .pred p, q;\n.reg .b64 b;\nsetp.ne.b32 p, %93, 0;\nsetp.eq.b32 q, %94, 0;\n@q bra.uni PV_SMALL;\n"
               PV6 PV1(88, 89, 90, 91, 768, 1) "wgmma.commit_group.sync.aligned;\nbra.uni PV_DONE;\n"
               "PV_SMALL:\n" PV6 "wgmma.commit_group.sync.aligned;\nPV_DONE:\n}\n"
               : F8(d, 0), F8(d, 8), F8(d, 16), F8(d, 24), F8(d, 32), F8(d, 40), F8(d, 48), F8(d, 56)
               : U4(a, 0), U4(a, 4), U4(a, 8), U4(a, 12), U4(a, 16), U4(a, 20), U4(a, 24), "l"(dv), "r"((int)acc), "r"((int)big) : "memory");
}
#define R48 R32A ", %32, %33, %34, %35, %36, %37, %38, %39, %40, %41, %42, %43, %44, %45, %46, %47"
#define R56 R48 ", %48, %49, %50, %51, %52, %53, %54, %55"
#define QK1(N, R, A, B, oa, ob, acc) "add.s64 a, " A ", " #oa ";\nadd.s64 b, " B ", " #ob ";\n" \
  "wgmma.mma_async.sync.aligned.m64n" #N "k16.f32.bf16.bf16 {" R "}, a, b, " #acc ", 1, 1, 0, 0;\n"
#define QK8(N, R, A, B) "{\n.reg .b64 a, b;\nwgmma.fence.sync.aligned;\n" QK1(N, R, A, B, 0, 0, 0) QK1(N, R, A, B, 128, 2, 1) \
  QK1(N, R, A, B, 256, 4, 1) QK1(N, R, A, B, 384, 6, 1) QK1(N, R, A, B, 512, 1024, 1) QK1(N, R, A, B, 640, 1026, 1) \
  QK1(N, R, A, B, 768, 1028, 1) QK1(N, R, A, B, 896, 1030, 1) "wgmma.commit_group.sync.aligned;\n}\n"
#define O8(d, o) "=f"(d[o]), "=f"(d[o + 1]), "=f"(d[o + 2]), "=f"(d[o + 3]), "=f"(d[o + 4]), "=f"(d[o + 5]), "=f"(d[o + 6]), "=f"(d[o + 7])
__device__ __forceinline__ void mma_qk(float (&d)[56], uint64_t dq, uint64_t dk) {
  asm volatile(QK8(112, R56, "%56", "%57")
               : O8(d, 0), O8(d, 8), O8(d, 16), O8(d, 24), O8(d, 32), O8(d, 40), O8(d, 48) : "l"(dq), "l"(dk) : "memory");
}
__device__ __forceinline__ void mma_qk(float (&d)[48], uint64_t dq, uint64_t dk) {
  asm volatile(QK8(96, R48, "%48", "%49")
               : O8(d, 0), O8(d, 8), O8(d, 16), O8(d, 24), O8(d, 32), O8(d, 40) : "l"(dq), "l"(dk) : "memory");
}
__device__ __forceinline__ void mma_n64t(float (&d)[32], uint32_t a0, uint32_t a1, uint32_t a2, uint32_t a3, uint64_t db, int acc) {
  asm volatile("{\n.reg .pred p;\nsetp.ne.b32 p, %37, 0;\n"
               "wgmma.mma_async.sync.aligned.m64n64k16.f32.bf16.bf16 {" R32A "}, {%32, %33, %34, %35}, %36, p, 1, 1, 1;\n}\n"
               : F8(d, 0), F8(d, 8), F8(d, 16), F8(d, 24)
               : "r"(a0), "r"(a1), "r"(a2), "r"(a3), "l"(db), "r"(acc));
}
__device__ __forceinline__ void mma_n8(float (&d)[4], uint64_t da, uint64_t db, int acc) {
  asm volatile("{\n.reg .pred p;\nsetp.ne.b32 p, %6, 0;\n"
               "wgmma.mma_async.sync.aligned.m64n8k16.f32.bf16.bf16 {%0, %1, %2, %3}, %4, %5, p, 1, 1, 1, 0;\n}\n"
               : "+f"(d[0]), "+f"(d[1]), "+f"(d[2]), "+f"(d[3])
               : "l"(da), "l"(db), "r"(acc));
}
__device__ __forceinline__ void hmma_k8(float (&d)[4], uint32_t a0, uint32_t a1, uint32_t b0) {
  asm volatile("mma.sync.aligned.m16n8k8.row.col.f32.bf16.bf16.f32 {%0, %1, %2, %3}, {%4, %5}, {%6}, {%0, %1, %2, %3};"
               : "+f"(d[0]), "+f"(d[1]), "+f"(d[2]), "+f"(d[3]) : "r"(a0), "r"(a1), "r"(b0));
}
__device__ __forceinline__ void hmma_k16(float (&d)[4], uint32_t a0, uint32_t a1, uint32_t a2, uint32_t a3, uint32_t b0, uint32_t b1) {
  asm volatile("mma.sync.aligned.m16n8k16.row.col.f32.bf16.bf16.f32 {%0, %1, %2, %3}, {%4, %5, %6, %7}, {%8, %9}, {%0, %1, %2, %3};"
               : "+f"(d[0]), "+f"(d[1]), "+f"(d[2]), "+f"(d[3]) : "r"(a0), "r"(a1), "r"(a2), "r"(a3), "r"(b0), "r"(b1));
}

__device__ __forceinline__ uint32_t pack2(float lo, float hi) {
  uint32_t r;
  asm("cvt.rn.bf16x2.f32 %0, %1, %2;" : "=r"(r) : "f"(hi), "f"(lo));
  return r;
}
__device__ __forceinline__ float bf_lo(uint32_t w) { return __uint_as_float(w << 16); }
__device__ __forceinline__ float bf_hi(uint32_t w) { return __uint_as_float(w & 0xFFFF0000u); }
__device__ __forceinline__ float bfr(float x) { return __bfloat162float(__float2bfloat16_rn(x)); }
__device__ __forceinline__ uint32_t sub2(uint32_t a, uint32_t b) {
  uint32_t r;
  asm("sub.rn.bf16x2 %0, %1, %2;" : "=r"(r) : "r"(a), "r"(b));
  return r;
}
__device__ __forceinline__ uint32_t add2(uint32_t a, uint32_t b) {
  uint32_t r;
  asm("add.rn.bf16x2 %0, %1, %2;" : "=r"(r) : "r"(a), "r"(b));
  return r;
}
__device__ __forceinline__ uint32_t fma2(uint32_t a, uint32_t b, uint32_t c) {
  uint32_t r;
  asm("fma.rn.bf16x2 %0, %1, %2, %3;" : "=r"(r) : "r"(a), "r"(b), "r"(c));
  return r;
}
__device__ __forceinline__ float ex2(float x) {
  float r;
  asm("ex2.approx.ftz.f32 %0, %1;" : "=f"(r) : "f"(x));
  return r;
}
__device__ __forceinline__ float rcp(float x) {
  float r;
  asm("rcp.approx.ftz.f32 %0, %1;" : "=f"(r) : "f"(x));
  return r;
}
__device__ __forceinline__ float silu_f(float t) { return t * rcp(1.0f + ex2(-1.4426950408889634f * t)); }
__device__ __forceinline__ void lds128(uint32_t a, uint32_t& x, uint32_t& y, uint32_t& z, uint32_t& w) {
  asm volatile("ld.shared.v4.u32 {%0, %1, %2, %3}, [%4];" : "=r"(x), "=r"(y), "=r"(z), "=r"(w) : "r"(a) : "memory");
}
__device__ __forceinline__ void ldsm4(uint32_t a, uint32_t& x, uint32_t& y, uint32_t& z, uint32_t& w) {
  asm volatile("ldmatrix.sync.aligned.m8n8.x4.shared.b16 {%0, %1, %2, %3}, [%4];" : "=r"(x), "=r"(y), "=r"(z), "=r"(w) : "r"(a) : "memory");
}
constexpr uint32_t TAG = 0x10000;
__device__ __forceinline__ void st_gran(uint4* p, uint32_t x, uint32_t y, uint32_t z, uint32_t w) {
  asm volatile("st.relaxed.gpu.global.v4.b32 [%0], {%1, %2, %3, %4};" ::"l"(p), "r"(x), "r"(y), "r"(z), "r"(w) : "memory");
}
__device__ __forceinline__ void ld_gran(const uint4* p, uint32_t& x, uint32_t& y, uint32_t& z, uint32_t& w) {
  asm volatile("ld.relaxed.gpu.global.v4.b32 {%0, %1, %2, %3}, [%4];" : "=r"(x), "=r"(y), "=r"(z), "=r"(w) : "l"(p) : "memory");
}
__device__ __forceinline__ void stsm4(uint32_t a, uint32_t x, uint32_t y, uint32_t z, uint32_t w) {
  asm volatile("stmatrix.sync.aligned.m8n8.x4.shared.b16 [%0], {%1, %2, %3, %4};" ::"r"(a), "r"(x), "r"(y), "r"(z), "r"(w) : "memory");
}
__device__ __forceinline__ void cp16(uint32_t dst, const void* src) {
  asm volatile("cp.async.cg.shared.global [%0], [%1], 16;" ::"r"(dst), "l"(src) : "memory");
}
__device__ __forceinline__ void cp_wait_all() { asm volatile("cp.async.wait_all;" ::: "memory"); }
__device__ __forceinline__ void add_granules(float (&red)[32], const uint32_t (&g)[16]) {
#pragma unroll
  for (int i = 0; i < 16; i++) { red[2 * i] += bf_lo(g[i]); red[2 * i + 1] += bf_hi((i & 3) ? g[i] : g[i] & ~TAG); }
}
__device__ __forceinline__ bool granules_ok(const uint32_t (&g)[16], uint32_t tag) {
  uint32_t a, b;
  asm("lop3.b32 %0, %1, %2, %3, 0x7E;" : "=r"(a) : "r"(g[0]), "r"(g[4]), "r"(tag));
  asm("lop3.b32 %0, %1, %2, %3, 0x7E;" : "=r"(b) : "r"(g[8]), "r"(g[12]), "r"(tag));
  return __all_sync(0xffffffffu, ((a | b) & TAG) == 0);
}
__device__ __forceinline__ unsigned ld_acquire(const unsigned* p) {
  unsigned v;
  asm volatile("ld.acquire.gpu.global.u32 %0, [%1];" : "=r"(v) : "l"(p) : "memory");
  return v;
}
__device__ __forceinline__ unsigned atom_add_acq_rel(unsigned* p) {
  unsigned v;
  asm volatile("atom.acq_rel.gpu.global.add.u32 %0, [%1], 1;" : "=r"(v) : "l"(p) : "memory");
  return v;
}

struct LnAcc {
  float sm[2][4], sq[8][4];
  __device__ __forceinline__ void clear() {
#pragma unroll
    for (int i = 0; i < 4; i++) {
      sm[0][i] = sm[1][i] = 0.f;
#pragma unroll
      for (int j = 0; j < 8; j++) sq[j][i] = 0.f;
    }
  }
};
template <int K0, int K1>
__device__ __forceinline__ void ln_fetch(uint32_t (&xa)[144], uint32_t boxes, uint32_t lo) {
#pragma unroll
  for (int k = K0; k < K1; k++) ldsm4(boxes + (k >> 2) * 8192 + (lo ^ ((k & 3) << 5)), xa[4 * k], xa[4 * k + 1], xa[4 * k + 2], xa[4 * k + 3]);
}
__device__ __forceinline__ void ln_accum1(LnAcc& a, int h, uint32_t x0, uint32_t x1, uint32_t x2, uint32_t x3) {
  const uint32_t ONES = 0x3F803F80u;
  hmma_k16(a.sm[h], x0, x1, x2, x3, ONES, ONES);
  hmma_k8(a.sq[4 * h], x0, x1, x0);
  hmma_k8(a.sq[4 * h + 1], x0, x1, x1);
  hmma_k8(a.sq[4 * h + 2], x2, x3, x2);
  hmma_k8(a.sq[4 * h + 3], x2, x3, x3);
}
template <int K0, int K1>
__device__ __forceinline__ void ln_accum(const uint32_t (&xa)[144], LnAcc& a) {
#pragma unroll
  for (int k = K0; k < K1; k++) ln_accum1(a, k & 1, xa[4 * k], xa[4 * k + 1], xa[4 * k + 2], xa[4 * k + 3]);
}
__device__ __forceinline__ void ln_row(float sum, float sq, float& mean_b, float& rstd) {
  const float mean = sum * (1.0f / DM);
  const uint32_t mv = pack2(mean, fmaxf(sq * (1.0f / DM) - mean * mean, 0.0f));
  mean_b = bf_lo(mv);
  float sd;
  asm("sqrt.approx.f32 %0, %1;" : "=f"(sd) : "f"(bf_lo(pack2(bf_hi(mv) + 1e-5f, 0.f))));
  rstd = rcp(bf_lo(pack2(sd, 0.f)));
}
__device__ __forceinline__ void ln_diag(const LnAcc& a, int lane, float& t0, float& t1) {
  const bool odd = (lane >> 2) & 1;
  t0 = odd ? (a.sq[0][1] + a.sq[2][1]) + (a.sq[4][1] + a.sq[6][1]) : (a.sq[0][0] + a.sq[2][0]) + (a.sq[4][0] + a.sq[6][0]);
  t1 = odd ? (a.sq[1][3] + a.sq[3][3]) + (a.sq[5][3] + a.sq[7][3]) : (a.sq[1][2] + a.sq[3][2]) + (a.sq[5][2] + a.sq[7][2]);
}
__device__ __forceinline__ void ln_stats(const LnAcc& a, int lane, float& mean0, float& rstd0, float& mean1, float& rstd1) {
  float t0, t1;
  ln_diag(a, lane, t0, t1);
  const int src = (lane & ~3) | (lane >> 3);
  t0 = __shfl_sync(0xffffffffu, t0, src);
  t1 = __shfl_sync(0xffffffffu, t1, src);
  ln_row(a.sm[0][0] + a.sm[1][0], t0, mean0, rstd0);
  ln_row(a.sm[0][2] + a.sm[1][2], t1, mean1, rstd1);
}

template <bool ROUTED>
__device__ __forceinline__ uint32_t gate2(uint32_t x2, float mean_b, float rstd, float2 upd = make_float2(0.f, 0.f)) {
  const uint32_t xc = sub2(x2, pack2(mean_b, mean_b));
  uint32_t t = pack2(bf_lo(xc) * rstd, bf_hi(xc) * rstd);
  if (ROUTED) t = pack2(bf_lo(t) + upd.x, bf_hi(t) + upd.y);
  return pack2(silu_f(bf_lo(t)), silu_f(bf_hi(t)));
}

#define PF_D 4
#define X_SPLIT 38
#define X_SPLITA 36
#define X_SPLITS 32
#define X_SPLITSA 30
#define X_PA 8
#define X_PG 2
#define X_E0 10
#define X_F2 10
#define X_LD 0
#define X_ORDER 0
#define X_PFX 1
#define X_F1 0
#define X_BF2 1
#define X_EARLY 1
template <int V> struct IC { static constexpr int value = V; };

struct Ctx {
  uint32_t sb;
  uint8_t* sp;
  uint32_t rank;
  Scratch* g;
};

template <class LoadX>
__device__ __forceinline__ void attn_producer(const Ctx& cx, int qb, int hs, const CUtensorMap* tmKV,
                                              const CUtensorMap* tmWq, const CUtensorMap* tmWo, LoadX load_x) {
  const uint32_t full = cx.sb + SM_FULL, empty = cx.sb + SM_EMPTY, ring = cx.sb + SM_RING + cx.rank * 16384;
  const uint64_t last_use = policy_evict_first();
  auto acquire = [&](uint32_t r, uint32_t n, uint32_t bytes) {
    mbar_wait(empty + 8 * r, (n ^ (r >> 1) ^ 1) & 1);
    mbar_expect_tx(full + 8 * r, bytes);
  };
  int st = 0;
#pragma unroll 1
  for (int p = 0; p < 4; p++) {
    const int n0 = (hs * 4 + (p ^ (p >> 1))) * DH + cx.rank * 64;
#pragma unroll 1
    for (int i = 0; i < 5; i++, st++) {
      const uint32_t r = (st ^ ((st >> 1) & 1)) & 3;
      acquire(r, st >> 2, i == 2 ? 16384 : 32768);
      const int k0 = i < 3 ? 128 * i : 128 * i - 64;
      tma2d_mc(ring + r * STAGE, tmWq, n0, k0, full + 8 * r, last_use);
      if (i != 2) tma2d_mc(ring + r * STAGE + 8192, tmWq, n0, k0 + 64, full + 8 * r, last_use);
      if (st < 3) TSP(72 + st)
      if (X_ORDER && X_ORDER < 3 && st == X_ORDER - 1) load_x(1);
      if (st == 1) {
#pragma unroll 1
        for (int b = 8 + qb; b < 72; b += 16) tma2d_prefetch(tmWq, (hs * 4 + ((b / 18) ^ (b / 36))) * DH + (b & 1) * 64, ((b % 18) >> 1) * 64);
      }
      if (st == 8 && qb < 2 * PF_D) tma2d_prefetch(tmKV + ((qb >> 1) & 1), cx.rank * 64, hs * 2 * SEQ + (qb >> 2) * 96);
    }
  }
  uint32_t r = 0, n = 5;
#pragma unroll 1
  for (int u = 0; u < NST_KV; u++) {
    const bool big = blk_big(u >> 1);
    acquire(r, n, big ? 112 * 256 : 96 * 256);
    tma2d_mc(ring + r * STAGE, tmKV + (u & 1) + (big ? 0 : 2), cx.rank * 64, hs * 2 * SEQ + blk_row(u >> 1), full + 8 * r, last_use);
    if (((u ^ (qb >> 1)) & 7) == 0 && u + PF_D < NST_KV)
      tma2d_prefetch(tmKV + ((u + PF_D) & 1), cx.rank * 64, hs * 2 * SEQ + blk_row((u + PF_D) >> 1));
    if ((unsigned)(u - 32) < 36 && (u & 15) == qb) tma2d_prefetch(tmWo, ((u - 32) >> 2) * 64, hs * 512 + (u & 3) * 128);
    if (++r == 3) { r = 0; n++; }
  }
#pragma unroll 1
  for (int u = 0; u < NST_O; u++) {
    const int s = u >> 1;
    const int blk = s == 0 ? 8 : ((hs + s) & 7);
    r = (u + 1) & 3;
    acquire(r, (u >> 2) ^ (u >> 1), 32768);
    tma2d_mc(ring + r * STAGE, tmWo, blk * 64, hs * 512 + ((u & 1) + cx.rank * 2) * 128, full + 8 * r, last_use);
  }
}

__device__ __forceinline__ void attn_gate(const Ctx& cx, int qb, int hs, int t, const __nv_bfloat16* x) {
  uint4 nx = *(const uint4*)(x + (size_t)(qb * 128 + (t >> 3)) * DM + hs * 64 + (t & 7) * 8);
  bar_sync(BAR_GATE, 352);
#pragma unroll 1
  for (int ch = t; ch < 1152; ch += 96) {
    const uint4 v = nx;
    const int n = ch + 96;
    if (n < 1152) nx = *(const uint4*)(x + (size_t)(qb * 128 + (n < 1024 ? n >> 3 : hs * 16 + ((n - 1024) >> 3))) * DM + (n < 1024 ? hs * 64 : 512) + (t & 7) * 8);
    const int lr = ch < 1024 ? ch >> 3 : hs * 16 + ((ch - 1024) >> 3);
    const float2 st = *(const float2*)(cx.sp + SM_STATS + 8 * lr);
    cx.g->gate[blockIdx.x * 1152 + (ch ^ ((ch >> 3) & 7))] =
        make_uint4(gate2<false>(v.x, st.x, st.y), gate2<false>(v.y, st.x, st.y), gate2<false>(v.z, st.x, st.y), gate2<false>(v.w, st.x, st.y));
  }
}

constexpr uint32_t SM_XO = SM_SLOT, SM_GO = SM_SLOT + STAGE, SM_P8 = SM_SLOT + 2 * STAGE;
__device__ __forceinline__ void attn_helper(const Ctx& cx, int qb, int hs, int lane, const CUtensorMap* tmX16) {
  unsigned e = 0;
  if (lane == 0) {
    e = cx.g->launch[blockIdx.x];
    cx.g->launch[blockIdx.x] = e + 1;
    *(uint32_t*)(cx.sp + SM_TAG) = (~e & 1) * TAG;
    mbar_arrive(cx.sb + SM_BAR_MISC);
  }
  e = __shfl_sync(0xffffffffu, e, 0);
  const uint32_t tag = (~e & 1) * TAG;
  const uint4* src = cx.g->part + (size_t)((qb * 64 + 56) * 2 + (hs >> 2)) * 4 * 128 + (hs & 3) * 32 + lane;
  const uint32_t stg = cx.sb + SM_P8 + lane * 16;
  bar_sync(BAR_OA, 352);
  asm volatile("fence.proxy.async;" ::: "memory");
  if (lane == 0) {
    mbar_expect_tx(cx.sb + SM_BAR_MISC, 2 * 18432);
    bulk_load(cx.sb + SM_GO, cx.g->gate + blockIdx.x * 1152, 18432, cx.sb + SM_BAR_MISC);
#pragma unroll 1
    for (int i = 0; i < 9; i++)
      tma2d_stream(cx.sb + SM_XO + i * 2048, tmX16, i < 8 ? hs * 64 : 512, qb * 128 + (i < 8 ? i : hs) * 16, cx.sb + SM_BAR_MISC);
  }
#pragma unroll 1
  for (int n = 0; n < (1 << 16); n++) {
    __nanosleep(n ? 500 : 2000);
    uint32_t a, b, d, t;
    ld_gran(src - lane + (lane & 7) * (2 * 4 * 128) + 3 * 128 + 31, a, b, d, t);
    if (__all_sync(0xffffffffu, (a & TAG) == tag)) break;
  }
#pragma unroll 1
  for (int n = 0; n < (1 << 16); n++) {
#pragma unroll 1
    for (int i = 0; i < 8; i++) {
#pragma unroll
      for (int g = 0; g < 4; g++) cp16(stg + (i * 4 + g) * 512, src + i * (2 * 4 * 128) + g * 128);
    }
    cp_wait_all();
    uint32_t bad = 0;
#pragma unroll 4
    for (int i = 0; i < 32; i++) bad |= *(const volatile uint32_t*)(cx.sp + SM_P8 + lane * 16 + i * 512) ^ tag;
    if (__all_sync(0xffffffffu, (bad & TAG) == 0)) break;
  }
#pragma unroll 1
  for (int n = 0; n < (1 << 16) && ld_acquire(&cx.g->ycnt) != 4 * (e + 1); n++) __nanosleep(200);
  const int2 sel = __ldcg(&cx.g->sel[lane & 7]);
  const int lr = sel.x - qb * 128;
  uint32_t m = __ballot_sync(0xffffffffu, lane < 16 && ((lane & 8) ? (lr >> 4) == hs : (lr >> 7) == 0));
  mbar_wait(cx.sb + SM_BAR_MISC, 1);
#pragma unroll 1
  for (; m; m &= m - 1) {
    const int i = __ffs(m) - 1, row = __shfl_sync(0xffffffffu, lr, i);
    const float rs = __int_as_float(__shfl_sync(0xffffffffu, sel.y, i));
    const float* p = cx.g->ypart + (i & 7) * DM + (i < 8 ? hs * 64 : 512) + 2 * lane;
    const float2 a = __ldcg((const float2*)p), b = __ldcg((const float2*)(p + TOPC * DM)), c = __ldcg((const float2*)(p + 2 * TOPC * DM)),
                 d = __ldcg((const float2*)(p + 3 * TOPC * DM));
    const uint32_t y = pack2((a.x + b.x) + (c.x + d.x), (a.y + b.y) + (c.y + d.y));
    const uint32_t u = pack2(bf_lo(y) * rs, bf_hi(y) * rs);
    const float2 st = *(const float2*)(cx.sp + SM_STATS + 8 * row);
    const int o = (i < 8 ? row : 128 + (row & 15)) * 128 + ((lane * 4) ^ ((row & 7) << 4));
    *(uint32_t*)(cx.sp + SM_GO + o) = gate2<true>(*(const uint32_t*)(cx.sp + SM_XO + o), st.x, st.y, make_float2(bf_lo(u), bf_hi(u)));
  }
  __syncwarp();
  if (lane == 0) mbar_arrive(cx.sb + SM_BAR_XG);
}
__device__ __forceinline__ void attn_finish8(const Ctx& cx, int qb, int hs, int hw, int lane, __nv_bfloat16* out) {
  bar_sync(BAR_GATE, 96);
#pragma unroll 1
  for (int g = hw; g < 4; g += 3) {
    float acc[8] = {0.f, 0.f, 0.f, 0.f, 0.f, 0.f, 0.f, 0.f};
#pragma unroll 2
    for (int sidx = 0; sidx < 8; sidx++) {
      uint32_t a, b, d, t;
      lds128(cx.sb + SM_P8 + lane * 16 + (sidx * 4 + g) * 512, a, b, d, t);
      acc[0] += bf_lo(a); acc[1] += bf_hi(a & ~TAG); acc[2] += bf_lo(b); acc[3] += bf_hi(b);
      acc[4] += bf_lo(d); acc[5] += bf_hi(d); acc[6] += bf_lo(t); acc[7] += bf_hi(t);
    }
#pragma unroll
    for (int j = 0; j < 4; j++) {
      const int o = (128 + (lane >> 2) + (j & 1) * 8) * 128 + (((2 * g + (j >> 1)) ^ (lane >> 2)) << 4) + (lane & 3) * 4;
      uint32_t* xp = (uint32_t*)(cx.sp + SM_XO + o);
      *xp = fma2(pack2(acc[2 * j], acc[2 * j + 1]), *(const uint32_t*)(cx.sp + SM_GO + o), *xp);
    }
  }
  bar_sync(BAR_GATE, 96);
  for (int ch = hw * 32 + lane; ch < 128; ch += 96)
    *(uint4*)(out + (size_t)(qb * 128 + hs * 16 + (ch >> 3)) * DM + 512 + (ch & 7) * 8) =
        *(const uint4*)(cx.sp + SM_XO + 16384 + (ch ^ ((ch >> 3) & 7)) * 16);
}

constexpr float SUM_HI = 1.8446744e19f, SUM_LO = 9.0949470e-13f;

template <int LO, int HI, int N>
__device__ __forceinline__ void softmax_exp(float (&s)[N]) {
#pragma unroll
  for (int i = LO; i < HI; i++) s[i] = ex2(s[i]);
}
__device__ __forceinline__ void sum_tree(const uint32_t (&pf)[28], bool big, uint32_t& h0, uint32_t& h1) {
  uint32_t t0 = add2(add2(pf[16], pf[18]), add2(pf[20], pf[22])), t1 = add2(add2(pf[17], pf[19]), add2(pf[21], pf[23]));
  if (big) { t0 = add2(t0, add2(pf[24], pf[26])); t1 = add2(t1, add2(pf[25], pf[27])); }
  h0 = add2(add2(add2(add2(pf[0], pf[2]), add2(pf[4], pf[6])), add2(add2(pf[8], pf[10]), add2(pf[12], pf[14]))), t0);
  h1 = add2(add2(add2(add2(pf[1], pf[3]), add2(pf[5], pf[7])), add2(add2(pf[9], pf[11]), add2(pf[13], pf[15]))), t1);
}
__device__ __forceinline__ void exact_attention(float (&o)[64], float& l0, float& l1, uint32_t qaddr, const __nv_bfloat16* kh,
                                                const __nv_bfloat16* vh, int lane) {
  const int off = (lane >> 2) * DH + (lane & 3) * 2;
  float m0 = -3.0e38f, m1 = -3.0e38f;
  l0 = l1 = 0.f;
#pragma unroll
  for (int i = 0; i < 64; i++) o[i] = 0.f;
#pragma unroll 1
  for (int key = 0; key < SEQ; key += 16) {
    const __nv_bfloat16 *kp = kh + key * DH + off, *vp = vh + key * DH + off;
    float d0[4] = {0.f, 0.f, 0.f, 0.f}, d1[4] = {0.f, 0.f, 0.f, 0.f};
#pragma unroll 4
    for (int k = 0; k < 8; k++) {
      uint32_t q0, q1, q2, q3;
      ldsm4(qaddr + k * 2048, q0, q1, q2, q3);
      hmma_k16(d0, q0, q1, q2, q3, *(const uint32_t*)(kp + k * 16), *(const uint32_t*)(kp + k * 16 + 8));
      hmma_k16(d1, q0, q1, q2, q3, *(const uint32_t*)(kp + 8 * DH + k * 16), *(const uint32_t*)(kp + 8 * DH + k * 16 + 8));
    }
    float x0 = fmaxf(fmaxf(d0[0], d0[1]), fmaxf(d1[0], d1[1])), x1 = fmaxf(fmaxf(d0[2], d0[3]), fmaxf(d1[2], d1[3]));
    x0 = fmaxf(x0, __shfl_xor_sync(0xffffffffu, x0, 1));
    x1 = fmaxf(x1, __shfl_xor_sync(0xffffffffu, x1, 1));
    x0 = fmaxf(fmaxf(x0, __shfl_xor_sync(0xffffffffu, x0, 2)), m0);
    x1 = fmaxf(fmaxf(x1, __shfl_xor_sync(0xffffffffu, x1, 2)), m1);
    const float sc0 = ex2(m0 - x0), sc1 = ex2(m1 - x1);
    m0 = x0; m1 = x1;
    const uint32_t p0 = pack2(ex2(d0[0] - m0), ex2(d0[1] - m0)), p1 = pack2(ex2(d0[2] - m1), ex2(d0[3] - m1)),
                   p2 = pack2(ex2(d1[0] - m0), ex2(d1[1] - m0)), p3 = pack2(ex2(d1[2] - m1), ex2(d1[3] - m1));
    l0 = fmaf(l0, sc0, (bf_lo(p0) + bf_hi(p0)) + (bf_lo(p2) + bf_hi(p2)));
    l1 = fmaf(l1, sc1, (bf_lo(p1) + bf_hi(p1)) + (bf_lo(p3) + bf_hi(p3)));
#pragma unroll
    for (int nb = 0; nb < 16; nb++) {
      uint32_t b0, b1;
      asm("movmatrix.sync.aligned.m8n8.trans.b16 %0, %1;" : "=r"(b0) : "r"(*(const uint32_t*)(vp + nb * 8)));
      asm("movmatrix.sync.aligned.m8n8.trans.b16 %0, %1;" : "=r"(b1) : "r"(*(const uint32_t*)(vp + 8 * DH + nb * 8)));
      o[4 * nb] *= sc0; o[4 * nb + 1] *= sc0; o[4 * nb + 2] *= sc1; o[4 * nb + 3] *= sc1;
      hmma_k16(*(float (*)[4])&o[4 * nb], p0, p1, p2, p3, b0, b1);
    }
  }
}
__device__ __forceinline__ int fresh_lane() {
  int l;
  asm volatile("mov.u32 %0, %%laneid;" : "=r"(l));
  return l;
}
__device__ __forceinline__ bool inv_sums(float l0, float l1, float& i0, float& i1) {
  l0 += __shfl_xor_sync(0xffffffffu, l0, 1); l1 += __shfl_xor_sync(0xffffffffu, l1, 1);
  l0 += __shfl_xor_sync(0xffffffffu, l0, 2); l1 += __shfl_xor_sync(0xffffffffu, l1, 2);
  i0 = rcp(l0);
  i1 = rcp(l1);
  return !(l0 + l1 <= SUM_HI) | (fminf(l0, l1) < SUM_LO);
}
template <int LO, int HI>
__device__ __forceinline__ void park(uint32_t a, const float (&o)[64], float i0, float i1, bool on = true) {
#pragma unroll
  for (int i = LO; i < HI; i++)
    asm volatile("{\n.reg .pred p;\nsetp.ne.u32 p, %5, 0;\n@p stmatrix.sync.aligned.m8n8.x4.shared.b16 [%0], {%1, %2, %3, %4};\n}"
                 ::"r"(a + i * 2048), "r"(pack2(o[8 * i] * i0, o[8 * i + 1] * i0)), "r"(pack2(o[8 * i + 2] * i1, o[8 * i + 3] * i1)),
                 "r"(pack2(o[8 * i + 4] * i0, o[8 * i + 5] * i0)), "r"(pack2(o[8 * i + 6] * i1, o[8 * i + 7] * i1)), "r"((uint32_t)on) : "memory");
}

template <int I, int NP, int E0, int N, int NS>
__device__ __forceinline__ void exp_park(float (&s)[NS], uint32_t a, const float (&o)[64], float i0, float i1, bool on, int id) {
  if constexpr (I < NP) {
    constexpr int E1 = E0 + (N - E0) * X_PG / (NP - I);
    softmax_exp<E0, E1>(s);
    park<I, I + X_PG>(a, o, i0, i1, on);
    if (I + X_PG < NP) {
#pragma unroll
      for (int i = E0; i < E1; i++) asm volatile("" : "+f"(s[i])::"memory");
      block_fence(id + I);
    }
    exp_park<I + X_PG, NP, E1, N>(s, a, o, i0, i1, on, id);
  }
}

__device__ __forceinline__ void attn_consumer(const Ctx& cx, int qb, int hs, int wg, int cw, int lane, const __nv_bfloat16* x,
                                              const __nv_bfloat16* kc, const __nv_bfloat16* vc, __nv_bfloat16* out) {
  const uint32_t full = cx.sb + SM_FULL;
  const uint32_t ring = cx.sb + SM_RING;
  const uint32_t qwg = ring + wg * 16384;
  auto qlane = [&](int l) { return qwg + (cw & 3) * 256 + (l >> 4) * 1024 + (l & 15) * 16; };
  const bool signaller = lane == 0 && (cw & 3) < 2;
  const int my_turn = 1 + wg, other_turn = 2 - wg;

  float oA[64], oB[64], i0, i1;
  uint32_t xl[32];
  uint32_t empty_c;
  {
    const int r = lane >> 2, c = lane & 3;
    const int lr0 = cw * 16 + r;
    uint32_t xa[144];
    float rstd0, rstd1, sq0, sq1;
    {
      const uint32_t xb = cx.sb + SM_X + wg * 73728, xf = cx.sb + SM_XFULL + wg * 24;
      const uint32_t lo = ((cw & 3) * 16 + (lane & 15)) * 128 + (((lane >> 4) ^ (lane & 7)) << 4);
      LnAcc a;
      a.clear();
      prof(wg, 0);
      empty_c = mapa(cx.sb + SM_EMPTY, cw & 1);
      TS4(1)
      mbar_wait(xf, 0);
      TS4(2)
      ln_fetch<0, 12>(xa, xb, lo);
      ln_accum<0, 12>(xa, a);
      mbar_wait(xf + 8, 0);
      TS4(3)
      ln_fetch<12, 24>(xa, xb, lo);
      if (wg == 0) {
        bar_sync(4, 128);
        if (signaller) {
          asm volatile("mbarrier.arrive.shared::cluster.b64 _, [%0], 2;" ::"r"(empty_c + 16) : "memory");
          asm volatile("mbarrier.arrive.shared::cluster.b64 _, [%0], 2;" ::"r"(empty_c + 24) : "memory");
        }
      }
      ln_accum<12, 24>(xa, a);
      mbar_wait(xf + 16, 0);
      TS4(4)
      prof(wg, 1);
      ln_fetch<24, 36>(xa, xb, lo);
#pragma unroll
      for (int k = 24; k < 36; k++) hmma_k16(a.sm[k & 1], xa[4 * k], xa[4 * k + 1], xa[4 * k + 2], xa[4 * k + 3], 0x3F803F80u, 0x3F803F80u);
      ln_diag(a, lane, sq0, sq1);
      if (c != (r >> 1)) sq0 = sq1 = 0.f;
      rstd0 = a.sm[0][0] + a.sm[1][0];
      rstd1 = a.sm[0][2] + a.sm[1][2];
    }
    const uint32_t mm0 = pack2(rstd0 * (1.0f / DM), rstd0 * (1.0f / DM)), mm1 = pack2(rstd1 * (1.0f / DM), rstd1 * (1.0f / DM));
#pragma unroll
    for (int i = 0; i < 16; i++) { xa[2 * i] = sub2(xa[2 * i], mm0); xa[2 * i + 1] = sub2(xa[2 * i + 1], mm1); }
    pin(xa);
    prof(wg, 2);
    TS4(5)

    float (&acc)[64] = oB;
#pragma unroll 1
    for (int p = 0; p < 4; p++) {
      const int st0 = p * 5;
#pragma unroll
      for (int i = 0; i < 5; i++) {
        if (i == 4 && p == 3) break;
        const int st = st0 + i;
        const uint32_t sl = (st ^ ((st >> 1) & 1)) & 3, slp = ((st - 1) ^ (((st - 1) >> 1) & 1)) & 3;
        mbar_wait(full + 8 * sl, (st >> 2) & 1);
        TS4(8 + 2 * st)
        const bool join = wg && p == 3;
        if (p && i != (wg ? 4 : 1) && !(join && i == 3)) bar_sync(my_turn, 256);
        wg_fence();
        const uint64_t db = mkdesc(ring + sl * STAGE, 16384);
        const int kb0 = i < 3 ? 8 * i : 8 * i - 4;
#pragma unroll
        for (int k = 0; k < (i == 2 ? 4 : 8); k++) {
          const int kb = kb0 + k;
          mma_n128<1>(acc, xa[4 * kb], xa[4 * kb + 1], xa[4 * kb + 2], xa[4 * kb + 3], db + k * 128, kb > 0);
        }
        wg_commit();
        TS4(9 + 2 * st)
        if (wg ? (i == 4 || (p && (i < 2 || i == (join ? 3 : 2)))) : (p && i)) bar_arrive(other_turn, 256);
        if (p == 0 && i < 4) {
          if (i < 2) {
#pragma unroll
            for (int j = 48 + 12 * i; j < 60 + 12 * i; j++) {
              sq0 = fmaf(bf_lo(xa[2 * j]), bf_lo(xa[2 * j]), fmaf(bf_hi(xa[2 * j]), bf_hi(xa[2 * j]), sq0));
              sq1 = fmaf(bf_lo(xa[2 * j + 1]), bf_lo(xa[2 * j + 1]), fmaf(bf_hi(xa[2 * j + 1]), bf_hi(xa[2 * j + 1]), sq1));
            }
          }
          if (i == 1) {
            sq0 += __shfl_xor_sync(0xffffffffu, sq0, 1); sq1 += __shfl_xor_sync(0xffffffffu, sq1, 1);
            sq0 += __shfl_xor_sync(0xffffffffu, sq0, 2); sq1 += __shfl_xor_sync(0xffffffffu, sq1, 2);
            float mean0, mean1;
            ln_row(rstd0, sq0, mean0, rstd0);
            ln_row(rstd1, sq1, mean1, rstd1);
            if (c == 0) {
              *(float2*)(cx.sp + SM_STATS + 8 * lr0) = make_float2(mean0, rstd0);
              *(float2*)(cx.sp + SM_STATS + 8 * (lr0 + 8)) = make_float2(mean1, rstd1);
            }
            *((uint32_t*)(cx.sp + SM_COLD) + wg) = 0;
            bar_arrive(BAR_GATE, 352);
            bar_sync(4 + wg, 128);
            rstd0 *= SM_SCALE_LOG2;
            rstd1 *= SM_SCALE_LOG2;
          }
#pragma unroll
          for (int j = 0; j < 72; j++)
            if (j >= 2 * (i < 2 ? 8 * i + 8 : 8 * i + 4) && j < 2 * (i == 0 ? 16 : 8 * i + 12)) {
              xa[2 * j] = sub2(xa[2 * j], mm0);
              xa[2 * j + 1] = sub2(xa[2 * j + 1], mm1);
            }
          pin(xa);
        }
        if (i == 0) {
          if (wg) {
            wg_wait<0>();
            if (signaller) mbar_arrive_cluster(empty_c + 8 * sl);
          }
        } else if (i == 2) {
          if (!join) {
            wg_wait<0>();
            if (signaller) mbar_arrive_cluster(empty_c + 8 * sl);
          }
        } else if (i != 3) {
          wg_wait<1>();
          if (signaller && (i == 4 || !wg)) mbar_arrive_cluster(empty_c + 8 * slp);
          wg_wait<0>();
          if (signaller) mbar_arrive_cluster(empty_c + 8 * sl);
        }
      }
      if (p == 3) break;
      pin(acc);
      prof(wg, 3 + p);
      TS4(50 + 2 * p)
      park<0, 8>(qlane(lane) + (4 + p) * STAGE, acc, rstd0, rstd1);
      asm volatile("fence.proxy.async.shared::cta;" ::: "memory");
      TS4(51 + 2 * p)
    }
    wg_wait<1>();
    if (signaller && wg) mbar_arrive_cluster(empty_c + 8 * 1);
    wg_wait<0>();
    pin(acc);
    prof(wg, 6);
#pragma unroll
    for (int i = 0; i < 32; i++) xl[i] = xa[112 + i];
    i0 = rstd0;
    i1 = rstd1;
  }

  uint32_t oa[128];
  float acc[32];
  {
    uint32_t pf[28];
    uint32_t bad = 0;
    float lA0 = 0.f, lA1 = 0.f, lB0 = 0.f, lB1 = 0.f;
    int t = 0;
    uint32_t ra = 0, rb = 2 * 2048, rc = 0, par = 1;
    const uint64_t dk0 = mkdesc(ring, 16), dv0 = mkdesc(ring, 16384);
    uint64_t dqA = mkdesc_q(qwg + 4 * STAGE), dqB = dqA + 2048;
    auto turn = [&](auto kc_, auto bc_) {
      constexpr int KIND = decltype(kc_)::value, BIG = decltype(bc_)::value;
      constexpr int HB = KIND == 1, ID = 10 * KIND + 30 * BIG, T0 = BIG ? 38 : 0;
      constexpr int NS = BIG ? 56 : 48, SPLIT = BIG ? (HB ? X_SPLIT : X_SPLITA) : (HB ? X_SPLITS : X_SPLITSA);
      float s[NS];
      float (&op)[64] = HB ? oA : oB;
      uint32_t h0 = 0, h1 = 0;
      TS2(0)
      bar_sync(my_turn, 256);
      TS2(1)
      if (KIND) { pin(pf); pin(op); }
      mma_qk(s, HB ? dqB : dqA, dk0 + (HB ? ra : rc));
      TS2(2)
      if (KIND) {
        const bool bigp = HB ? BIG : BIG ? t != 10 : t == 66;
        if (X_BF2) block_fence(ID + 9);
        pin(pf);
        sum_tree(pf, bigp, h0, h1);
        asm volatile("" : "+r"(h0), "+r"(h1)::"memory");
        if (HB) mbar_wait(full + (rb >> 8), par);
        mma_pv(op, pf, dv0 + rb, t != T0 + 2 - HB, bigp);
      } else {
        mbar_wait(full + (rb >> 8), (NST_Q - 1) >> 2 & 1);
#pragma unroll
        for (int k = 0; k < 8; k++) mma_n128<1>(op, xl[4 * k], xl[4 * k + 1], xl[4 * k + 2], xl[4 * k + 3], dv0 + rb + k * 128, 1);
        wg_commit();
      }
      TS2(3)
      bar_arrive(other_turn, 256);
      (HB ? lA0 : lB0) += bf_lo(h0) + bf_hi(h0);
      (HB ? lA1 : lB1) += bf_lo(h1) + bf_hi(h1);
      wg_wait<1>();
      pin(s);
      TS1(t)
      TS2(4)
      if (KIND == 1) mbar_arrive_cluster_now<ID + 3>(empty_c + (ra >> 8), signaller);
      if (BIG && t == T0 + HB) {
        const uint32_t a = qlane(fresh_lane()) + (4 + HB) * STAGE;
        const bool ok = !__any_sync(0xffffffffu, inv_sums(HB ? lB0 : lA0, HB ? lB1 : lA1, i0, i1));
        bad = (HB ? bad : 0) | (ok ? 0 : 1 << HB);
        (HB ? lB0 : lA0) = 0.f;
        (HB ? lB1 : lA1) = 0.f;
        softmax_exp<0, X_E0>(s);
#pragma unroll
        for (int i = 0; i < X_E0; i++) asm volatile("" : "+f"(s[i])::"memory");
        block_fence(ID + 7);
        exp_park<0, X_PA, X_E0, SPLIT>(s, a, HB ? oB : oA, i0, i1, ok, 200 + ID);
        if (!HB) dqB += 2048;
        prof(wg, 8 + HB);
      } else {
        if (HB && !BIG) bad = (bad & 3) | (inv_sums(lA0, lA1, i0, i1) ? 4 : 0);
        softmax_exp<0, SPLIT>(s);
      }
      pin(s);
      if (!BIG) block_fence(ID + 4);
      TS2(5)
      wg_wait<0>();
      TS2(6)
      pin(op);
      if (KIND) pin(pf); else pin(xl);
      if (HB) {
        par ^= rc == 0;
        if (BIG && t == 37) dqA -= 2048;
      } else {
        mbar_arrive_cluster_now<ID + 5>(empty_c + (rb >> 8), signaller);
        if (KIND) {
          par ^= ra == 0;
          const uint32_t x = ra;
          ra = rc; rc = rb; rb = x;
        }
      }
      softmax_exp<SPLIT, NS>(s);
#pragma unroll
      for (int i = 0; i < NS / 2; i++) pf[i] = pack2(s[2 * i], s[2 * i + 1]);
      pin(pf);
      if (KIND == 0) {
        block_fence(ID + 6);
        park<0, 8>(qlane(fresh_lane()) + 3 * STAGE, oB, i0, i1);
        asm volatile("fence.proxy.async.shared::cta;" ::: "memory");
        prof(wg, 7);
      }
      if (BIG && X_PA < 8 && t == T0 + HB) park<X_PA, 8>(qlane(fresh_lane()) + (4 + HB) * STAGE, HB ? oB : oA, i0, i1, !(bad >> HB));
      if (HB) mbar_wait(full + (rc >> 8), par);
      t++;
    };
#pragma unroll
    for (int i = 24; i < 28; i++) asm volatile("" : "=r"(pf[i]));
    mbar_wait(full, (NST_Q >> 2) & 1);
    turn(IC<0>(), IC<0>());
    rb = 2048; rc = 2 * 2048;
    kill(oA);
    const bool never = blockIdx.y == 1;
#pragma unroll 1
    while (true) {
      turn(IC<1>(), IC<0>());
      if (t == 76) break;
      if (t == 10) {
#pragma unroll 1
        do {
#pragma unroll 1
          do turn(IC<2>(), IC<1>()); while (never);
          turn(IC<1>(), IC<1>());
        } while (t != 66);
      }
#pragma unroll 1
      do turn(IC<2>(), IC<0>()); while (never);
    }
    const uint32_t ql = qlane(fresh_lane());
    auto scale = [&](auto lo, auto hi) {
#pragma unroll
      for (int i = decltype(lo)::value; i < decltype(hi)::value; i++) {
        oa[32 + 2 * i] = pack2(oA[4 * i] * i0, oA[4 * i + 1] * i0);
        oa[32 + 2 * i + 1] = pack2(oA[4 * i + 2] * i1, oA[4 * i + 3] * i1);
        asm volatile("" : "+r"(oa[32 + 2 * i]), "+r"(oa[32 + 2 * i + 1])::"memory");
      }
    };
    TS3(1)
    if (X_LD == 0) {
#pragma unroll
      for (int i = 0; i < 8; i++) ldsm4(ql + 4 * STAGE + i * 2048, oa[4 * i], oa[4 * i + 1], oa[4 * i + 2], oa[4 * i + 3]);
    }
    {
      uint32_t h0, h1;
      sum_tree(pf, false, h0, h1);
      if (inv_sums(lB0 + (bf_lo(h0) + bf_hi(h0)), lB1 + (bf_lo(h1) + bf_hi(h1)), lB0, lB1)) bad |= 8;
    }
    scale(IC<0>(), IC<X_F1>());
    volatile uint32_t* const cold = (volatile uint32_t*)(cx.sp + SM_COLD) + wg;
    if (bad) *cold = 1;
    block_fence(93);
    TS3(2)
    bar_sync(my_turn, 256);
    const uint32_t is_cold = *cold;
    TS3(3)
    pin(pf); pin(oB);
    mma_pv(oB, pf, dv0, true, false);
    mbar_arrive_cluster_now<91>(empty_c + 8 * 3, signaller && !is_cold);
    TS3(4)
    if (X_LD == 1) {
#pragma unroll
      for (int i = 0; i < 8; i++) ldsm4(ql + 4 * STAGE + i * 2048, oa[4 * i], oa[4 * i + 1], oa[4 * i + 2], oa[4 * i + 3]);
    }
    const uint64_t db = mkdesc(ring + STAGE, 16);
    scale(IC<X_F1>(), IC<X_F2>());
    block_fence(94);
#pragma unroll
    for (int i = 0; i < 32; i++) asm volatile("" : "+r"(oa[i])::"memory");
    wg_fence();
#pragma unroll
    for (int k = 0; k < 8; k++) mma_n64t(acc, oa[4 * k], oa[4 * k + 1], oa[4 * k + 2], oa[4 * k + 3], db + k * 128, k > 0);
    if (X_F2 < 16) {
      wg_commit();
      block_fence(95);
      scale(IC<X_F2>(), IC<16>());
      TS3(5)
      wg_fence();
    }
#pragma unroll
    for (int k = 8; k < 16; k++) mma_n64t(acc, oa[4 * k], oa[4 * k + 1], oa[4 * k + 2], oa[4 * k + 3], db + k * 128, 1);
    wg_commit();
    bar_arrive(other_turn, 256);
    wg_wait<(X_F2 < 16 ? 2 : 1)>();
    pin(oB); pin(pf);
    TS(76)
    TS3(6)
    if (signaller) mbar_arrive_cluster(empty_c);
#pragma unroll
    for (int i = 16; i < 24; i++) ldsm4(ql + 5 * STAGE + (i & 7) * 2048, oa[4 * i], oa[4 * i + 1], oa[4 * i + 2], oa[4 * i + 3]);
#pragma unroll
    for (int i = 0; i < 16; i++) {
      oa[96 + 2 * i] = pack2(oB[4 * i] * lB0, oB[4 * i + 1] * lB0);
      oa[96 + 2 * i + 1] = pack2(oB[4 * i + 2] * lB1, oB[4 * i + 3] * lB1);
    }
    TS3(7)
    mbar_wait(full + 8 * 2, 0);
    TS3(8)
    wg_wait<0>();
    pin(acc); pin(oa);
    if (__any_sync(0xffffffffu, is_cold)) {
      bad = __reduce_or_sync(0xffffffffu, bad);
      if (!(bad & 8)) {
#pragma unroll
        for (int i = 24; i < 32; i++) stsm4(ql + 6 * STAGE + (i & 7) * 2048, oa[4 * i], oa[4 * i + 1], oa[4 * i + 2], oa[4 * i + 3]);
      }
#pragma unroll 1
      for (int h = 0; h < 4; h++) {
        if (bad >> h & 1) {
          const uint32_t a = ql + ((0x6354 >> (4 * h)) & 7) * STAGE;
          const size_t o = (size_t)(hs * 2 + (h >> 1)) * SEQ * DH;
          float ox[64], l0, l1;
          exact_attention(ox, l0, l1, a, kc + o, vc + o, fresh_lane());
          inv_sums(l0, l1, l0, l1);
          __syncwarp();
          park<0, 8>(a, ox, l0, l1);
        }
      }
      __syncwarp();
#pragma unroll
      for (int i = 0; i < 32; i++)
        if ((i >> 3) != 1 || (bad & 4))
          ldsm4(ql + ((0x6534 >> (4 * (i >> 3))) & 7) * STAGE + (i & 7) * 2048, oa[4 * i], oa[4 * i + 1], oa[4 * i + 2], oa[4 * i + 3]);
      pin(oa);
      asm volatile("fence.proxy.async.shared::cta;" ::: "memory");
      bar_sync(4 + wg, 128);
      if (signaller) mbar_arrive_cluster(empty_c + 8 * 3);
      wg_fence();
#pragma unroll
      for (int k = 0; k < 16; k++) mma_n64t(acc, oa[4 * k], oa[4 * k + 1], oa[4 * k + 2], oa[4 * k + 3], db + k * 128, k > 0);
      wg_commit();
      wg_wait<0>();
      pin(acc);
    }
    if (signaller) mbar_arrive_cluster(empty_c + 8 * 1);
  }

  prof(wg, 10);
  TS3(9)
  {
    lane = fresh_lane();
    const int tw = (cw & 3) * 32 + lane;
    float red[32];
    kill(red);
    uint32_t tag = 0;
    uint4* const xch = cx.g->part + (size_t)(qb * 64 * 2 + wg) * 4 * 128 + tw;
    int nrx = 1;
    auto region = [](int s, int h) { return (2 * s + h + 1) & 3; };
    auto half_step = [&](int s, auto hc, bool arrive) {
      constexpr int h = decltype(hc)::value;
      const uint64_t db = mkdesc(ring + region(s, h) * STAGE, 16);
      bar_sync(my_turn, 256);
      pin(oa);
      wg_fence();
#pragma unroll
      for (int k = 0; k < 16; k++) {
        const int kb = h * 16 + k;
        mma_n64t(acc, oa[4 * kb], oa[4 * kb + 1], oa[4 * kb + 2], oa[4 * kb + 3], db + k * 128, kb > 0);
      }
      wg_commit();
      if (arrive) bar_arrive(other_turn, 256);
    };
    auto await = [&](int s, int h) { mbar_wait(full + 8 * region(s, h), ((s >> 1) ^ s) & 1); };
    auto fetch = [&](uint32_t (&g)[16], int n) {
      const uint4* p = xch + (hs * 7 + n - 1) * (2 * 4 * 128);
#pragma unroll
      for (int i = 0; i < 4; i++) ld_gran(p + i * 128, g[4 * i], g[4 * i + 1], g[4 * i + 2], g[4 * i + 3]);
    };
    uint32_t g[16];
#pragma unroll 1
    for (int s = 0; s < 8; s++) {
      const bool pend = nrx < s - 1;
      if (pend) fetch(g, nrx);
      half_step(s, IC<1>(), true);
      TS3(s < 3 ? 16 + 8 * s : 75)
      if (s == 0) {
        mbar_wait(cx.sb + SM_BAR_MISC, 0);
        tag = *(const volatile uint32_t*)(cx.sp + SM_TAG);
        bar_arrive(BAR_OA, 352);
#pragma unroll
        for (int i = 0; i < 32; i++) red[i] = 0.f;
      }
      await(s + 1, 0);
      TS3(s < 3 ? 17 + 8 * s : 75)
      wg_wait<0>();
      TS3(s < 3 ? 18 + 8 * s : 75)
      if (signaller && s < 7) mbar_arrive_cluster(empty_c + 8 * region(s, 1));
      pin(acc);
      TS(77 + s)
      prof(wg, 12 + s);
      uint4* p = xch + (s == 0 ? 56 + hs : ((hs + s) & 7) * 7 + s - 1) * (2 * 4 * 128);
#pragma unroll
      for (int i = 0; i < 4; i++)
        st_gran(p + i * 128, (pack2(acc[8 * i], acc[8 * i + 1]) & ~TAG) | tag, pack2(acc[8 * i + 2], acc[8 * i + 3]),
                pack2(acc[8 * i + 4], acc[8 * i + 5]), pack2(acc[8 * i + 6], acc[8 * i + 7]));
      TS3(s < 3 ? 19 + 8 * s : 75)
      half_step(s + 1, IC<0>(), true);
      TS3(s < 3 ? 20 + 8 * s : 75)
      await(s + 1, 1);
      TS3(s < 3 ? 21 + 8 * s : 75)
      if (pend && granules_ok(g, tag)) { add_granules(red, g); nrx++; }
      if (X_EARLY == 2 && s == 7) fetch(g, nrx);
      wg_wait<0>();
      TS3(s < 3 ? 22 + 8 * s : 75)
      if (signaller && s < 6) mbar_arrive_cluster(empty_c + 8 * region(s + 1, 0));
    }
    uint32_t xv[16], gt[16], g2[16];
    if (X_EARLY < 2) fetch(g, nrx);
    mbar_wait(cx.sb + SM_BAR_XG, 0);
    const bool two = nrx < 7;
    bool ok;
    {
      const uint64_t db = mkdesc(ring + 2 * STAGE, 16);
      if (X_EARLY == 2) ok = granules_ok(g, tag);
      bar_sync(my_turn, 256);
      if (X_EARLY == 2) fetch(g2, 7);
#pragma unroll
      for (int i = 64; i < 128; i++) asm volatile("" : "+r"(oa[i])::"memory");
      wg_fence();
#pragma unroll
      for (int k = 16; k < 32; k++) mma_n64t(acc, oa[4 * k], oa[4 * k + 1], oa[4 * k + 2], oa[4 * k + 3], db + (k - 16) * 128, 1);
      wg_commit();
      if (wg == 0) bar_arrive(other_turn, 256);
    }
    if (X_EARLY < 2) {
      ok = granules_ok(g, tag);
      fetch(g2, 7);
    }
    const uint32_t frag = (cw * 16 + (lane & 15)) * 128 + (((lane >> 4) ^ (lane & 7)) << 4);
#pragma unroll
    for (int i = 0; i < 4; i++) {
      ldsm4(cx.sb + SM_XO + (frag ^ (i << 5)), xv[4 * i], xv[4 * i + 1], xv[4 * i + 2], xv[4 * i + 3]);
      ldsm4(cx.sb + SM_GO + (frag ^ (i << 5)), gt[4 * i], gt[4 * i + 1], gt[4 * i + 2], gt[4 * i + 3]);
    }
    if (ok) { add_granules(red, g); nrx++; }
    wg_wait<0>();
    pin(acc);
    TS(85)
#pragma unroll
    for (int i = 0; i < 32; i++) red[i] += acc[i];
    pin(red);
    block_fence(90);
    int last = 8;
    if (two && granules_ok(g2, tag)) { add_granules(red, g2); last = 7; }
#pragma unroll 1
    for (int spins = 0; nrx < last && spins < (1 << 16); spins++) {
      fetch(g, nrx);
      if (granules_ok(g, tag)) { add_granules(red, g); nrx++; }
    }
    prof(wg, 20);
    TS(86)
    uint32_t ow[16];
#pragma unroll
    for (int i = 0; i < 16; i++) ow[i] = fma2(pack2(red[2 * i], red[2 * i + 1]), gt[i], xv[i]);
#pragma unroll
    for (int i = 0; i < 4; i++) stsm4(cx.sb + SM_XO + (frag ^ (i << 5)), ow[4 * i], ow[4 * i + 1], ow[4 * i + 2], ow[4 * i + 3]);
    __syncwarp();
#pragma unroll
    for (int i = 0; i < 4; i++) {
      uint4 v;
      const int row = cw * 16 + i * 4 + (lane >> 3);
      lds128(cx.sb + SM_XO + row * 128 + (((lane ^ row) & 7) << 4), v.x, v.y, v.z, v.w);
      *(uint4*)(out + (size_t)(qb * 128 + row) * DM + hs * 64 + (lane & 7) * 8) = v;
    }
    prof(wg, 22);
    TS(87)
    TS_DUMP()
  }
}

constexpr int FST_X = 24, FST_END = FST_X + 14 * 12;
__device__ __forceinline__ void ffn_producer(const Ctx& cx, int f, const CUtensorMap* tmX, const CUtensorMap* tmG,
                                             const CUtensorMap* tmU, const CUtensorMap* tmD) {
  const uint32_t full = cx.sb + SM_FULL, empty = cx.sb + SM_EMPTY;
  int pair = -2, u = 0;
#pragma unroll 1
  for (int st = 0; st < FST_END; st++) {
    const uint32_t sl = st & 7;
    const int unit = pair * 2 + (u & 1), k = u >> 1, k3 = k >= 3 ? k - 3 : k;
    if (unit < 27) {
      mbar_wait(empty + 8 * sl, ((st >> 3) & 1) ^ 1);
      mbar_expect_tx(full + 8 * sl, FSTAGE);
      if (pair < 0) tma3d(cx.sb + sl * FSTAGE, tmX, f * 512 + ((pair + 2) * 4 + (k >= 3) * 2 + (u & 1)) * 64, k3 * 3, full + 8 * sl);
      else if (pair < 9) tma2d_stream(cx.sb + sl * FSTAGE, k < 3 ? tmG : tmU, f * 1152 + unit * 64, k3 * 192, full + 8 * sl);
      else tma2d_stream(cx.sb + sl * FSTAGE, tmD, (unit - 18) * 64, f * 1152 + k * 192, full + 8 * sl);
    }
    if (++u == 12) { u = 0; pair++; }
  }
}

__device__ __forceinline__ void ffn_consumer(const Ctx& cx, int f, int wg, int cw, int lane, const __nv_bfloat16* x,
                                             const __nv_bfloat16* w_r) {
  const int r = lane >> 2, c = lane & 3, tid = cw * 32 + lane;
  unsigned e = 0;
  if (tid == 0) {
    e = cx.g->launch[blockIdx.x];
    cx.g->launch[blockIdx.x] = e + 1;
    *(unsigned*)(cx.sp + SM_TAG) = e;
  }
  if (tid < 72) *(uint4*)(cx.sp + SM_H + tid * 16) = *(const uint4*)(w_r + tid * 8);
  bar_sync(3, 256);
  prof(wg, 0);
  const uint32_t full = cx.sb + SM_FULL, empty = cx.sb + SM_EMPTY;
  const bool signaller = (tid & 127) == 0;
#pragma unroll 1
  for (int b = wg; b < 8; b += 2) {
    const int row0 = f * 512 + b * 64 + (cw & 3) * 16 + r;
    const uint32_t lo = ((cw & 3) * 16 + (lane & 15)) * 128 + (((lane >> 4) ^ (lane & 7)) << 4);
    LnAcc a;
    a.clear();
#pragma unroll 1
    for (int bx = 0; bx < 9; bx++) {
      const int st = (b >> 1) * 6 + (bx / 3) * 2 + wg;
      if (bx % 3 == 0) mbar_wait(full + 8 * (st & 7), (st >> 3) & 1);
#pragma unroll
      for (int k = 0; k < 4; k++) {
        uint32_t x0, x1, x2, x3;
        ldsm4(cx.sb + (st & 7) * FSTAGE + (bx % 3) * 8192 + (lo ^ (k << 5)), x0, x1, x2, x3);
        ln_accum1(a, k & 1, x0, x1, x2, x3);
      }
    }
    prof(wg, 8 + (b >> 1) * 3);
    float mean0, rstd0, mean1, rstd1;
    ln_stats(a, lane, mean0, rstd0, mean1, rstd1);
    prof(wg, 9 + (b >> 1) * 3);
    const uint32_t mm0 = pack2(mean0, mean0), mm1 = pack2(mean1, mean1);
    float d0[4] = {0, 0, 0, 0}, d1[4] = {0, 0, 0, 0};
#pragma unroll 1
    for (int bx = 0; bx < 9; bx++) {
      const int st = (b >> 1) * 6 + (bx / 3) * 2 + wg;
#pragma unroll
      for (int k = 0; k < 4; k++) {
        uint32_t n[4];
        ldsm4(cx.sb + (st & 7) * FSTAGE + (bx % 3) * 8192 + (lo ^ (k << 5)), n[0], n[1], n[2], n[3]);
        const uint8_t* wp = cx.sp + SM_H + (bx * 4 + k) * 32 + 4 * c;
#pragma unroll
        for (int i = 0; i < 4; i++) {
          const uint32_t t = sub2(n[i], (i & 1) ? mm1 : mm0);
          const float rs = (i & 1) ? rstd1 : rstd0;
          n[i] = pack2(bf_lo(t) * rs, bf_hi(t) * rs);
        }
        if (k & 1) hmma_k16(d1, n[0], n[1], n[2], n[3], *(const uint32_t*)wp, *(const uint32_t*)(wp + 16));
        else hmma_k16(d0, n[0], n[1], n[2], n[3], *(const uint32_t*)wp, *(const uint32_t*)(wp + 16));
      }
    }
    prof(wg, 10 + (b >> 1) * 3);
    bar_sync(4 + wg, 128);
    if (signaller) {
#pragma unroll
      for (int i = 0; i < 3; i++) mbar_arrive(empty + 8 * (((b >> 1) * 6 + i * 2 + wg) & 7));
    }
    if (c == 0) {
      cx.g->r[row0] = bfr(d0[0] + d1[0]);
      cx.g->r[row0 + 8] = bfr(d0[2] + d1[2]);
      cx.g->stats[row0] = make_float2(mean0, rstd0);
      cx.g->stats[row0 + 8] = make_float2(mean1, rstd1);
    }
  }
  prof(wg, 1);
  bar_sync(3, 256);
  e = *(const unsigned*)(cx.sp + SM_TAG);
  if (tid == 0) {
    atom_add_acq_rel(&cx.g->rcnt);
#pragma unroll 1
    for (int n = 0; n < (1 << 16) && (int)(ld_acquire(&cx.g->rcnt) - 4 * (e + 1)) < 0; n++) {}
  }
  bar_sync(3, 256);
  prof(wg, 2);
  uint32_t key[8];
#pragma unroll
  for (int i = 0; i < 8; i++) {
    const int row = i * 256 + tid;
    const uint32_t b = __float_as_uint(__ldcg(&cx.g->r[row])) >> 16;
    key[i] = (((b & 0x8000u) ? (~b & 0xFFFFu) : (b | 0x8000u)) << 16) | (uint32_t)(0xFFFF - row);
  }
  int mysel = 0;
#pragma unroll 1
  for (int k = 0; k < TOPC; k++) {
    uint32_t m = key[0];
#pragma unroll
    for (int i = 1; i < 8; i++) m = max(m, key[i]);
    m = __reduce_max_sync(0xffffffffu, m);
    uint32_t* tk = (uint32_t*)(cx.sp + SM_TOPK) + (k & 1) * 8;
    if (lane == 0) tk[cw] = m;
    bar_sync(3, 256);
    m = __reduce_max_sync(0xffffffffu, tk[lane & 7]);
#pragma unroll
    for (int i = 0; i < 8; i++) if (key[i] == m) key[i] = 0;
    if (k == cw) mysel = 0xFFFF - (int)(m & 0xFFFF);
  }
  {
    const float2 st = __ldcg(&cx.g->stats[mysel]);
    const uint32_t mm = pack2(st.x, st.x);
#pragma unroll 3
    for (int i = 0; i < 9; i++) {
      const uint32_t t = sub2(*(const uint32_t*)(x + (size_t)mysel * DM + i * 64 + 2 * lane), mm);
      *(uint32_t*)(cx.sp + SM_XSEL + i * 1024 + cw * 128 + (((lane >> 2) ^ cw) << 4) + (lane & 3) * 4) =
          pack2(bf_lo(t) * st.y, bf_hi(t) * st.y);
    }
    if (lane == 0 && f == 0) cx.g->sel[cw] = make_int2(mysel, __float_as_int(bfr(rcp(1.0f + ex2(-1.4426950408889634f * __ldcg(&cx.g->r[mysel]))))));
  }
  asm volatile("fence.proxy.async.shared::cta;" ::: "memory");
  bar_sync(3, 256);
  prof(wg, 3);
  auto run = [&](float (&acc)[4], int st, int n, uint32_t b) {
#pragma unroll 1
    for (int u = 0; u < n; u++, st += 2, b += 3072) {
      const uint32_t sl = st & 7;
      mbar_wait(full + 8 * sl, (st >> 3) & 1);
      wg_fence();
      const uint64_t da = mkdesc(cx.sb + sl * FSTAGE, 16), db = mkdesc(b, 16);
#pragma unroll
      for (int k = 0; k < 12; k++) mma_n8(acc, da + k * 128, db + (k >> 2) * 64 + (k & 3) * 2, u > 0 || k > 0);
      wg_commit();
      wg_wait<0>();
      if (signaller) mbar_arrive(empty + 8 * sl);
    }
    pin(acc);
  };
#pragma unroll 1
  for (int unit = wg; unit < 27; unit += 2) {
    if (unit >> 1 == 9) {
      asm volatile("fence.proxy.async.shared::cta;" ::: "memory");
      bar_sync(3, 256);
      prof(wg, 4);
    }
    const bool gu = unit < 18;
    float a0[4], a1[4];
#pragma unroll 1
    for (int m = 0; m < (gu ? 2 : 1); m++) {
      run(a1, FST_X + (unit >> 1) * 12 + m * 6 + wg, gu ? 3 : 6, cx.sb + (gu ? SM_XSEL : SM_H));
      if (m == 0) { a0[0] = a1[0]; a0[1] = a1[1]; a0[2] = a1[2]; a0[3] = a1[3]; }
    }
#pragma unroll
    for (int i = 0; i < 4; i++) {
      const int fl = (cw & 3) * 16 + r + (i >> 1) * 8, tok = 2 * c + (i & 1);
      if (gu) {
        const float h = bfr(silu_f(bfr(a0[i]))) * bfr(a1[i]);
        *(__nv_bfloat16*)(cx.sp + SM_H + unit * 1024 + tok * 128 + (((fl >> 3) ^ tok) << 4) + (fl & 7) * 2) = __float2bfloat16_rn(h);
      } else {
        cx.g->ypart[(f * TOPC + tok) * DM + (unit - 18) * 64 + fl] = a1[i];
      }
    }
  }
  prof(wg, 5);
  bar_sync(3, 256);
  if (tid == 0) atom_add_acq_rel(&cx.g->ycnt);
  prof(wg, 6);
}

struct KvMaps { CUtensorMap m[4]; };
__global__ void __cluster_dims__(2, 1, 1) __launch_bounds__(THREADS, 1)
fused_kernel(const __nv_bfloat16* __restrict__ x, const __nv_bfloat16* __restrict__ w_r, const __nv_bfloat16* __restrict__ kc,
             const __nv_bfloat16* __restrict__ vc, __nv_bfloat16* __restrict__ out, Scratch* scratch,
             const __grid_constant__ CUtensorMap tmX, const __grid_constant__ CUtensorMap tmWq,
             const __grid_constant__ KvMaps tmKV, const __grid_constant__ CUtensorMap tmWo,
             const __grid_constant__ CUtensorMap tmG, const __grid_constant__ CUtensorMap tmU,
             const __grid_constant__ CUtensorMap tmD, const __grid_constant__ CUtensorMap tmX16) {
  extern __shared__ __align__(1024) uint8_t smem_raw[];
  prof(0, 23, 511);
  if (X_PFX && threadIdx.x == 160) { prefetch_tmap(&tmX); prefetch_tmap(&tmWq); }
  Ctx cx;
  cx.sb = smem_u32(smem_raw);
  cx.sp = smem_raw;
  cx.g = scratch;
  cx.rank = blockIdx.x & 1;
  const int warp = __shfl_sync(0xffffffffu, threadIdx.x >> 5, 0);
  const int cluster = blockIdx.x >> 1;
  const bool is_ffn = blockIdx.x >= N_ATT_CTA;
  const int c7 = ((cluster - 36) * 37) >> 8;
  const int hs = cluster < 4 ? 4 + cluster : cluster < 36 ? (cluster - 4) >> 3 : 4 + c7;
  const int qb = (cluster < 4 ? 0 : cluster < 36 ? (cluster - 4) & 7 : cluster - 35 - 7 * c7) * 2 + cx.rank;

  auto load_x = [&](int w) {
#pragma unroll
    for (int i = 0; i < 3; i++) {
      mbar_expect_tx(cx.sb + SM_XFULL + 24 * w + 8 * i, 24576);
      tma3d(cx.sb + SM_X + (3 * w + i) * 24576, &tmX, qb * 128 + w * 64, i * 3, cx.sb + SM_XFULL + 24 * w + 8 * i);
    }
  };
  if (warp < 4) {
    asm volatile("setmaxnreg.dec.sync.aligned.u32 24;");
    if (elect_one()) {
      if (warp == 0) {
        TSP(64)
#pragma unroll
        for (int i = 0; i < 4; i++) mbar_init(cx.sb + SM_FULL + 8 * i, 1);
#pragma unroll
        for (int i = 3; i < 6; i++) if (X_ORDER != 3) mbar_init(cx.sb + SM_XFULL + 8 * i, 1);
        TSP(65)
      } else if (warp == 1) {
#pragma unroll
        for (int i = 0; i < 4; i++) mbar_init(cx.sb + SM_EMPTY + 8 * i, is_ffn ? 1 : 4);
        mbar_init(cx.sb + SM_BAR_MISC, 1);
        mbar_init(cx.sb + SM_BAR_XG, 1);
      } else if (warp == 2) {
        if (is_ffn) { prefetch_tmap(&tmG); prefetch_tmap(&tmU); prefetch_tmap(&tmD); }
        else if (!X_PFX) prefetch_tmap(&tmWq);
      } else if (is_ffn) {
#pragma unroll
        for (int i = 4; i < 8; i++) { mbar_init(cx.sb + SM_FULL + 8 * i, 1); mbar_init(cx.sb + SM_EMPTY + 8 * i, 1); }
      }
      asm volatile("fence.mbarrier_init.release.cluster;" ::: "memory");
    }
    __syncwarp();
    cluster_arrive();
    if (X_ORDER == 0 && warp == 0 && !is_ffn && elect_one()) {
      load_x(1);
    }
    __syncwarp();
    if (warp == 0) TSP(70)
    cluster_wait();
    if (warp == 0) TSP(71)
    prof(0, 24, 511);
    if (warp == 0) {
      if (elect_one()) {
        if (is_ffn) ffn_producer(cx, blockIdx.x - N_ATT_CTA, &tmX, &tmG, &tmU, &tmD);
        else attn_producer(cx, qb, hs, tmKV.m, &tmWq, &tmWo, load_x);
        prof(0, 25, 511);
      }
    } else if (!is_ffn) {
      attn_gate(cx, qb, hs, threadIdx.x - 32, x);
      asm volatile("fence.proxy.async;" ::: "memory");
      if (warp == 1) attn_helper(cx, qb, hs, read_lane(), &tmX16);
      else bar_arrive(BAR_OA, 352);
      attn_finish8(cx, qb, hs, warp - 1, read_lane(), out);
    }
    __syncwarp();
    cluster_arrive();
    cluster_wait();
  } else {
    if ((warp == 4 || (X_ORDER == 3 && warp == 8)) && !is_ffn && elect_one()) {
      const int w = X_ORDER == 3 ? warp >> 3 : 0;
#pragma unroll
      for (int i = 0; i < 3; i++) mbar_init(cx.sb + SM_XFULL + 24 * w + 8 * i, 1);
      asm volatile("fence.mbarrier_init.release.cluster;" ::: "memory");
      if (!w) TSP(66)
      load_x(w);
      if (!w) TSP(67)
    }
    __syncwarp();
    cluster_arrive();
    asm volatile("setmaxnreg.inc.sync.aligned.u32 240;");
    cluster_wait();
    const int cw = warp - 4, wg = cw >> 2;
    if (is_ffn) ffn_consumer(cx, blockIdx.x - N_ATT_CTA, wg, cw, read_lane(), x, w_r);
    else attn_consumer(cx, qb, hs, wg, cw, read_lane(), x, kc, vc, out);
  }
}

typedef CUresult (*EncodeFn)(CUtensorMap*, CUtensorMapDataType, cuuint32_t, void*, const cuuint64_t*, const cuuint64_t*,
                             const cuuint32_t*, const cuuint32_t*, CUtensorMapInterleave, CUtensorMapSwizzle,
                             CUtensorMapL2promotion, CUtensorMapFloatOOBfill);

void encode(EncodeFn fn, CUtensorMap* m, const void* p, int rank, const cuuint64_t* dims, const cuuint64_t* strides,
            const cuuint32_t* box) {
  const cuuint32_t es[5] = {1, 1, 1, 1, 1};
  fn(m, CU_TENSOR_MAP_DATA_TYPE_BFLOAT16, rank, const_cast<void*>(p), dims, strides, box, es, CU_TENSOR_MAP_INTERLEAVE_NONE,
     CU_TENSOR_MAP_SWIZZLE_128B, CU_TENSOR_MAP_L2_PROMOTION_L2_128B, CU_TENSOR_MAP_FLOAT_OOB_FILL_NONE);
}
void encode2d(EncodeFn fn, CUtensorMap* m, const void* p, uint64_t rows, uint64_t cols, uint32_t box_rows) {
  const cuuint64_t dims[2] = {cols, rows}, strides[1] = {cols * 2};
  const cuuint32_t box[2] = {64, box_rows};
  encode(fn, m, p, 2, dims, strides, box);
}

}

extern "C" void kernel_launch(void* const* d_in, const int* in_sizes, int n_in, void* d_out, int out_size) {
  (void)in_sizes; (void)n_in; (void)out_size;
  void* fnp = nullptr;
  cudaDriverEntryPointQueryResult qr;
  cudaGetDriverEntryPoint("cuTensorMapEncodeTiled", &fnp, cudaEnableDefault, &qr);
  EncodeFn fn = (EncodeFn)fnp;
  CUtensorMap tmWq, tmWo, tmG, tmU, tmD, tmX, tmX16;
  encode2d(fn, &tmX16, d_in[0], SEQ, DM, 16);
  KvMaps tmKV;
  for (int i = 0; i < 4; i++) encode2d(fn, &tmKV.m[i], d_in[1 + (i & 1)], 16 * SEQ, DH, i < 2 ? 112 : 96);
  encode2d(fn, &tmWq, d_in[3], DM, 4096, 64);
  {
    const cuuint64_t dims[3] = {64, SEQ, 9}, strides[2] = {DM * 2, 128};
    const cuuint32_t box[3] = {64, 64, 3};
    encode(fn, &tmX, d_in[0], 3, dims, strides, box);
  }
  encode2d(fn, &tmWo, d_in[4], 4096, DM, 128);
  encode2d(fn, &tmG, d_in[7], DM, FF, 192);
  encode2d(fn, &tmU, d_in[8], DM, FF, 192);
  encode2d(fn, &tmD, d_in[9], FF, DM, 192);
  cudaFuncSetAttribute(fused_kernel, cudaFuncAttributeMaxDynamicSharedMemorySize, SM_TOTAL);
  void* scratch = nullptr;
  cudaGetSymbolAddress(&scratch, g_scratch);
  fused_kernel<<<N_CTA, THREADS, SM_TOTAL>>>((const __nv_bfloat16*)d_in[0], (const __nv_bfloat16*)d_in[6], (const __nv_bfloat16*)d_in[1],
                                            (const __nv_bfloat16*)d_in[2], (__nv_bfloat16*)d_out, (Scratch*)scratch, tmX, tmWq, tmKV,
                                            tmWo, tmG, tmU, tmD, tmX16);
}
```

```cpp
#include <cuda_runtime.h>
#include <cuda_bf16.h>
#include <cuda.h>
#include <stdint.h>

namespace {

constexpr int SEQ = 2048, DM = 576, DH = 128, FF = 4608, TOPC = 8;
constexpr int N_ATT_CTA = 128, N_CTA = 132;
constexpr int THREADS = 384;

constexpr uint32_t SM_RING = 0;
constexpr uint32_t STAGE = 32768;
constexpr uint32_t SM_SLOT = 131072;
constexpr uint32_t FSTAGE = 24576;
constexpr uint32_t SM_XSEL = 196608;
constexpr uint32_t SM_H = 205824;
constexpr uint32_t SM_MISC = 229376;
constexpr uint32_t SM_FULL = SM_MISC, SM_EMPTY = SM_MISC + 32, SM_FFULL = SM_MISC + 64, SM_BAR_MISC = SM_MISC + 128,
                   SM_COLD = SM_MISC + 136, SM_TAG = SM_MISC + 144, SM_BAR_W = SM_MISC + 152, SM_ONES = SM_MISC + 160, SM_BAR_Q = SM_MISC + 176, SM_TOPK = SM_MISC + 192,
                   SM_XFULL = SM_MISC + 256, SM_BAR_XG = SM_MISC + 304, SM_STATS = SM_MISC + 320,
                   SM_FEMPTY = SM_MISC + 1344, SM_RAW = SM_FEMPTY, SM_WR = SM_MISC + 1408;
constexpr uint32_t SM_TOTAL = SM_MISC + 2560;
constexpr uint32_t SM_X = SM_MISC - 147456;

constexpr int BAR_GATE = 6, BAR_HELPER = 7, BAR_OA = 8, BAR_QS = 9, BAR_QF = 11;
constexpr int NST_Q = 18, NST_KV = 76, NST_O = 18;
__device__ __forceinline__ bool blk_big(int j) { return (unsigned)(j - 5) < 28; }
__device__ __forceinline__ int blk_row(int j) { return 112 * j - 16 * (min(j, 5) + max(j - 33, 0)); }
constexpr float SM_SCALE_LOG2 = 0.08838834764831845f * 1.4426950408889634f;

struct Scratch {
  uint4 part[16 * 64 * 2 * 4 * 128];
  uint4 gate[N_ATT_CTA * 1152];
  uint4 q[16 * 8 * 2 * 512];
  uint4 stats[SEQ];
  float ypart[4 * TOPC * DM];
  int2 sel[16];
  unsigned launch[160];
  unsigned pad0, ycnt, pad[30];
  unsigned qflag[128];
};
__device__ __align__(1024) Scratch g_scratch;

__device__ __forceinline__ void prof(int, int, int = 0) {}

#define TS(id) {}
#define TS_DUMP() {}
#define TS4(k) {}
#define TSP(k) {}
#define TS1(id) TS(id)
#define TS2(k) {}
#define TS3(k) {}

__device__ __forceinline__ uint32_t smem_u32(const void* p) { return (uint32_t)__cvta_generic_to_shared(p); }
__device__ __forceinline__ void mbar_init(uint32_t bar, uint32_t cnt) {
  asm volatile("mbarrier.init.shared::cta.b64 [%0], %1;" ::"r"(bar), "r"(cnt) : "memory");
}
__device__ __forceinline__ void mbar_expect_tx(uint32_t bar, uint32_t bytes) {
  asm volatile("mbarrier.arrive.expect_tx.shared::cta.b64 _, [%0], %1;" ::"r"(bar), "r"(bytes) : "memory");
}
__device__ __forceinline__ void mbar_arrive(uint32_t bar) {
  asm volatile("mbarrier.arrive.shared::cta.b64 _, [%0];" ::"r"(bar) : "memory");
}
__device__ __forceinline__ void mbar_arrive_cluster(uint32_t bar_cluster_addr) {
  asm volatile("mbarrier.arrive.shared::cluster.b64 _, [%0];" ::"r"(bar_cluster_addr) : "memory");
}
template <int ID>
__device__ __forceinline__ void mbar_arrive_cluster_now(uint32_t bar_cluster_addr, bool pred) {
  asm volatile("{\n.reg .pred p, q;\nsetp.ne.u32 p, %1, 0;\nsetp.eq.u32 q, %2, %3;\n"
               "ARR_LOOP:\n@p mbarrier.arrive.shared::cluster.b64 _, [%0];\n@q bra.uni ARR_LOOP;\n}"
               ::"r"(bar_cluster_addr), "r"((uint32_t)pred), "r"(blockIdx.y), "n"(ID) : "memory");
}
__device__ __forceinline__ void block_fence(int id) {
  asm volatile("{\n.reg .pred q;\nsetp.eq.u32 q, %0, %1;\nBF_LOOP:\n@q st.volatile.shared.u32 [%0], %0;\n@q bra.uni BF_LOOP;\n}"
               ::"r"(blockIdx.y), "r"(id) : "memory");
}
__device__ __forceinline__ void mbar_wait(uint32_t bar, uint32_t parity) {
  asm volatile("{\n.reg .pred p, q;\n.reg .u32 n;\nmov.u32 n, 0;\n"
               "WAIT_LOOP:\nmbarrier.try_wait.parity.shared::cta.b64 p, [%0], %1;\n"
               "add.u32 n, n, 1;\nsetp.lt.u32 q, n, 4194304;\nand.pred q, q, !p;\n@q bra WAIT_LOOP;\n}"
               ::"r"(bar), "r"(parity) : "memory");
}
__device__ __forceinline__ uint32_t mapa(uint32_t addr, uint32_t rank) {
  uint32_t r;
  asm volatile("mapa.shared::cluster.u32 %0, %1, %2;" : "=r"(r) : "r"(addr), "r"(rank));
  return r;
}
__device__ __forceinline__ void cluster_arrive() { asm volatile("barrier.cluster.arrive.relaxed.aligned;" ::: "memory"); }
__device__ __forceinline__ bool elect_one() {
  uint32_t p;
  asm volatile("{\n.reg .pred p;\nelect.sync _|p, 0xffffffff;\nselp.u32 %0, 1, 0, p;\n}" : "=r"(p));
  return p;
}
__device__ __forceinline__ int read_lane() { return threadIdx.x & 31; }
__device__ __forceinline__ int fresh_lane() {
  int l;
  asm volatile("mov.u32 %0, %%laneid;" : "=r"(l));
  return l;
}
__device__ __forceinline__ void cluster_wait() { asm volatile("barrier.cluster.wait.acquire.aligned;" ::: "memory"); }
__device__ __forceinline__ void bar_sync(int id, int n) { asm volatile("barrier.cta.sync %0, %1;" ::"r"(id), "r"(n) : "memory"); }
__device__ __forceinline__ void bar_arrive(int id, int n) { asm volatile("barrier.cta.arrive %0, %1;" ::"r"(id), "r"(n) : "memory"); }

__device__ __forceinline__ uint64_t policy_evict_first() {
  uint64_t p;
  asm("createpolicy.fractional.L2::evict_first.b64 %0, 1.0;" : "=l"(p));
  return p;
}
__device__ __forceinline__ void tma2d_mc(uint32_t dst, const CUtensorMap* tm, int c0, int c1, uint32_t bar, uint64_t pol) {
  asm volatile("cp.async.bulk.tensor.2d.shared::cluster.global.mbarrier::complete_tx::bytes.multicast::cluster.L2::cache_hint"
               " [%0], [%1, {%2, %3}], [%4], %5, %6;"
               ::"r"(dst), "l"(tm), "r"(c0), "r"(c1), "r"(bar), "h"((uint16_t)3), "l"(pol) : "memory");
}
__device__ __forceinline__ void tma3d(uint32_t dst, const CUtensorMap* tm, int c1, int c2, uint32_t bar) {
  asm volatile("cp.async.bulk.tensor.3d.shared::cluster.global.mbarrier::complete_tx::bytes [%0], [%1, {%2, %3, %4}], [%5];"
               ::"r"(dst), "l"(tm), "r"(0), "r"(c1), "r"(c2), "r"(bar) : "memory");
}
__device__ __forceinline__ void tma2d_stream(uint32_t dst, const CUtensorMap* tm, int c0, int c1, uint32_t bar) {
  asm volatile("{\n.reg .b64 pol;\ncreatepolicy.fractional.L2::evict_first.b64 pol, 1.0;\n"
               "cp.async.bulk.tensor.2d.shared::cluster.global.mbarrier::complete_tx::bytes.L2::cache_hint [%0], [%1, {%2, %3}], [%4], pol;\n}"
               ::"r"(dst), "l"(tm), "r"(c0), "r"(c1), "r"(bar) : "memory");
}
__device__ __forceinline__ void bulk_load(uint32_t dst, const void* src, uint32_t bytes, uint32_t bar) {
  asm volatile("cp.async.bulk.shared::cluster.global.mbarrier::complete_tx::bytes [%0], [%1], %2, [%3];"
               ::"r"(dst), "l"(src), "r"(bytes), "r"(bar) : "memory");
}
__device__ __forceinline__ void tma2d_prefetch(const CUtensorMap* tm, int c0, int c1) {
  asm volatile("cp.async.bulk.prefetch.tensor.2d.L2.global [%0, {%1, %2}];" ::"l"(tm), "r"(c0), "r"(c1) : "memory");
}
__device__ __forceinline__ void prefetch_tmap(const CUtensorMap* tm) {
  asm volatile("prefetch.tensormap [%0];" ::"l"(tm) : "memory");
}

__device__ __forceinline__ void wg_fence() { asm volatile("wgmma.fence.sync.aligned;" ::: "memory"); }
__device__ __forceinline__ void wg_commit() { asm volatile("wgmma.commit_group.sync.aligned;" ::: "memory"); }
template <int N> __device__ __forceinline__ void wg_wait() { asm volatile("wgmma.wait_group.sync.aligned %0;" ::"n"(N) : "memory"); }

__device__ __forceinline__ uint64_t mkdesc(uint32_t addr, uint32_t lbo_bytes) {
  return (uint64_t)(((addr & 0x3FFFF) >> 4) | ((lbo_bytes >> 4) << 16)) | ((uint64_t)0x40000040u << 32);
}
__device__ __forceinline__ uint64_t mkdesc_q(uint32_t addr) {
  return (uint64_t)(((addr & 0x3FFFF) >> 4) | (64u << 16)) | ((uint64_t)8 << 32);
}
template <int N> __device__ __forceinline__ void pin(float (&a)[N]) {
#pragma unroll
  for (int i = 0; i < N; i++) asm volatile("" : "+f"(a[i])::"memory");
}
template <int N> __device__ __forceinline__ void kill(float (&a)[N]) {
#pragma unroll
  for (int i = 0; i < N; i++) asm volatile("" : "=f"(a[i]));
}
template <int N> __device__ __forceinline__ void pin(uint32_t (&a)[N]) {
#pragma unroll
  for (int i = 0; i < N; i++) asm volatile("" : "+r"(a[i])::"memory");
}

#define F8(d, o) "+f"(d[o]), "+f"(d[o + 1]), "+f"(d[o + 2]), "+f"(d[o + 3]), "+f"(d[o + 4]), "+f"(d[o + 5]), "+f"(d[o + 6]), "+f"(d[o + 7])
#define R32A "%0, %1, %2, %3, %4, %5, %6, %7, %8, %9, %10, %11, %12, %13, %14, %15, %16, %17, %18, %19, %20, %21, %22, %23, %24, %25, %26, %27, %28, %29, %30, %31"
#define R32B "%32, %33, %34, %35, %36, %37, %38, %39, %40, %41, %42, %43, %44, %45, %46, %47, %48, %49, %50, %51, %52, %53, %54, %55, %56, %57, %58, %59, %60, %61, %62, %63"

#define O8(d, o) "=f"(d[o]), "=f"(d[o + 1]), "=f"(d[o + 2]), "=f"(d[o + 3]), "=f"(d[o + 4]), "=f"(d[o + 5]), "=f"(d[o + 6]), "=f"(d[o + 7])

__device__ __forceinline__ void mma_n128t(float (&d)[64], uint32_t a0, uint32_t a1, uint32_t a2, uint32_t a3, uint64_t db, bool acc) {
  if (acc)
    asm volatile("wgmma.mma_async.sync.aligned.m64n128k16.f32.bf16.bf16 {" R32A ", " R32B "}, {%64, %65, %66, %67}, %68, 1, 1, 1, 1;\n"
                 : F8(d, 0), F8(d, 8), F8(d, 16), F8(d, 24), F8(d, 32), F8(d, 40), F8(d, 48), F8(d, 56)
                 : "r"(a0), "r"(a1), "r"(a2), "r"(a3), "l"(db));
  else
    asm volatile("wgmma.mma_async.sync.aligned.m64n128k16.f32.bf16.bf16 {" R32A ", " R32B "}, {%64, %65, %66, %67}, %68, 0, 1, 1, 1;\n"
                 : O8(d, 0), O8(d, 8), O8(d, 16), O8(d, 24), O8(d, 32), O8(d, 40), O8(d, 48), O8(d, 56)
                 : "r"(a0), "r"(a1), "r"(a2), "r"(a3), "l"(db));
}
#define PV1(a0, a1, a2, a3, ob, acc) "add.s64 b, %92, " #ob ";\n" \
  "wgmma.mma_async.sync.aligned.m64n128k16.f32.bf16.bf16 {" R32A ", " R32B "}, {%" #a0 ", %" #a1 ", %" #a2 ", %" #a3 "}, b, " #acc ", 1, 1, 1;\n"
#define PV6 "wgmma.fence.sync.aligned;\n" PV1(64, 65, 66, 67, 0, p) PV1(68, 69, 70, 71, 128, 1) PV1(72, 73, 74, 75, 256, 1) \
  PV1(76, 77, 78, 79, 384, 1) PV1(80, 81, 82, 83, 512, 1) PV1(84, 85, 86, 87, 640, 1)
#define U4(a, o) "r"(a[o]), "r"(a[o + 1]), "r"(a[o + 2]), "r"(a[o + 3])
__device__ __forceinline__ void mma_pv(float (&d)[64], const uint32_t (&a)[28], uint64_t dv, bool acc, bool big) {
  asm volatile("{\n.reg .pred p, q;\n.reg .b64 b;\nsetp.ne.b32 p, %93, 0;\nsetp.eq.b32 q, %94, 0;\n@q bra.uni PV_SMALL;\n"
               PV6 PV1(88, 89, 90, 91, 768, 1) "wgmma.commit_group.sync.aligned;\nbra.uni PV_DONE;\n"
               "PV_SMALL:\n" PV6 "wgmma.commit_group.sync.aligned;\nPV_DONE:\n}\n"
               : F8(d, 0), F8(d, 8), F8(d, 16), F8(d, 24), F8(d, 32), F8(d, 40), F8(d, 48), F8(d, 56)
               : U4(a, 0), U4(a, 4), U4(a, 8), U4(a, 12), U4(a, 16), U4(a, 20), U4(a, 24), "l"(dv), "r"((int)acc), "r"((int)big) : "memory");
}
#define R48 R32A ", %32, %33, %34, %35, %36, %37, %38, %39, %40, %41, %42, %43, %44, %45, %46, %47"
#define R56 R48 ", %48, %49, %50, %51, %52, %53, %54, %55"
#define QK1(N, R, A, B, oa, ob, acc) "add.s64 a, " A ", " #oa ";\nadd.s64 b, " B ", " #ob ";\n" \
  "wgmma.mma_async.sync.aligned.m64n" #N "k16.f32.bf16.bf16 {" R "}, a, b, " #acc ", 1, 1, 0, 0;\n"
#define QK8(N, R, A, B) "{\n.reg .b64 a, b;\nwgmma.fence.sync.aligned;\n" QK1(N, R, A, B, 0, 0, 0) QK1(N, R, A, B, 128, 2, 1) \
  QK1(N, R, A, B, 256, 4, 1) QK1(N, R, A, B, 384, 6, 1) QK1(N, R, A, B, 512, 1024, 1) QK1(N, R, A, B, 640, 1026, 1) \
  QK1(N, R, A, B, 768, 1028, 1) QK1(N, R, A, B, 896, 1030, 1) "wgmma.commit_group.sync.aligned;\n}\n"
__device__ __forceinline__ void mma_qk(float (&d)[56], uint64_t dq, uint64_t dk) {
  asm volatile(QK8(112, R56, "%56", "%57")
               : O8(d, 0), O8(d, 8), O8(d, 16), O8(d, 24), O8(d, 32), O8(d, 40), O8(d, 48) : "l"(dq), "l"(dk) : "memory");
}
__device__ __forceinline__ void mma_qk(float (&d)[48], uint64_t dq, uint64_t dk) {
  asm volatile(QK8(96, R48, "%48", "%49")
               : O8(d, 0), O8(d, 8), O8(d, 16), O8(d, 24), O8(d, 32), O8(d, 40) : "l"(dq), "l"(dk) : "memory");
}
__device__ __forceinline__ void mma_n64t(float (&d)[32], uint32_t a0, uint32_t a1, uint32_t a2, uint32_t a3, uint64_t db, bool acc) {
  if (acc)
    asm volatile("wgmma.mma_async.sync.aligned.m64n64k16.f32.bf16.bf16 {" R32A "}, {%32, %33, %34, %35}, %36, 1, 1, 1, 1;\n"
                 : F8(d, 0), F8(d, 8), F8(d, 16), F8(d, 24) : "r"(a0), "r"(a1), "r"(a2), "r"(a3), "l"(db));
  else
    asm volatile("wgmma.mma_async.sync.aligned.m64n64k16.f32.bf16.bf16 {" R32A "}, {%32, %33, %34, %35}, %36, 0, 1, 1, 1;\n"
                 : O8(d, 0), O8(d, 8), O8(d, 16), O8(d, 24) : "r"(a0), "r"(a1), "r"(a2), "r"(a3), "l"(db));
}
__device__ __forceinline__ void mma_n64t_dyn(float (&d)[32], uint32_t a0, uint32_t a1, uint32_t a2, uint32_t a3, uint64_t db, int acc) {
  asm volatile("{\n.reg .pred p;\nsetp.ne.b32 p, %37, 0;\n"
               "wgmma.mma_async.sync.aligned.m64n64k16.f32.bf16.bf16 {" R32A "}, {%32, %33, %34, %35}, %36, p, 1, 1, 1;\n}\n"
               : F8(d, 0), F8(d, 8), F8(d, 16), F8(d, 24) : "r"(a0), "r"(a1), "r"(a2), "r"(a3), "l"(db), "r"(acc));
}
__device__ __forceinline__ void mma_n8(float (&d)[4], uint64_t da, uint64_t db, int acc) {
  asm volatile("{\n.reg .pred p;\nsetp.ne.b32 p, %6, 0;\n"
               "wgmma.mma_async.sync.aligned.m64n8k16.f32.bf16.bf16 {%0, %1, %2, %3}, %4, %5, p, 1, 1, 1, 0;\n}\n"
               : "+f"(d[0]), "+f"(d[1]), "+f"(d[2]), "+f"(d[3])
               : "l"(da), "l"(db), "r"(acc));
}
__device__ __forceinline__ void hmma_k8(float (&d)[4], uint32_t a0, uint32_t a1, uint32_t b0) {
  asm volatile("mma.sync.aligned.m16n8k8.row.col.f32.bf16.bf16.f32 {%0, %1, %2, %3}, {%4, %5}, {%6}, {%0, %1, %2, %3};"
               : "+f"(d[0]), "+f"(d[1]), "+f"(d[2]), "+f"(d[3]) : "r"(a0), "r"(a1), "r"(b0));
}
__device__ __forceinline__ void hmma_k16(float (&d)[4], uint32_t a0, uint32_t a1, uint32_t a2, uint32_t a3, uint32_t b0, uint32_t b1) {
  asm volatile("mma.sync.aligned.m16n8k16.row.col.f32.bf16.bf16.f32 {%0, %1, %2, %3}, {%4, %5, %6, %7}, {%8, %9}, {%0, %1, %2, %3};"
               : "+f"(d[0]), "+f"(d[1]), "+f"(d[2]), "+f"(d[3]) : "r"(a0), "r"(a1), "r"(a2), "r"(a3), "r"(b0), "r"(b1));
}

__device__ __forceinline__ uint32_t pack2(float lo, float hi) {
  uint32_t r;
  asm("cvt.rn.bf16x2.f32 %0, %1, %2;" : "=r"(r) : "f"(hi), "f"(lo));
  return r;
}
__device__ __forceinline__ float bf_lo(uint32_t w) { return __uint_as_float(w << 16); }
__device__ __forceinline__ float bf_hi(uint32_t w) { return __uint_as_float(w & 0xFFFF0000u); }
__device__ __forceinline__ float bfr(float x) { return __bfloat162float(__float2bfloat16_rn(x)); }
__device__ __forceinline__ uint32_t sub2(uint32_t a, uint32_t b) {
  uint32_t r;
  asm("sub.rn.bf16x2 %0, %1, %2;" : "=r"(r) : "r"(a), "r"(b));
  return r;
}
__device__ __forceinline__ uint32_t add2(uint32_t a, uint32_t b) {
  uint32_t r;
  asm("add.rn.bf16x2 %0, %1, %2;" : "=r"(r) : "r"(a), "r"(b));
  return r;
}
__device__ __forceinline__ uint32_t fma2(uint32_t a, uint32_t b, uint32_t c) {
  uint32_t r;
  asm("fma.rn.bf16x2 %0, %1, %2, %3;" : "=r"(r) : "r"(a), "r"(b), "r"(c));
  return r;
}
__device__ __forceinline__ float ex2(float x) {
  float r;
  asm("ex2.approx.ftz.f32 %0, %1;" : "=f"(r) : "f"(x));
  return r;
}
__device__ __forceinline__ float rcp(float x) {
  float r;
  asm("rcp.approx.ftz.f32 %0, %1;" : "=f"(r) : "f"(x));
  return r;
}
__device__ __forceinline__ float silu_f(float t) { return t * rcp(1.0f + ex2(-1.4426950408889634f * t)); }
__device__ __forceinline__ void lds128(uint32_t a, uint32_t& x, uint32_t& y, uint32_t& z, uint32_t& w) {
  asm volatile("ld.shared.v4.u32 {%0, %1, %2, %3}, [%4];" : "=r"(x), "=r"(y), "=r"(z), "=r"(w) : "r"(a) : "memory");
}
__device__ __forceinline__ void ldsm4(uint32_t a, uint32_t& x, uint32_t& y, uint32_t& z, uint32_t& w) {
  asm volatile("ldmatrix.sync.aligned.m8n8.x4.shared.b16 {%0, %1, %2, %3}, [%4];" : "=r"(x), "=r"(y), "=r"(z), "=r"(w) : "r"(a) : "memory");
}
constexpr uint32_t TAG = 0x10000;
__device__ __forceinline__ void st_gran(uint4* p, uint32_t x, uint32_t y, uint32_t z, uint32_t w) {
  asm volatile("st.relaxed.gpu.global.v4.b32 [%0], {%1, %2, %3, %4};" ::"l"(p), "r"(x), "r"(y), "r"(z), "r"(w) : "memory");
}
__device__ __forceinline__ void ld_gran(const uint4* p, uint32_t& x, uint32_t& y, uint32_t& z, uint32_t& w) {
  asm volatile("ld.relaxed.gpu.global.v4.b32 {%0, %1, %2, %3}, [%4];" : "=r"(x), "=r"(y), "=r"(z), "=r"(w) : "l"(p) : "memory");
}
__device__ __forceinline__ void stsm4(uint32_t a, uint32_t x, uint32_t y, uint32_t z, uint32_t w) {
  asm volatile("stmatrix.sync.aligned.m8n8.x4.shared.b16 [%0], {%1, %2, %3, %4};" ::"r"(a), "r"(x), "r"(y), "r"(z), "r"(w) : "memory");
}
__device__ __forceinline__ void cp16(uint32_t dst, const void* src) {
  asm volatile("cp.async.cg.shared.global [%0], [%1], 16;" ::"r"(dst), "l"(src) : "memory");
}
__device__ __forceinline__ void cp_wait_all() { asm volatile("cp.async.wait_all;" ::: "memory"); }
__device__ __forceinline__ void add_granules(float (&red)[32], const uint32_t (&g)[16]) {
#pragma unroll
  for (int i = 0; i < 16; i++) { red[2 * i] += bf_lo(g[i]); red[2 * i + 1] += bf_hi((i & 3) ? g[i] : g[i] & ~TAG); }
}
__device__ __forceinline__ bool granules_ok(const uint32_t (&g)[16], uint32_t tag) {
  uint32_t a, b;
  asm("lop3.b32 %0, %1, %2, %3, 0x7E;" : "=r"(a) : "r"(g[0]), "r"(g[4]), "r"(tag));
  asm("lop3.b32 %0, %1, %2, %3, 0x7E;" : "=r"(b) : "r"(g[8]), "r"(g[12]), "r"(tag));
  return __all_sync(0xffffffffu, ((a | b) & TAG) == 0);
}
__device__ __forceinline__ unsigned ld_acquire(const unsigned* p) {
  unsigned v;
  asm volatile("ld.acquire.gpu.global.u32 %0, [%1];" : "=r"(v) : "l"(p) : "memory");
  return v;
}
__device__ __forceinline__ unsigned atom_add_acq_rel(unsigned* p) {
  unsigned v;
  asm volatile("atom.acq_rel.gpu.global.add.u32 %0, [%1], 1;" : "=r"(v) : "l"(p) : "memory");
  return v;
}

struct LnAcc {
  float sm[2][4], sq[8][4];
  __device__ __forceinline__ void clear() {
#pragma unroll
    for (int i = 0; i < 4; i++) {
      sm[0][i] = sm[1][i] = 0.f;
#pragma unroll
      for (int j = 0; j < 8; j++) sq[j][i] = 0.f;
    }
  }
};
template <int K0, int K1>
__device__ __forceinline__ void ln_fetch(uint32_t (&xa)[144], uint32_t boxes, uint32_t lo) {
#pragma unroll
  for (int k = K0; k < K1; k++) ldsm4(boxes + (k >> 2) * 8192 + (lo ^ ((k & 3) << 5)), xa[4 * k], xa[4 * k + 1], xa[4 * k + 2], xa[4 * k + 3]);
}
__device__ __forceinline__ void ln_fetch_b(uint32_t (&b)[24], uint32_t& wb, uint32_t ws) {
#pragma unroll
  for (int j = 0; j < 6; j++, wb += ws) ldsm4(wb, b[4 * j], b[4 * j + 1], b[4 * j + 2], b[4 * j + 3]);
}
template <int K0, bool SQ>
__device__ __forceinline__ void ln_accum(const uint32_t (&xa)[144], LnAcc& a, const uint32_t (&b)[24]) {
#pragma unroll
  for (int k = K0; k < K0 + 12; k++) {
    const int h = k & 1;
    hmma_k16(a.sm[h], xa[4 * k], xa[4 * k + 1], xa[4 * k + 2], xa[4 * k + 3], b[2 * (k - K0)], b[2 * (k - K0) + 1]);
    if (SQ) {
      hmma_k8(a.sq[4 * h], xa[4 * k], xa[4 * k + 1], xa[4 * k]);
      hmma_k8(a.sq[4 * h + 1], xa[4 * k], xa[4 * k + 1], xa[4 * k + 1]);
      hmma_k8(a.sq[4 * h + 2], xa[4 * k + 2], xa[4 * k + 3], xa[4 * k + 2]);
      hmma_k8(a.sq[4 * h + 3], xa[4 * k + 2], xa[4 * k + 3], xa[4 * k + 3]);
    }
  }
}
__device__ __forceinline__ void ln_row(float sum, float sq, float& mean_b, float& rstd) {
  const float mean = sum * (1.0f / DM);
  const uint32_t mv = pack2(mean, fmaxf(sq * (1.0f / DM) - mean * mean, 0.0f));
  mean_b = bf_lo(mv);
  float sd;
  asm("sqrt.approx.f32 %0, %1;" : "=f"(sd) : "f"(bf_lo(pack2(bf_hi(mv) + 1e-5f, 0.f))));
  rstd = rcp(bf_lo(pack2(sd, 0.f)));
}
__device__ __forceinline__ void ln_diag(const LnAcc& a, int lane, float& t0, float& t1) {
  const bool odd = (lane >> 2) & 1;
  t0 = odd ? (a.sq[0][1] + a.sq[2][1]) + (a.sq[4][1] + a.sq[6][1]) : (a.sq[0][0] + a.sq[2][0]) + (a.sq[4][0] + a.sq[6][0]);
  t1 = odd ? (a.sq[1][3] + a.sq[3][3]) + (a.sq[5][3] + a.sq[7][3]) : (a.sq[1][2] + a.sq[3][2]) + (a.sq[5][2] + a.sq[7][2]);
}

template <bool ROUTED>
__device__ __forceinline__ uint32_t gate2(uint32_t x2, float mean_b, float rstd, float2 upd = make_float2(0.f, 0.f)) {
  const uint32_t xc = sub2(x2, pack2(mean_b, mean_b));
  uint32_t t = pack2(bf_lo(xc) * rstd, bf_hi(xc) * rstd);
  if (ROUTED) t = pack2(bf_lo(t) + upd.x, bf_hi(t) + upd.y);
  return pack2(silu_f(bf_lo(t)), silu_f(bf_hi(t)));
}

#define PF_D 4
#define X_SPLIT 38
#define X_SPLITA 36
#define X_SPLITS 32
#define X_SPLITSA 30
#define X_PA 8
#define X_PG 2
#define X_E0 10
#define X_F2 10
#define X_LD 0
#define X_NOR 0
#define X_HOIST 0
#define X_FENCE 1
#define X_WAKE 31
#define X_PFX 1
#define X_F1 0
#define X_BF2 1
#define X_EARLY 1
template <int V> struct IC { static constexpr int value = V; };

struct Ctx {
  uint32_t sb;
  uint8_t* sp;
  uint32_t rank;
  Scratch* g;
};

__device__ __forceinline__ bool acquire(const Ctx& cx, uint32_t r, uint32_t n, uint32_t bytes) {
  mbar_wait(cx.sb + SM_EMPTY + 8 * r, (n ^ (r >> 1) ^ 1) & 1);
  __syncwarp();
  const bool e = elect_one();
  if (e) mbar_expect_tx(cx.sb + SM_FULL + 8 * r, bytes);
  return e;
}
__device__ __forceinline__ void load_wq(const Ctx& cx, const CUtensorMap* tmWq, int st, int i, int n0, uint64_t pol) {
  const uint32_t r = st & 3, dst = cx.sb + SM_RING + r * STAGE + cx.rank * 16384, bar = cx.sb + SM_FULL + 8 * r;
  const int k0 = i < 3 ? 128 * i : 128 * i - 64;
  if (acquire(cx, r, st >> 2, i == 2 ? 16384 : 32768)) {
    tma2d_mc(dst, tmWq, n0, k0, bar, pol);
    if (i != 2) tma2d_mc(dst + 8192, tmWq, n0, k0 + 64, bar, pol);
  }
}
__device__ __forceinline__ void attn_producer(const Ctx& cx, int qb, int hs, const CUtensorMap* tmKV, const CUtensorMap* tmWq,
                                              const CUtensorMap* tmWq96, const CUtensorMap* tmWo) {
  const uint32_t full = cx.sb + SM_FULL, ring = cx.sb + SM_RING + cx.rank * 16384;
  const uint64_t last_use = policy_evict_first();
  int st = 0;
#pragma unroll 1
  for (int p = 0; p < 4; p++) {
#pragma unroll 1
    for (int i = 0; i < (p == 2 ? 3 : 5); i++, st++) {
      if (p == 2) {
        if (acquire(cx, st & 3, st >> 2, 24576))
          tma2d_mc(cx.sb + SM_RING + (st & 3) * STAGE + cx.rank * 12288, tmWq96, (hs * 4 + 3) * DH, 192 * i + 96 * cx.rank, full + 8 * (st & 3), last_use);
      } else {
        load_wq(cx, tmWq, st, i, (hs * 4 + (p ^ (p >> 1))) * DH + cx.rank * 64, last_use);
      }
      if (st < 3) TSP(72 + st)
      if (st == 1) {
#pragma unroll 1
        for (int b = 8 + qb; b < 72; b += 16)
          if (elect_one()) tma2d_prefetch(tmWq, (hs * 4 + ((b / 18) ^ (b / 36))) * DH + (b & 1) * 64, ((b % 18) >> 1) * 64);
      }
      if (st == 8 && qb < 2 * PF_D && elect_one()) tma2d_prefetch(tmKV + ((qb >> 1) & 1), cx.rank * 64, hs * 2 * SEQ + (qb >> 2) * 96);
    }
  }
  uint32_t r = 2, n = 4;
#pragma unroll 1
  for (int u = 0; u < NST_KV; u++) {
    const bool big = blk_big(u >> 1);
    if (acquire(cx, r, n, big ? 112 * 256 : 96 * 256)) {
      tma2d_mc(ring + r * STAGE, tmKV + (u & 1) + (big ? 0 : 2), cx.rank * 64, hs * 2 * SEQ + blk_row(u >> 1), full + 8 * r, last_use);
      if (((u ^ (qb >> 1)) & 7) == 0 && u + PF_D < NST_KV)
        tma2d_prefetch(tmKV + ((u + PF_D) & 1), cx.rank * 64, hs * 2 * SEQ + blk_row((u + PF_D) >> 1));
      if ((unsigned)(u - 32) < 36 && (u & 15) == qb) tma2d_prefetch(tmWo, ((u - 32) >> 2) * 64, hs * 512 + (u & 3) * 128);
    }
    if (++r == 4) { r = 1; n++; }
  }
#pragma unroll 1
  for (int u = 0; u < NST_O; u++) {
    const int s = u >> 1;
    const int blk = s == 0 ? 8 : ((hs + s) & 7);
    r = (0x87 >> (2 * (u & 3))) & 3;
    if (acquire(cx, r, (u >> 2) ^ ~u, 32768))
      tma2d_mc(ring + r * STAGE, tmWo, blk * 64, hs * 512 + ((u & 1) + cx.rank * 2) * 128, full + 8 * r, last_use);
  }
}

__device__ __forceinline__ void attn_gate(const Ctx& cx, int qb, int hs, int t, const __nv_bfloat16* x) {
  uint4 nx = *(const uint4*)(x + (size_t)(qb * 128 + (t >> 3)) * DM + hs * 64 + (t & 7) * 8);
  float wsum = 0.f;
  if (t < 32) {
    if (t == 0) {
      const unsigned e = cx.g->launch[qb * 8 + hs]++;
      *(uint2*)(cx.sp + SM_TAG) = make_uint2((~e & 1) * TAG, e);
    }
    mbar_wait(cx.sb + SM_BAR_W, 0);
#pragma unroll 3
    for (int i = 0; i < 9; i++) {
      const uint32_t w = *(const uint32_t*)(cx.sp + SM_WR + i * 128 + t * 4);
      wsum += bf_lo(w) + bf_hi(w);
    }
#pragma unroll
    for (int i = 1; i < 32; i *= 2) wsum += __shfl_xor_sync(0xffffffffu, wsum, i);
  }
  bar_sync(BAR_GATE, 352);
  if (t < 16) {
    const float2 st = *(const float2*)(cx.sp + SM_STATS + 8 * (hs * 16 + t));
    st_gran(cx.g->stats + qb * 128 + hs * 16 + t, __float_as_uint(st.x), __float_as_uint(st.y),
            __float_as_uint(bfr(fmaf(-st.x, wsum, *(const float*)(cx.sp + SM_RAW + 4 * t)) * st.y)), *(const uint32_t*)(cx.sp + SM_TAG + 4) + 1);
  }
#pragma unroll 1
  for (int ch = t; ch < 1152; ch += 96) {
    const uint4 v = nx;
    const int n = ch + 96;
    if (n < 1152) nx = *(const uint4*)(x + (size_t)(qb * 128 + (n < 1024 ? n >> 3 : hs * 16 + ((n - 1024) >> 3))) * DM + (n < 1024 ? hs * 64 : 512) + (t & 7) * 8);
    const int lr = ch < 1024 ? ch >> 3 : hs * 16 + ((ch - 1024) >> 3);
    const float2 st = *(const float2*)(cx.sp + SM_STATS + 8 * lr);
    cx.g->gate[blockIdx.x * 1152 + (ch ^ ((ch >> 3) & 7))] =
        make_uint4(gate2<false>(v.x, st.x, st.y), gate2<false>(v.y, st.x, st.y), gate2<false>(v.z, st.x, st.y), gate2<false>(v.w, st.x, st.y));
  }
}

constexpr uint32_t SM_XO = SM_SLOT, SM_GO = SM_SLOT + STAGE, SM_P8 = SM_SLOT + 2 * STAGE;
__device__ __forceinline__ void attn_helper(const Ctx& cx, int qb, int hs, int lane, const CUtensorMap* tmX16) {
  const unsigned e = *(const uint32_t*)(cx.sp + SM_TAG + 4);
  bar_sync(BAR_HELPER, 64);
  bool todo = lane < 2;
#pragma unroll 1
  for (int n = 0; __any_sync(0xffffffffu, todo); n++) {
    if (todo && (ld_acquire(&cx.g->qflag[(qb * 4 + (hs >> 1)) * 2 + lane]) == e + 1 || n == (1 << 16))) {
      asm volatile("fence.proxy.async;" ::: "memory");
      mbar_expect_tx(cx.sb + SM_BAR_Q + 8 * lane, 8192);
      bulk_load(cx.sb + SM_SLOT + 2 * STAGE + lane * 16384 + 8192, cx.g->q + ((qb * 8 + hs) * 2 + lane) * 512, 8192, cx.sb + SM_BAR_Q + 8 * lane);
      todo = false;
    }
  }
  const uint32_t tag = (~e & 1) * TAG;
  const uint4* src = cx.g->part + (size_t)((qb * 64 + 56) * 2 + (hs >> 2)) * 4 * 128 + (hs & 3) * 32 + lane;
  const uint32_t stg = cx.sb + SM_P8 + lane * 16;
  bar_sync(BAR_OA, 352);
  asm volatile("fence.proxy.async;" ::: "memory");
  if (lane == 0) {
    mbar_expect_tx(cx.sb + SM_BAR_MISC, 2 * 18432);
    bulk_load(cx.sb + SM_GO, cx.g->gate + blockIdx.x * 1152, 18432, cx.sb + SM_BAR_MISC);
#pragma unroll 1
    for (int i = 0; i < 9; i++)
      tma2d_stream(cx.sb + SM_XO + i * 2048, tmX16, i < 8 ? hs * 64 : 512, qb * 128 + (i < 8 ? i : hs) * 16, cx.sb + SM_BAR_MISC);
  }
#pragma unroll 1
  for (int n = 0; n < (1 << 16); n++) {
    __nanosleep(n ? 500 : 2000);
    uint32_t a, b, d, t;
    ld_gran(src - lane + (lane & 7) * (2 * 4 * 128) + 3 * 128 + 31, a, b, d, t);
    if (__all_sync(0xffffffffu, (a & TAG) == tag)) break;
  }
#pragma unroll 1
  for (int n = 0; n < (1 << 16); n++) {
#pragma unroll 1
    for (int i = 0; i < 8; i++) {
#pragma unroll
      for (int g = 0; g < 4; g++) cp16(stg + (i * 4 + g) * 512, src + i * (2 * 4 * 128) + g * 128);
    }
    cp_wait_all();
    uint32_t bad = 0;
#pragma unroll 4
    for (int i = 0; i < 32; i++) bad |= *(const volatile uint32_t*)(cx.sp + SM_P8 + lane * 16 + i * 512) ^ tag;
    if (__all_sync(0xffffffffu, (bad & TAG) == 0)) break;
  }
#pragma unroll 1
  for (int n = 0; n < (1 << 16) && ld_acquire(&cx.g->ycnt) != 4 * (e + 1); n++) __nanosleep(200);
  const int2 sel = __ldcg(&cx.g->sel[lane & 7]);
  const int lr = sel.x - qb * 128;
  uint32_t m = __ballot_sync(0xffffffffu, lane < 16 && ((lane & 8) ? (lr >> 4) == hs : (lr >> 7) == 0));
  mbar_wait(cx.sb + SM_BAR_MISC, 0);
#pragma unroll 1
  for (; m; m &= m - 1) {
    const int i = __ffs(m) - 1, row = __shfl_sync(0xffffffffu, lr, i);
    const float rs = __int_as_float(__shfl_sync(0xffffffffu, sel.y, i));
    const float* p = cx.g->ypart + (i & 7) * DM + (i < 8 ? hs * 64 : 512) + 2 * lane;
    const float2 a = __ldcg((const float2*)p), b = __ldcg((const float2*)(p + TOPC * DM)), c = __ldcg((const float2*)(p + 2 * TOPC * DM)),
                 d = __ldcg((const float2*)(p + 3 * TOPC * DM));
    const uint32_t y = pack2((a.x + b.x) + (c.x + d.x), (a.y + b.y) + (c.y + d.y));
    const uint32_t u = pack2(bf_lo(y) * rs, bf_hi(y) * rs);
    const float2 st = *(const float2*)(cx.sp + SM_STATS + 8 * row);
    const int o = (i < 8 ? row : 128 + (row & 15)) * 128 + ((lane * 4) ^ ((row & 7) << 4));
    *(uint32_t*)(cx.sp + SM_GO + o) = gate2<true>(*(const uint32_t*)(cx.sp + SM_XO + o), st.x, st.y, make_float2(bf_lo(u), bf_hi(u)));
  }
  __syncwarp();
  if (lane == 0) mbar_arrive(cx.sb + SM_BAR_XG);
}
__device__ __forceinline__ void attn_finish8(const Ctx& cx, int qb, int hs, int hw, int lane, __nv_bfloat16* out) {
  bar_sync(BAR_GATE, 96);
#pragma unroll 1
  for (int g = hw; g < 4; g += 3) {
    float acc[8] = {0.f, 0.f, 0.f, 0.f, 0.f, 0.f, 0.f, 0.f};
#pragma unroll 2
    for (int sidx = 0; sidx < 8; sidx++) {
      uint32_t a, b, d, t;
      lds128(cx.sb + SM_P8 + lane * 16 + (sidx * 4 + g) * 512, a, b, d, t);
      acc[0] += bf_lo(a); acc[1] += bf_hi(a & ~TAG); acc[2] += bf_lo(b); acc[3] += bf_hi(b);
      acc[4] += bf_lo(d); acc[5] += bf_hi(d); acc[6] += bf_lo(t); acc[7] += bf_hi(t);
    }
#pragma unroll
    for (int j = 0; j < 4; j++) {
      const int o = (128 + (lane >> 2) + (j & 1) * 8) * 128 + (((2 * g + (j >> 1)) ^ (lane >> 2)) << 4) + (lane & 3) * 4;
      uint32_t* xp = (uint32_t*)(cx.sp + SM_XO + o);
      *xp = fma2(pack2(acc[2 * j], acc[2 * j + 1]), *(const uint32_t*)(cx.sp + SM_GO + o), *xp);
    }
  }
  bar_sync(BAR_GATE, 96);
  for (int ch = hw * 32 + lane; ch < 128; ch += 96)
    *(uint4*)(out + (size_t)(qb * 128 + hs * 16 + (ch >> 3)) * DM + 512 + (ch & 7) * 8) =
        *(const uint4*)(cx.sp + SM_XO + 16384 + (ch ^ ((ch >> 3) & 7)) * 16);
}

__device__ __forceinline__ void ffn_producer(const Ctx& cx, int f, const CUtensorMap* tmWq, const CUtensorMap* tmG,
                                             const CUtensorMap* tmU, const CUtensorMap* tmD) {
  uint64_t keep;
  asm("createpolicy.fractional.L2::evict_normal.b64 %0, 1.0;" : "=l"(keep));
  int st = 0;
#pragma unroll 1
  for (int p = 0; p < 16; p++) {
#pragma unroll 1
    for (int i = 0; i < 5; i++, st++) load_wq(cx, tmWq, st, i, ((2 * (p & 3) + cx.rank) * 4 + 3) * DH + 64, keep);
  }
  const uint32_t full = cx.sb + SM_FFULL, empty = cx.sb + SM_FEMPTY;
  int pair = 0, u = 0;
#pragma unroll 1
  for (st = 0; st < 14 * 12; st++) {
    const uint32_t sl = st & 7;
    const int unit = pair * 2 + (u & 1), k = u >> 1, k3 = k >= 3 ? k - 3 : k;
    if (unit < 27) {
      mbar_wait(empty + 8 * sl, (st >> 3) & 1);
      __syncwarp();
      if (elect_one()) {
        mbar_expect_tx(full + 8 * sl, FSTAGE);
        if (pair < 9) tma2d_stream(cx.sb + sl * FSTAGE, k < 3 ? tmG : tmU, f * 1152 + unit * 64, k3 * 192, full + 8 * sl);
        else tma2d_stream(cx.sb + sl * FSTAGE, tmD, (unit - 18) * 64, f * 1152 + k * 192, full + 8 * sl);
      }
    }
    if (++u == 12) { u = 0; pair++; }
  }
}
__device__ __forceinline__ void load_x1(uint32_t dst, const CUtensorMap* tmX64, int row, int box, int n, uint32_t bar) {
  mbar_expect_tx(bar, n * 8192);
#pragma unroll 1
  for (int i = 0; i < n; i++) tma2d_stream(dst + i * 8192, tmX64, (box + i) * 64, row, bar);
}
__device__ __forceinline__ void ffn_publish(const Ctx& cx, int f, int w, int lane, const CUtensorMap* tmX64) {
  const uint32_t stg = cx.sb + SM_SLOT + w * 49152 + 32768;
#pragma unroll 1
  for (int n = 0; n < 16; n++) {
    bar_sync(BAR_QS + w, 160);
    if (lane == 0) {
#pragma unroll
      for (int i = 0; i < 2; i++)
        asm volatile("cp.async.bulk.global.shared::cta.bulk_group [%0], [%1], 8192;"
                     ::"l"(cx.g->q + (((f + (n & 12)) * 8 + 2 * (n & 3) + i) * 2 + w) * 512), "r"(stg + i * 8192) : "memory");
      asm volatile("cp.async.bulk.commit_group;\ncp.async.bulk.wait_group.read 0;" ::: "memory");
      if ((n & 3) == 3 && n < 12) load_x1(stg, tmX64, (f + n + 1) * 128 + w * 64, 8, 1, cx.sb + SM_XFULL + w * 24 + 16);
    }
    __syncwarp();
    bar_arrive(BAR_QF + w, 160);
    if (lane == 0) {
      asm volatile("cp.async.bulk.wait_group 0;\nfence.proxy.async;" ::: "memory");
      asm volatile("st.release.gpu.global.u32 [%0], %1;" ::"l"(&cx.g->qflag[((f + (n & 12)) * 4 + (n & 3)) * 2 + w]),
                   "r"(*(const uint32_t*)(cx.sp + SM_TAG + 4) + 1) : "memory");
    }
    __syncwarp();
  }
}

__device__ __forceinline__ void ffn_consumer(const Ctx& cx, int f, int wg, int cw, int lane, const __nv_bfloat16* x) {
  const int r = lane >> 2, c = lane & 3, tid = cw * 32 + lane;
  const uint32_t full = cx.sb + SM_FFULL, empty = cx.sb + SM_FEMPTY;
  const bool signaller = (tid & 127) == 0;
  prof(wg, 8);
  const unsigned e = *(const uint32_t*)(cx.sp + SM_TAG + 4);
  uint32_t key[8];
#pragma unroll 1
  for (int n = 0; n < (1 << 16); n++) {
    uint32_t bad = 0;
#pragma unroll
    for (int i = 0; i < 8; i++) {
      const int row = i * 256 + tid;
      uint32_t b, t;
      asm volatile("ld.relaxed.gpu.global.v2.b32 {%0, %1}, [%2];" : "=r"(b), "=r"(t) : "l"(&cx.g->stats[row].z) : "memory");
      bad |= t ^ (e + 1);
      b >>= 16;
      key[i] = (((b & 0x8000u) ? (~b & 0xFFFFu) : (b | 0x8000u)) << 16) | (uint32_t)(0xFFFF - row);
    }
    if (__all_sync(0xffffffffu, bad == 0)) break;
  }
  bar_sync(BAR_QF + wg, 160);
  bar_sync(3, 256);
  if (tid < 8) mbar_arrive(empty + 8 * tid);
  prof(wg, 9);
  int mysel = 0;
#pragma unroll 1
  for (int k = 0; k < TOPC; k++) {
    uint32_t m = key[0];
#pragma unroll
    for (int i = 1; i < 8; i++) m = max(m, key[i]);
    m = __reduce_max_sync(0xffffffffu, m);
    uint32_t* tk = (uint32_t*)(cx.sp + SM_TOPK) + (k & 1) * 8;
    if (lane == 0) tk[cw] = m;
    bar_sync(3, 256);
    m = __reduce_max_sync(0xffffffffu, tk[lane & 7]);
#pragma unroll
    for (int i = 0; i < 8; i++) if (key[i] == m) key[i] = 0;
    if (k == cw) mysel = 0xFFFF - (int)(m & 0xFFFF);
  }
  {
    const float4 st = __ldcg((const float4*)&cx.g->stats[mysel]);
    const uint32_t mm = pack2(st.x, st.x);
#pragma unroll 3
    for (int i = 0; i < 9; i++) {
      const uint32_t t = sub2(*(const uint32_t*)(x + (size_t)mysel * DM + i * 64 + 2 * lane), mm);
      *(uint32_t*)(cx.sp + SM_XSEL + i * 1024 + cw * 128 + (((lane >> 2) ^ cw) << 4) + (lane & 3) * 4) =
          pack2(bf_lo(t) * st.y, bf_hi(t) * st.y);
    }
    if (lane == 0 && f == 0) cx.g->sel[cw] = make_int2(mysel, __float_as_int(bfr(rcp(1.0f + ex2(-1.4426950408889634f * st.z)))));
  }
  asm volatile("fence.proxy.async.shared::cta;" ::: "memory");
  bar_sync(3, 256);
  prof(wg, 10);
  auto run = [&](float (&acc)[4], int st, int n, uint32_t b) {
#pragma unroll 1
    for (int u = 0; u < n; u++, st += 2, b += 3072) {
      const uint32_t sl = st & 7;
      mbar_wait(full + 8 * sl, (st >> 3) & 1);
      wg_fence();
      const uint64_t da = mkdesc(cx.sb + sl * FSTAGE, 16), db = mkdesc(b, 16);
#pragma unroll
      for (int k = 0; k < 12; k++) mma_n8(acc, da + k * 128, db + (k >> 2) * 64 + (k & 3) * 2, u > 0 || k > 0);
      wg_commit();
      wg_wait<0>();
      if (signaller) mbar_arrive(empty + 8 * sl);
    }
    pin(acc);
  };
#pragma unroll 1
  for (int unit = wg; unit < 27; unit += 2) {
    if (unit >> 1 == 9) {
      asm volatile("fence.proxy.async.shared::cta;" ::: "memory");
      bar_sync(3, 256);
      prof(wg, 11);
    }
    const bool gu = unit < 18;
    float a0[4], a1[4];
#pragma unroll 1
    for (int m = 0; m < (gu ? 2 : 1); m++) {
      run(a1, (unit >> 1) * 12 + m * 6 + wg, gu ? 3 : 6, cx.sb + (gu ? SM_XSEL : SM_H));
      if (m == 0) { a0[0] = a1[0]; a0[1] = a1[1]; a0[2] = a1[2]; a0[3] = a1[3]; }
    }
#pragma unroll
    for (int i = 0; i < 4; i++) {
      const int fl = (cw & 3) * 16 + r + (i >> 1) * 8, tok = 2 * c + (i & 1);
      if (gu) {
        const float h = bfr(silu_f(bfr(a0[i]))) * bfr(a1[i]);
        *(__nv_bfloat16*)(cx.sp + SM_H + unit * 1024 + tok * 128 + (((fl >> 3) ^ tok) << 4) + (fl & 7) * 2) = __float2bfloat16_rn(h);
      } else {
        cx.g->ypart[(f * TOPC + tok) * DM + (unit - 18) * 64 + fl] = a1[i];
      }
    }
  }
  prof(wg, 12);
  bar_sync(3, 256);
  if (tid == 0) atom_add_acq_rel(&cx.g->ycnt);
  prof(wg, 13);
}

constexpr float SUM_HI = 1.8446744e19f, SUM_LO = 9.0949470e-13f;

template <int LO, int HI, int N>
__device__ __forceinline__ void softmax_exp(float (&s)[N]) {
#pragma unroll
  for (int i = LO; i < HI; i++) s[i] = ex2(s[i]);
}
__device__ __forceinline__ void sum_tree(const uint32_t (&pf)[28], bool big, uint32_t& h0, uint32_t& h1) {
  uint32_t t0 = add2(add2(pf[16], pf[18]), add2(pf[20], pf[22])), t1 = add2(add2(pf[17], pf[19]), add2(pf[21], pf[23]));
  if (big) { t0 = add2(t0, add2(pf[24], pf[26])); t1 = add2(t1, add2(pf[25], pf[27])); }
  h0 = add2(add2(add2(add2(pf[0], pf[2]), add2(pf[4], pf[6])), add2(add2(pf[8], pf[10]), add2(pf[12], pf[14]))), t0);
  h1 = add2(add2(add2(add2(pf[1], pf[3]), add2(pf[5], pf[7])), add2(add2(pf[9], pf[11]), add2(pf[13], pf[15]))), t1);
}
__device__ __forceinline__ void exact_attention(float (&o)[64], float& l0, float& l1, uint32_t qaddr, const __nv_bfloat16* kh,
                                                const __nv_bfloat16* vh, int lane) {
  const int off = (lane >> 2) * DH + (lane & 3) * 2;
  float m0 = -3.0e38f, m1 = -3.0e38f;
  l0 = l1 = 0.f;
#pragma unroll
  for (int i = 0; i < 64; i++) o[i] = 0.f;
#pragma unroll 1
  for (int key = 0; key < SEQ; key += 16) {
    const __nv_bfloat16 *kp = kh + key * DH + off, *vp = vh + key * DH + off;
    float d0[4] = {0.f, 0.f, 0.f, 0.f}, d1[4] = {0.f, 0.f, 0.f, 0.f};
#pragma unroll 4
    for (int k = 0; k < 8; k++) {
      uint32_t q0, q1, q2, q3;
      ldsm4(qaddr + k * 2048, q0, q1, q2, q3);
      hmma_k16(d0, q0, q1, q2, q3, *(const uint32_t*)(kp + k * 16), *(const uint32_t*)(kp + k * 16 + 8));
      hmma_k16(d1, q0, q1, q2, q3, *(const uint32_t*)(kp + 8 * DH + k * 16), *(const uint32_t*)(kp + 8 * DH + k * 16 + 8));
    }
    float x0 = fmaxf(fmaxf(d0[0], d0[1]), fmaxf(d1[0], d1[1])), x1 = fmaxf(fmaxf(d0[2], d0[3]), fmaxf(d1[2], d1[3]));
    x0 = fmaxf(x0, __shfl_xor_sync(0xffffffffu, x0, 1));
    x1 = fmaxf(x1, __shfl_xor_sync(0xffffffffu, x1, 1));
    x0 = fmaxf(fmaxf(x0, __shfl_xor_sync(0xffffffffu, x0, 2)), m0);
    x1 = fmaxf(fmaxf(x1, __shfl_xor_sync(0xffffffffu, x1, 2)), m1);
    const float sc0 = ex2(m0 - x0), sc1 = ex2(m1 - x1);
    m0 = x0; m1 = x1;
    const uint32_t p0 = pack2(ex2(d0[0] - m0), ex2(d0[1] - m0)), p1 = pack2(ex2(d0[2] - m1), ex2(d0[3] - m1)),
                   p2 = pack2(ex2(d1[0] - m0), ex2(d1[1] - m0)), p3 = pack2(ex2(d1[2] - m1), ex2(d1[3] - m1));
    l0 = fmaf(l0, sc0, (bf_lo(p0) + bf_hi(p0)) + (bf_lo(p2) + bf_hi(p2)));
    l1 = fmaf(l1, sc1, (bf_lo(p1) + bf_hi(p1)) + (bf_lo(p3) + bf_hi(p3)));
#pragma unroll
    for (int nb = 0; nb < 16; nb++) {
      uint32_t b0, b1;
      asm("movmatrix.sync.aligned.m8n8.trans.b16 %0, %1;" : "=r"(b0) : "r"(*(const uint32_t*)(vp + nb * 8)));
      asm("movmatrix.sync.aligned.m8n8.trans.b16 %0, %1;" : "=r"(b1) : "r"(*(const uint32_t*)(vp + 8 * DH + nb * 8)));
      o[4 * nb] *= sc0; o[4 * nb + 1] *= sc0; o[4 * nb + 2] *= sc1; o[4 * nb + 3] *= sc1;
      hmma_k16(*(float (*)[4])&o[4 * nb], p0, p1, p2, p3, b0, b1);
    }
  }
}
__device__ __forceinline__ bool inv_sums(float l0, float l1, float& i0, float& i1) {
  l0 += __shfl_xor_sync(0xffffffffu, l0, 1); l1 += __shfl_xor_sync(0xffffffffu, l1, 1);
  l0 += __shfl_xor_sync(0xffffffffu, l0, 2); l1 += __shfl_xor_sync(0xffffffffu, l1, 2);
  i0 = rcp(l0);
  i1 = rcp(l1);
  return !(l0 + l1 <= SUM_HI) | (fminf(l0, l1) < SUM_LO);
}
template <int LO, int HI, int N>
__device__ __forceinline__ void park(uint32_t a, const float (&o)[N], float i0, float i1, bool on = true) {
#pragma unroll
  for (int i = LO; i < HI; i++)
    asm volatile("{\n.reg .pred p;\nsetp.ne.u32 p, %5, 0;\n@p stmatrix.sync.aligned.m8n8.x4.shared.b16 [%0], {%1, %2, %3, %4};\n}"
                 ::"r"(a + i * 2048), "r"(pack2(o[8 * i] * i0, o[8 * i + 1] * i0)), "r"(pack2(o[8 * i + 2] * i1, o[8 * i + 3] * i1)),
                 "r"(pack2(o[8 * i + 4] * i0, o[8 * i + 5] * i0)), "r"(pack2(o[8 * i + 6] * i1, o[8 * i + 7] * i1)), "r"((uint32_t)on) : "memory");
}

template <int I, int NP, int E0, int N, int NS>
__device__ __forceinline__ void exp_park(float (&s)[NS], uint32_t a, const float (&o)[64], float i0, float i1, bool on, int id) {
  if constexpr (I < NP) {
    constexpr int E1 = E0 + (N - E0) * X_PG / (NP - I);
    softmax_exp<E0, E1>(s);
    park<I, I + X_PG>(a, o, i0, i1, on);
    if (I + X_PG < NP) {
#pragma unroll
      for (int i = E0; i < E1; i++) asm volatile("" : "+f"(s[i])::"memory");
      block_fence(id + I);
    }
    exp_park<I + X_PG, NP, E1, N>(s, a, o, i0, i1, on, id);
  }
}

__device__ __forceinline__ void attn_consumer(const Ctx& cx, bool hlp, int qb, int hs, int wg, int cw, int lane, const __nv_bfloat16* x,
                                              const __nv_bfloat16* kc, const __nv_bfloat16* vc, __nv_bfloat16* out,
                                              const CUtensorMap* tmX64) {
  const uint32_t full = cx.sb + SM_FULL;
  const uint32_t ring = cx.sb + SM_RING;
  const uint32_t qwg = ring + wg * 16384;
  auto qlane = [&](int l) { return qwg + (cw & 3) * 256 + (l >> 4) * 1024 + (l & 15) * 16; };
  const bool signaller = lane == 0 && (cw & 3) < 2;
  const int my_turn = 1 + wg, other_turn = 2 - wg;
  const uint32_t empty_c = mapa(cx.sb + SM_EMPTY, cw & 1);

  float oA[64], oB[64], i0, i1;
  uint32_t xl[32];
  int st0 = 0;
  uint32_t mm0, mm1;
  float sq0, sq1;
  uint32_t st_e = 0;
  auto next_stats = [&](int b) {
    const uint4* p = cx.g->stats + (qb + 4 * b) * 128 + cw * 16 + (fresh_lane() >> 2);
    uint32_t u0, u1, z, t0, t1;
    ld_gran(p, mm0, u0, z, t0);
    ld_gran(p + 8, mm1, u1, z, t1);
    const uint32_t e1 = *(const uint32_t*)(cx.sp + SM_TAG + 4) + 1;
    sq0 = __uint_as_float(u0);
    sq1 = __uint_as_float(u1);
    st_e = (t0 ^ e1) | (t1 ^ e1);
  };
#pragma unroll 1
  for (int rb = 0;; rb++) {
    const int r = lane >> 2, c = lane & 3;
    const int lr0 = cw * 16 + r;
    uint32_t xa[144];
    float rstd0, rstd1;
    const uint32_t xf = cx.sb + SM_XFULL + wg * 24, xs = cx.sb + SM_SLOT + wg * 49152;
    auto lo_of = [&](int l) { return ((cw & 3) * 16 + (l & 15)) * 128 + (((l >> 4) ^ (l & 7)) << 4); };
    const uint32_t lo = lo_of(lane);
    prof(wg, 0);
    if (rb == 0) {
      const uint32_t xb = cx.sb + SM_X + wg * 73728;
      LnAcc a;
      a.clear();
      const uint32_t ws = (lane & 7) == 1 ? 64 : 0;
      uint32_t wb = cx.sb + (ws ? SM_WR + (lane >> 3) * 16 : SM_ONES);
      uint32_t b0[24], b1[24], b2[24];
      TS4(1)
      mbar_wait(cx.sb + SM_BAR_W, 0);
      ln_fetch_b(b0, wb, ws);
      ln_fetch_b(b1, wb, ws);
      ln_fetch_b(b2, wb, ws);
      mbar_wait(xf, 0);
      TS4(2)
      ln_fetch<0, 12>(xa, xb, lo);
      ln_accum<0, true>(xa, a, b0);
      mbar_wait(xf + 8, 0);
      TS4(3)
      ln_fetch<12, 24>(xa, xb, lo);
      if (wg == 0) {
        if (X_FENCE) asm volatile("fence.proxy.async.shared::cta;" ::: "memory");
        bar_sync(4, 128);
        if (signaller) {
          asm volatile("mbarrier.arrive.shared::cluster.b64 _, [%0], 2;" ::"r"(empty_c + 16) : "memory");
          asm volatile("mbarrier.arrive.shared::cluster.b64 _, [%0], 2;" ::"r"(empty_c + 24) : "memory");
        }
      }
      ln_accum<12, true>(xa, a, b1);
      mbar_wait(xf + 16, 0);
      TS4(4)
      prof(wg, 1);
      ln_fetch<24, 36>(xa, xb, lo);
      ln_accum<24, false>(xa, a, b2);
      if (cw == hs && c == 0) {
        *(float*)(cx.sp + SM_RAW + 4 * r) = a.sm[0][1] + a.sm[1][1];
        *(float*)(cx.sp + SM_RAW + 4 * r + 32) = a.sm[0][3] + a.sm[1][3];
      }
      ln_diag(a, lane, sq0, sq1);
      if (c != (r >> 1)) sq0 = sq1 = 0.f;
      rstd0 = a.sm[0][0] + a.sm[1][0];
      rstd1 = a.sm[0][2] + a.sm[1][2];
      mm0 = pack2(rstd0 * (1.0f / DM), rstd0 * (1.0f / DM));
      mm1 = pack2(rstd1 * (1.0f / DM), rstd1 * (1.0f / DM));
    } else {
      TS4(1)
      mbar_wait(xf, rb & 1);
      TS4(2)
      ln_fetch<0, 16>(xa, xs, lo_of(fresh_lane()));
#pragma unroll
      for (int i = 64; i < 144; i++) asm volatile("" : "=r"(xa[i]));
      asm volatile("fence.proxy.async.shared::cta;" ::: "memory");
      bar_sync(4 + wg, 128);
      TS4(3)
      if ((cw & 3) == 3 && elect_one()) load_x1(xs, tmX64, (qb + 4 * rb) * 128 + wg * 64, 4, 4, xf + 8);
      TS4(4)
#pragma unroll 1
      for (int n = 0; n < (1 << 16) && __any_sync(0xffffffffu, st_e); n++) next_stats(rb);
      mm0 = __byte_perm(mm0, 0, 0x3232);
      mm1 = __byte_perm(mm1, 0, 0x3232);
      rstd0 = sq0 * SM_SCALE_LOG2;
      rstd1 = sq1 * SM_SCALE_LOG2;
    }
#pragma unroll
    for (int i = 0; i < 16; i++) { xa[2 * i] = sub2(xa[2 * i], mm0); xa[2 * i + 1] = sub2(xa[2 * i + 1], mm1); }
    pin(xa);
    prof(wg, 2);
    TS4(5)

    float (&acc)[64] = oB;
#pragma unroll 1
    for (int p = 0; p < 4; p++) {
      const bool last = p == 3 && !hlp;
#pragma unroll
      for (int i = 0; i < 5; i++) {
        if (i == 4 && last) {
          wg_wait<1>();
          if (signaller && wg) mbar_arrive_cluster(empty_c + 8 * 3);
          wg_wait<0>();
          pin(acc);
          prof(wg, 6);
#pragma unroll
          for (int j = 0; j < 32; j++) xl[j] = xa[112 + j];
          i0 = rstd0;
          i1 = rstd1;
          goto attention;
        }
        const int st = st0 + i;
        const uint32_t sl = st & 3, slp = (st - 1) & 3;
        if (!X_HOIST || !st0 || i != (wg ? 4 : 1) || (i != 4 && i != 1)) mbar_wait(full + 8 * sl, (st >> 2) & 1);
        if (X_HOIST && (i == 0 || i == 3) && st0 && i == 3 * wg && !last) mbar_wait(full + 8 * ((st + 1) & 3), ((st + 1) >> 2) & 1);
        if (X_HOIST && i == 0 && !wg && last) mbar_wait(full + 8 * ((st + 1) & 3), ((st + 1) >> 2) & 1);
        TS4(8 + 2 * (p * 5 + i))
        const bool join = wg && last;
        if (st0 && i != (wg ? 4 : 1) && !(join && i == 3)) bar_sync(my_turn, 256);
        wg_fence();
        const uint64_t db = mkdesc(ring + sl * STAGE, 16384);
        const int kb0 = i < 3 ? 8 * i : 8 * i - 4;
#pragma unroll
        for (int k = 0; k < (i == 2 ? 4 : 8); k++) {
          const int kb = kb0 + k;
          mma_n128t(acc, xa[4 * kb], xa[4 * kb + 1], xa[4 * kb + 2], xa[4 * kb + 3], db + k * 128, kb > 0);
        }
        wg_commit();
        TS4(9 + 2 * (p * 5 + i))
        if (wg ? (i == 4 ? st0 < 75 : (st0 && (i < 2 || i == (join ? 3 : 2)))) : (st0 && i)) bar_arrive(other_turn, 256);
        if (p == 0 && i < 4) {
          if (i < 2 && !rb) {
#pragma unroll
            for (int j = 48 + 12 * i; j < 60 + 12 * i; j++) {
              sq0 = fmaf(bf_lo(xa[2 * j]), bf_lo(xa[2 * j]), fmaf(bf_hi(xa[2 * j]), bf_hi(xa[2 * j]), sq0));
              sq1 = fmaf(bf_lo(xa[2 * j + 1]), bf_lo(xa[2 * j + 1]), fmaf(bf_hi(xa[2 * j + 1]), bf_hi(xa[2 * j + 1]), sq1));
            }
          }
          if (i == 1 && rb) {
            mbar_wait(xf + 8, rb & 1);
            mbar_wait(xf + 16, rb & 1);
            ln_fetch<16, 36>(xa, xs - 32768, lo_of(fresh_lane()));
          }
          if (i == 1 && !rb) {
            sq0 += __shfl_xor_sync(0xffffffffu, sq0, 1); sq1 += __shfl_xor_sync(0xffffffffu, sq1, 1);
            sq0 += __shfl_xor_sync(0xffffffffu, sq0, 2); sq1 += __shfl_xor_sync(0xffffffffu, sq1, 2);
            float mean0, mean1;
            ln_row(rstd0, sq0, mean0, rstd0);
            ln_row(rstd1, sq1, mean1, rstd1);
            if (c == 0 && !hlp) {
              *(float2*)(cx.sp + SM_STATS + 8 * lr0) = make_float2(mean0, rstd0);
              *(float2*)(cx.sp + SM_STATS + 8 * (lr0 + 8)) = make_float2(mean1, rstd1);
            }
            *((uint32_t*)(cx.sp + SM_COLD) + wg) = 0;
            if (!hlp) bar_arrive(BAR_GATE, 352);
            bar_sync(4 + wg, 128);
            rstd0 *= SM_SCALE_LOG2;
            rstd1 *= SM_SCALE_LOG2;
          }
#pragma unroll
          for (int j = 0; j < 72; j++)
            if (j >= 2 * (i < 2 ? 8 * i + 8 : 8 * i + 4) && j < 2 * (i == 0 ? 16 : 8 * i + 12)) {
              xa[2 * j] = sub2(xa[2 * j], mm0);
              xa[2 * j + 1] = sub2(xa[2 * j + 1], mm1);
            }
          pin(xa);
        }
        if (hlp) {
          if (p == 1 && i == 2 && rb < 3 && (cw & 3) == 3 && elect_one()) load_x1(xs, tmX64, (qb + 4 * rb + 4) * 128 + wg * 64, 0, 4, xf);
          if (p == 3 && i == 2 && rb < 3) next_stats(rb + 1);
        }
        if (i == 0) {
          if (wg) {
            wg_wait<0>();
            if (signaller) mbar_arrive_cluster(empty_c + 8 * sl);
          }
        } else if (i == 2) {
          if (!join) {
            wg_wait<0>();
            if (signaller) mbar_arrive_cluster(empty_c + 8 * sl);
          }
        } else if (i != 3) {
          wg_wait<1>();
          if (signaller && (i == 4 || !wg)) mbar_arrive_cluster(empty_c + 8 * slp);
          wg_wait<0>();
          if (signaller) mbar_arrive_cluster(empty_c + 8 * sl);
        }
      }
      pin(acc);
      prof(wg, 3 + p);
      TS4(50 + 2 * p)
      st0 += 5;
      if (hlp && st0 > 5) bar_sync(BAR_QF + wg, 160);
      park<0, 8>(qlane(lane) + (hlp ? 5 + wg : 4 + p) * STAGE, acc, rstd0, rstd1);
      if (p || hlp) asm volatile("fence.proxy.async.shared::cta;" ::: "memory");
      if (hlp) bar_arrive(BAR_QS + wg, 160);
      TS4(51 + 2 * p)
      if (p == 1 && !hlp) {
        float (&ah)[32] = *(float (*)[32])&acc[0];
#pragma unroll
        for (int i = 0; i < 3; i++) {
          const uint32_t sl = (10 + i) & 3;
          mbar_wait(full + 8 * sl, ((10 + i) >> 2) & 1);
          TS4(28 + 2 * i)
          if (i == 0 || i == 2 - wg) bar_sync(my_turn, 256);
          wg_fence();
          const uint64_t db = mkdesc(ring + sl * STAGE, 16);
#pragma unroll
          for (int k = 0; k < 12; k++) {
            const int kb = 12 * i + k;
            if (kb) mma_n64t(ah, xa[4 * kb], xa[4 * kb + 1], xa[4 * kb + 2], xa[4 * kb + 3], db + k * 128, true);
            else mma_n64t_dyn(ah, xa[0], xa[1], xa[2], xa[3], db, blockIdx.y);
          }
          wg_commit();
          TS4(29 + 2 * i)
          if (i == 2 || i != wg) {
            bar_arrive(other_turn, 256);
            if (i) {
              wg_wait<1>();
              if (signaller && i == wg + 1) mbar_arrive_cluster(empty_c + 8 * ((9 + i) & 3));
            }
            wg_wait<0>();
            if (signaller) mbar_arrive_cluster(empty_c + 8 * sl);
          }
        }
        pin(ah);
        TS4(54)
        park<0, 4>(qlane(lane) + 6 * STAGE, ah, rstd0, rstd1);
        TS4(55)
        st0 = 13;
        p = 2;
      }
    }
    if (rb == 3) {
      TS_DUMP()
      ffn_consumer(cx, blockIdx.x & 3, wg, cw, fresh_lane(), x);
      return;
    }
  }

attention:
  uint32_t oa[128];
  float acc[32];
  {
    uint32_t pf[28];
    uint32_t bad = 0;
    float lA0 = 0.f, lA1 = 0.f, lB0 = 0.f, lB1 = 0.f;
    int t = 0;
    uint32_t ra = 2 * 2048, rb = 2048, rc = 2 * 2048, par = 0;
    const uint64_t dk0 = mkdesc(ring, 16), dv0 = mkdesc(ring, 16384);
    uint64_t dqA = mkdesc_q(qwg + 4 * STAGE), dqB = dqA + 2048;
    auto turn = [&](auto kc_, auto bc_) {
      constexpr int KIND = decltype(kc_)::value, BIG = decltype(bc_)::value;
      constexpr int HB = KIND == 1, ID = 10 * KIND + 30 * BIG, T0 = BIG ? 38 : 0;
      constexpr int NS = BIG ? 56 : 48, SPLIT = BIG ? (HB ? X_SPLIT : X_SPLITA) : (HB ? X_SPLITS : X_SPLITSA);
      float s[NS];
      float (&op)[64] = HB ? oA : oB;
      uint32_t h0 = 0, h1 = 0;
      TS2(0)
      bar_sync(my_turn, 256);
      TS2(1)
      if (KIND) { pin(pf); pin(op); }
      mma_qk(s, HB ? dqB : dqA, dk0 + (HB ? ra : rc));
      TS2(2)
      if (KIND) {
        const bool bigp = HB ? BIG : BIG ? t != 10 : t == 66;
        if (X_BF2) block_fence(ID + 9);
        pin(pf);
        sum_tree(pf, bigp, h0, h1);
        asm volatile("" : "+r"(h0), "+r"(h1)::"memory");
        if (HB) mbar_wait(full + (rb >> 8), par);
        mma_pv(op, pf, dv0 + rb, t != T0 + 2 - HB, bigp);
      } else {
        mbar_wait(full + (rb >> 8), (NST_Q - 1) >> 2 & 1);
#pragma unroll
        for (int k = 0; k < 8; k++) mma_n128t(op, xl[4 * k], xl[4 * k + 1], xl[4 * k + 2], xl[4 * k + 3], dv0 + rb + k * 128, 1);
        wg_commit();
      }
      TS2(3)
      bar_arrive(other_turn, 256);
      (HB ? lA0 : lB0) += bf_lo(h0) + bf_hi(h0);
      (HB ? lA1 : lB1) += bf_lo(h1) + bf_hi(h1);
      wg_wait<1>();
      pin(s);
      TS1(t)
      TS2(4)
      if (KIND == 1) mbar_arrive_cluster_now<ID + 3>(empty_c + (ra >> 8), signaller);
      if (BIG && t == T0 + HB) {
        const uint32_t a = qlane(fresh_lane()) + (4 + HB) * STAGE;
        const bool ok = !__any_sync(0xffffffffu, inv_sums(HB ? lB0 : lA0, HB ? lB1 : lA1, i0, i1));
        bad = (HB ? bad : 0) | (ok ? 0 : 1 << HB);
        (HB ? lB0 : lA0) = 0.f;
        (HB ? lB1 : lA1) = 0.f;
        softmax_exp<0, X_E0>(s);
#pragma unroll
        for (int i = 0; i < X_E0; i++) asm volatile("" : "+f"(s[i])::"memory");
        block_fence(ID + 7);
        exp_park<0, X_PA, X_E0, SPLIT>(s, a, HB ? oB : oA, i0, i1, ok, 200 + ID);
        if (!HB) dqB += 2048;
        prof(wg, 8 + HB);
      } else {
        if (HB && !BIG) bad = (bad & 3) | (inv_sums(lA0, lA1, i0, i1) ? 4 : 0);
        softmax_exp<0, SPLIT>(s);
      }
      pin(s);
      if (!BIG) block_fence(ID + 4);
      TS2(5)
      wg_wait<0>();
      TS2(6)
      pin(op);
      if (KIND) pin(pf); else pin(xl);
      if (HB) {
        par ^= rc == 2048;
        if (BIG && t == 37) dqA -= 4 * 2048;
        if (BIG && t == X_WAKE && cw == 0) bar_arrive(BAR_HELPER, 64);
      } else {
        mbar_arrive_cluster_now<ID + 5>(empty_c + (rb >> 8), signaller);
        if (KIND) {
          par ^= ra == 2048;
          const uint32_t x = ra;
          ra = rc; rc = rb; rb = x;
        }
      }
      softmax_exp<SPLIT, NS>(s);
#pragma unroll
      for (int i = 0; i < NS / 2; i++) pf[i] = pack2(s[2 * i], s[2 * i + 1]);
      pin(pf);
      if (KIND == 0) {
        block_fence(ID + 6);
        park<0, 8>(qlane(fresh_lane()), oB, i0, i1);
        asm volatile("fence.proxy.async.shared::cta;" ::: "memory");
        prof(wg, 7);
      }
      if (BIG && X_PA < 8 && t == T0 + HB) park<X_PA, 8>(qlane(fresh_lane()) + (4 + HB) * STAGE, HB ? oB : oA, i0, i1, !(bad >> HB));
      if (BIG && !HB && t == T0) mbar_wait(cx.sb + SM_BAR_Q + 8 * wg, 0);
      if (HB) mbar_wait(full + (rc >> 8), par);
      t++;
    };
#pragma unroll
    for (int i = 24; i < 28; i++) asm volatile("" : "=r"(pf[i]));
    mbar_wait(full + 8 * 2, 0);
    turn(IC<0>(), IC<0>());
    rb = 3 * 2048; rc = 2048;
    kill(oA);
    const bool never = blockIdx.y == 1;
#pragma unroll 1
    while (true) {
      turn(IC<1>(), IC<0>());
      if (t == 76) break;
      if (t == 10) {
#pragma unroll 1
        do {
#pragma unroll 1
          do turn(IC<2>(), IC<1>()); while (never);
          turn(IC<1>(), IC<1>());
        } while (t != 66);
      }
#pragma unroll 1
      do turn(IC<2>(), IC<0>()); while (never);
    }
    const uint32_t ql = qlane(fresh_lane());
    auto scale = [&](auto lo, auto hi) {
#pragma unroll
      for (int i = decltype(lo)::value; i < decltype(hi)::value; i++) {
        oa[32 + 2 * i] = pack2(oA[4 * i] * i0, oA[4 * i + 1] * i0);
        oa[32 + 2 * i + 1] = pack2(oA[4 * i + 2] * i1, oA[4 * i + 3] * i1);
        asm volatile("" : "+r"(oa[32 + 2 * i]), "+r"(oa[32 + 2 * i + 1])::"memory");
      }
    };
    TS3(1)
    if (X_LD == 0) {
#pragma unroll
      for (int i = 0; i < 8; i++) ldsm4(ql + 4 * STAGE + i * 2048, oa[4 * i], oa[4 * i + 1], oa[4 * i + 2], oa[4 * i + 3]);
    }
    {
      uint32_t h0, h1;
      sum_tree(pf, false, h0, h1);
      if (inv_sums(lB0 + (bf_lo(h0) + bf_hi(h0)), lB1 + (bf_lo(h1) + bf_hi(h1)), lB0, lB1)) bad |= 8;
    }
    scale(IC<0>(), IC<X_F1>());
    volatile uint32_t* const cold = (volatile uint32_t*)(cx.sp + SM_COLD) + wg;
    if (bad) *cold = 1;
    block_fence(93);
    TS3(2)
    bar_sync(my_turn, 256);
    const uint32_t is_cold = *cold;
    TS3(3)
    pin(pf); pin(oB);
    mma_pv(oB, pf, dv0 + 2 * 2048, true, false);
    mbar_arrive_cluster_now<91>(empty_c, signaller && !is_cold);
    TS3(4)
    if (X_LD == 1) {
#pragma unroll
      for (int i = 0; i < 8; i++) ldsm4(ql + 4 * STAGE + i * 2048, oa[4 * i], oa[4 * i + 1], oa[4 * i + 2], oa[4 * i + 3]);
    }
    const uint64_t db = mkdesc(ring + 3 * STAGE, 16);
    scale(IC<X_F1>(), IC<X_F2>());
    block_fence(94);
#pragma unroll
    for (int i = 0; i < 32; i++) asm volatile("" : "+r"(oa[i])::"memory");
    wg_fence();
#pragma unroll
    for (int k = 0; k < 8; k++) mma_n64t(acc, oa[4 * k], oa[4 * k + 1], oa[4 * k + 2], oa[4 * k + 3], db + k * 128, k > 0);
    if (X_F2 < 16) {
      wg_commit();
      block_fence(95);
      scale(IC<X_F2>(), IC<16>());
      TS3(5)
      wg_fence();
    }
#pragma unroll
    for (int k = 8; k < 16; k++) mma_n64t(acc, oa[4 * k], oa[4 * k + 1], oa[4 * k + 2], oa[4 * k + 3], db + k * 128, 1);
    wg_commit();
    bar_arrive(other_turn, 256);
    wg_wait<(X_F2 < 16 ? 2 : 1)>();
    pin(oB); pin(pf);
    TS(76)
    TS3(6)
    if (signaller) mbar_arrive_cluster(empty_c + 8 * 2);
#pragma unroll
    for (int i = 16; i < 24; i++) ldsm4(ql + 5 * STAGE + (i & 7) * 2048, oa[4 * i], oa[4 * i + 1], oa[4 * i + 2], oa[4 * i + 3]);
#pragma unroll
    for (int i = 0; i < 16; i++) {
      oa[96 + 2 * i] = pack2(oB[4 * i] * lB0, oB[4 * i + 1] * lB0);
      oa[96 + 2 * i + 1] = pack2(oB[4 * i + 2] * lB1, oB[4 * i + 3] * lB1);
    }
    TS3(7)
    mbar_wait(full + 8 * 1, 0);
    TS3(8)
    wg_wait<0>();
    pin(acc); pin(oa);
    if (__any_sync(0xffffffffu, is_cold)) {
      bad = __reduce_or_sync(0xffffffffu, bad);
      if (!(bad & 8)) {
#pragma unroll
        for (int i = 24; i < 32; i++) stsm4(ql + 6 * STAGE + (i & 7) * 2048, oa[4 * i], oa[4 * i + 1], oa[4 * i + 2], oa[4 * i + 3]);
      }
#pragma unroll 1
      for (int h = 0; h < 4; h++) {
        if (bad >> h & 1) {
          const uint32_t a = ql + ((0x6054 >> (4 * h)) & 7) * STAGE;
          const size_t o = (size_t)(hs * 2 + (h >> 1)) * SEQ * DH;
          float ox[64], l0, l1;
          exact_attention(ox, l0, l1, a, kc + o, vc + o, fresh_lane());
          inv_sums(l0, l1, l0, l1);
          __syncwarp();
          park<0, 8>(a, ox, l0, l1);
        }
      }
      __syncwarp();
#pragma unroll
      for (int i = 0; i < 32; i++)
        if ((i >> 3) != 1 || (bad & 4))
          ldsm4(ql + ((0x6504 >> (4 * (i >> 3))) & 7) * STAGE + (i & 7) * 2048, oa[4 * i], oa[4 * i + 1], oa[4 * i + 2], oa[4 * i + 3]);
      pin(oa);
      asm volatile("fence.proxy.async.shared::cta;" ::: "memory");
      bar_sync(4 + wg, 128);
      if (signaller) mbar_arrive_cluster(empty_c);
      wg_fence();
#pragma unroll
      for (int k = 0; k < 16; k++) mma_n64t(acc, oa[4 * k], oa[4 * k + 1], oa[4 * k + 2], oa[4 * k + 3], db + k * 128, k > 0);
      wg_commit();
      wg_wait<0>();
      pin(acc);
    }
    if (signaller) mbar_arrive_cluster(empty_c + 8 * 3);
  }

  prof(wg, 10);
  TS3(9)
  {
    lane = fresh_lane();
    const int tw = (cw & 3) * 32 + lane;
    float red[32];
    kill(red);
    const uint32_t tag = *(const uint32_t*)(cx.sp + SM_TAG);
    uint4* const xch = cx.g->part + (size_t)(qb * 64 * 2 + wg) * 4 * 128 + tw;
    int nrx = 1;
    auto region = [](int s, int h) { return h ? 1 + (s & 1) : (s & 1) ? 0 : 3; };
    auto half_step = [&](int s, auto hc, bool arrive) {
      constexpr int h = decltype(hc)::value;
      const uint64_t db = mkdesc(ring + region(s, h) * STAGE, 16);
      bar_sync(my_turn, 256);
      pin(oa);
      wg_fence();
#pragma unroll
      for (int k = 0; k < 16; k++) {
        const int kb = h * 16 + k;
        mma_n64t(acc, oa[4 * kb], oa[4 * kb + 1], oa[4 * kb + 2], oa[4 * kb + 3], db + k * 128, kb > 0);
      }
      wg_commit();
      if (arrive) bar_arrive(other_turn, 256);
    };
    auto await = [&](int s, int h) { mbar_wait(full + 8 * region(s, h), ((s >> 1) ^ h ^ 1) & 1); };
    auto fetch = [&](uint32_t (&g)[16], int n) {
      const uint4* p = xch + (hs * 7 + n - 1) * (2 * 4 * 128);
#pragma unroll
      for (int i = 0; i < 4; i++) ld_gran(p + i * 128, g[4 * i], g[4 * i + 1], g[4 * i + 2], g[4 * i + 3]);
    };
    uint32_t g[16];
#pragma unroll 1
    for (int s = 0; s < 8; s++) {
      const bool pend = nrx < s - 1;
      if (pend) fetch(g, nrx);
      half_step(s, IC<1>(), true);
      TS3(s < 3 ? 16 + 8 * s : 75)
      if (s == 0) {
        bar_arrive(BAR_OA, 352);
#pragma unroll
        for (int i = 0; i < 32; i++) red[i] = 0.f;
      }
      await(s + 1, 0);
      TS3(s < 3 ? 17 + 8 * s : 75)
      wg_wait<0>();
      TS3(s < 3 ? 18 + 8 * s : 75)
      if (signaller && s < 7) mbar_arrive_cluster(empty_c + 8 * region(s, 1));
      pin(acc);
      TS(77 + s)
      prof(wg, 12 + s);
      uint4* p = xch + (s == 0 ? 56 + hs : ((hs + s) & 7) * 7 + s - 1) * (2 * 4 * 128);
#pragma unroll
      for (int i = 0; i < 4; i++)
        st_gran(p + i * 128, (pack2(acc[8 * i], acc[8 * i + 1]) & ~TAG) | tag, pack2(acc[8 * i + 2], acc[8 * i + 3]),
                pack2(acc[8 * i + 4], acc[8 * i + 5]), pack2(acc[8 * i + 6], acc[8 * i + 7]));
      TS3(s < 3 ? 19 + 8 * s : 75)
      half_step(s + 1, IC<0>(), true);
      TS3(s < 3 ? 20 + 8 * s : 75)
      await(s + 1, 1);
      TS3(s < 3 ? 21 + 8 * s : 75)
      if (pend && granules_ok(g, tag)) { add_granules(red, g); nrx++; }
      if (X_EARLY == 2 && s == 7) fetch(g, nrx);
      wg_wait<0>();
      TS3(s < 3 ? 22 + 8 * s : 75)
      if (signaller && s < 6) mbar_arrive_cluster(empty_c + 8 * region(s + 1, 0));
    }
    uint32_t xv[16], gt[16], g2[16];
    if (X_EARLY < 2) fetch(g, nrx);
    mbar_wait(cx.sb + SM_BAR_XG, 0);
    const bool two = nrx < 7;
    bool ok;
    {
      const uint64_t db = mkdesc(ring + STAGE, 16);
      if (X_EARLY == 2) ok = granules_ok(g, tag);
      bar_sync(my_turn, 256);
      if (X_EARLY == 2) fetch(g2, 7);
#pragma unroll
      for (int i = 64; i < 128; i++) asm volatile("" : "+r"(oa[i])::"memory");
      wg_fence();
#pragma unroll
      for (int k = 16; k < 32; k++) mma_n64t(acc, oa[4 * k], oa[4 * k + 1], oa[4 * k + 2], oa[4 * k + 3], db + (k - 16) * 128, 1);
      wg_commit();
      if (wg == 0) bar_arrive(other_turn, 256);
    }
    if (X_EARLY < 2) {
      ok = granules_ok(g, tag);
      fetch(g2, 7);
    }
    const uint32_t frag = (cw * 16 + (lane & 15)) * 128 + (((lane >> 4) ^ (lane & 7)) << 4);
#pragma unroll
    for (int i = 0; i < 4; i++) {
      ldsm4(cx.sb + SM_XO + (frag ^ (i << 5)), xv[4 * i], xv[4 * i + 1], xv[4 * i + 2], xv[4 * i + 3]);
      ldsm4(cx.sb + SM_GO + (frag ^ (i << 5)), gt[4 * i], gt[4 * i + 1], gt[4 * i + 2], gt[4 * i + 3]);
    }
    if (ok) { add_granules(red, g); nrx++; }
    wg_wait<0>();
    pin(acc);
    TS(85)
#pragma unroll
    for (int i = 0; i < 32; i++) red[i] += acc[i];
    pin(red);
    block_fence(90);
    int last = 8;
    if (two && granules_ok(g2, tag)) { add_granules(red, g2); last = 7; }
#pragma unroll 1
    for (int spins = 0; nrx < last && spins < (1 << 16); spins++) {
      fetch(g, nrx);
      if (granules_ok(g, tag)) { add_granules(red, g); nrx++; }
    }
    prof(wg, 20);
    TS(86)
    uint32_t ow[16];
#pragma unroll
    for (int i = 0; i < 16; i++) ow[i] = fma2(pack2(red[2 * i], red[2 * i + 1]), gt[i], xv[i]);
#pragma unroll
    for (int i = 0; i < 4; i++) stsm4(cx.sb + SM_XO + (frag ^ (i << 5)), ow[4 * i], ow[4 * i + 1], ow[4 * i + 2], ow[4 * i + 3]);
    __syncwarp();
#pragma unroll
    for (int i = 0; i < 4; i++) {
      uint4 v;
      const int row = cw * 16 + i * 4 + (lane >> 3);
      lds128(cx.sb + SM_XO + row * 128 + (((lane ^ row) & 7) << 4), v.x, v.y, v.z, v.w);
      asm volatile("st.global.v4.b32 [%0], {%1, %2, %3, %4};" ::"l"(out + (size_t)(qb * 128 + row) * DM + hs * 64 + (lane & 7) * 8),
                   "r"(v.x), "r"(v.y), "r"(v.z), "r"(v.w) : "memory");
    }
    prof(wg, 22);
    TS(87)
    TS_DUMP()
  }
}

struct KvMaps { CUtensorMap m[4]; };
__global__ void __cluster_dims__(2, 1, 1) __launch_bounds__(THREADS, 1)
fused_kernel(const __nv_bfloat16* __restrict__ x, const __nv_bfloat16* __restrict__ w_r, const __nv_bfloat16* __restrict__ kc,
             const __nv_bfloat16* __restrict__ vc, __nv_bfloat16* __restrict__ out, Scratch* scratch,
             const __grid_constant__ CUtensorMap tmX, const __grid_constant__ CUtensorMap tmWq,
             const __grid_constant__ KvMaps tmKV, const __grid_constant__ CUtensorMap tmWo,
             const __grid_constant__ CUtensorMap tmG, const __grid_constant__ CUtensorMap tmU,
             const __grid_constant__ CUtensorMap tmD, const __grid_constant__ CUtensorMap tmX16,
             const __grid_constant__ CUtensorMap tmWq96, const __grid_constant__ CUtensorMap tmX64) {
  extern __shared__ __align__(1024) uint8_t smem_raw[];
  prof(0, 23, 511);
  if (X_PFX && threadIdx.x == 192) { prefetch_tmap(&tmX); prefetch_tmap(&tmWq); }
  Ctx cx;
  cx.sb = smem_u32(smem_raw);
  cx.sp = smem_raw;
  cx.g = scratch;
  cx.rank = blockIdx.x & 1;
  const int warp = __shfl_sync(0xffffffffu, threadIdx.x >> 5, 0);
  const int cluster = blockIdx.x >> 1;
  const bool is_ffn = blockIdx.x >= N_ATT_CTA;
  const int c7 = ((cluster - 36) * 37) >> 8;
  const int hs = cluster < 4 ? 4 + cluster : cluster < 36 ? (cluster - 4) >> 3 : 4 + c7;
  const int qb = (cluster < 4 ? 0 : cluster < 36 ? (cluster - 4) & 7 : cluster - (is_ffn ? 36 : 35) - 7 * c7) * 2 + cx.rank;

  auto load_x = [&](int w) {
#pragma unroll
    for (int i = 0; i < 3; i++) {
      mbar_expect_tx(cx.sb + SM_XFULL + 24 * w + 8 * i, 24576);
      tma3d(cx.sb + SM_X + (3 * w + i) * 24576, &tmX, qb * 128 + w * 64, i * 3, cx.sb + SM_XFULL + 24 * w + 8 * i);
    }
  };
  if (warp < 4) {
    asm volatile("setmaxnreg.dec.sync.aligned.u32 24;");
    if (elect_one()) {
      if (warp == 0) {
        TSP(64)
#pragma unroll
        for (int i = 0; i < 4; i++) mbar_init(cx.sb + SM_FULL + 8 * i, 1);
#pragma unroll
        for (int i = 3; i < 6; i++) mbar_init(cx.sb + SM_XFULL + 8 * i, 1);
        TSP(65)
      } else if (warp == 1) {
#pragma unroll
        for (int i = 0; i < 4; i++) mbar_init(cx.sb + SM_EMPTY + 8 * i, 4);
        mbar_init(cx.sb + SM_BAR_MISC, 1);
        mbar_init(cx.sb + SM_BAR_XG, 1);
        mbar_init(cx.sb + SM_BAR_Q, 1);
        mbar_init(cx.sb + SM_BAR_Q + 8, 1);
      } else if (is_ffn) {
#pragma unroll
        for (int i = 0; i < 8; i++) mbar_init(cx.sb + (warp == 2 ? SM_FFULL : SM_FEMPTY) + 8 * i, 1);
      }
      asm volatile("fence.mbarrier_init.release.cluster;" ::: "memory");
    }
    __syncwarp();
    cluster_arrive();
    if (warp == 0 && elect_one()) load_x(1);
    __syncwarp();
    if (warp == 0) TSP(70)
    cluster_wait();
    if (warp == 0) TSP(71)
    prof(0, 24, 511);
    if (warp == 0) {
      if (is_ffn) ffn_producer(cx, qb, &tmWq, &tmG, &tmU, &tmD);
      else attn_producer(cx, qb, hs, tmKV.m, &tmWq, &tmWq96, &tmWo);
      prof(0, 25, 511);
    } else if (!is_ffn) {
      attn_gate(cx, qb, hs, threadIdx.x - 32, x);
      asm volatile("fence.proxy.async;" ::: "memory");
      if (warp == 1) attn_helper(cx, qb, hs, read_lane(), &tmX16);
      else bar_arrive(BAR_OA, 352);
      attn_finish8(cx, qb, hs, warp - 1, read_lane(), out);
    } else if (warp < 3) {
      ffn_publish(cx, qb, warp - 1, read_lane(), &tmX64);
    }
    __syncwarp();
    cluster_arrive();
    cluster_wait();
  } else {
    if (warp == 4 && elect_one()) {
#pragma unroll
      for (int i = 0; i < 3; i++) mbar_init(cx.sb + SM_XFULL + 8 * i, 1);
      asm volatile("fence.mbarrier_init.release.cluster;" ::: "memory");
      TSP(66)
      load_x(0);
      TSP(67)
    }
    if (warp == 5 && elect_one()) {
      mbar_init(cx.sb + SM_BAR_W, 1);
      asm volatile("fence.mbarrier_init.release.cluster;" ::: "memory");
      *(uint4*)(cx.sp + SM_ONES) = make_uint4(0x3F803F80u, 0x3F803F80u, 0x3F803F80u, 0x3F803F80u);
      mbar_expect_tx(cx.sb + SM_BAR_W, DM * 2);
      bulk_load(cx.sb + SM_WR, w_r, DM * 2, cx.sb + SM_BAR_W);
    }
    __syncwarp();
    cluster_arrive();
    asm volatile("setmaxnreg.inc.sync.aligned.u32 240;");
    const int cw = warp - 4, wg = cw >> 2;
    if (is_ffn && (threadIdx.x & 127) == 96) *(uint32_t*)(cx.sp + SM_TAG + 4) = cx.g->launch[blockIdx.x + 4 * wg]++;
    cluster_wait();
    attn_consumer(cx, is_ffn, qb, hs, wg, cw, read_lane(), x, kc, vc, out, &tmX64);
  }
}

typedef CUresult (*EncodeFn)(CUtensorMap*, CUtensorMapDataType, cuuint32_t, void*, const cuuint64_t*, const cuuint64_t*,
                             const cuuint32_t*, const cuuint32_t*, CUtensorMapInterleave, CUtensorMapSwizzle,
                             CUtensorMapL2promotion, CUtensorMapFloatOOBfill);

void encode(EncodeFn fn, CUtensorMap* m, const void* p, int rank, const cuuint64_t* dims, const cuuint64_t* strides,
            const cuuint32_t* box) {
  const cuuint32_t es[5] = {1, 1, 1, 1, 1};
  fn(m, CU_TENSOR_MAP_DATA_TYPE_BFLOAT16, rank, const_cast<void*>(p), dims, strides, box, es, CU_TENSOR_MAP_INTERLEAVE_NONE,
     CU_TENSOR_MAP_SWIZZLE_128B, CU_TENSOR_MAP_L2_PROMOTION_L2_128B, CU_TENSOR_MAP_FLOAT_OOB_FILL_NONE);
}
void encode2d(EncodeFn fn, CUtensorMap* m, const void* p, uint64_t rows, uint64_t cols, uint32_t box_rows) {
  const cuuint64_t dims[2] = {cols, rows}, strides[1] = {cols * 2};
  const cuuint32_t box[2] = {64, box_rows};
  encode(fn, m, p, 2, dims, strides, box);
}

}

extern "C" void kernel_launch(void* const* d_in, const int* in_sizes, int n_in, void* d_out, int out_size) {
  (void)in_sizes; (void)n_in; (void)out_size;
  void* fnp = nullptr;
  cudaDriverEntryPointQueryResult qr;
  cudaGetDriverEntryPoint("cuTensorMapEncodeTiled", &fnp, cudaEnableDefault, &qr);
  EncodeFn fn = (EncodeFn)fnp;
  CUtensorMap tmWq, tmWo, tmG, tmU, tmD, tmX, tmX16, tmWq96, tmX64;
  encode2d(fn, &tmX64, d_in[0], SEQ, DM, 64);
  encode2d(fn, &tmWq96, d_in[3], DM, 4096, 96);
  encode2d(fn, &tmX16, d_in[0], SEQ, DM, 16);
  KvMaps tmKV;
  for (int i = 0; i < 4; i++) encode2d(fn, &tmKV.m[i], d_in[1 + (i & 1)], 16 * SEQ, DH, i < 2 ? 112 : 96);
  encode2d(fn, &tmWq, d_in[3], DM, 4096, 64);
  {
    const cuuint64_t dims[3] = {64, SEQ, 9}, strides[2] = {DM * 2, 128};
    const cuuint32_t box[3] = {64, 64, 3};
    encode(fn, &tmX, d_in[0], 3, dims, strides, box);
  }
  encode2d(fn, &tmWo, d_in[4], 4096, DM, 128);
  encode2d(fn, &tmG, d_in[7], DM, FF, 192);
  encode2d(fn, &tmU, d_in[8], DM, FF, 192);
  encode2d(fn, &tmD, d_in[9], FF, DM, 192);
  cudaFuncSetAttribute(fused_kernel, cudaFuncAttributeMaxDynamicSharedMemorySize, SM_TOTAL);
  void* scratch = nullptr;
  cudaGetSymbolAddress(&scratch, g_scratch);
  fused_kernel<<<N_CTA, THREADS, SM_TOTAL>>>((const __nv_bfloat16*)d_in[0], (const __nv_bfloat16*)d_in[6], (const __nv_bfloat16*)d_in[1],
                                            (const __nv_bfloat16*)d_in[2], (__nv_bfloat16*)d_out, (Scratch*)scratch, tmX, tmWq, tmKV,
                                            tmWo, tmG, tmU, tmD, tmX16, tmWq96, tmX64);
}
```

```cpp
#include <cuda_runtime.h>
#include <cuda_bf16.h>
#include <cuda.h>
#include <stdint.h>

namespace {

constexpr int SEQ = 2048, DM = 576, DH = 128, FF = 4608, TOPC = 8;
constexpr int N_ATT_CTA = 128, N_CTA = 132;
constexpr int THREADS = 384;

constexpr uint32_t SM_RING = 0;
constexpr uint32_t STAGE = 32768;
constexpr uint32_t SM_SLOT = 131072;
constexpr uint32_t FSTAGE = 24576;
constexpr uint32_t SM_XSEL = 196608;
constexpr uint32_t SM_H = 205824;
constexpr uint32_t SM_MISC = 229376;
constexpr uint32_t SM_FULL = SM_MISC, SM_EMPTY = SM_MISC + 32, SM_FFULL = SM_MISC + 64, SM_BAR_MISC = SM_MISC + 128,
                   SM_COLD = SM_MISC + 136, SM_TAG = SM_MISC + 144, SM_BAR_W = SM_MISC + 152, SM_ONES = SM_MISC + 160, SM_BAR_Q = SM_MISC + 176, SM_TOPK = SM_MISC + 192,
                   SM_XFULL = SM_MISC + 256, SM_BAR_XG = SM_MISC + 304, SM_STATS = SM_MISC + 320,
                   SM_FEMPTY = SM_MISC + 1344, SM_RAW = SM_FEMPTY, SM_WR = SM_MISC + 1408;
constexpr uint32_t SM_TOTAL = SM_MISC + 2560;
constexpr uint32_t SM_X = SM_MISC - 147456;

constexpr int BAR_GATE = 6, BAR_HELPER = 7, BAR_OA = 8, BAR_QS = 9, BAR_QF = 11;
constexpr int NST_Q = 18, NST_KV = 76, NST_O = 18;
__device__ __forceinline__ bool blk_big(int j) { return (unsigned)(j - 5) < 28; }
__device__ __forceinline__ int blk_row(int j) { return 112 * j - 16 * (min(j, 5) + max(j - 33, 0)); }
constexpr float SM_SCALE_LOG2 = 0.08838834764831845f * 1.4426950408889634f;

struct Scratch {
  uint4 part[16 * 64 * 2 * 4 * 128];
  uint4 gate[N_ATT_CTA * 1152];
  uint4 q[16 * 8 * 2 * 512];
  uint4 stats[SEQ];
  float ypart[4 * TOPC * DM];
  int2 sel[16];
  unsigned launch[160];
  unsigned pad0, ycnt, pad[30];
  unsigned qflag[128];
};
__device__ __align__(1024) Scratch g_scratch;

__device__ __forceinline__ void prof(int, int, int = 0) {}

#define TS(id) {}
#define TS_DUMP() {}
#define TS4(k) {}
#define TSP(k) {}
#define TS1(id) TS(id)
#define TS2(k) {}
#define TS3(k) {}

__device__ __forceinline__ uint32_t smem_u32(const void* p) { return (uint32_t)__cvta_generic_to_shared(p); }
__device__ __forceinline__ void mbar_init(uint32_t bar, uint32_t cnt) {
  asm volatile("mbarrier.init.shared::cta.b64 [%0], %1;" ::"r"(bar), "r"(cnt) : "memory");
}
__device__ __forceinline__ void mbar_expect_tx(uint32_t bar, uint32_t bytes) {
  asm volatile("mbarrier.arrive.expect_tx.shared::cta.b64 _, [%0], %1;" ::"r"(bar), "r"(bytes) : "memory");
}
__device__ __forceinline__ void mbar_arrive(uint32_t bar) {
  asm volatile("mbarrier.arrive.shared::cta.b64 _, [%0];" ::"r"(bar) : "memory");
}
__device__ __forceinline__ void mbar_arrive_cluster(uint32_t bar_cluster_addr) {
  asm volatile("mbarrier.arrive.shared::cluster.b64 _, [%0];" ::"r"(bar_cluster_addr) : "memory");
}
template <int ID>
__device__ __forceinline__ void mbar_arrive_cluster_now(uint32_t bar_cluster_addr, bool pred) {
  asm volatile("{\n.reg .pred p, q;\nsetp.ne.u32 p, %1, 0;\nsetp.eq.u32 q, %2, %3;\n"
               "ARR_LOOP:\n@p mbarrier.arrive.shared::cluster.b64 _, [%0];\n@q bra.uni ARR_LOOP;\n}"
               ::"r"(bar_cluster_addr), "r"((uint32_t)pred), "r"(blockIdx.y), "n"(ID) : "memory");
}
__device__ __forceinline__ void block_fence(int id) {
  asm volatile("{\n.reg .pred q;\nsetp.eq.u32 q, %0, %1;\nBF_LOOP:\n@q st.volatile.shared.u32 [%0], %0;\n@q bra.uni BF_LOOP;\n}"
               ::"r"(blockIdx.y), "r"(id) : "memory");
}
__device__ __forceinline__ void mbar_wait(uint32_t bar, uint32_t parity) {
  asm volatile("{\n.reg .pred p, q;\n.reg .u32 n;\nmov.u32 n, 0;\n"
               "WAIT_LOOP:\nmbarrier.try_wait.parity.shared::cta.b64 p, [%0], %1;\n"
               "add.u32 n, n, 1;\nsetp.lt.u32 q, n, 4194304;\nand.pred q, q, !p;\n@q bra WAIT_LOOP;\n}"
               ::"r"(bar), "r"(parity) : "memory");
}
__device__ __forceinline__ uint32_t mapa(uint32_t addr, uint32_t rank) {
  uint32_t r;
  asm volatile("mapa.shared::cluster.u32 %0, %1, %2;" : "=r"(r) : "r"(addr), "r"(rank));
  return r;
}
__device__ __forceinline__ void cluster_arrive() { asm volatile("barrier.cluster.arrive.relaxed.aligned;" ::: "memory"); }
__device__ __forceinline__ bool elect_one() {
  uint32_t p;
  asm volatile("{\n.reg .pred p;\nelect.sync _|p, 0xffffffff;\nselp.u32 %0, 1, 0, p;\n}" : "=r"(p));
  return p;
}
__device__ __forceinline__ int read_lane() { return threadIdx.x & 31; }
__device__ __forceinline__ int fresh_lane() {
  int l;
  asm volatile("mov.u32 %0, %%laneid;" : "=r"(l));
  return l;
}
__device__ __forceinline__ void cluster_wait() { asm volatile("barrier.cluster.wait.acquire.aligned;" ::: "memory"); }
__device__ __forceinline__ void bar_sync(int id, int n) { asm volatile("barrier.cta.sync %0, %1;" ::"r"(id), "r"(n) : "memory"); }
__device__ __forceinline__ void bar_arrive(int id, int n) { asm volatile("barrier.cta.arrive %0, %1;" ::"r"(id), "r"(n) : "memory"); }

__device__ __forceinline__ uint64_t policy_evict_first() {
  uint64_t p;
  asm("createpolicy.fractional.L2::evict_first.b64 %0, 1.0;" : "=l"(p));
  return p;
}
__device__ __forceinline__ void tma2d_mc(uint32_t dst, const CUtensorMap* tm, int c0, int c1, uint32_t bar, uint64_t pol) {
  asm volatile("cp.async.bulk.tensor.2d.shared::cluster.global.mbarrier::complete_tx::bytes.multicast::cluster.L2::cache_hint"
               " [%0], [%1, {%2, %3}], [%4], %5, %6;"
               ::"r"(dst), "l"(tm), "r"(c0), "r"(c1), "r"(bar), "h"((uint16_t)3), "l"(pol) : "memory");
}
__device__ __forceinline__ void tma3d(uint32_t dst, const CUtensorMap* tm, int c1, int c2, uint32_t bar) {
  asm volatile("cp.async.bulk.tensor.3d.shared::cluster.global.mbarrier::complete_tx::bytes [%0], [%1, {%2, %3, %4}], [%5];"
               ::"r"(dst), "l"(tm), "r"(0), "r"(c1), "r"(c2), "r"(bar) : "memory");
}
__device__ __forceinline__ void tma2d_stream(uint32_t dst, const CUtensorMap* tm, int c0, int c1, uint32_t bar) {
  asm volatile("{\n.reg .b64 pol;\ncreatepolicy.fractional.L2::evict_first.b64 pol, 1.0;\n"
               "cp.async.bulk.tensor.2d.shared::cluster.global.mbarrier::complete_tx::bytes.L2::cache_hint [%0], [%1, {%2, %3}], [%4], pol;\n}"
               ::"r"(dst), "l"(tm), "r"(c0), "r"(c1), "r"(bar) : "memory");
}
__device__ __forceinline__ void bulk_load(uint32_t dst, const void* src, uint32_t bytes, uint32_t bar) {
  asm volatile("cp.async.bulk.shared::cluster.global.mbarrier::complete_tx::bytes [%0], [%1], %2, [%3];"
               ::"r"(dst), "l"(src), "r"(bytes), "r"(bar) : "memory");
}
__device__ __forceinline__ void tma2d_prefetch(const CUtensorMap* tm, int c0, int c1) {
  asm volatile("cp.async.bulk.prefetch.tensor.2d.L2.global [%0, {%1, %2}];" ::"l"(tm), "r"(c0), "r"(c1) : "memory");
}
__device__ __forceinline__ void prefetch_tmap(const CUtensorMap* tm) {
  asm volatile("prefetch.tensormap [%0];" ::"l"(tm) : "memory");
}

__device__ __forceinline__ void wg_fence() { asm volatile("wgmma.fence.sync.aligned;" ::: "memory"); }
__device__ __forceinline__ void wg_commit() { asm volatile("wgmma.commit_group.sync.aligned;" ::: "memory"); }
template <int N> __device__ __forceinline__ void wg_wait() { asm volatile("wgmma.wait_group.sync.aligned %0;" ::"n"(N) : "memory"); }

__device__ __forceinline__ uint64_t mkdesc(uint32_t addr, uint32_t lbo_bytes) {
  return (uint64_t)(((addr & 0x3FFFF) >> 4) | ((lbo_bytes >> 4) << 16)) | ((uint64_t)0x40000040u << 32);
}
__device__ __forceinline__ uint64_t mkdesc_q(uint32_t addr) {
  return (uint64_t)(((addr & 0x3FFFF) >> 4) | (64u << 16)) | ((uint64_t)8 << 32);
}
template <int N> __device__ __forceinline__ void pin(float (&a)[N]) {
#pragma unroll
  for (int i = 0; i < N; i++) asm volatile("" : "+f"(a[i])::"memory");
}
template <int N> __device__ __forceinline__ void kill(float (&a)[N]) {
#pragma unroll
  for (int i = 0; i < N; i++) asm volatile("" : "=f"(a[i]));
}
template <int N> __device__ __forceinline__ void pin(uint32_t (&a)[N]) {
#pragma unroll
  for (int i = 0; i < N; i++) asm volatile("" : "+r"(a[i])::"memory");
}

#define F8(d, o) "+f"(d[o]), "+f"(d[o + 1]), "+f"(d[o + 2]), "+f"(d[o + 3]), "+f"(d[o + 4]), "+f"(d[o + 5]), "+f"(d[o + 6]), "+f"(d[o + 7])
#define R32A "%0, %1, %2, %3, %4, %5, %6, %7, %8, %9, %10, %11, %12, %13, %14, %15, %16, %17, %18, %19, %20, %21, %22, %23, %24, %25, %26, %27, %28, %29, %30, %31"
#define R32B "%32, %33, %34, %35, %36, %37, %38, %39, %40, %41, %42, %43, %44, %45, %46, %47, %48, %49, %50, %51, %52, %53, %54, %55, %56, %57, %58, %59, %60, %61, %62, %63"

#define O8(d, o) "=f"(d[o]), "=f"(d[o + 1]), "=f"(d[o + 2]), "=f"(d[o + 3]), "=f"(d[o + 4]), "=f"(d[o + 5]), "=f"(d[o + 6]), "=f"(d[o + 7])

__device__ __forceinline__ void mma_n128t(float (&d)[64], uint32_t a0, uint32_t a1, uint32_t a2, uint32_t a3, uint64_t db, bool acc) {
  if (acc)
    asm volatile("wgmma.mma_async.sync.aligned.m64n128k16.f32.bf16.bf16 {" R32A ", " R32B "}, {%64, %65, %66, %67}, %68, 1, 1, 1, 1;\n"
                 : F8(d, 0), F8(d, 8), F8(d, 16), F8(d, 24), F8(d, 32), F8(d, 40), F8(d, 48), F8(d, 56)
                 : "r"(a0), "r"(a1), "r"(a2), "r"(a3), "l"(db));
  else
    asm volatile("wgmma.mma_async.sync.aligned.m64n128k16.f32.bf16.bf16 {" R32A ", " R32B "}, {%64, %65, %66, %67}, %68, 0, 1, 1, 1;\n"
                 : O8(d, 0), O8(d, 8), O8(d, 16), O8(d, 24), O8(d, 32), O8(d, 40), O8(d, 48), O8(d, 56)
                 : "r"(a0), "r"(a1), "r"(a2), "r"(a3), "l"(db));
}
#define PV1(a0, a1, a2, a3, ob, acc) "add.s64 b, %92, " #ob ";\n" \
  "wgmma.mma_async.sync.aligned.m64n128k16.f32.bf16.bf16 {" R32A ", " R32B "}, {%" #a0 ", %" #a1 ", %" #a2 ", %" #a3 "}, b, " #acc ", 1, 1, 1;\n"
#define PV6 "wgmma.fence.sync.aligned;\n" PV1(64, 65, 66, 67, 0, p) PV1(68, 69, 70, 71, 128, 1) PV1(72, 73, 74, 75, 256, 1) \
  PV1(76, 77, 78, 79, 384, 1) PV1(80, 81, 82, 83, 512, 1) PV1(84, 85, 86, 87, 640, 1)
#define U4(a, o) "r"(a[o]), "r"(a[o + 1]), "r"(a[o + 2]), "r"(a[o + 3])
__device__ __forceinline__ void mma_pv(float (&d)[64], const uint32_t (&a)[28], uint64_t dv, bool acc, bool big) {
  asm volatile("{\n.reg .pred p, q;\n.reg .b64 b;\nsetp.ne.b32 p, %93, 0;\nsetp.eq.b32 q, %94, 0;\n@q bra.uni PV_SMALL;\n"
               PV6 PV1(88, 89, 90, 91, 768, 1) "wgmma.commit_group.sync.aligned;\nbra.uni PV_DONE;\n"
               "PV_SMALL:\n" PV6 "wgmma.commit_group.sync.aligned;\nPV_DONE:\n}\n"
               : F8(d, 0), F8(d, 8), F8(d, 16), F8(d, 24), F8(d, 32), F8(d, 40), F8(d, 48), F8(d, 56)
               : U4(a, 0), U4(a, 4), U4(a, 8), U4(a, 12), U4(a, 16), U4(a, 20), U4(a, 24), "l"(dv), "r"((int)acc), "r"((int)big) : "memory");
}
#define R48 R32A ", %32, %33, %34, %35, %36, %37, %38, %39, %40, %41, %42, %43, %44, %45, %46, %47"
#define R56 R48 ", %48, %49, %50, %51, %52, %53, %54, %55"
#define QK1(N, R, A, B, oa, ob, acc) "add.s64 a, " A ", " #oa ";\nadd.s64 b, " B ", " #ob ";\n" \
  "wgmma.mma_async.sync.aligned.m64n" #N "k16.f32.bf16.bf16 {" R "}, a, b, " #acc ", 1, 1, 0, 0;\n"
#define QK8(N, R, A, B) "{\n.reg .b64 a, b;\nwgmma.fence.sync.aligned;\n" QK1(N, R, A, B, 0, 0, 0) QK1(N, R, A, B, 128, 2, 1) \
  QK1(N, R, A, B, 256, 4, 1) QK1(N, R, A, B, 384, 6, 1) QK1(N, R, A, B, 512, 1024, 1) QK1(N, R, A, B, 640, 1026, 1) \
  QK1(N, R, A, B, 768, 1028, 1) QK1(N, R, A, B, 896, 1030, 1) "wgmma.commit_group.sync.aligned;\n}\n"
__device__ __forceinline__ void mma_qk(float (&d)[56], uint64_t dq, uint64_t dk) {
  asm volatile(QK8(112, R56, "%56", "%57")
               : O8(d, 0), O8(d, 8), O8(d, 16), O8(d, 24), O8(d, 32), O8(d, 40), O8(d, 48) : "l"(dq), "l"(dk) : "memory");
}
__device__ __forceinline__ void mma_qk(float (&d)[48], uint64_t dq, uint64_t dk) {
  asm volatile(QK8(96, R48, "%48", "%49")
               : O8(d, 0), O8(d, 8), O8(d, 16), O8(d, 24), O8(d, 32), O8(d, 40) : "l"(dq), "l"(dk) : "memory");
}
__device__ __forceinline__ void mma_n64t(float (&d)[32], uint32_t a0, uint32_t a1, uint32_t a2, uint32_t a3, uint64_t db, bool acc) {
  if (acc)
    asm volatile("wgmma.mma_async.sync.aligned.m64n64k16.f32.bf16.bf16 {" R32A "}, {%32, %33, %34, %35}, %36, 1, 1, 1, 1;\n"
                 : F8(d, 0), F8(d, 8), F8(d, 16), F8(d, 24) : "r"(a0), "r"(a1), "r"(a2), "r"(a3), "l"(db));
  else
    asm volatile("wgmma.mma_async.sync.aligned.m64n64k16.f32.bf16.bf16 {" R32A "}, {%32, %33, %34, %35}, %36, 0, 1, 1, 1;\n"
                 : O8(d, 0), O8(d, 8), O8(d, 16), O8(d, 24) : "r"(a0), "r"(a1), "r"(a2), "r"(a3), "l"(db));
}
__device__ __forceinline__ void mma_n64t_dyn(float (&d)[32], uint32_t a0, uint32_t a1, uint32_t a2, uint32_t a3, uint64_t db, int acc) {
  asm volatile("{\n.reg .pred p;\nsetp.ne.b32 p, %37, 0;\n"
               "wgmma.mma_async.sync.aligned.m64n64k16.f32.bf16.bf16 {" R32A "}, {%32, %33, %34, %35}, %36, p, 1, 1, 1;\n}\n"
               : F8(d, 0), F8(d, 8), F8(d, 16), F8(d, 24) : "r"(a0), "r"(a1), "r"(a2), "r"(a3), "l"(db), "r"(acc));
}
__device__ __forceinline__ void mma_n8(float (&d)[4], uint64_t da, uint64_t db, int acc) {
  asm volatile("{\n.reg .pred p;\nsetp.ne.b32 p, %6, 0;\n"
               "wgmma.mma_async.sync.aligned.m64n8k16.f32.bf16.bf16 {%0, %1, %2, %3}, %4, %5, p, 1, 1, 1, 0;\n}\n"
               : "+f"(d[0]), "+f"(d[1]), "+f"(d[2]), "+f"(d[3])
               : "l"(da), "l"(db), "r"(acc));
}
__device__ __forceinline__ void hmma_k8(float (&d)[4], uint32_t a0, uint32_t a1, uint32_t b0) {
  asm volatile("mma.sync.aligned.m16n8k8.row.col.f32.bf16.bf16.f32 {%0, %1, %2, %3}, {%4, %5}, {%6}, {%0, %1, %2, %3};"
               : "+f"(d[0]), "+f"(d[1]), "+f"(d[2]), "+f"(d[3]) : "r"(a0), "r"(a1), "r"(b0));
}
__device__ __forceinline__ void hmma_k16(float (&d)[4], uint32_t a0, uint32_t a1, uint32_t a2, uint32_t a3, uint32_t b0, uint32_t b1) {
  asm volatile("mma.sync.aligned.m16n8k16.row.col.f32.bf16.bf16.f32 {%0, %1, %2, %3}, {%4, %5, %6, %7}, {%8, %9}, {%0, %1, %2, %3};"
               : "+f"(d[0]), "+f"(d[1]), "+f"(d[2]), "+f"(d[3]) : "r"(a0), "r"(a1), "r"(a2), "r"(a3), "r"(b0), "r"(b1));
}

__device__ __forceinline__ uint32_t pack2(float lo, float hi) {
  uint32_t r;
  asm("cvt.rn.bf16x2.f32 %0, %1, %2;" : "=r"(r) : "f"(hi), "f"(lo));
  return r;
}
__device__ __forceinline__ float bf_lo(uint32_t w) { return __uint_as_float(w << 16); }
__device__ __forceinline__ float bf_hi(uint32_t w) { return __uint_as_float(w & 0xFFFF0000u); }
__device__ __forceinline__ float bfr(float x) { return __bfloat162float(__float2bfloat16_rn(x)); }
__device__ __forceinline__ uint32_t sub2(uint32_t a, uint32_t b) {
  uint32_t r;
  asm("sub.rn.bf16x2 %0, %1, %2;" : "=r"(r) : "r"(a), "r"(b));
  return r;
}
__device__ __forceinline__ uint32_t add2(uint32_t a, uint32_t b) {
  uint32_t r;
  asm("add.rn.bf16x2 %0, %1, %2;" : "=r"(r) : "r"(a), "r"(b));
  return r;
}
__device__ __forceinline__ uint32_t fma2(uint32_t a, uint32_t b, uint32_t c) {
  uint32_t r;
  asm("fma.rn.bf16x2 %0, %1, %2, %3;" : "=r"(r) : "r"(a), "r"(b), "r"(c));
  return r;
}
__device__ __forceinline__ float ex2(float x) {
  float r;
  asm("ex2.approx.ftz.f32 %0, %1;" : "=f"(r) : "f"(x));
  return r;
}
__device__ __forceinline__ float rcp(float x) {
  float r;
  asm("rcp.approx.ftz.f32 %0, %1;" : "=f"(r) : "f"(x));
  return r;
}
__device__ __forceinline__ float silu_f(float t) { return t * rcp(1.0f + ex2(-1.4426950408889634f * t)); }
__device__ __forceinline__ void lds128(uint32_t a, uint32_t& x, uint32_t& y, uint32_t& z, uint32_t& w) {
  asm volatile("ld.shared.v4.u32 {%0, %1, %2, %3}, [%4];" : "=r"(x), "=r"(y), "=r"(z), "=r"(w) : "r"(a) : "memory");
}
__device__ __forceinline__ void ldsm4(uint32_t a, uint32_t& x, uint32_t& y, uint32_t& z, uint32_t& w) {
  asm volatile("ldmatrix.sync.aligned.m8n8.x4.shared.b16 {%0, %1, %2, %3}, [%4];" : "=r"(x), "=r"(y), "=r"(z), "=r"(w) : "r"(a) : "memory");
}
constexpr uint32_t TAG = 0x10000;
__device__ __forceinline__ void st_gran(uint4* p, uint32_t x, uint32_t y, uint32_t z, uint32_t w) {
  asm volatile("st.relaxed.gpu.global.v4.b32 [%0], {%1, %2, %3, %4};" ::"l"(p), "r"(x), "r"(y), "r"(z), "r"(w) : "memory");
}
__device__ __forceinline__ void ld_gran(const uint4* p, uint32_t& x, uint32_t& y, uint32_t& z, uint32_t& w) {
  asm volatile("ld.relaxed.gpu.global.v4.b32 {%0, %1, %2, %3}, [%4];" : "=r"(x), "=r"(y), "=r"(z), "=r"(w) : "l"(p) : "memory");
}
__device__ __forceinline__ void stsm4(uint32_t a, uint32_t x, uint32_t y, uint32_t z, uint32_t w) {
  asm volatile("stmatrix.sync.aligned.m8n8.x4.shared.b16 [%0], {%1, %2, %3, %4};" ::"r"(a), "r"(x), "r"(y), "r"(z), "r"(w) : "memory");
}
__device__ __forceinline__ void cp16(uint32_t dst, const void* src) {
  asm volatile("cp.async.cg.shared.global [%0], [%1], 16;" ::"r"(dst), "l"(src) : "memory");
}
__device__ __forceinline__ void cp_wait_all() { asm volatile("cp.async.wait_all;" ::: "memory"); }
__device__ __forceinline__ void add_granules(float (&red)[32], const uint32_t (&g)[16]) {
#pragma unroll
  for (int i = 0; i < 16; i++) { red[2 * i] += bf_lo(g[i]); red[2 * i + 1] += bf_hi((i & 3) ? g[i] : g[i] & ~TAG); }
}
__device__ __forceinline__ bool granules_ok(const uint32_t (&g)[16], uint32_t tag) {
  uint32_t a, b;
  asm("lop3.b32 %0, %1, %2, %3, 0x7E;" : "=r"(a) : "r"(g[0]), "r"(g[4]), "r"(tag));
  asm("lop3.b32 %0, %1, %2, %3, 0x7E;" : "=r"(b) : "r"(g[8]), "r"(g[12]), "r"(tag));
  return __all_sync(0xffffffffu, ((a | b) & TAG) == 0);
}
__device__ __forceinline__ unsigned ld_acquire(const unsigned* p) {
  unsigned v;
  asm volatile("ld.acquire.gpu.global.u32 %0, [%1];" : "=r"(v) : "l"(p) : "memory");
  return v;
}
__device__ __forceinline__ unsigned atom_add_acq_rel(unsigned* p) {
  unsigned v;
  asm volatile("atom.acq_rel.gpu.global.add.u32 %0, [%1], 1;" : "=r"(v) : "l"(p) : "memory");
  return v;
}

struct LnAcc {
  float sm[2][4], sq[8][4];
  __device__ __forceinline__ void clear() {
#pragma unroll
    for (int i = 0; i < 4; i++) {
      sm[0][i] = sm[1][i] = 0.f;
#pragma unroll
      for (int j = 0; j < 8; j++) sq[j][i] = 0.f;
    }
  }
};
template <int K0, int K1>
__device__ __forceinline__ void ln_fetch(uint32_t (&xa)[144], uint32_t boxes, uint32_t lo) {
#pragma unroll
  for (int k = K0; k < K1; k++) ldsm4(boxes + (k >> 2) * 8192 + (lo ^ ((k & 3) << 5)), xa[4 * k], xa[4 * k + 1], xa[4 * k + 2], xa[4 * k + 3]);
}
__device__ __forceinline__ void ln_fetch_b(uint32_t (&b)[24], uint32_t& wb, uint32_t ws) {
#pragma unroll
  for (int j = 0; j < 6; j++, wb += ws) ldsm4(wb, b[4 * j], b[4 * j + 1], b[4 * j + 2], b[4 * j + 3]);
}
template <int K0, bool SQ>
__device__ __forceinline__ void ln_accum(const uint32_t (&xa)[144], LnAcc& a, const uint32_t (&b)[24]) {
#pragma unroll
  for (int k = K0; k < K0 + 12; k++) {
    const int h = k & 1;
    hmma_k16(a.sm[h], xa[4 * k], xa[4 * k + 1], xa[4 * k + 2], xa[4 * k + 3], b[2 * (k - K0)], b[2 * (k - K0) + 1]);
    if (SQ) {
      hmma_k8(a.sq[4 * h], xa[4 * k], xa[4 * k + 1], xa[4 * k]);
      hmma_k8(a.sq[4 * h + 1], xa[4 * k], xa[4 * k + 1], xa[4 * k + 1]);
      hmma_k8(a.sq[4 * h + 2], xa[4 * k + 2], xa[4 * k + 3], xa[4 * k + 2]);
      hmma_k8(a.sq[4 * h + 3], xa[4 * k + 2], xa[4 * k + 3], xa[4 * k + 3]);
    }
  }
}
__device__ __forceinline__ void ln_row(float sum, float sq, float& mean_b, float& rstd) {
  const float mean = sum * (1.0f / DM);
  const uint32_t mv = pack2(mean, fmaxf(sq * (1.0f / DM) - mean * mean, 0.0f));
  mean_b = bf_lo(mv);
  float sd;
  asm("sqrt.approx.f32 %0, %1;" : "=f"(sd) : "f"(bf_lo(pack2(bf_hi(mv) + 1e-5f, 0.f))));
  rstd = rcp(bf_lo(pack2(sd, 0.f)));
}
__device__ __forceinline__ void ln_diag(const LnAcc& a, int lane, float& t0, float& t1) {
  const bool odd = (lane >> 2) & 1;
  t0 = odd ? (a.sq[0][1] + a.sq[2][1]) + (a.sq[4][1] + a.sq[6][1]) : (a.sq[0][0] + a.sq[2][0]) + (a.sq[4][0] + a.sq[6][0]);
  t1 = odd ? (a.sq[1][3] + a.sq[3][3]) + (a.sq[5][3] + a.sq[7][3]) : (a.sq[1][2] + a.sq[3][2]) + (a.sq[5][2] + a.sq[7][2]);
}

template <bool ROUTED>
__device__ __forceinline__ uint32_t gate2(uint32_t x2, float mean_b, float rstd, float2 upd = make_float2(0.f, 0.f)) {
  const uint32_t xc = sub2(x2, pack2(mean_b, mean_b));
  uint32_t t = pack2(bf_lo(xc) * rstd, bf_hi(xc) * rstd);
  if (ROUTED) t = pack2(bf_lo(t) + upd.x, bf_hi(t) + upd.y);
  return pack2(silu_f(bf_lo(t)), silu_f(bf_hi(t)));
}

#define PF_D 4
#define X_SPLIT 38
#define X_SPLITA 36
#define X_SPLITS 32
#define X_SPLITSA 30
#define X_PA 8
#define X_PG 2
#define X_E0 10
#define X_F2 10
#define X_LD 0
#define X_FENCE 1
#define X_WAKE 31
#define X_PFX 1
#define X_F1 0
#define X_BF2 1
#define X_EARLY 1
template <int V> struct IC { static constexpr int value = V; };

struct Ctx {
  uint32_t sb;
  uint8_t* sp;
  uint32_t rank;
  Scratch* g;
};

__device__ __forceinline__ bool acquire(const Ctx& cx, uint32_t r, uint32_t n, uint32_t bytes) {
  mbar_wait(cx.sb + SM_EMPTY + 8 * r, (n ^ (r >> 1) ^ 1) & 1);
  __syncwarp();
  const bool e = elect_one();
  if (e) mbar_expect_tx(cx.sb + SM_FULL + 8 * r, bytes);
  return e;
}
__device__ __forceinline__ void load_wq(const Ctx& cx, const CUtensorMap* tmWq, int st, int i, int n0, uint64_t pol) {
  const uint32_t r = st & 3, dst = cx.sb + SM_RING + r * STAGE + cx.rank * 16384, bar = cx.sb + SM_FULL + 8 * r;
  const int k0 = i < 3 ? 128 * i : 128 * i - 64;
  if (acquire(cx, r, st >> 2, i == 2 ? 16384 : 32768)) {
    tma2d_mc(dst, tmWq, n0, k0, bar, pol);
    if (i != 2) tma2d_mc(dst + 8192, tmWq, n0, k0 + 64, bar, pol);
  }
}
__device__ __forceinline__ void attn_producer(const Ctx& cx, int qb, int hs, const CUtensorMap* tmKV, const CUtensorMap* tmWq,
                                              const CUtensorMap* tmWq96, const CUtensorMap* tmWo) {
  const uint32_t full = cx.sb + SM_FULL, ring = cx.sb + SM_RING + cx.rank * 16384;
  const uint64_t last_use = policy_evict_first();
  int st = 0;
#pragma unroll 1
  for (int p = 0; p < 4; p++) {
#pragma unroll 1
    for (int i = 0; i < (p == 2 ? 3 : 5); i++, st++) {
      if (p == 2) {
        if (acquire(cx, st & 3, st >> 2, 24576))
          tma2d_mc(cx.sb + SM_RING + (st & 3) * STAGE + cx.rank * 12288, tmWq96, (hs * 4 + 3) * DH, 192 * i + 96 * cx.rank, full + 8 * (st & 3), last_use);
      } else {
        load_wq(cx, tmWq, st, i, (hs * 4 + (p ^ (p >> 1))) * DH + cx.rank * 64, last_use);
      }
      if (st < 3) TSP(72 + st)
      if (st == 1) {
#pragma unroll 1
        for (int b = 8 + qb; b < 72; b += 16)
          if (elect_one()) tma2d_prefetch(tmWq, (hs * 4 + ((b / 18) ^ (b / 36))) * DH + (b & 1) * 64, ((b % 18) >> 1) * 64);
      }
      if (st == 8 && qb < 2 * PF_D && elect_one()) tma2d_prefetch(tmKV + ((qb >> 1) & 1), cx.rank * 64, hs * 2 * SEQ + (qb >> 2) * 96);
    }
  }
  uint32_t r = 2, n = 4;
#pragma unroll 1
  for (int u = 0; u < NST_KV; u++) {
    const bool big = blk_big(u >> 1);
    if (acquire(cx, r, n, big ? 112 * 256 : 96 * 256)) {
      tma2d_mc(ring + r * STAGE, tmKV + (u & 1) + (big ? 0 : 2), cx.rank * 64, hs * 2 * SEQ + blk_row(u >> 1), full + 8 * r, last_use);
      if (((u ^ (qb >> 1)) & 7) == 0 && u + PF_D < NST_KV)
        tma2d_prefetch(tmKV + ((u + PF_D) & 1), cx.rank * 64, hs * 2 * SEQ + blk_row((u + PF_D) >> 1));
      if ((unsigned)(u - 32) < 36 && (u & 15) == qb) tma2d_prefetch(tmWo, ((u - 32) >> 2) * 64, hs * 512 + (u & 3) * 128);
    }
    if (++r == 4) { r = 1; n++; }
  }
#pragma unroll 1
  for (int u = 0; u < NST_O; u++) {
    const int s = u >> 1;
    const int blk = s == 0 ? 8 : ((hs + s) & 7);
    r = (0x87 >> (2 * (u & 3))) & 3;
    if (acquire(cx, r, (u >> 2) ^ ~u, 32768))
      tma2d_mc(ring + r * STAGE, tmWo, blk * 64, hs * 512 + ((u & 1) + cx.rank * 2) * 128, full + 8 * r, last_use);
  }
}

__device__ __forceinline__ void attn_gate(const Ctx& cx, int qb, int hs, int t, const __nv_bfloat16* x) {
  uint4 nx = *(const uint4*)(x + (size_t)(qb * 128 + (t >> 3)) * DM + hs * 64 + (t & 7) * 8);
  float wsum = 0.f;
  if (t < 32) {
    if (t == 0) {
      const unsigned e = cx.g->launch[qb * 8 + hs]++;
      *(uint2*)(cx.sp + SM_TAG) = make_uint2((~e & 1) * TAG, e);
    }
    mbar_wait(cx.sb + SM_BAR_W, 0);
#pragma unroll 3
    for (int i = 0; i < 9; i++) {
      const uint32_t w = *(const uint32_t*)(cx.sp + SM_WR + i * 128 + t * 4);
      wsum += bf_lo(w) + bf_hi(w);
    }
#pragma unroll
    for (int i = 1; i < 32; i *= 2) wsum += __shfl_xor_sync(0xffffffffu, wsum, i);
  }
  bar_sync(BAR_GATE, 352);
  if (t < 16) {
    const float2 st = *(const float2*)(cx.sp + SM_STATS + 8 * (hs * 16 + t));
    st_gran(cx.g->stats + qb * 128 + hs * 16 + t, __float_as_uint(st.x), __float_as_uint(st.y),
            __float_as_uint(bfr(fmaf(-st.x, wsum, *(const float*)(cx.sp + SM_RAW + 4 * t)) * st.y)), *(const uint32_t*)(cx.sp + SM_TAG + 4) + 1);
  }
#pragma unroll 1
  for (int ch = t; ch < 1152; ch += 96) {
    const uint4 v = nx;
    const int n = ch + 96;
    if (n < 1152) nx = *(const uint4*)(x + (size_t)(qb * 128 + (n < 1024 ? n >> 3 : hs * 16 + ((n - 1024) >> 3))) * DM + (n < 1024 ? hs * 64 : 512) + (t & 7) * 8);
    const int lr = ch < 1024 ? ch >> 3 : hs * 16 + ((ch - 1024) >> 3);
    const float2 st = *(const float2*)(cx.sp + SM_STATS + 8 * lr);
    cx.g->gate[blockIdx.x * 1152 + (ch ^ ((ch >> 3) & 7))] =
        make_uint4(gate2<false>(v.x, st.x, st.y), gate2<false>(v.y, st.x, st.y), gate2<false>(v.z, st.x, st.y), gate2<false>(v.w, st.x, st.y));
  }
}

constexpr uint32_t SM_XO = SM_SLOT, SM_GO = SM_SLOT + STAGE, SM_P8 = SM_SLOT + 2 * STAGE;
__device__ __forceinline__ void attn_helper(const Ctx& cx, int qb, int hs, int lane, const CUtensorMap* tmX16) {
  const unsigned e = *(const uint32_t*)(cx.sp + SM_TAG + 4);
  bar_sync(BAR_HELPER, 64);
  bool todo = lane < 2;
#pragma unroll 1
  for (int n = 0; __any_sync(0xffffffffu, todo); n++) {
    if (todo && (ld_acquire(&cx.g->qflag[(qb * 4 + (hs >> 1)) * 2 + lane]) == e + 1 || n == (1 << 16))) {
      asm volatile("fence.proxy.async;" ::: "memory");
      mbar_expect_tx(cx.sb + SM_BAR_Q + 8 * lane, 8192);
      bulk_load(cx.sb + SM_SLOT + 2 * STAGE + lane * 16384 + 8192, cx.g->q + ((qb * 8 + hs) * 2 + lane) * 512, 8192, cx.sb + SM_BAR_Q + 8 * lane);
      todo = false;
    }
  }
  const uint32_t tag = (~e & 1) * TAG;
  const uint4* src = cx.g->part + (size_t)((qb * 64 + 56) * 2 + (hs >> 2)) * 4 * 128 + (hs & 3) * 32 + lane;
  const uint32_t stg = cx.sb + SM_P8 + lane * 16;
  bar_sync(BAR_OA, 352);
  asm volatile("fence.proxy.async;" ::: "memory");
  if (lane == 0) {
    mbar_expect_tx(cx.sb + SM_BAR_MISC, 2 * 18432);
    bulk_load(cx.sb + SM_GO, cx.g->gate + blockIdx.x * 1152, 18432, cx.sb + SM_BAR_MISC);
#pragma unroll 1
    for (int i = 0; i < 9; i++)
      tma2d_stream(cx.sb + SM_XO + i * 2048, tmX16, i < 8 ? hs * 64 : 512, qb * 128 + (i < 8 ? i : hs) * 16, cx.sb + SM_BAR_MISC);
  }
#pragma unroll 1
  for (int n = 0; n < (1 << 16); n++) {
    __nanosleep(n ? 500 : 2000);
    uint32_t a, b, d, t;
    ld_gran(src - lane + (lane & 7) * (2 * 4 * 128) + 3 * 128 + 31, a, b, d, t);
    if (__all_sync(0xffffffffu, (a & TAG) == tag)) break;
  }
#pragma unroll 1
  for (int n = 0; n < (1 << 16); n++) {
#pragma unroll 1
    for (int i = 0; i < 8; i++) {
#pragma unroll
      for (int g = 0; g < 4; g++) cp16(stg + (i * 4 + g) * 512, src + i * (2 * 4 * 128) + g * 128);
    }
    cp_wait_all();
    uint32_t bad = 0;
#pragma unroll 4
    for (int i = 0; i < 32; i++) bad |= *(const volatile uint32_t*)(cx.sp + SM_P8 + lane * 16 + i * 512) ^ tag;
    if (__all_sync(0xffffffffu, (bad & TAG) == 0)) break;
  }
#pragma unroll 1
  for (int n = 0; n < (1 << 16) && ld_acquire(&cx.g->ycnt) != 4 * (e + 1); n++) __nanosleep(200);
  const int2 sel = __ldcg(&cx.g->sel[lane & 7]);
  const int lr = sel.x - qb * 128;
  uint32_t m = __ballot_sync(0xffffffffu, lane < 16 && ((lane & 8) ? (lr >> 4) == hs : (lr >> 7) == 0));
  mbar_wait(cx.sb + SM_BAR_MISC, 0);
#pragma unroll 1
  for (; m; m &= m - 1) {
    const int i = __ffs(m) - 1, row = __shfl_sync(0xffffffffu, lr, i);
    const float rs = __int_as_float(__shfl_sync(0xffffffffu, sel.y, i));
    const float* p = cx.g->ypart + (i & 7) * DM + (i < 8 ? hs * 64 : 512) + 2 * lane;
    const float2 a = __ldcg((const float2*)p), b = __ldcg((const float2*)(p + TOPC * DM)), c = __ldcg((const float2*)(p + 2 * TOPC * DM)),
                 d = __ldcg((const float2*)(p + 3 * TOPC * DM));
    const uint32_t y = pack2((a.x + b.x) + (c.x + d.x), (a.y + b.y) + (c.y + d.y));
    const uint32_t u = pack2(bf_lo(y) * rs, bf_hi(y) * rs);
    const float2 st = *(const float2*)(cx.sp + SM_STATS + 8 * row);
    const int o = (i < 8 ? row : 128 + (row & 15)) * 128 + ((lane * 4) ^ ((row & 7) << 4));
    *(uint32_t*)(cx.sp + SM_GO + o) = gate2<true>(*(const uint32_t*)(cx.sp + SM_XO + o), st.x, st.y, make_float2(bf_lo(u), bf_hi(u)));
  }
  __syncwarp();
  if (lane == 0) mbar_arrive(cx.sb + SM_BAR_XG);
}
__device__ __forceinline__ void attn_finish8(const Ctx& cx, int qb, int hs, int hw, int lane, __nv_bfloat16* out) {
  bar_sync(BAR_GATE, 96);
#pragma unroll 1
  for (int g = hw; g < 4; g += 3) {
    float acc[8] = {0.f, 0.f, 0.f, 0.f, 0.f, 0.f, 0.f, 0.f};
#pragma unroll 2
    for (int sidx = 0; sidx < 8; sidx++) {
      uint32_t a, b, d, t;
      lds128(cx.sb + SM_P8 + lane * 16 + (sidx * 4 + g) * 512, a, b, d, t);
      acc[0] += bf_lo(a); acc[1] += bf_hi(a & ~TAG); acc[2] += bf_lo(b); acc[3] += bf_hi(b);
      acc[4] += bf_lo(d); acc[5] += bf_hi(d); acc[6] += bf_lo(t); acc[7] += bf_hi(t);
    }
#pragma unroll
    for (int j = 0; j < 4; j++) {
      const int o = (128 + (lane >> 2) + (j & 1) * 8) * 128 + (((2 * g + (j >> 1)) ^ (lane >> 2)) << 4) + (lane & 3) * 4;
      uint32_t* xp = (uint32_t*)(cx.sp + SM_XO + o);
      *xp = fma2(pack2(acc[2 * j], acc[2 * j + 1]), *(const uint32_t*)(cx.sp + SM_GO + o), *xp);
    }
  }
  bar_sync(BAR_GATE, 96);
  for (int ch = hw * 32 + lane; ch < 128; ch += 96)
    *(uint4*)(out + (size_t)(qb * 128 + hs * 16 + (ch >> 3)) * DM + 512 + (ch & 7) * 8) =
        *(const uint4*)(cx.sp + SM_XO + 16384 + (ch ^ ((ch >> 3) & 7)) * 16);
}

__device__ __forceinline__ void ffn_producer(const Ctx& cx, int f, const CUtensorMap* tmWq, const CUtensorMap* tmG,
                                             const CUtensorMap* tmU, const CUtensorMap* tmD) {
  uint64_t keep;
  asm("createpolicy.fractional.L2::evict_normal.b64 %0, 1.0;" : "=l"(keep));
  int st = 0;
#pragma unroll 1
  for (int p = 0; p < 16; p++) {
#pragma unroll 1
    for (int i = 0; i < 5; i++, st++) load_wq(cx, tmWq, st, i, ((2 * (p & 3) + cx.rank) * 4 + 3) * DH + 64, keep);
  }
  const uint32_t full = cx.sb + SM_FFULL, empty = cx.sb + SM_FEMPTY;
  int pair = 0, u = 0;
#pragma unroll 1
  for (st = 0; st < 14 * 12; st++) {
    const uint32_t sl = st & 7;
    const int unit = pair * 2 + (u & 1), k = u >> 1, k3 = k >= 3 ? k - 3 : k;
    if (unit < 27) {
      mbar_wait(empty + 8 * sl, (st >> 3) & 1);
      __syncwarp();
      if (elect_one()) {
        mbar_expect_tx(full + 8 * sl, FSTAGE);
        if (pair < 9) tma2d_stream(cx.sb + sl * FSTAGE, k < 3 ? tmG : tmU, f * 1152 + unit * 64, k3 * 192, full + 8 * sl);
        else tma2d_stream(cx.sb + sl * FSTAGE, tmD, (unit - 18) * 64, f * 1152 + k * 192, full + 8 * sl);
      }
    }
    if (++u == 12) { u = 0; pair++; }
  }
}
__device__ __forceinline__ void load_x1(uint32_t dst, const CUtensorMap* tmX64, int row, int box, int n, uint32_t bar) {
  mbar_expect_tx(bar, n * 8192);
#pragma unroll 1
  for (int i = 0; i < n; i++) tma2d_stream(dst + i * 8192, tmX64, (box + i) * 64, row, bar);
}
__device__ __forceinline__ void ffn_publish(const Ctx& cx, int f, int w, int lane, const CUtensorMap* tmX64) {
  const uint32_t xs = cx.sb + SM_SLOT + w * 49152, xf = cx.sb + SM_XFULL + w * 24;
#pragma unroll 1
  for (int n = 0; n < 16; n++) {
    const int p = n & 3, row = (f + (n & 12) + 4) * 128 + w * 64;
    bar_sync(BAR_QS + w, 160);
    const uint32_t e1 = *(const uint32_t*)(cx.sp + SM_TAG + 4) + 1;
    if (lane == 0) {
#pragma unroll
      for (int i = 0; i < 2; i++)
        asm volatile("cp.async.bulk.global.shared::cta.bulk_group [%0], [%1], 8192;"
                     ::"l"(cx.g->q + (((f + (n & 12)) * 8 + 2 * p + i) * 2 + w) * 512), "r"(xs + 32768 + i * 8192) : "memory");
      asm volatile("cp.async.bulk.commit_group;" ::: "memory");
      if (n < 12 && (p == 0 || p == 3)) load_x1(xs, tmX64, row, p ? 4 : 0, 4, xf + (p ? 8 : 0));
      asm volatile("cp.async.bulk.wait_group.read 0;" ::: "memory");
      if (n < 12 && p == 3) load_x1(xs + 32768, tmX64, row, 8, 1, xf + 16);
      asm volatile("cp.async.bulk.wait_group 0;\nfence.proxy.async;" ::: "memory");
      asm volatile("st.release.gpu.global.u32 [%0], %1;" ::"l"(&cx.g->qflag[((f + (n & 12)) * 4 + p) * 2 + w]), "r"(e1) : "memory");
    }
    __syncwarp();
    if (n < 12 && p == 1) {
#pragma unroll 1
      for (int i = 0, k = 0; i < 64 && k < (1 << 16); k++) {
        uint32_t m, r, z, t;
        ld_gran(cx.g->stats + row + i + lane, m, r, z, t);
        *(uint2*)(cx.sp + SM_STATS + 8 * (w * 64 + i + lane)) = make_uint2(m, r);
        if (__all_sync(0xffffffffu, t == e1)) i += 32;
      }
    }
    bar_arrive(BAR_QF + w, 160);
  }
}

__device__ __forceinline__ void ffn_consumer(const Ctx& cx, int f, int wg, int cw, int lane, const __nv_bfloat16* x) {
  const int r = lane >> 2, c = lane & 3, tid = cw * 32 + lane;
  const uint32_t full = cx.sb + SM_FFULL, empty = cx.sb + SM_FEMPTY;
  const bool signaller = (tid & 127) == 0;
  prof(wg, 8);
  const unsigned e = *(const uint32_t*)(cx.sp + SM_TAG + 4);
  uint32_t key[8];
#pragma unroll 1
  for (int n = 0; n < (1 << 16); n++) {
    uint32_t bad = 0;
#pragma unroll
    for (int i = 0; i < 8; i++) {
      const int row = i * 256 + tid;
      uint32_t b, t;
      asm volatile("ld.relaxed.gpu.global.v2.b32 {%0, %1}, [%2];" : "=r"(b), "=r"(t) : "l"(&cx.g->stats[row].z) : "memory");
      bad |= t ^ (e + 1);
      b >>= 16;
      key[i] = (((b & 0x8000u) ? (~b & 0xFFFFu) : (b | 0x8000u)) << 16) | (uint32_t)(0xFFFF - row);
    }
    if (__all_sync(0xffffffffu, bad == 0)) break;
  }
  bar_sync(BAR_QF + wg, 160);
  bar_sync(3, 256);
  if (tid < 8) mbar_arrive(empty + 8 * tid);
  prof(wg, 9);
  int mysel = 0;
#pragma unroll 1
  for (int k = 0; k < TOPC; k++) {
    uint32_t m = key[0];
#pragma unroll
    for (int i = 1; i < 8; i++) m = max(m, key[i]);
    m = __reduce_max_sync(0xffffffffu, m);
    uint32_t* tk = (uint32_t*)(cx.sp + SM_TOPK) + (k & 1) * 8;
    if (lane == 0) tk[cw] = m;
    bar_sync(3, 256);
    m = __reduce_max_sync(0xffffffffu, tk[lane & 7]);
#pragma unroll
    for (int i = 0; i < 8; i++) if (key[i] == m) key[i] = 0;
    if (k == cw) mysel = 0xFFFF - (int)(m & 0xFFFF);
  }
  {
    const float4 st = __ldcg((const float4*)&cx.g->stats[mysel]);
    const uint32_t mm = pack2(st.x, st.x);
#pragma unroll 3
    for (int i = 0; i < 9; i++) {
      const uint32_t t = sub2(*(const uint32_t*)(x + (size_t)mysel * DM + i * 64 + 2 * lane), mm);
      *(uint32_t*)(cx.sp + SM_XSEL + i * 1024 + cw * 128 + (((lane >> 2) ^ cw) << 4) + (lane & 3) * 4) =
          pack2(bf_lo(t) * st.y, bf_hi(t) * st.y);
    }
    if (lane == 0 && f == 0) cx.g->sel[cw] = make_int2(mysel, __float_as_int(bfr(rcp(1.0f + ex2(-1.4426950408889634f * st.z)))));
  }
  asm volatile("fence.proxy.async.shared::cta;" ::: "memory");
  bar_sync(3, 256);
  prof(wg, 10);
  auto run = [&](float (&acc)[4], int st, int n, uint32_t b) {
#pragma unroll 1
    for (int u = 0; u < n; u++, st += 2, b += 3072) {
      const uint32_t sl = st & 7;
      mbar_wait(full + 8 * sl, (st >> 3) & 1);
      wg_fence();
      const uint64_t da = mkdesc(cx.sb + sl * FSTAGE, 16), db = mkdesc(b, 16);
#pragma unroll
      for (int k = 0; k < 12; k++) mma_n8(acc, da + k * 128, db + (k >> 2) * 64 + (k & 3) * 2, u > 0 || k > 0);
      wg_commit();
      wg_wait<0>();
      if (signaller) mbar_arrive(empty + 8 * sl);
    }
    pin(acc);
  };
#pragma unroll 1
  for (int unit = wg; unit < 27; unit += 2) {
    if (unit >> 1 == 9) {
      asm volatile("fence.proxy.async.shared::cta;" ::: "memory");
      bar_sync(3, 256);
      prof(wg, 11);
    }
    const bool gu = unit < 18;
    float a0[4], a1[4];
#pragma unroll 1
    for (int m = 0; m < (gu ? 2 : 1); m++) {
      run(a1, (unit >> 1) * 12 + m * 6 + wg, gu ? 3 : 6, cx.sb + (gu ? SM_XSEL : SM_H));
      if (m == 0) { a0[0] = a1[0]; a0[1] = a1[1]; a0[2] = a1[2]; a0[3] = a1[3]; }
    }
#pragma unroll
    for (int i = 0; i < 4; i++) {
      const int fl = (cw & 3) * 16 + r + (i >> 1) * 8, tok = 2 * c + (i & 1);
      if (gu) {
        const float h = bfr(silu_f(bfr(a0[i]))) * bfr(a1[i]);
        *(__nv_bfloat16*)(cx.sp + SM_H + unit * 1024 + tok * 128 + (((fl >> 3) ^ tok) << 4) + (fl & 7) * 2) = __float2bfloat16_rn(h);
      } else {
        cx.g->ypart[(f * TOPC + tok) * DM + (unit - 18) * 64 + fl] = a1[i];
      }
    }
  }
  prof(wg, 12);
  bar_sync(3, 256);
  if (tid == 0) atom_add_acq_rel(&cx.g->ycnt);
  prof(wg, 13);
}

constexpr float SUM_HI = 1.8446744e19f, SUM_LO = 9.0949470e-13f;

template <int LO, int HI, int N>
__device__ __forceinline__ void softmax_exp(float (&s)[N]) {
#pragma unroll
  for (int i = LO; i < HI; i++) s[i] = ex2(s[i]);
}
__device__ __forceinline__ void sum_tree(const uint32_t (&pf)[28], bool big, uint32_t& h0, uint32_t& h1) {
  uint32_t t0 = add2(add2(pf[16], pf[18]), add2(pf[20], pf[22])), t1 = add2(add2(pf[17], pf[19]), add2(pf[21], pf[23]));
  if (big) { t0 = add2(t0, add2(pf[24], pf[26])); t1 = add2(t1, add2(pf[25], pf[27])); }
  h0 = add2(add2(add2(add2(pf[0], pf[2]), add2(pf[4], pf[6])), add2(add2(pf[8], pf[10]), add2(pf[12], pf[14]))), t0);
  h1 = add2(add2(add2(add2(pf[1], pf[3]), add2(pf[5], pf[7])), add2(add2(pf[9], pf[11]), add2(pf[13], pf[15]))), t1);
}
__device__ __forceinline__ void exact_attention(float (&o)[64], float& l0, float& l1, uint32_t qaddr, const __nv_bfloat16* kh,
                                                const __nv_bfloat16* vh, int lane) {
  const int off = (lane >> 2) * DH + (lane & 3) * 2;
  float m0 = -3.0e38f, m1 = -3.0e38f;
  l0 = l1 = 0.f;
#pragma unroll
  for (int i = 0; i < 64; i++) o[i] = 0.f;
#pragma unroll 1
  for (int key = 0; key < SEQ; key += 16) {
    const __nv_bfloat16 *kp = kh + key * DH + off, *vp = vh + key * DH + off;
    float d0[4] = {0.f, 0.f, 0.f, 0.f}, d1[4] = {0.f, 0.f, 0.f, 0.f};
#pragma unroll 4
    for (int k = 0; k < 8; k++) {
      uint32_t q0, q1, q2, q3;
      ldsm4(qaddr + k * 2048, q0, q1, q2, q3);
      hmma_k16(d0, q0, q1, q2, q3, *(const uint32_t*)(kp + k * 16), *(const uint32_t*)(kp + k * 16 + 8));
      hmma_k16(d1, q0, q1, q2, q3, *(const uint32_t*)(kp + 8 * DH + k * 16), *(const uint32_t*)(kp + 8 * DH + k * 16 + 8));
    }
    float x0 = fmaxf(fmaxf(d0[0], d0[1]), fmaxf(d1[0], d1[1])), x1 = fmaxf(fmaxf(d0[2], d0[3]), fmaxf(d1[2], d1[3]));
    x0 = fmaxf(x0, __shfl_xor_sync(0xffffffffu, x0, 1));
    x1 = fmaxf(x1, __shfl_xor_sync(0xffffffffu, x1, 1));
    x0 = fmaxf(fmaxf(x0, __shfl_xor_sync(0xffffffffu, x0, 2)), m0);
    x1 = fmaxf(fmaxf(x1, __shfl_xor_sync(0xffffffffu, x1, 2)), m1);
    const float sc0 = ex2(m0 - x0), sc1 = ex2(m1 - x1);
    m0 = x0; m1 = x1;
    const uint32_t p0 = pack2(ex2(d0[0] - m0), ex2(d0[1] - m0)), p1 = pack2(ex2(d0[2] - m1), ex2(d0[3] - m1)),
                   p2 = pack2(ex2(d1[0] - m0), ex2(d1[1] - m0)), p3 = pack2(ex2(d1[2] - m1), ex2(d1[3] - m1));
    l0 = fmaf(l0, sc0, (bf_lo(p0) + bf_hi(p0)) + (bf_lo(p2) + bf_hi(p2)));
    l1 = fmaf(l1, sc1, (bf_lo(p1) + bf_hi(p1)) + (bf_lo(p3) + bf_hi(p3)));
#pragma unroll
    for (int nb = 0; nb < 16; nb++) {
      uint32_t b0, b1;
      asm("movmatrix.sync.aligned.m8n8.trans.b16 %0, %1;" : "=r"(b0) : "r"(*(const uint32_t*)(vp + nb * 8)));
      asm("movmatrix.sync.aligned.m8n8.trans.b16 %0, %1;" : "=r"(b1) : "r"(*(const uint32_t*)(vp + 8 * DH + nb * 8)));
      o[4 * nb] *= sc0; o[4 * nb + 1] *= sc0; o[4 * nb + 2] *= sc1; o[4 * nb + 3] *= sc1;
      hmma_k16(*(float (*)[4])&o[4 * nb], p0, p1, p2, p3, b0, b1);
    }
  }
}
__device__ __forceinline__ bool inv_sums(float l0, float l1, float& i0, float& i1) {
  l0 += __shfl_xor_sync(0xffffffffu, l0, 1); l1 += __shfl_xor_sync(0xffffffffu, l1, 1);
  l0 += __shfl_xor_sync(0xffffffffu, l0, 2); l1 += __shfl_xor_sync(0xffffffffu, l1, 2);
  i0 = rcp(l0);
  i1 = rcp(l1);
  return !(l0 + l1 <= SUM_HI) | (fminf(l0, l1) < SUM_LO);
}
template <int LO, int HI, int N>
__device__ __forceinline__ void park(uint32_t a, const float (&o)[N], float i0, float i1, bool on = true) {
#pragma unroll
  for (int i = LO; i < HI; i++)
    asm volatile("{\n.reg .pred p;\nsetp.ne.u32 p, %5, 0;\n@p stmatrix.sync.aligned.m8n8.x4.shared.b16 [%0], {%1, %2, %3, %4};\n}"
                 ::"r"(a + i * 2048), "r"(pack2(o[8 * i] * i0, o[8 * i + 1] * i0)), "r"(pack2(o[8 * i + 2] * i1, o[8 * i + 3] * i1)),
                 "r"(pack2(o[8 * i + 4] * i0, o[8 * i + 5] * i0)), "r"(pack2(o[8 * i + 6] * i1, o[8 * i + 7] * i1)), "r"((uint32_t)on) : "memory");
}

template <int I, int NP, int E0, int N, int NS>
__device__ __forceinline__ void exp_park(float (&s)[NS], uint32_t a, const float (&o)[64], float i0, float i1, bool on, int id) {
  if constexpr (I < NP) {
    constexpr int E1 = E0 + (N - E0) * X_PG / (NP - I);
    softmax_exp<E0, E1>(s);
    park<I, I + X_PG>(a, o, i0, i1, on);
    if (I + X_PG < NP) {
#pragma unroll
      for (int i = E0; i < E1; i++) asm volatile("" : "+f"(s[i])::"memory");
      block_fence(id + I);
    }
    exp_park<I + X_PG, NP, E1, N>(s, a, o, i0, i1, on, id);
  }
}

__device__ __forceinline__ void attn_consumer(const Ctx& cx, bool hlp, int qb, int hs, int wg, int cw, int lane, const __nv_bfloat16* x,
                                              const __nv_bfloat16* kc, const __nv_bfloat16* vc, __nv_bfloat16* out) {
  const uint32_t full = cx.sb + SM_FULL;
  const uint32_t ring = cx.sb + SM_RING;
  const uint32_t qwg = ring + wg * 16384;
  auto qlane = [&](int l) { return qwg + (cw & 3) * 256 + (l >> 4) * 1024 + (l & 15) * 16; };
  const bool signaller = lane == 0 && (cw & 3) < 2;
  const int my_turn = 1 + wg, other_turn = 2 - wg;
  const uint32_t empty_c = mapa(cx.sb + SM_EMPTY, cw & 1);

  float oA[64], oB[64], i0, i1;
  uint32_t xl[32];
  {
    const int r = lane >> 2, c = lane & 3;
    const int lr0 = cw * 16 + r;
    uint32_t xa[144];
    uint32_t mm0, mm1;
    float rstd0, rstd1, sq0, sq1;
    const uint32_t xf = cx.sb + SM_XFULL + wg * 24, xs = cx.sb + SM_SLOT + wg * 49152;
    auto lo_of = [&](int l) { return ((cw & 3) * 16 + (l & 15)) * 128 + (((l >> 4) ^ (l & 7)) << 4); };
    prof(wg, 0);
    {
      const uint32_t lo = lo_of(lane);
      const uint32_t xb = cx.sb + SM_X + wg * 73728;
      LnAcc a;
      a.clear();
      const uint32_t ws = (lane & 7) == 1 ? 64 : 0;
      uint32_t wb = cx.sb + (ws ? SM_WR + (lane >> 3) * 16 : SM_ONES);
      uint32_t b0[24], b1[24], b2[24];
      TS4(1)
      mbar_wait(cx.sb + SM_BAR_W, 0);
      ln_fetch_b(b0, wb, ws);
      ln_fetch_b(b1, wb, ws);
      ln_fetch_b(b2, wb, ws);
      mbar_wait(xf, 0);
      TS4(2)
      ln_fetch<0, 12>(xa, xb, lo);
      ln_accum<0, true>(xa, a, b0);
      mbar_wait(xf + 8, 0);
      TS4(3)
      ln_fetch<12, 24>(xa, xb, lo);
      if (wg == 0) {
        if (X_FENCE) asm volatile("fence.proxy.async.shared::cta;" ::: "memory");
        bar_sync(4, 128);
        if (signaller) {
          asm volatile("mbarrier.arrive.shared::cluster.b64 _, [%0], 2;" ::"r"(empty_c + 16) : "memory");
          asm volatile("mbarrier.arrive.shared::cluster.b64 _, [%0], 2;" ::"r"(empty_c + 24) : "memory");
        }
      }
      ln_accum<12, true>(xa, a, b1);
      mbar_wait(xf + 16, 0);
      TS4(4)
      prof(wg, 1);
      ln_fetch<24, 36>(xa, xb, lo);
      ln_accum<24, false>(xa, a, b2);
      if (cw == hs && c == 0) {
        *(float*)(cx.sp + SM_RAW + 4 * r) = a.sm[0][1] + a.sm[1][1];
        *(float*)(cx.sp + SM_RAW + 4 * r + 32) = a.sm[0][3] + a.sm[1][3];
      }
      ln_diag(a, lane, sq0, sq1);
      if (c != (r >> 1)) sq0 = sq1 = 0.f;
      rstd0 = a.sm[0][0] + a.sm[1][0];
      rstd1 = a.sm[0][2] + a.sm[1][2];
      mm0 = pack2(rstd0 * (1.0f / DM), rstd0 * (1.0f / DM));
      mm1 = pack2(rstd1 * (1.0f / DM), rstd1 * (1.0f / DM));
    }
#pragma unroll
    for (int i = 0; i < 16; i++) { xa[2 * i] = sub2(xa[2 * i], mm0); xa[2 * i + 1] = sub2(xa[2 * i + 1], mm1); }
    pin(xa);
    prof(wg, 2);
    TS4(5)

    float (&acc)[64] = oB;
    int st0 = 0;
#pragma unroll 1
    for (int n = 0; n < 16; n++) {
      const int p = n & 3, rb = n >> 2;
      const bool last = p == 3 && !hlp;
#pragma unroll
      for (int i = 0; i < 5; i++) {
        if (i == 4 && last) {
          wg_wait<1>();
          if (signaller && wg) mbar_arrive_cluster(empty_c + 8 * 3);
          wg_wait<0>();
          pin(acc);
          prof(wg, 6);
#pragma unroll
          for (int j = 0; j < 32; j++) xl[j] = xa[112 + j];
          i0 = rstd0;
          i1 = rstd1;
          goto attention;
        }
        const int st = st0 + i;
        const uint32_t sl = st & 3, slp = (st - 1) & 3;
        mbar_wait(full + 8 * sl, (st >> 2) & 1);
        TS4(8 + 2 * (p * 5 + i))
        const bool join = wg && last;
        if (st0 && i != (wg ? 4 : 1) && !(join && i == 3)) bar_sync(my_turn, 256);
        wg_fence();
        const uint64_t db = mkdesc(ring + sl * STAGE, 16384);
        const int kb0 = i < 3 ? 8 * i : 8 * i - 4;
#pragma unroll
        for (int k = 0; k < (i == 2 ? 4 : 8); k++) {
          const int kb = kb0 + k;
          mma_n128t(acc, xa[4 * kb], xa[4 * kb + 1], xa[4 * kb + 2], xa[4 * kb + 3], db + k * 128, kb > 0);
        }
        wg_commit();
        TS4(9 + 2 * (p * 5 + i))
        if (wg ? (i == 4 ? st0 < 75 : (st0 && (i < 2 || i == (join ? 3 : 2)))) : (st0 && i)) bar_arrive(other_turn, 256);
        if (p == 0 && i < 4) {
          if (i < 2 && !rb) {
#pragma unroll
            for (int j = 48 + 12 * i; j < 60 + 12 * i; j++) {
              sq0 = fmaf(bf_lo(xa[2 * j]), bf_lo(xa[2 * j]), fmaf(bf_hi(xa[2 * j]), bf_hi(xa[2 * j]), sq0));
              sq1 = fmaf(bf_lo(xa[2 * j + 1]), bf_lo(xa[2 * j + 1]), fmaf(bf_hi(xa[2 * j + 1]), bf_hi(xa[2 * j + 1]), sq1));
            }
          }
          if (i == 1 && rb) {
            mbar_wait(xf + 8, rb & 1);
            mbar_wait(xf + 16, rb & 1);
            ln_fetch<16, 36>(xa, xs - 32768, lo_of(fresh_lane()));
          }
          if (i == 1 && !rb) {
            sq0 += __shfl_xor_sync(0xffffffffu, sq0, 1); sq1 += __shfl_xor_sync(0xffffffffu, sq1, 1);
            sq0 += __shfl_xor_sync(0xffffffffu, sq0, 2); sq1 += __shfl_xor_sync(0xffffffffu, sq1, 2);
            float mean0, mean1;
            ln_row(rstd0, sq0, mean0, rstd0);
            ln_row(rstd1, sq1, mean1, rstd1);
            if (c == 0 && !hlp) {
              *(float2*)(cx.sp + SM_STATS + 8 * lr0) = make_float2(mean0, rstd0);
              *(float2*)(cx.sp + SM_STATS + 8 * (lr0 + 8)) = make_float2(mean1, rstd1);
            }
            *((uint32_t*)(cx.sp + SM_COLD) + wg) = 0;
            if (!hlp) bar_arrive(BAR_GATE, 352);
            bar_sync(4 + wg, 128);
            rstd0 *= SM_SCALE_LOG2;
            rstd1 *= SM_SCALE_LOG2;
          }
#pragma unroll
          for (int j = 0; j < 72; j++)
            if (j >= 2 * (i < 2 ? 8 * i + 8 : 8 * i + 4) && j < 2 * (i == 0 ? 16 : 8 * i + 12)) {
              xa[2 * j] = sub2(xa[2 * j], mm0);
              xa[2 * j + 1] = sub2(xa[2 * j + 1], mm1);
            }
          pin(xa);
        }
        if (i == 4 && p == 3 && rb < 3) {
          const float2* sp = (const float2*)(cx.sp + SM_STATS) + cw * 16 + (fresh_lane() >> 2);
          mm0 = pack2(sp[0].x, sp[0].x);
          mm1 = pack2(sp[8].x, sp[8].x);
          sq0 = sp[0].y * SM_SCALE_LOG2;
          sq1 = sp[8].y * SM_SCALE_LOG2;
#pragma unroll
          for (int j = 0; j < 16; j++) { xa[2 * j] = sub2(xa[2 * j], mm0); xa[2 * j + 1] = sub2(xa[2 * j + 1], mm1); }
          pin(xa);
        }
        if (i == 0) {
          if (wg) {
            wg_wait<0>();
            if (signaller) mbar_arrive_cluster(empty_c + 8 * sl);
          }
        } else if (i == 2) {
          if (!join) {
            wg_wait<0>();
            if (signaller) mbar_arrive_cluster(empty_c + 8 * sl);
          }
          if (hlp && p == 3 && rb < 3) {
            mbar_wait(xf, ~rb & 1);
            ln_fetch<0, 16>(xa, xs, lo_of(fresh_lane()));
            pin(xa);
          }
        } else if (i != 3) {
          wg_wait<1>();
          if (signaller && (i == 4 || !wg)) mbar_arrive_cluster(empty_c + 8 * slp);
          wg_wait<0>();
          if (signaller) mbar_arrive_cluster(empty_c + 8 * sl);
        }
      }
      pin(acc);
      prof(wg, 3 + p);
      TS4(50 + 2 * p)
      st0 += 5;
      if (hlp && st0 > 5) bar_sync(BAR_QF + wg, 160);
      park<0, 8>(qlane(lane) + (hlp ? 5 + wg : 4 + p) * STAGE, acc, rstd0, rstd1);
      if (p || hlp) asm volatile("fence.proxy.async.shared::cta;" ::: "memory");
      if (hlp) bar_arrive(BAR_QS + wg, 160);
      if (p == 3) { rstd0 = sq0; rstd1 = sq1; }
      TS4(51 + 2 * p)
      if (p == 1 && !hlp) {
        float (&ah)[32] = *(float (*)[32])&acc[0];
#pragma unroll
        for (int i = 0; i < 3; i++) {
          const uint32_t sl = (10 + i) & 3;
          mbar_wait(full + 8 * sl, ((10 + i) >> 2) & 1);
          TS4(28 + 2 * i)
          if (i == 0 || i == 2 - wg) bar_sync(my_turn, 256);
          wg_fence();
          const uint64_t db = mkdesc(ring + sl * STAGE, 16);
#pragma unroll
          for (int k = 0; k < 12; k++) {
            const int kb = 12 * i + k;
            if (kb) mma_n64t(ah, xa[4 * kb], xa[4 * kb + 1], xa[4 * kb + 2], xa[4 * kb + 3], db + k * 128, true);
            else mma_n64t_dyn(ah, xa[0], xa[1], xa[2], xa[3], db, blockIdx.y);
          }
          wg_commit();
          TS4(29 + 2 * i)
          if (i == 2 || i != wg) {
            bar_arrive(other_turn, 256);
            if (i) {
              wg_wait<1>();
              if (signaller && i == wg + 1) mbar_arrive_cluster(empty_c + 8 * ((9 + i) & 3));
            }
            wg_wait<0>();
            if (signaller) mbar_arrive_cluster(empty_c + 8 * sl);
          }
        }
        pin(ah);
        TS4(54)
        park<0, 4>(qlane(lane) + 6 * STAGE, ah, rstd0, rstd1);
        TS4(55)
        st0 = 13;
        n = 2;
      }
    }
    TS_DUMP()
    ffn_consumer(cx, blockIdx.x & 3, wg, cw, fresh_lane(), x);
    return;
  }

attention:
  uint32_t oa[128];
  float acc[32];
  {
    uint32_t pf[28];
    uint32_t bad = 0;
    float lA0 = 0.f, lA1 = 0.f, lB0 = 0.f, lB1 = 0.f;
    int t = 0;
    uint32_t ra = 2 * 2048, rb = 2048, rc = 2 * 2048, par = 0;
    const uint64_t dk0 = mkdesc(ring, 16), dv0 = mkdesc(ring, 16384);
    uint64_t dqA = mkdesc_q(qwg + 4 * STAGE), dqB = dqA + 2048;
    auto turn = [&](auto kc_, auto bc_) {
      constexpr int KIND = decltype(kc_)::value, BIG = decltype(bc_)::value;
      constexpr int HB = KIND == 1, ID = 10 * KIND + 30 * BIG, T0 = BIG ? 38 : 0;
      constexpr int NS = BIG ? 56 : 48, SPLIT = BIG ? (HB ? X_SPLIT : X_SPLITA) : (HB ? X_SPLITS : X_SPLITSA);
      float s[NS];
      float (&op)[64] = HB ? oA : oB;
      uint32_t h0 = 0, h1 = 0;
      TS2(0)
      bar_sync(my_turn, 256);
      TS2(1)
      if (KIND) { pin(pf); pin(op); }
      mma_qk(s, HB ? dqB : dqA, dk0 + (HB ? ra : rc));
      TS2(2)
      if (KIND) {
        const bool bigp = HB ? BIG : BIG ? t != 10 : t == 66;
        if (X_BF2) block_fence(ID + 9);
        pin(pf);
        sum_tree(pf, bigp, h0, h1);
        asm volatile("" : "+r"(h0), "+r"(h1)::"memory");
        if (HB) mbar_wait(full + (rb >> 8), par);
        mma_pv(op, pf, dv0 + rb, t != T0 + 2 - HB, bigp);
      } else {
        mbar_wait(full + (rb >> 8), (NST_Q - 1) >> 2 & 1);
#pragma unroll
        for (int k = 0; k < 8; k++) mma_n128t(op, xl[4 * k], xl[4 * k + 1], xl[4 * k + 2], xl[4 * k + 3], dv0 + rb + k * 128, 1);
        wg_commit();
      }
      TS2(3)
      bar_arrive(other_turn, 256);
      (HB ? lA0 : lB0) += bf_lo(h0) + bf_hi(h0);
      (HB ? lA1 : lB1) += bf_lo(h1) + bf_hi(h1);
      wg_wait<1>();
      pin(s);
      TS1(t)
      TS2(4)
      if (KIND == 1) mbar_arrive_cluster_now<ID + 3>(empty_c + (ra >> 8), signaller);
      if (BIG && t == T0 + HB) {
        const uint32_t a = qlane(fresh_lane()) + (4 + HB) * STAGE;
        const bool ok = !__any_sync(0xffffffffu, inv_sums(HB ? lB0 : lA0, HB ? lB1 : lA1, i0, i1));
        bad = (HB ? bad : 0) | (ok ? 0 : 1 << HB);
        (HB ? lB0 : lA0) = 0.f;
        (HB ? lB1 : lA1) = 0.f;
        softmax_exp<0, X_E0>(s);
#pragma unroll
        for (int i = 0; i < X_E0; i++) asm volatile("" : "+f"(s[i])::"memory");
        block_fence(ID + 7);
        exp_park<0, X_PA, X_E0, SPLIT>(s, a, HB ? oB : oA, i0, i1, ok, 200 + ID);
        if (!HB) dqB += 2048;
        prof(wg, 8 + HB);
      } else {
        if (HB && !BIG) bad = (bad & 3) | (inv_sums(lA0, lA1, i0, i1) ? 4 : 0);
        softmax_exp<0, SPLIT>(s);
      }
      pin(s);
      if (!BIG) block_fence(ID + 4);
      TS2(5)
      wg_wait<0>();
      TS2(6)
      pin(op);
      if (KIND) pin(pf); else pin(xl);
      if (HB) {
        par ^= rc == 2048;
        if (BIG && t == 37) dqA -= 4 * 2048;
        if (BIG && t == X_WAKE && cw == 0) bar_arrive(BAR_HELPER, 64);
      } else {
        mbar_arrive_cluster_now<ID + 5>(empty_c + (rb >> 8), signaller);
        if (KIND) {
          par ^= ra == 2048;
          const uint32_t x = ra;
          ra = rc; rc = rb; rb = x;
        }
      }
      softmax_exp<SPLIT, NS>(s);
#pragma unroll
      for (int i = 0; i < NS / 2; i++) pf[i] = pack2(s[2 * i], s[2 * i + 1]);
      pin(pf);
      if (KIND == 0) {
        block_fence(ID + 6);
        park<0, 8>(qlane(fresh_lane()), oB, i0, i1);
        asm volatile("fence.proxy.async.shared::cta;" ::: "memory");
        prof(wg, 7);
      }
      if (BIG && X_PA < 8 && t == T0 + HB) park<X_PA, 8>(qlane(fresh_lane()) + (4 + HB) * STAGE, HB ? oB : oA, i0, i1, !(bad >> HB));
      if (BIG && !HB && t == T0) mbar_wait(cx.sb + SM_BAR_Q + 8 * wg, 0);
      if (HB) mbar_wait(full + (rc >> 8), par);
      t++;
    };
#pragma unroll
    for (int i = 24; i < 28; i++) asm volatile("" : "=r"(pf[i]));
    mbar_wait(full + 8 * 2, 0);
    turn(IC<0>(), IC<0>());
    rb = 3 * 2048; rc = 2048;
    kill(oA);
    const bool never = blockIdx.y == 1;
#pragma unroll 1
    while (true) {
      turn(IC<1>(), IC<0>());
      if (t == 76) break;
      if (t == 10) {
#pragma unroll 1
        do {
#pragma unroll 1
          do turn(IC<2>(), IC<1>()); while (never);
          turn(IC<1>(), IC<1>());
        } while (t != 66);
      }
#pragma unroll 1
      do turn(IC<2>(), IC<0>()); while (never);
    }
    const uint32_t ql = qlane(fresh_lane());
    auto scale = [&](auto lo, auto hi) {
#pragma unroll
      for (int i = decltype(lo)::value; i < decltype(hi)::value; i++) {
        oa[32 + 2 * i] = pack2(oA[4 * i] * i0, oA[4 * i + 1] * i0);
        oa[32 + 2 * i + 1] = pack2(oA[4 * i + 2] * i1, oA[4 * i + 3] * i1);
        asm volatile("" : "+r"(oa[32 + 2 * i]), "+r"(oa[32 + 2 * i + 1])::"memory");
      }
    };
    TS3(1)
    if (X_LD == 0) {
#pragma unroll
      for (int i = 0; i < 8; i++) ldsm4(ql + 4 * STAGE + i * 2048, oa[4 * i], oa[4 * i + 1], oa[4 * i + 2], oa[4 * i + 3]);
    }
    {
      uint32_t h0, h1;
      sum_tree(pf, false, h0, h1);
      if (inv_sums(lB0 + (bf_lo(h0) + bf_hi(h0)), lB1 + (bf_lo(h1) + bf_hi(h1)), lB0, lB1)) bad |= 8;
    }
    scale(IC<0>(), IC<X_F1>());
    volatile uint32_t* const cold = (volatile uint32_t*)(cx.sp + SM_COLD) + wg;
    if (bad) *cold = 1;
    block_fence(93);
    TS3(2)
    bar_sync(my_turn, 256);
    const uint32_t is_cold = *cold;
    TS3(3)
    pin(pf); pin(oB);
    mma_pv(oB, pf, dv0 + 2 * 2048, true, false);
    mbar_arrive_cluster_now<91>(empty_c, signaller && !is_cold);
    TS3(4)
    if (X_LD == 1) {
#pragma unroll
      for (int i = 0; i < 8; i++) ldsm4(ql + 4 * STAGE + i * 2048, oa[4 * i], oa[4 * i + 1], oa[4 * i + 2], oa[4 * i + 3]);
    }
    const uint64_t db = mkdesc(ring + 3 * STAGE, 16);
    scale(IC<X_F1>(), IC<X_F2>());
    block_fence(94);
#pragma unroll
    for (int i = 0; i < 32; i++) asm volatile("" : "+r"(oa[i])::"memory");
    wg_fence();
#pragma unroll
    for (int k = 0; k < 8; k++) mma_n64t(acc, oa[4 * k], oa[4 * k + 1], oa[4 * k + 2], oa[4 * k + 3], db + k * 128, k > 0);
    if (X_F2 < 16) {
      wg_commit();
      block_fence(95);
      scale(IC<X_F2>(), IC<16>());
      TS3(5)
      wg_fence();
    }
#pragma unroll
    for (int k = 8; k < 16; k++) mma_n64t(acc, oa[4 * k], oa[4 * k + 1], oa[4 * k + 2], oa[4 * k + 3], db + k * 128, 1);
    wg_commit();
    bar_arrive(other_turn, 256);
    wg_wait<(X_F2 < 16 ? 2 : 1)>();
    pin(oB); pin(pf);
    TS(76)
    TS3(6)
    if (signaller) mbar_arrive_cluster(empty_c + 8 * 2);
#pragma unroll
    for (int i = 16; i < 24; i++) ldsm4(ql + 5 * STAGE + (i & 7) * 2048, oa[4 * i], oa[4 * i + 1], oa[4 * i + 2], oa[4 * i + 3]);
#pragma unroll
    for (int i = 0; i < 16; i++) {
      oa[96 + 2 * i] = pack2(oB[4 * i] * lB0, oB[4 * i + 1] * lB0);
      oa[96 + 2 * i + 1] = pack2(oB[4 * i + 2] * lB1, oB[4 * i + 3] * lB1);
    }
    TS3(7)
    mbar_wait(full + 8 * 1, 0);
    TS3(8)
    wg_wait<0>();
    pin(acc); pin(oa);
    if (__any_sync(0xffffffffu, is_cold)) {
      bad = __reduce_or_sync(0xffffffffu, bad);
      if (!(bad & 8)) {
#pragma unroll
        for (int i = 24; i < 32; i++) stsm4(ql + 6 * STAGE + (i & 7) * 2048, oa[4 * i], oa[4 * i + 1], oa[4 * i + 2], oa[4 * i + 3]);
      }
#pragma unroll 1
      for (int h = 0; h < 4; h++) {
        if (bad >> h & 1) {
          const uint32_t a = ql + ((0x6054 >> (4 * h)) & 7) * STAGE;
          const size_t o = (size_t)(hs * 2 + (h >> 1)) * SEQ * DH;
          float ox[64], l0, l1;
          exact_attention(ox, l0, l1, a, kc + o, vc + o, fresh_lane());
          inv_sums(l0, l1, l0, l1);
          __syncwarp();
          park<0, 8>(a, ox, l0, l1);
        }
      }
      __syncwarp();
#pragma unroll
      for (int i = 0; i < 32; i++)
        if ((i >> 3) != 1 || (bad & 4))
          ldsm4(ql + ((0x6504 >> (4 * (i >> 3))) & 7) * STAGE + (i & 7) * 2048, oa[4 * i], oa[4 * i + 1], oa[4 * i + 2], oa[4 * i + 3]);
      pin(oa);
      asm volatile("fence.proxy.async.shared::cta;" ::: "memory");
      bar_sync(4 + wg, 128);
      if (signaller) mbar_arrive_cluster(empty_c);
      wg_fence();
#pragma unroll
      for (int k = 0; k < 16; k++) mma_n64t(acc, oa[4 * k], oa[4 * k + 1], oa[4 * k + 2], oa[4 * k + 3], db + k * 128, k > 0);
      wg_commit();
      wg_wait<0>();
      pin(acc);
    }
    if (signaller) mbar_arrive_cluster(empty_c + 8 * 3);
  }

  prof(wg, 10);
  TS3(9)
  {
    lane = fresh_lane();
    const int tw = (cw & 3) * 32 + lane;
    float red[32];
    kill(red);
    const uint32_t tag = *(const uint32_t*)(cx.sp + SM_TAG);
    uint4* const xch = cx.g->part + (size_t)(qb * 64 * 2 + wg) * 4 * 128 + tw;
    int nrx = 1;
    auto region = [](int s, int h) { return h ? 1 + (s & 1) : (s & 1) ? 0 : 3; };
    auto half_step = [&](int s, auto hc, bool arrive) {
      constexpr int h = decltype(hc)::value;
      const uint64_t db = mkdesc(ring + region(s, h) * STAGE, 16);
      bar_sync(my_turn, 256);
      pin(oa);
      wg_fence();
#pragma unroll
      for (int k = 0; k < 16; k++) {
        const int kb = h * 16 + k;
        mma_n64t(acc, oa[4 * kb], oa[4 * kb + 1], oa[4 * kb + 2], oa[4 * kb + 3], db + k * 128, kb > 0);
      }
      wg_commit();
      if (arrive) bar_arrive(other_turn, 256);
    };
    auto await = [&](int s, int h) { mbar_wait(full + 8 * region(s, h), ((s >> 1) ^ h ^ 1) & 1); };
    auto fetch = [&](uint32_t (&g)[16], int n) {
      const uint4* p = xch + (hs * 7 + n - 1) * (2 * 4 * 128);
#pragma unroll
      for (int i = 0; i < 4; i++) ld_gran(p + i * 128, g[4 * i], g[4 * i + 1], g[4 * i + 2], g[4 * i + 3]);
    };
    uint32_t g[16];
#pragma unroll 1
    for (int s = 0; s < 8; s++) {
      const bool pend = nrx < s - 1;
      if (pend) fetch(g, nrx);
      half_step(s, IC<1>(), true);
      TS3(s < 3 ? 16 + 8 * s : 75)
      if (s == 0) {
        bar_arrive(BAR_OA, 352);
#pragma unroll
        for (int i = 0; i < 32; i++) red[i] = 0.f;
      }
      await(s + 1, 0);
      TS3(s < 3 ? 17 + 8 * s : 75)
      wg_wait<0>();
      TS3(s < 3 ? 18 + 8 * s : 75)
      if (signaller && s < 7) mbar_arrive_cluster(empty_c + 8 * region(s, 1));
      pin(acc);
      TS(77 + s)
      prof(wg, 12 + s);
      uint4* p = xch + (s == 0 ? 56 + hs : ((hs + s) & 7) * 7 + s - 1) * (2 * 4 * 128);
#pragma unroll
      for (int i = 0; i < 4; i++)
        st_gran(p + i * 128, (pack2(acc[8 * i], acc[8 * i + 1]) & ~TAG) | tag, pack2(acc[8 * i + 2], acc[8 * i + 3]),
                pack2(acc[8 * i + 4], acc[8 * i + 5]), pack2(acc[8 * i + 6], acc[8 * i + 7]));
      TS3(s < 3 ? 19 + 8 * s : 75)
      half_step(s + 1, IC<0>(), true);
      TS3(s < 3 ? 20 + 8 * s : 75)
      await(s + 1, 1);
      TS3(s < 3 ? 21 + 8 * s : 75)
      if (pend && granules_ok(g, tag)) { add_granules(red, g); nrx++; }
      if (X_EARLY == 2 && s == 7) fetch(g, nrx);
      wg_wait<0>();
      TS3(s < 3 ? 22 + 8 * s : 75)
      if (signaller && s < 6) mbar_arrive_cluster(empty_c + 8 * region(s + 1, 0));
    }
    uint32_t xv[16], gt[16], g2[16];
    if (X_EARLY < 2) fetch(g, nrx);
    mbar_wait(cx.sb + SM_BAR_XG, 0);
    const bool two = nrx < 7;
    bool ok;
    {
      const uint64_t db = mkdesc(ring + STAGE, 16);
      if (X_EARLY == 2) ok = granules_ok(g, tag);
      bar_sync(my_turn, 256);
      if (X_EARLY == 2) fetch(g2, 7);
#pragma unroll
      for (int i = 64; i < 128; i++) asm volatile("" : "+r"(oa[i])::"memory");
      wg_fence();
#pragma unroll
      for (int k = 16; k < 32; k++) mma_n64t(acc, oa[4 * k], oa[4 * k + 1], oa[4 * k + 2], oa[4 * k + 3], db + (k - 16) * 128, 1);
      wg_commit();
      if (wg == 0) bar_arrive(other_turn, 256);
    }
    if (X_EARLY < 2) {
      ok = granules_ok(g, tag);
      fetch(g2, 7);
    }
    const uint32_t frag = (cw * 16 + (lane & 15)) * 128 + (((lane >> 4) ^ (lane & 7)) << 4);
#pragma unroll
    for (int i = 0; i < 4; i++) {
      ldsm4(cx.sb + SM_XO + (frag ^ (i << 5)), xv[4 * i], xv[4 * i + 1], xv[4 * i + 2], xv[4 * i + 3]);
      ldsm4(cx.sb + SM_GO + (frag ^ (i << 5)), gt[4 * i], gt[4 * i + 1], gt[4 * i + 2], gt[4 * i + 3]);
    }
    if (ok) { add_granules(red, g); nrx++; }
    wg_wait<0>();
    pin(acc);
    TS(85)
#pragma unroll
    for (int i = 0; i < 32; i++) red[i] += acc[i];
    pin(red);
    block_fence(90);
    int last = 8;
    if (two && granules_ok(g2, tag)) { add_granules(red, g2); last = 7; }
#pragma unroll 1
    for (int spins = 0; nrx < last && spins < (1 << 16); spins++) {
      fetch(g, nrx);
      if (granules_ok(g, tag)) { add_granules(red, g); nrx++; }
    }
    prof(wg, 20);
    TS(86)
    uint32_t ow[16];
#pragma unroll
    for (int i = 0; i < 16; i++) ow[i] = fma2(pack2(red[2 * i], red[2 * i + 1]), gt[i], xv[i]);
#pragma unroll
    for (int i = 0; i < 4; i++) stsm4(cx.sb + SM_XO + (frag ^ (i << 5)), ow[4 * i], ow[4 * i + 1], ow[4 * i + 2], ow[4 * i + 3]);
    __syncwarp();
#pragma unroll
    for (int i = 0; i < 4; i++) {
      uint4 v;
      const int row = cw * 16 + i * 4 + (lane >> 3);
      lds128(cx.sb + SM_XO + row * 128 + (((lane ^ row) & 7) << 4), v.x, v.y, v.z, v.w);
      asm volatile("st.global.v4.b32 [%0], {%1, %2, %3, %4};" ::"l"(out + (size_t)(qb * 128 + row) * DM + hs * 64 + (lane & 7) * 8),
                   "r"(v.x), "r"(v.y), "r"(v.z), "r"(v.w) : "memory");
    }
    prof(wg, 22);
    TS(87)
    TS_DUMP()
  }
}

struct KvMaps { CUtensorMap m[4]; };
__global__ void __cluster_dims__(2, 1, 1) __launch_bounds__(THREADS, 1)
fused_kernel(const __nv_bfloat16* __restrict__ x, const __nv_bfloat16* __restrict__ w_r, const __nv_bfloat16* __restrict__ kc,
             const __nv_bfloat16* __restrict__ vc, __nv_bfloat16* __restrict__ out, Scratch* scratch,
             const __grid_constant__ CUtensorMap tmX, const __grid_constant__ CUtensorMap tmWq,
             const __grid_constant__ KvMaps tmKV, const __grid_constant__ CUtensorMap tmWo,
             const __grid_constant__ CUtensorMap tmG, const __grid_constant__ CUtensorMap tmU,
             const __grid_constant__ CUtensorMap tmD, const __grid_constant__ CUtensorMap tmX16,
             const __grid_constant__ CUtensorMap tmWq96, const __grid_constant__ CUtensorMap tmX64) {
  extern __shared__ __align__(1024) uint8_t smem_raw[];
  prof(0, 23, 511);
  if (X_PFX && threadIdx.x == 192) { prefetch_tmap(&tmX); prefetch_tmap(&tmWq); }
  Ctx cx;
  cx.sb = smem_u32(smem_raw);
  cx.sp = smem_raw;
  cx.g = scratch;
  cx.rank = blockIdx.x & 1;
  const int warp = __shfl_sync(0xffffffffu, threadIdx.x >> 5, 0);
  const int cluster = blockIdx.x >> 1;
  const bool is_ffn = blockIdx.x >= N_ATT_CTA;
  const int c7 = ((cluster - 36) * 37) >> 8;
  const int hs = cluster < 4 ? 4 + cluster : cluster < 36 ? (cluster - 4) >> 3 : 4 + c7;
  const int qb = (cluster < 4 ? 0 : cluster < 36 ? (cluster - 4) & 7 : cluster - (is_ffn ? 36 : 35) - 7 * c7) * 2 + cx.rank;

  auto load_x = [&](int w) {
#pragma unroll
    for (int i = 0; i < 3; i++) {
      mbar_expect_tx(cx.sb + SM_XFULL + 24 * w + 8 * i, 24576);
      tma3d(cx.sb + SM_X + (3 * w + i) * 24576, &tmX, qb * 128 + w * 64, i * 3, cx.sb + SM_XFULL + 24 * w + 8 * i);
    }
  };
  if (warp < 4) {
    asm volatile("setmaxnreg.dec.sync.aligned.u32 24;");
    if (elect_one()) {
      if (warp == 0) {
        TSP(64)
#pragma unroll
        for (int i = 0; i < 4; i++) mbar_init(cx.sb + SM_FULL + 8 * i, 1);
#pragma unroll
        for (int i = 3; i < 6; i++) mbar_init(cx.sb + SM_XFULL + 8 * i, 1);
        TSP(65)
      } else if (warp == 1) {
#pragma unroll
        for (int i = 0; i < 4; i++) mbar_init(cx.sb + SM_EMPTY + 8 * i, 4);
        mbar_init(cx.sb + SM_BAR_MISC, 1);
        mbar_init(cx.sb + SM_BAR_XG, 1);
        mbar_init(cx.sb + SM_BAR_Q, 1);
        mbar_init(cx.sb + SM_BAR_Q + 8, 1);
      } else if (is_ffn) {
#pragma unroll
        for (int i = 0; i < 8; i++) mbar_init(cx.sb + (warp == 2 ? SM_FFULL : SM_FEMPTY) + 8 * i, 1);
      }
      asm volatile("fence.mbarrier_init.release.cluster;" ::: "memory");
    }
    __syncwarp();
    cluster_arrive();
    if (warp == 0 && elect_one()) load_x(1);
    __syncwarp();
    if (warp == 0) TSP(70)
    cluster_wait();
    if (warp == 0) TSP(71)
    prof(0, 24, 511);
    if (warp == 0) {
      if (is_ffn) ffn_producer(cx, qb, &tmWq, &tmG, &tmU, &tmD);
      else attn_producer(cx, qb, hs, tmKV.m, &tmWq, &tmWq96, &tmWo);
      prof(0, 25, 511);
    } else if (!is_ffn) {
      attn_gate(cx, qb, hs, threadIdx.x - 32, x);
      asm volatile("fence.proxy.async;" ::: "memory");
      if (warp == 1) attn_helper(cx, qb, hs, read_lane(), &tmX16);
      else bar_arrive(BAR_OA, 352);
      attn_finish8(cx, qb, hs, warp - 1, read_lane(), out);
    } else if (warp < 3) {
      ffn_publish(cx, qb, warp - 1, read_lane(), &tmX64);
    }
    __syncwarp();
    cluster_arrive();
    cluster_wait();
  } else {
    if (warp == 4 && elect_one()) {
#pragma unroll
      for (int i = 0; i < 3; i++) mbar_init(cx.sb + SM_XFULL + 8 * i, 1);
      asm volatile("fence.mbarrier_init.release.cluster;" ::: "memory");
      TSP(66)
      load_x(0);
      TSP(67)
    }
    if (warp == 5 && elect_one()) {
      mbar_init(cx.sb + SM_BAR_W, 1);
      asm volatile("fence.mbarrier_init.release.cluster;" ::: "memory");
      *(uint4*)(cx.sp + SM_ONES) = make_uint4(0x3F803F80u, 0x3F803F80u, 0x3F803F80u, 0x3F803F80u);
      mbar_expect_tx(cx.sb + SM_BAR_W, DM * 2);
      bulk_load(cx.sb + SM_WR, w_r, DM * 2, cx.sb + SM_BAR_W);
    }
    __syncwarp();
    cluster_arrive();
    asm volatile("setmaxnreg.inc.sync.aligned.u32 240;");
    const int cw = warp - 4, wg = cw >> 2;
    if (is_ffn && (threadIdx.x & 127) == 96) *(uint32_t*)(cx.sp + SM_TAG + 4) = cx.g->launch[blockIdx.x + 4 * wg]++;
    cluster_wait();
    attn_consumer(cx, is_ffn, qb, hs, wg, cw, read_lane(), x, kc, vc, out);
  }
}

typedef CUresult (*EncodeFn)(CUtensorMap*, CUtensorMapDataType, cuuint32_t, void*, const cuuint64_t*, const cuuint64_t*,
                             const cuuint32_t*, const cuuint32_t*, CUtensorMapInterleave, CUtensorMapSwizzle,
                             CUtensorMapL2promotion, CUtensorMapFloatOOBfill);

void encode(EncodeFn fn, CUtensorMap* m, const void* p, int rank, const cuuint64_t* dims, const cuuint64_t* strides,
            const cuuint32_t* box) {
  const cuuint32_t es[5] = {1, 1, 1, 1, 1};
  fn(m, CU_TENSOR_MAP_DATA_TYPE_BFLOAT16, rank, const_cast<void*>(p), dims, strides, box, es, CU_TENSOR_MAP_INTERLEAVE_NONE,
     CU_TENSOR_MAP_SWIZZLE_128B, CU_TENSOR_MAP_L2_PROMOTION_L2_128B, CU_TENSOR_MAP_FLOAT_OOB_FILL_NONE);
}
void encode2d(EncodeFn fn, CUtensorMap* m, const void* p, uint64_t rows, uint64_t cols, uint32_t box_rows) {
  const cuuint64_t dims[2] = {cols, rows}, strides[1] = {cols * 2};
  const cuuint32_t box[2] = {64, box_rows};
  encode(fn, m, p, 2, dims, strides, box);
}

}

extern "C" void kernel_launch(void* const* d_in, const int* in_sizes, int n_in, void* d_out, int out_size) {
  (void)in_sizes; (void)n_in; (void)out_size;
  void* fnp = nullptr;
  cudaDriverEntryPointQueryResult qr;
  cudaGetDriverEntryPoint("cuTensorMapEncodeTiled", &fnp, cudaEnableDefault, &qr);
  EncodeFn fn = (EncodeFn)fnp;
  CUtensorMap tmWq, tmWo, tmG, tmU, tmD, tmX, tmX16, tmWq96, tmX64;
  encode2d(fn, &tmX64, d_in[0], SEQ, DM, 64);
  encode2d(fn, &tmWq96, d_in[3], DM, 4096, 96);
  encode2d(fn, &tmX16, d_in[0], SEQ, DM, 16);
  KvMaps tmKV;
  for (int i = 0; i < 4; i++) encode2d(fn, &tmKV.m[i], d_in[1 + (i & 1)], 16 * SEQ, DH, i < 2 ? 112 : 96);
  encode2d(fn, &tmWq, d_in[3], DM, 4096, 64);
  {
    const cuuint64_t dims[3] = {64, SEQ, 9}, strides[2] = {DM * 2, 128};
    const cuuint32_t box[3] = {64, 64, 3};
    encode(fn, &tmX, d_in[0], 3, dims, strides, box);
  }
  encode2d(fn, &tmWo, d_in[4], 4096, DM, 128);
  encode2d(fn, &tmG, d_in[7], DM, FF, 192);
  encode2d(fn, &tmU, d_in[8], DM, FF, 192);
  encode2d(fn, &tmD, d_in[9], FF, DM, 192);
  cudaFuncSetAttribute(fused_kernel, cudaFuncAttributeMaxDynamicSharedMemorySize, SM_TOTAL);
  void* scratch = nullptr;
  cudaGetSymbolAddress(&scratch, g_scratch);
  fused_kernel<<<N_CTA, THREADS, SM_TOTAL>>>((const __nv_bfloat16*)d_in[0], (const __nv_bfloat16*)d_in[6], (const __nv_bfloat16*)d_in[1],
                                            (const __nv_bfloat16*)d_in[2], (__nv_bfloat16*)d_out, (Scratch*)scratch, tmX, tmWq, tmKV,
                                            tmWo, tmG, tmU, tmD, tmX16, tmWq96, tmX64);
}
```

```cpp
#include <cuda_runtime.h>
#include <cuda_bf16.h>
#include <cuda.h>
#include <stdint.h>

#define X_PFW 1
#define X_SPLIT 38
#define X_SPLITA 36
#define X_SPLITS 32
#define X_SPLITSA 30
#define X_PA 8
#define X_PG 2
#define X_E0 10
#define X_F2 10
#define X_LD 0
#define X_LN 0
#define X_WAKE 31
#define X_PFX 1
#define X_F1 0
#define X_BF2 1
#define X_SQI 4
#define X_SQS 300
#define X_P0 1
#define X_ORD 3
#define X_NS 4
namespace {

constexpr int SEQ = 2048, DM = 576, DH = 128, FF = 4608, TOPC = 8;
constexpr int N_ATT_CTA = 128, N_CTA = 132;
constexpr int THREADS = 384;

constexpr uint32_t SM_RING = 0;
constexpr uint32_t STAGE = 32768;
constexpr uint32_t SM_SLOT = 131072;
constexpr uint32_t FSTAGE = 24576;
constexpr uint32_t SM_XSEL = 196608;
constexpr uint32_t SM_H = 205824;
constexpr uint32_t SM_MISC = 229376;
constexpr uint32_t SM_FULL = SM_MISC, SM_EMPTY = SM_MISC + 32, SM_FFULL = SM_MISC + 64, SM_BAR_MISC = SM_MISC + 128,
                   SM_COLD = SM_MISC + 136, SM_TAG = SM_MISC + 144, SM_BAR_W = SM_MISC + 152, SM_ONES = SM_MISC + 160,
                   SM_BAR_Q = SM_MISC + 176, SM_XFULL = SM_MISC + 192, SM_BAR_XG = SM_MISC + 304, SM_BAR_SQ = SM_MISC + 312,
                   SM_STATS = SM_MISC + 320, SM_FEMPTY = SM_MISC + 1344, SM_RAW = SM_FEMPTY, SM_WR = SM_MISC + 1408, SM_TOPK = SM_WR;
constexpr uint32_t SM_TOTAL = SM_MISC + 2560;
constexpr uint32_t SM_X = SM_MISC - 147456;

constexpr int BAR_GATE = 6, BAR_HELPER = 7, BAR_OA = 8, BAR_XREL = 13, BAR_QS = 9, BAR_QF = 11;
constexpr int NST_Q = 18, NST_KV = 76, NST_O = 18;
constexpr float SM_SCALE_LOG2 = 0.08838834764831845f * 1.4426950408889634f;

struct Scratch {
  uint4 part[16 * 64 * 2 * 4 * 128];
  uint4 gate[N_ATT_CTA * 1152];
  uint4 q[16 * 8 * 2 * 512];
  uint2 sq[SEQ];
  uint4 stats[SEQ];
  float ypart[4 * TOPC * DM];
  int2 sel[16];
  unsigned launch[160];
  unsigned pad0, ycnt, pad[30];
  unsigned qflag[128];
};
__device__ __align__(1024) Scratch g_scratch;

__device__ __forceinline__ void prof(int, int, int = 0) {}

#define TS(id) {}
#define TS_DUMP() {}
#define TS4(k) {}
#define TSP(k) {}
#define TS1(id) TS(id)
#define TS2(k) {}
#define TS3(k) {}

__device__ __forceinline__ uint32_t smem_u32(const void* p) { return (uint32_t)__cvta_generic_to_shared(p); }
__device__ __forceinline__ void mbar_init(uint32_t bar, uint32_t cnt) {
  asm volatile("mbarrier.init.shared::cta.b64 [%0], %1;" ::"r"(bar), "r"(cnt) : "memory");
}
__device__ __forceinline__ void mbar_expect_tx(uint32_t bar, uint32_t bytes) {
  asm volatile("mbarrier.arrive.expect_tx.shared::cta.b64 _, [%0], %1;" ::"r"(bar), "r"(bytes) : "memory");
}
__device__ __forceinline__ void mbar_arrive(uint32_t bar) {
  asm volatile("mbarrier.arrive.shared::cta.b64 _, [%0];" ::"r"(bar) : "memory");
}
__device__ __forceinline__ void mbar_arrive_cluster(uint32_t bar_cluster_addr) {
  asm volatile("mbarrier.arrive.shared::cluster.b64 _, [%0];" ::"r"(bar_cluster_addr) : "memory");
}
template <int ID>
__device__ __forceinline__ void mbar_arrive_cluster_now(uint32_t bar_cluster_addr, bool pred) {
  asm volatile("{\n.reg .pred p, q;\nsetp.ne.u32 p, %1, 0;\nsetp.eq.u32 q, %2, %3;\n"
               "ARR_LOOP:\n@p mbarrier.arrive.shared::cluster.b64 _, [%0];\n@q bra.uni ARR_LOOP;\n}"
               ::"r"(bar_cluster_addr), "r"((uint32_t)pred), "r"(blockIdx.y), "n"(ID) : "memory");
}
__device__ __forceinline__ void block_fence(int id) {
  asm volatile("{\n.reg .pred q;\nsetp.eq.u32 q, %0, %1;\nBF_LOOP:\n@q st.volatile.shared.u32 [%0], %0;\n@q bra.uni BF_LOOP;\n}"
               ::"r"(blockIdx.y), "r"(id) : "memory");
}
__device__ __forceinline__ void mbar_wait(uint32_t bar, uint32_t parity) {
  asm volatile("{\n.reg .pred p, q;\n.reg .u32 n;\nmov.u32 n, 0;\n"
               "WAIT_LOOP:\nmbarrier.try_wait.parity.shared::cta.b64 p, [%0], %1;\n"
               "add.u32 n, n, 1;\nsetp.lt.u32 q, n, 4194304;\nand.pred q, q, !p;\n@q bra WAIT_LOOP;\n}"
               ::"r"(bar), "r"(parity) : "memory");
}
__device__ __forceinline__ uint32_t mapa(uint32_t addr, uint32_t rank) {
  uint32_t r;
  asm volatile("mapa.shared::cluster.u32 %0, %1, %2;" : "=r"(r) : "r"(addr), "r"(rank));
  return r;
}
__device__ __forceinline__ void cluster_arrive() { asm volatile("barrier.cluster.arrive.relaxed.aligned;" ::: "memory"); }
__device__ __forceinline__ bool elect_one() {
  uint32_t p;
  asm volatile("{\n.reg .pred p;\nelect.sync _|p, 0xffffffff;\nselp.u32 %0, 1, 0, p;\n}" : "=r"(p));
  return p;
}
__device__ __forceinline__ int read_lane() { return threadIdx.x & 31; }
__device__ __forceinline__ int fresh_lane() {
  int l;
  asm volatile("mov.u32 %0, %%laneid;" : "=r"(l));
  return l;
}
__device__ __forceinline__ void cluster_wait() { asm volatile("barrier.cluster.wait.acquire.aligned;" ::: "memory"); }
__device__ __forceinline__ void bar_sync(int id, int n) { asm volatile("barrier.cta.sync %0, %1;" ::"r"(id), "r"(n) : "memory"); }
__device__ __forceinline__ void bar_arrive(int id, int n) { asm volatile("barrier.cta.arrive %0, %1;" ::"r"(id), "r"(n) : "memory"); }

__device__ __forceinline__ uint64_t policy_evict_first() {
  uint64_t p;
  asm("createpolicy.fractional.L2::evict_first.b64 %0, 1.0;" : "=l"(p));
  return p;
}
__device__ __forceinline__ void tma2d_mc(uint32_t dst, const CUtensorMap* tm, int c0, int c1, uint32_t bar, uint64_t pol) {
  asm volatile("cp.async.bulk.tensor.2d.shared::cluster.global.mbarrier::complete_tx::bytes.multicast::cluster.L2::cache_hint"
               " [%0], [%1, {%2, %3}], [%4], %5, %6;"
               ::"r"(dst), "l"(tm), "r"(c0), "r"(c1), "r"(bar), "h"((uint16_t)3), "l"(pol) : "memory");
}
__device__ __forceinline__ void tma3d(uint32_t dst, const CUtensorMap* tm, int c1, int c2, uint32_t bar) {
  asm volatile("cp.async.bulk.tensor.3d.shared::cluster.global.mbarrier::complete_tx::bytes [%0], [%1, {%2, %3, %4}], [%5];"
               ::"r"(dst), "l"(tm), "r"(0), "r"(c1), "r"(c2), "r"(bar) : "memory");
}
__device__ __forceinline__ void tma2d(uint32_t dst, const CUtensorMap* tm, int c0, int c1, uint32_t bar) {
  asm volatile("cp.async.bulk.tensor.2d.shared::cluster.global.mbarrier::complete_tx::bytes [%0], [%1, {%2, %3}], [%4];"
               ::"r"(dst), "l"(tm), "r"(c0), "r"(c1), "r"(bar) : "memory");
}
__device__ __forceinline__ void tma2d_stream(uint32_t dst, const CUtensorMap* tm, int c0, int c1, uint32_t bar) {
  asm volatile("{\n.reg .b64 pol;\ncreatepolicy.fractional.L2::evict_first.b64 pol, 1.0;\n"
               "cp.async.bulk.tensor.2d.shared::cluster.global.mbarrier::complete_tx::bytes.L2::cache_hint [%0], [%1, {%2, %3}], [%4], pol;\n}"
               ::"r"(dst), "l"(tm), "r"(c0), "r"(c1), "r"(bar) : "memory");
}
__device__ __forceinline__ void bulk_load(uint32_t dst, const void* src, uint32_t bytes, uint32_t bar) {
  asm volatile("cp.async.bulk.shared::cluster.global.mbarrier::complete_tx::bytes [%0], [%1], %2, [%3];"
               ::"r"(dst), "l"(src), "r"(bytes), "r"(bar) : "memory");
}
__device__ __forceinline__ void tma2d_prefetch(const CUtensorMap* tm, int c0, int c1) {
  asm volatile("cp.async.bulk.prefetch.tensor.2d.L2.global [%0, {%1, %2}];" ::"l"(tm), "r"(c0), "r"(c1) : "memory");
}
__device__ __forceinline__ void prefetch_tmap(const CUtensorMap* tm) {
  asm volatile("prefetch.tensormap [%0];" ::"l"(tm) : "memory");
}

__device__ __forceinline__ void wg_fence() { asm volatile("wgmma.fence.sync.aligned;" ::: "memory"); }
__device__ __forceinline__ void wg_commit() { asm volatile("wgmma.commit_group.sync.aligned;" ::: "memory"); }
template <int N> __device__ __forceinline__ void wg_wait() { asm volatile("wgmma.wait_group.sync.aligned %0;" ::"n"(N) : "memory"); }

__device__ __forceinline__ uint64_t mkdesc(uint32_t addr, uint32_t lbo_bytes) {
  return (uint64_t)(((addr & 0x3FFFF) >> 4) | ((lbo_bytes >> 4) << 16)) | ((uint64_t)0x40000040u << 32);
}
__device__ __forceinline__ uint64_t mkdesc_q(uint32_t addr) {
  return (uint64_t)(((addr & 0x3FFFF) >> 4) | (64u << 16)) | ((uint64_t)8 << 32);
}
template <int N> __device__ __forceinline__ void pin(float (&a)[N]) {
#pragma unroll
  for (int i = 0; i < N; i++) asm volatile("" : "+f"(a[i])::"memory");
}
template <int N> __device__ __forceinline__ void kill(float (&a)[N]) {
#pragma unroll
  for (int i = 0; i < N; i++) asm volatile("" : "=f"(a[i]));
}
template <int N> __device__ __forceinline__ void pin(uint32_t (&a)[N]) {
#pragma unroll
  for (int i = 0; i < N; i++) asm volatile("" : "+r"(a[i])::"memory");
}

#define F8(d, o) "+f"(d[o]), "+f"(d[o + 1]), "+f"(d[o + 2]), "+f"(d[o + 3]), "+f"(d[o + 4]), "+f"(d[o + 5]), "+f"(d[o + 6]), "+f"(d[o + 7])
#define R32A "%0, %1, %2, %3, %4, %5, %6, %7, %8, %9, %10, %11, %12, %13, %14, %15, %16, %17, %18, %19, %20, %21, %22, %23, %24, %25, %26, %27, %28, %29, %30, %31"
#define R32B "%32, %33, %34, %35, %36, %37, %38, %39, %40, %41, %42, %43, %44, %45, %46, %47, %48, %49, %50, %51, %52, %53, %54, %55, %56, %57, %58, %59, %60, %61, %62, %63"

#define O8(d, o) "=f"(d[o]), "=f"(d[o + 1]), "=f"(d[o + 2]), "=f"(d[o + 3]), "=f"(d[o + 4]), "=f"(d[o + 5]), "=f"(d[o + 6]), "=f"(d[o + 7])

__device__ __forceinline__ void mma_n128t(float (&d)[64], uint32_t a0, uint32_t a1, uint32_t a2, uint32_t a3, uint64_t db, bool acc) {
  if (acc)
    asm volatile("wgmma.mma_async.sync.aligned.m64n128k16.f32.bf16.bf16 {" R32A ", " R32B "}, {%64, %65, %66, %67}, %68, 1, 1, 1, 1;\n"
                 : F8(d, 0), F8(d, 8), F8(d, 16), F8(d, 24), F8(d, 32), F8(d, 40), F8(d, 48), F8(d, 56)
                 : "r"(a0), "r"(a1), "r"(a2), "r"(a3), "l"(db));
  else
    asm volatile("wgmma.mma_async.sync.aligned.m64n128k16.f32.bf16.bf16 {" R32A ", " R32B "}, {%64, %65, %66, %67}, %68, 0, 1, 1, 1;\n"
                 : O8(d, 0), O8(d, 8), O8(d, 16), O8(d, 24), O8(d, 32), O8(d, 40), O8(d, 48), O8(d, 56)
                 : "r"(a0), "r"(a1), "r"(a2), "r"(a3), "l"(db));
}
#define PV1(a0, a1, a2, a3, ob, acc) "add.s64 b, %92, " #ob ";\n" \
  "wgmma.mma_async.sync.aligned.m64n128k16.f32.bf16.bf16 {" R32A ", " R32B "}, {%" #a0 ", %" #a1 ", %" #a2 ", %" #a3 "}, b, " #acc ", 1, 1, 1;\n"
#define PV6 "wgmma.fence.sync.aligned;\n" PV1(64, 65, 66, 67, 0, p) PV1(68, 69, 70, 71, 128, 1) PV1(72, 73, 74, 75, 256, 1) \
  PV1(76, 77, 78, 79, 384, 1) PV1(80, 81, 82, 83, 512, 1) PV1(84, 85, 86, 87, 640, 1)
#define U4(a, o) "r"(a[o]), "r"(a[o + 1]), "r"(a[o + 2]), "r"(a[o + 3])
__device__ __forceinline__ void mma_pv(float (&d)[64], const uint32_t (&a)[28], uint64_t dv, bool acc, bool big) {
  asm volatile("{\n.reg .pred p, q;\n.reg .b64 b;\nsetp.ne.b32 p, %93, 0;\nsetp.eq.b32 q, %94, 0;\n@q bra.uni PV_SMALL;\n"
               PV6 PV1(88, 89, 90, 91, 768, 1) "wgmma.commit_group.sync.aligned;\nbra.uni PV_DONE;\n"
               "PV_SMALL:\n" PV6 "wgmma.commit_group.sync.aligned;\nPV_DONE:\n}\n"
               : F8(d, 0), F8(d, 8), F8(d, 16), F8(d, 24), F8(d, 32), F8(d, 40), F8(d, 48), F8(d, 56)
               : U4(a, 0), U4(a, 4), U4(a, 8), U4(a, 12), U4(a, 16), U4(a, 20), U4(a, 24), "l"(dv), "r"((int)acc), "r"((int)big) : "memory");
}
#define R48 R32A ", %32, %33, %34, %35, %36, %37, %38, %39, %40, %41, %42, %43, %44, %45, %46, %47"
#define R56 R48 ", %48, %49, %50, %51, %52, %53, %54, %55"
#define QK1(N, R, A, B, oa, ob, acc) "add.s64 a, " A ", " #oa ";\nadd.s64 b, " B ", " #ob ";\n" \
  "wgmma.mma_async.sync.aligned.m64n" #N "k16.f32.bf16.bf16 {" R "}, a, b, " #acc ", 1, 1, 0, 0;\n"
#define QK8(N, R, A, B) "{\n.reg .b64 a, b;\nwgmma.fence.sync.aligned;\n" QK1(N, R, A, B, 0, 0, 0) QK1(N, R, A, B, 128, 2, 1) \
  QK1(N, R, A, B, 256, 4, 1) QK1(N, R, A, B, 384, 6, 1) QK1(N, R, A, B, 512, 1024, 1) QK1(N, R, A, B, 640, 1026, 1) \
  QK1(N, R, A, B, 768, 1028, 1) QK1(N, R, A, B, 896, 1030, 1) "wgmma.commit_group.sync.aligned;\n}\n"
__device__ __forceinline__ void mma_qk(float (&d)[56], uint64_t dq, uint64_t dk) {
  asm volatile(QK8(112, R56, "%56", "%57")
               : O8(d, 0), O8(d, 8), O8(d, 16), O8(d, 24), O8(d, 32), O8(d, 40), O8(d, 48) : "l"(dq), "l"(dk) : "memory");
}
__device__ __forceinline__ void mma_qk(float (&d)[48], uint64_t dq, uint64_t dk) {
  asm volatile(QK8(96, R48, "%48", "%49")
               : O8(d, 0), O8(d, 8), O8(d, 16), O8(d, 24), O8(d, 32), O8(d, 40) : "l"(dq), "l"(dk) : "memory");
}
__device__ __forceinline__ void mma_n64t(float (&d)[32], uint32_t a0, uint32_t a1, uint32_t a2, uint32_t a3, uint64_t db, bool acc) {
  if (acc)
    asm volatile("wgmma.mma_async.sync.aligned.m64n64k16.f32.bf16.bf16 {" R32A "}, {%32, %33, %34, %35}, %36, 1, 1, 1, 1;\n"
                 : F8(d, 0), F8(d, 8), F8(d, 16), F8(d, 24) : "r"(a0), "r"(a1), "r"(a2), "r"(a3), "l"(db));
  else
    asm volatile("wgmma.mma_async.sync.aligned.m64n64k16.f32.bf16.bf16 {" R32A "}, {%32, %33, %34, %35}, %36, 0, 1, 1, 1;\n"
                 : O8(d, 0), O8(d, 8), O8(d, 16), O8(d, 24) : "r"(a0), "r"(a1), "r"(a2), "r"(a3), "l"(db));
}
__device__ __forceinline__ void mma_n64t_dyn(float (&d)[32], uint32_t a0, uint32_t a1, uint32_t a2, uint32_t a3, uint64_t db, int acc) {
  asm volatile("{\n.reg .pred p;\nsetp.ne.b32 p, %37, 0;\n"
               "wgmma.mma_async.sync.aligned.m64n64k16.f32.bf16.bf16 {" R32A "}, {%32, %33, %34, %35}, %36, p, 1, 1, 1;\n}\n"
               : F8(d, 0), F8(d, 8), F8(d, 16), F8(d, 24) : "r"(a0), "r"(a1), "r"(a2), "r"(a3), "l"(db), "r"(acc));
}
__device__ __forceinline__ void mma_n8(float (&d)[4], uint64_t da, uint64_t db, int acc) {
  asm volatile("{\n.reg .pred p;\nsetp.ne.b32 p, %6, 0;\n"
               "wgmma.mma_async.sync.aligned.m64n8k16.f32.bf16.bf16 {%0, %1, %2, %3}, %4, %5, p, 1, 1, 1, 0;\n}\n"
               : "+f"(d[0]), "+f"(d[1]), "+f"(d[2]), "+f"(d[3])
               : "l"(da), "l"(db), "r"(acc));
}
__device__ __forceinline__ void hmma_k16(float (&d)[4], uint32_t a0, uint32_t a1, uint32_t a2, uint32_t a3, uint32_t b0, uint32_t b1) {
  asm volatile("mma.sync.aligned.m16n8k16.row.col.f32.bf16.bf16.f32 {%0, %1, %2, %3}, {%4, %5, %6, %7}, {%8, %9}, {%0, %1, %2, %3};"
               : "+f"(d[0]), "+f"(d[1]), "+f"(d[2]), "+f"(d[3]) : "r"(a0), "r"(a1), "r"(a2), "r"(a3), "r"(b0), "r"(b1));
}

__device__ __forceinline__ uint32_t pack2(float lo, float hi) {
  uint32_t r;
  asm("cvt.rn.bf16x2.f32 %0, %1, %2;" : "=r"(r) : "f"(hi), "f"(lo));
  return r;
}
__device__ __forceinline__ float bf_lo(uint32_t w) { return __uint_as_float(w << 16); }
__device__ __forceinline__ float bf_hi(uint32_t w) { return __uint_as_float(w & 0xFFFF0000u); }
__device__ __forceinline__ float bfr(float x) { return __bfloat162float(__float2bfloat16_rn(x)); }
__device__ __forceinline__ uint32_t sub2(uint32_t a, uint32_t b) {
  uint32_t r;
  asm("sub.rn.bf16x2 %0, %1, %2;" : "=r"(r) : "r"(a), "r"(b));
  return r;
}
__device__ __forceinline__ uint32_t add2(uint32_t a, uint32_t b) {
  uint32_t r;
  asm("add.rn.bf16x2 %0, %1, %2;" : "=r"(r) : "r"(a), "r"(b));
  return r;
}
__device__ __forceinline__ uint32_t fma2(uint32_t a, uint32_t b, uint32_t c) {
  uint32_t r;
  asm("fma.rn.bf16x2 %0, %1, %2, %3;" : "=r"(r) : "r"(a), "r"(b), "r"(c));
  return r;
}
__device__ __forceinline__ float ex2(float x) {
  float r;
  asm("ex2.approx.ftz.f32 %0, %1;" : "=f"(r) : "f"(x));
  return r;
}
__device__ __forceinline__ float rcp(float x) {
  float r;
  asm("rcp.approx.ftz.f32 %0, %1;" : "=f"(r) : "f"(x));
  return r;
}
__device__ __forceinline__ float silu_f(float t) { return t * rcp(1.0f + ex2(-1.4426950408889634f * t)); }
__device__ __forceinline__ void lds128(uint32_t a, uint32_t& x, uint32_t& y, uint32_t& z, uint32_t& w) {
  asm volatile("ld.shared.v4.u32 {%0, %1, %2, %3}, [%4];" : "=r"(x), "=r"(y), "=r"(z), "=r"(w) : "r"(a) : "memory");
}
__device__ __forceinline__ void ldsm4(uint32_t a, uint32_t& x, uint32_t& y, uint32_t& z, uint32_t& w) {
  asm volatile("ldmatrix.sync.aligned.m8n8.x4.shared.b16 {%0, %1, %2, %3}, [%4];" : "=r"(x), "=r"(y), "=r"(z), "=r"(w) : "r"(a) : "memory");
}
constexpr uint32_t TAG = 0x10000;
__device__ __forceinline__ void st_gran(uint4* p, uint32_t x, uint32_t y, uint32_t z, uint32_t w) {
  asm volatile("st.relaxed.gpu.global.v4.b32 [%0], {%1, %2, %3, %4};" ::"l"(p), "r"(x), "r"(y), "r"(z), "r"(w) : "memory");
}
__device__ __forceinline__ void ld_gran(const uint4* p, uint32_t& x, uint32_t& y, uint32_t& z, uint32_t& w) {
  asm volatile("ld.relaxed.gpu.global.v4.b32 {%0, %1, %2, %3}, [%4];" : "=r"(x), "=r"(y), "=r"(z), "=r"(w) : "l"(p) : "memory");
}
__device__ __forceinline__ void stsm4(uint32_t a, uint32_t x, uint32_t y, uint32_t z, uint32_t w) {
  asm volatile("stmatrix.sync.aligned.m8n8.x4.shared.b16 [%0], {%1, %2, %3, %4};" ::"r"(a), "r"(x), "r"(y), "r"(z), "r"(w) : "memory");
}
__device__ __forceinline__ void cp16(uint32_t dst, const void* src) {
  asm volatile("cp.async.cg.shared.global [%0], [%1], 16;" ::"r"(dst), "l"(src) : "memory");
}
__device__ __forceinline__ void cp_wait_all() { asm volatile("cp.async.wait_all;" ::: "memory"); }
__device__ __forceinline__ void add_granules(float (&red)[32], const uint32_t (&g)[16]) {
#pragma unroll
  for (int i = 0; i < 16; i++) { red[2 * i] += bf_lo(g[i]); red[2 * i + 1] += bf_hi((i & 3) ? g[i] : g[i] & ~TAG); }
}
__device__ __forceinline__ bool granules_ok(const uint32_t (&g)[16], uint32_t tag) {
  uint32_t a, b;
  asm("lop3.b32 %0, %1, %2, %3, 0x7E;" : "=r"(a) : "r"(g[0]), "r"(g[4]), "r"(tag));
  asm("lop3.b32 %0, %1, %2, %3, 0x7E;" : "=r"(b) : "r"(g[8]), "r"(g[12]), "r"(tag));
  return __all_sync(0xffffffffu, ((a | b) & TAG) == 0);
}
__device__ __forceinline__ unsigned ld_acquire(const unsigned* p) {
  unsigned v;
  asm volatile("ld.acquire.gpu.global.u32 %0, [%1];" : "=r"(v) : "l"(p) : "memory");
  return v;
}
__device__ __forceinline__ unsigned atom_add_acq_rel(unsigned* p) {
  unsigned v;
  asm volatile("atom.acq_rel.gpu.global.add.u32 %0, [%1], 1;" : "=r"(v) : "l"(p) : "memory");
  return v;
}

template <int K0, int K1>
__device__ __forceinline__ void ln_fetch(uint32_t (&xa)[144], uint32_t boxes, uint32_t lo) {
#pragma unroll
  for (int k = K0; k < K1; k++) ldsm4(boxes + (k >> 2) * 8192 + (lo ^ ((k & 3) << 5)), xa[4 * k], xa[4 * k + 1], xa[4 * k + 2], xa[4 * k + 3]);
}
__device__ __forceinline__ void ln_fetch_b(uint32_t (&b)[24], uint32_t& wb, uint32_t ws) {
#pragma unroll
  for (int j = 0; j < 6; j++, wb += ws) ldsm4(wb, b[4 * j], b[4 * j + 1], b[4 * j + 2], b[4 * j + 3]);
}
template <int K0, int K1>
__device__ __forceinline__ void ln_sums(const uint32_t (&xa)[144], float (&sm)[X_NS][4], const uint32_t (&b)[24]) {
#pragma unroll
  for (int k = K0; k < K1; k++)
    hmma_k16(sm[k % X_NS], xa[4 * k], xa[4 * k + 1], xa[4 * k + 2], xa[4 * k + 3], b[2 * (k % 12)], b[2 * (k % 12) + 1]);
}
__device__ __forceinline__ void ln_row(float sum, float sq, float& mean_b, float& rstd) {
  const float mean = sum * (1.0f / DM);
  const uint32_t mv = pack2(mean, fmaxf(sq * (1.0f / DM) - mean * mean, 0.0f));
  mean_b = bf_lo(mv);
  float sd;
  asm("sqrt.approx.f32 %0, %1;" : "=f"(sd) : "f"(bf_lo(pack2(bf_hi(mv) + 1e-5f, 0.f))));
  rstd = rcp(bf_lo(pack2(sd, 0.f)));
}

template <bool ROUTED>
__device__ __forceinline__ uint32_t gate2(uint32_t x2, float mean_b, float rstd, float2 upd = make_float2(0.f, 0.f)) {
  const uint32_t xc = sub2(x2, pack2(mean_b, mean_b));
  uint32_t t = pack2(bf_lo(xc) * rstd, bf_hi(xc) * rstd);
  if (ROUTED) t = pack2(bf_lo(t) + upd.x, bf_hi(t) + upd.y);
  return pack2(silu_f(bf_lo(t)), silu_f(bf_hi(t)));
}

template <int V> struct IC { static constexpr int value = V; };

struct Ctx {
  uint32_t sb;
  uint8_t* sp;
  uint32_t rank;
  Scratch* g;
};

__device__ __forceinline__ bool acquire(const Ctx& cx, uint32_t r, uint32_t n, uint32_t bytes) {
  mbar_wait(cx.sb + SM_EMPTY + 8 * r, (n ^ (r >> 1) ^ 1) & 1);
  __syncwarp();
  const bool e = elect_one();
  if (e) mbar_expect_tx(cx.sb + SM_FULL + 8 * r, bytes);
  return e;
}
__device__ __forceinline__ void load_wq(const Ctx& cx, const CUtensorMap* tmWq, int st, int i, int n0, uint64_t pol) {
  const uint32_t r = st & 3, dst = cx.sb + SM_RING + r * STAGE + cx.rank * 16384, bar = cx.sb + SM_FULL + 8 * r;
  const int k0 = i < 3 ? 128 * i : 128 * i - 64;
  if (acquire(cx, r, st >> 2, i == 2 ? 16384 : 32768)) {
    tma2d_mc(dst, tmWq, n0, k0, bar, pol);
    if (i != 2) tma2d_mc(dst + 8192, tmWq, n0, k0 + 64, bar, pol);
  }
}
__device__ __forceinline__ void attn_producer(const Ctx& cx, int qb, int hs, const CUtensorMap* tmKV, const CUtensorMap* tmWq,
                                              const CUtensorMap* tmWq96, const CUtensorMap* tmWo) {
  const uint32_t full = cx.sb + SM_FULL, ring = cx.sb + SM_RING + cx.rank * 16384;
  const uint64_t last_use = policy_evict_first();
  int st = 0;
#pragma unroll 1
  for (int p = 0; p < 4; p++) {
#pragma unroll 1
    for (int i = 0; i < (p == 2 ? 3 : 5); i++, st++) {
      if (p == 2) {
        if (acquire(cx, st & 3, st >> 2, 24576))
          tma2d_mc(cx.sb + SM_RING + (st & 3) * STAGE + cx.rank * 12288, tmWq96, (hs * 4 + 3) * DH, 192 * i + 96 * cx.rank, full + 8 * (st & 3), last_use);
      } else {
        if (st > 1) load_wq(cx, tmWq, st, i, (hs * 4 + (p ^ (p >> 1))) * DH + cx.rank * 64, last_use);
      }
      if (st == 1 || st == 2) TSP(72 + st)
      if (st == X_PFW) {
#pragma unroll 1
        for (int b = qb < 8; b < 5 - (qb >> 3); b++)
          if (elect_one()) tma2d_prefetch(tmWq, hs * 512 + (b < 4 ? (b ^ (b >> 1)) * DH + (qb & 1) * 64 : qb * 64), b < 4 ? (qb >> 1) * 64 : 512);
      }
      if (st == 8 && qb < 8 && elect_one()) tma2d_prefetch(tmKV + ((qb >> 1) & 1), cx.rank * 64, hs * 2 * SEQ + (qb >> 2) * 96);
    }
  }
  uint32_t r = 2, n = 4;
  int row = hs * 2 * SEQ, rows = 96;
  const CUtensorMap* tm = tmKV + 2;
#pragma unroll 1
  for (int u = 0; u < NST_KV; u++) {
    if (acquire(cx, r, n, rows * 256)) {
      tma2d_mc(ring + r * STAGE, tm, cx.rank * 64, row, full + 8 * r, last_use);
      if (((u ^ (qb >> 1)) & 7) == 0 && u < NST_KV - 4) tma2d_prefetch(tmKV + (u & 1), cx.rank * 64, row + 208);
      if ((unsigned)(u - 32) < 36 && (u & 15) == qb) tma2d_prefetch(tmWo, ((u - 32) >> 2) * 64, hs * 512 + (u & 3) * 128);
    }
    if (++r == 4) { r = 1; n++; }
    if (u & 1) row += rows;
    const bool big = (unsigned)(u - 9) < 56;
    rows = big ? 112 : 96;
    tm = tmKV + (~u & 1) + (big ? 0 : 2);
  }
#pragma unroll 1
  for (int u = 0; u < NST_O; u++) {
    const int s = u >> 1;
    const int blk = s == 0 ? 8 : ((hs + s) & 7);
    r = (0x87 >> (2 * (u & 3))) & 3;
    if (acquire(cx, r, (u >> 2) ^ ~u, 32768))
      tma2d_mc(ring + r * STAGE, tmWo, blk * 64, hs * 512 + ((u & 1) + cx.rank * 2) * 128, full + 8 * r, last_use);
  }
}

__device__ __forceinline__ void sq_publish(const Ctx& cx, int qb, int hs, int j, int lane) {
  if (j == 2 && lane == 0) {
    const unsigned e = cx.g->launch[hs * 16 + qb]++;
    *(uint2*)(cx.sp + SM_TAG) = make_uint2((~e & 1) * TAG, e);
  }
  const int row = (hs & 3) * 16 + (lane >> 1);
  uint32_t a = cx.sb + SM_X + (hs >> 2) * 73728 + j * 8192 + row * 128 + (((lane & 1) ^ (row & 7)) << 4);
  float s0 = 0.f, s1 = 0.f;
#pragma unroll 1
  for (int b = 0; b < 6; b++) {
    if (b == (hs < 4 ? 4 : 0)) {
      const int n = 224 + (__float_as_uint(s1) & blockIdx.y);
      if (j == 1) {
        bar_sync(BAR_XREL, n);
        if (lane < 4) asm volatile("mbarrier.arrive.shared::cluster.b64 _, [%0], 2;" ::"r"(mapa(cx.sb + SM_EMPTY + 16 + 8 * (lane >> 1), lane & 1)) : "memory");
      } else {
        bar_arrive(BAR_XREL, n);
      }
      __syncwarp();
      if (hs == 8) return;
    }
    if (!(b & 1)) mbar_wait(cx.sb + SM_XFULL + 32 * (hs >> 2) + 4 * b, 0);
    uint32_t v[8];
    lds128(a, v[0], v[1], v[2], v[3]);
    lds128(a ^ 32, v[4], v[5], v[6], v[7]);
    a = (a ^ 64) + (b & 1) * 24576;
#pragma unroll
    for (int i = 0; i < 8; i++) { s0 = fmaf(bf_lo(v[i]), bf_lo(v[i]), s0); s1 = fmaf(bf_hi(v[i]), bf_hi(v[i]), s1); }
  }
  s0 += s1;
  s0 += __shfl_xor_sync(0xffffffffu, s0, 1);
  float* part = (float*)(cx.sp + SM_STATS) + (lane >> 1) * 2;
  if (j < 2) {
    part[32 * j] = s0;
    bar_arrive(BAR_HELPER, 96);
  } else {
    bar_sync(BAR_HELPER, 96);
    TSP(68)
    if (!(lane & 1))
      asm volatile("st.relaxed.gpu.global.v2.b32 [%0], {%1, %2};" ::"l"(cx.g->sq + qb * 128 + hs * 16 + (lane >> 1)),
                   "r"(__float_as_uint((part[0] + part[32]) + s0)), "r"(*(const uint32_t*)(cx.sp + SM_TAG + 4) + 1) : "memory");
  }
}
__device__ __forceinline__ void sq_collect(const Ctx& cx, int qb, int lane) {
  const uint32_t e1 = *(const uint32_t*)(cx.sp + SM_TAG + 4) + 1;
#pragma unroll 1
  for (int n = 0; n < (1 << 16); n++) {
    __nanosleep(X_SQS);
    uint32_t bad = 0;
#pragma unroll
    for (int i = 0; i < 2; i++) {
      uint32_t a, t0, b, t1;
      ld_gran((const uint4*)(cx.g->sq + qb * 128) + i * 32 + lane, a, t0, b, t1);
      *(uint32_t*)(cx.sp + SM_STATS + (i * 32 + lane) * 16 + 4) = a;
      *(uint32_t*)(cx.sp + SM_STATS + (i * 32 + lane) * 16 + 12) = b;
      bad |= (t0 ^ e1) | (t1 ^ e1);
    }
    if (__all_sync(0xffffffffu, bad == 0)) break;
  }
  __syncwarp();
  if (lane == 0) mbar_arrive(cx.sb + SM_BAR_SQ);
  TSP(69)
}
__device__ __forceinline__ void attn_gate(const Ctx& cx, int qb, int hs, int t, const __nv_bfloat16* x) {
  uint4 nx = *(const uint4*)(x + (size_t)(qb * 128 + (t >> 3)) * DM + hs * 64 + (t & 7) * 8);
  float wsum = 0.f;
  if (t < 32) {
    mbar_wait(cx.sb + SM_BAR_W, 0);
#pragma unroll 3
    for (int i = 0; i < 9; i++) {
      const uint32_t w = *(const uint32_t*)(cx.sp + SM_WR + i * 128 + t * 4);
      wsum += bf_lo(w) + bf_hi(w);
    }
#pragma unroll
    for (int i = 1; i < 32; i *= 2) wsum += __shfl_xor_sync(0xffffffffu, wsum, i);
  }
  bar_sync(BAR_GATE, 352);
  if (t < 16) {
    const float2 st = *(const float2*)(cx.sp + SM_STATS + 8 * (hs * 16 + t));
    const int row = qb * 128 + hs * 16 + t;
    const uint32_t b = pack2(0.f, fmaf(-st.x, wsum, *(const float*)(cx.sp + SM_RAW + 4 * t)) * st.y);
    st_gran(cx.g->stats + row, __float_as_uint(st.x), __float_as_uint(st.y), (b ^ ((int)b < 0 ? 0xFFFF0000u : 0x80000000u)) | (0xFFFF - row),
            *(const uint32_t*)(cx.sp + SM_TAG + 4) + 1);
  }
#pragma unroll 1
  for (int ch = t; ch < 1152; ch += 96) {
    const uint4 v = nx;
    const int n = ch + 96;
    if (n < 1152) nx = *(const uint4*)(x + (size_t)(qb * 128 + (n < 1024 ? n >> 3 : hs * 16 + ((n - 1024) >> 3))) * DM + (n < 1024 ? hs * 64 : 512) + (t & 7) * 8);
    const int lr = ch < 1024 ? ch >> 3 : hs * 16 + ((ch - 1024) >> 3);
    const float2 st = *(const float2*)(cx.sp + SM_STATS + 8 * lr);
    cx.g->gate[blockIdx.x * 1152 + (ch ^ ((ch >> 3) & 7))] =
        make_uint4(gate2<false>(v.x, st.x, st.y), gate2<false>(v.y, st.x, st.y), gate2<false>(v.z, st.x, st.y), gate2<false>(v.w, st.x, st.y));
  }
}

constexpr uint32_t SM_XO = SM_SLOT, SM_GO = SM_SLOT + STAGE, SM_P8 = SM_SLOT + 2 * STAGE;
__device__ __forceinline__ void attn_helper(const Ctx& cx, int qb, int hs, int lane, const CUtensorMap* tmX16) {
  const unsigned e = *(const uint32_t*)(cx.sp + SM_TAG + 4);
  bar_sync(BAR_HELPER, 64);
  bool todo = lane < 2;
#pragma unroll 1
  for (int n = 0; __any_sync(0xffffffffu, todo); n++) {
    if (todo && (ld_acquire(&cx.g->qflag[(qb * 4 + (hs >> 1)) * 2 + lane]) == e + 1 || n == (1 << 16))) {
      asm volatile("fence.proxy.async.global;" ::: "memory");
      mbar_expect_tx(cx.sb + SM_BAR_Q + 8 * lane, 8192);
      bulk_load(cx.sb + SM_SLOT + 2 * STAGE + lane * 16384 + 8192, cx.g->q + ((qb * 8 + hs) * 2 + lane) * 512, 8192, cx.sb + SM_BAR_Q + 8 * lane);
      todo = false;
    }
  }
  const uint32_t tag = (~e & 1) * TAG;
  const uint4* src = cx.g->part + (size_t)((qb * 64 + 56) * 2 + (hs >> 2)) * 4 * 128 + (hs & 3) * 32 + lane;
  const uint32_t stg = cx.sb + SM_P8 + lane * 16;
  bar_sync(BAR_OA, 352);
  asm volatile("fence.proxy.async.global;" ::: "memory");
  if (lane == 0) {
    mbar_expect_tx(cx.sb + SM_BAR_MISC, 2 * 18432);
    bulk_load(cx.sb + SM_GO, cx.g->gate + blockIdx.x * 1152, 18432, cx.sb + SM_BAR_MISC);
#pragma unroll 1
    for (int i = 0; i < 9; i++)
      tma2d(cx.sb + SM_XO + i * 2048, tmX16, i < 8 ? hs * 64 : 512, qb * 128 + (i < 8 ? i : hs) * 16, cx.sb + SM_BAR_MISC);
  }
#pragma unroll 1
  for (int n = 0; n < (1 << 16); n++) {
    __nanosleep(n ? 500 : 2000);
    uint32_t a, b, d, t;
    ld_gran(src - lane + (lane & 7) * (2 * 4 * 128) + 3 * 128 + 31, a, b, d, t);
    if (__all_sync(0xffffffffu, (a & TAG) == tag)) break;
  }
#pragma unroll 1
  for (int n = 0; n < (1 << 16); n++) {
#pragma unroll 1
    for (int i = 0; i < 8; i++) {
#pragma unroll
      for (int g = 0; g < 4; g++) cp16(stg + (i * 4 + g) * 512, src + i * (2 * 4 * 128) + g * 128);
    }
    cp_wait_all();
    uint32_t bad = 0;
#pragma unroll 4
    for (int i = 0; i < 32; i++) bad |= *(const volatile uint32_t*)(cx.sp + SM_P8 + lane * 16 + i * 512) ^ tag;
    if (__all_sync(0xffffffffu, (bad & TAG) == 0)) break;
  }
#pragma unroll 1
  for (int n = 0; n < (1 << 16) && ld_acquire(&cx.g->ycnt) != 4 * (e + 1); n++) __nanosleep(200);
  const int2 sel = __ldcg(&cx.g->sel[lane & 7]);
  const int lr = sel.x - qb * 128;
  uint32_t m = __ballot_sync(0xffffffffu, lane < 16 && ((lane & 8) ? (lr >> 4) == hs : (lr >> 7) == 0));
  mbar_wait(cx.sb + SM_BAR_MISC, 0);
#pragma unroll 1
  for (; m; m &= m - 1) {
    const int i = __ffs(m) - 1, row = __shfl_sync(0xffffffffu, lr, i);
    const float rs = __int_as_float(__shfl_sync(0xffffffffu, sel.y, i));
    const float* p = cx.g->ypart + (i & 7) * DM + (i < 8 ? hs * 64 : 512) + 2 * lane;
    const float2 a = __ldcg((const float2*)p), b = __ldcg((const float2*)(p + TOPC * DM)), c = __ldcg((const float2*)(p + 2 * TOPC * DM)),
                 d = __ldcg((const float2*)(p + 3 * TOPC * DM));
    const uint32_t y = pack2((a.x + b.x) + (c.x + d.x), (a.y + b.y) + (c.y + d.y));
    const uint32_t u = pack2(bf_lo(y) * rs, bf_hi(y) * rs);
    const float2 st = *(const float2*)(cx.sp + SM_STATS + 8 * row);
    const int o = (i < 8 ? row : 128 + (row & 15)) * 128 + ((lane * 4) ^ ((row & 7) << 4));
    *(uint32_t*)(cx.sp + SM_GO + o) = gate2<true>(*(const uint32_t*)(cx.sp + SM_XO + o), st.x, st.y, make_float2(bf_lo(u), bf_hi(u)));
  }
  __syncwarp();
  if (lane == 0) mbar_arrive(cx.sb + SM_BAR_XG);
}
__device__ __forceinline__ void attn_finish8(const Ctx& cx, int qb, int hs, int hw, int lane, __nv_bfloat16* out) {
  bar_sync(BAR_GATE, 96);
#pragma unroll 1
  for (int g = hw; g < 4; g += 3) {
    float acc[8] = {0.f, 0.f, 0.f, 0.f, 0.f, 0.f, 0.f, 0.f};
#pragma unroll 2
    for (int sidx = 0; sidx < 8; sidx++) {
      uint32_t a, b, d, t;
      lds128(cx.sb + SM_P8 + lane * 16 + (sidx * 4 + g) * 512, a, b, d, t);
      acc[0] += bf_lo(a); acc[1] += bf_hi(a & ~TAG); acc[2] += bf_lo(b); acc[3] += bf_hi(b);
      acc[4] += bf_lo(d); acc[5] += bf_hi(d); acc[6] += bf_lo(t); acc[7] += bf_hi(t);
    }
#pragma unroll
    for (int j = 0; j < 4; j++) {
      const int o = (128 + (lane >> 2) + (j & 1) * 8) * 128 + (((2 * g + (j >> 1)) ^ (lane >> 2)) << 4) + (lane & 3) * 4;
      uint32_t* xp = (uint32_t*)(cx.sp + SM_XO + o);
      *xp = fma2(pack2(acc[2 * j], acc[2 * j + 1]), *(const uint32_t*)(cx.sp + SM_GO + o), *xp);
    }
  }
  bar_sync(BAR_GATE, 96);
#pragma unroll 1
  for (int ch = threadIdx.x - 32; ch < 128; ch += 96)
    *(uint4*)(out + (size_t)(qb * 128 + hs * 16 + (ch >> 3)) * DM + 512 + (ch & 7) * 8) =
        *(const uint4*)(cx.sp + SM_XO + 16384 + (ch ^ ((ch >> 3) & 7)) * 16);
}

__device__ __forceinline__ void ffn_producer(const Ctx& cx, int f, const CUtensorMap* tmWq, const CUtensorMap* tmG,
                                             const CUtensorMap* tmU, const CUtensorMap* tmD) {
  uint64_t keep;
  asm("createpolicy.fractional.L2::evict_normal.b64 %0, 1.0;" : "=l"(keep));
  int st = 0;
#pragma unroll 1
  for (int p = 0; p < 16; p++) {
#pragma unroll 1
    for (int i = 0; i < 5; i++, st++) if (st > 1) load_wq(cx, tmWq, st, i, ((2 * (p & 3) + cx.rank) * 4 + 3) * DH + 64, keep);
  }
  const uint32_t full = cx.sb + SM_FFULL, empty = cx.sb + SM_FEMPTY;
  int pair = 0, u = 0;
#pragma unroll 1
  for (st = 0; st < 14 * 12; st++) {
    const uint32_t sl = st & 7;
    const int unit = pair * 2 + (u & 1), k = u >> 1, k3 = k >= 3 ? k - 3 : k;
    if (unit < 27) {
      mbar_wait(empty + 8 * sl, (st >> 3) & 1);
      __syncwarp();
      if (elect_one()) {
        mbar_expect_tx(full + 8 * sl, FSTAGE);
        if (pair < 9) tma2d_stream(cx.sb + sl * FSTAGE, k < 3 ? tmG : tmU, f * 1152 + unit * 64, k3 * 192, full + 8 * sl);
        else tma2d_stream(cx.sb + sl * FSTAGE, tmD, (unit - 18) * 64, f * 1152 + k * 192, full + 8 * sl);
      }
    }
    if (++u == 12) { u = 0; pair++; }
  }
}
__device__ __forceinline__ void load_x1(uint32_t dst, const CUtensorMap* tmX64, int row, int box, int n, uint32_t bar) {
  mbar_expect_tx(bar, n * 8192);
#pragma unroll 1
  for (int i = 0; i < n; i++) tma2d(dst + i * 8192, tmX64, (box + i) * 64, row, bar);
}
__device__ __forceinline__ void ffn_publish(const Ctx& cx, int f, int w, int lane, const CUtensorMap* tmX64) {
  const uint32_t xs = cx.sb + SM_SLOT + w * 49152, xf = cx.sb + SM_XFULL + w * 32;
#pragma unroll 1
  for (int n = 0; n < 16; n++) {
    const int p = n & 3, row = (f + (n & 12) + 4) * 128 + w * 64;
    bar_sync(BAR_QS + w, 160);
    const uint32_t e1 = *(const uint32_t*)(cx.sp + SM_TAG + 4) + 1;
    if (lane == 0) {
#pragma unroll
      for (int i = 0; i < 2; i++)
        asm volatile("cp.async.bulk.global.shared::cta.bulk_group [%0], [%1], 8192;"
                     ::"l"(cx.g->q + (((f + (n & 12)) * 8 + 2 * p + i) * 2 + w) * 512), "r"(xs + 32768 + i * 8192) : "memory");
      asm volatile("cp.async.bulk.commit_group;" ::: "memory");
      if (n < 12 && (p == 0 || p == 3)) load_x1(xs, tmX64, row, p ? 4 : 0, 4, xf + (p ? 8 : 0));
      asm volatile("cp.async.bulk.wait_group.read 0;" ::: "memory");
      if (n < 12 && p == 3) load_x1(xs + 32768, tmX64, row, 8, 1, xf + 16);
      asm volatile("cp.async.bulk.wait_group 0;\nfence.proxy.async.global;" ::: "memory");
      asm volatile("st.release.gpu.global.u32 [%0], %1;" ::"l"(&cx.g->qflag[((f + (n & 12)) * 4 + p) * 2 + w]), "r"(e1) : "memory");
    }
    __syncwarp();
    if (n < 12 && p == 1) {
#pragma unroll 1
      for (int i = 0, k = 0; i < 64 && k < (1 << 16); k++) {
        uint32_t m, r, z, t;
        ld_gran(cx.g->stats + row + i + lane, m, r, z, t);
        *(uint2*)(cx.sp + SM_STATS + 8 * (w * 64 + i + lane)) = make_uint2(m, r);
        if (__all_sync(0xffffffffu, t == e1)) i += 32;
      }
    }
    bar_arrive(BAR_QF + w, 160);
  }
}

__device__ __forceinline__ void ffn_consumer(const Ctx& cx, int f, int wg, int cw, int lane, const __nv_bfloat16* x) {
  const int r = lane >> 2, c = lane & 3, tid = cw * 32 + lane;
  const uint32_t full = cx.sb + SM_FFULL, empty = cx.sb + SM_FEMPTY;
  const bool signaller = (tid & 127) == 0;
  prof(wg, 8);
  const unsigned e = *(const uint32_t*)(cx.sp + SM_TAG + 4);
  uint32_t key[8];
#pragma unroll 1
  for (int n = 0; n < (1 << 16); n++) {
    uint32_t bad = 0;
#pragma unroll
    for (int i = 0; i < 8; i++) {
      uint32_t t;
      asm volatile("ld.relaxed.gpu.global.v2.b32 {%0, %1}, [%2];" : "=r"(key[i]), "=r"(t) : "l"(&cx.g->stats[i * 256 + tid].z) : "memory");
      bad |= t ^ (e + 1);
    }
    if (__all_sync(0xffffffffu, bad == 0)) break;
  }
  bar_sync(BAR_QF + wg, 160);
  bar_sync(3, 256);
  if (tid < 8) mbar_arrive(empty + 8 * tid);
  prof(wg, 9);
  int mysel = 0;
#pragma unroll 1
  for (int k = 0; k < TOPC; k++) {
    uint32_t m = key[0];
#pragma unroll
    for (int i = 1; i < 8; i++) m = max(m, key[i]);
    m = __reduce_max_sync(0xffffffffu, m);
    uint32_t* tk = (uint32_t*)(cx.sp + SM_TOPK) + (k & 1) * 8;
    if (lane == 0) tk[cw] = m;
    bar_sync(3, 256);
    m = __reduce_max_sync(0xffffffffu, tk[lane & 7]);
#pragma unroll
    for (int i = 0; i < 8; i++) if (key[i] == m) key[i] = 0;
    if (k == cw) mysel = 0xFFFF - (int)(m & 0xFFFF);
  }
  {
    const float4 st = __ldcg((const float4*)&cx.g->stats[mysel]);
    const uint32_t mm = pack2(st.x, st.x);
#pragma unroll 3
    for (int i = 0; i < 9; i++) {
      const uint32_t t = sub2(*(const uint32_t*)(x + (size_t)mysel * DM + i * 64 + 2 * lane), mm);
      *(uint32_t*)(cx.sp + SM_XSEL + i * 1024 + cw * 128 + (((lane >> 2) ^ cw) << 4) + (lane & 3) * 4) =
          pack2(bf_lo(t) * st.y, bf_hi(t) * st.y);
    }
    const uint32_t k = __float_as_uint(st.z);
    const float score = bf_hi(k ^ ((int)k < 0 ? 0x80000000u : 0xFFFF0000u));
    if (lane == 0 && f == 0) cx.g->sel[cw] = make_int2(mysel, __float_as_int(bfr(rcp(1.0f + ex2(-1.4426950408889634f * score)))));
  }
  asm volatile("fence.proxy.async.shared::cta;" ::: "memory");
  bar_sync(3, 256);
  prof(wg, 10);
  auto run = [&](float (&acc)[4], int st, int n, uint32_t b) {
#pragma unroll 1
    for (int u = 0; u < n; u++, st += 2, b += 3072) {
      const uint32_t sl = st & 7;
      mbar_wait(full + 8 * sl, (st >> 3) & 1);
      wg_fence();
      const uint64_t da = mkdesc(cx.sb + sl * FSTAGE, 16), db = mkdesc(b, 16);
#pragma unroll
      for (int k = 0; k < 12; k++) mma_n8(acc, da + k * 128, db + (k >> 2) * 64 + (k & 3) * 2, u > 0 || k > 0);
      wg_commit();
      wg_wait<0>();
      if (signaller) mbar_arrive(empty + 8 * sl);
    }
    pin(acc);
  };
#pragma unroll 1
  for (int unit = wg; unit < 27; unit += 2) {
    if (unit >> 1 == 9) {
      asm volatile("fence.proxy.async.shared::cta;" ::: "memory");
      bar_sync(3, 256);
      prof(wg, 11);
    }
    const bool gu = unit < 18;
    float a0[4], a1[4];
#pragma unroll 1
    for (int m = 0; m < (gu ? 2 : 1); m++) {
      run(a1, (unit >> 1) * 12 + m * 6 + wg, gu ? 3 : 6, cx.sb + (gu ? SM_XSEL : SM_H));
      if (m == 0) { a0[0] = a1[0]; a0[1] = a1[1]; a0[2] = a1[2]; a0[3] = a1[3]; }
    }
    float u0 = a1[0], u1 = a1[1];
#pragma unroll 1
    for (int i = 0; i < 2; i++) {
      const int fl = (cw & 3) * 16 + r + i * 8;
      if (gu) {
        const uint32_t g = pack2(a0[0], a0[1]);
        const uint32_t h = fma2(pack2(silu_f(bf_lo(g)), silu_f(bf_hi(g))), pack2(u0, u1), 0x80008000u);
        uint8_t* hp = cx.sp + SM_H + unit * 1024 + c * 256 + (fl & 7) * 2;
        *(uint16_t*)(hp + (((fl >> 3) ^ (2 * c)) << 4)) = (uint16_t)h;
        *(uint16_t*)(hp + 128 + (((fl >> 3) ^ (2 * c + 1)) << 4)) = (uint16_t)(h >> 16);
      } else {
        float* yp = cx.g->ypart + (f * TOPC + 2 * c) * DM + (unit - 18) * 64 + fl;
        yp[0] = u0;
        yp[DM] = u1;
      }
      a0[0] = a0[2]; a0[1] = a0[3]; u0 = a1[2]; u1 = a1[3];
    }
  }
  prof(wg, 12);
  bar_sync(3, 256);
  if (tid == 0) atom_add_acq_rel(&cx.g->ycnt);
  prof(wg, 13);
}

constexpr float SUM_HI = 1.8446744e19f, SUM_LO = 9.0949470e-13f;

template <int LO, int HI, int N>
__device__ __forceinline__ void softmax_exp(float (&s)[N]) {
#pragma unroll
  for (int i = LO; i < HI; i++) s[i] = ex2(s[i]);
}
__device__ __forceinline__ void sum_tree(const uint32_t (&pf)[28], bool big, uint32_t& h0, uint32_t& h1) {
  uint32_t t0 = add2(add2(pf[16], pf[18]), add2(pf[20], pf[22])), t1 = add2(add2(pf[17], pf[19]), add2(pf[21], pf[23]));
  if (big) { t0 = add2(t0, add2(pf[24], pf[26])); t1 = add2(t1, add2(pf[25], pf[27])); }
  h0 = add2(add2(add2(add2(pf[0], pf[2]), add2(pf[4], pf[6])), add2(add2(pf[8], pf[10]), add2(pf[12], pf[14]))), t0);
  h1 = add2(add2(add2(add2(pf[1], pf[3]), add2(pf[5], pf[7])), add2(add2(pf[9], pf[11]), add2(pf[13], pf[15]))), t1);
}
__device__ __forceinline__ void exact_attention(float (&o)[16], float& l0, float& l1, const uint32_t (&q)[32], const __nv_bfloat16* kp,
                                                const __nv_bfloat16* vp) {
  float m0 = -3.0e38f, m1 = -3.0e38f;
  l0 = l1 = 0.f;
#pragma unroll
  for (int i = 0; i < 16; i++) o[i] = 0.f;
#pragma unroll 1
  for (int key = 0; key < SEQ; key += 8, kp += 8 * DH, vp += 8 * DH) {
    float d[4] = {0.f, 0.f, 0.f, 0.f};
#pragma unroll
    for (int k = 0; k < 8; k++)
      hmma_k16(d, q[4 * k], q[4 * k + 1], q[4 * k + 2], q[4 * k + 3], *(const uint32_t*)(kp + k * 16), *(const uint32_t*)(kp + k * 16 + 8));
    float x0 = fmaxf(d[0], d[1]), x1 = fmaxf(d[2], d[3]);
    x0 = fmaxf(x0, __shfl_xor_sync(0xffffffffu, x0, 1));
    x1 = fmaxf(x1, __shfl_xor_sync(0xffffffffu, x1, 1));
    x0 = fmaxf(fmaxf(x0, __shfl_xor_sync(0xffffffffu, x0, 2)), m0);
    x1 = fmaxf(fmaxf(x1, __shfl_xor_sync(0xffffffffu, x1, 2)), m1);
    const float sc0 = ex2(m0 - x0), sc1 = ex2(m1 - x1);
    m0 = x0; m1 = x1;
    const uint32_t p0 = pack2(ex2(d[0] - m0), ex2(d[1] - m0)), p1 = pack2(ex2(d[2] - m1), ex2(d[3] - m1));
    l0 = fmaf(l0, sc0, bf_lo(p0) + bf_hi(p0));
    l1 = fmaf(l1, sc1, bf_lo(p1) + bf_hi(p1));
#pragma unroll
    for (int nb = 0; nb < 4; nb++) {
      uint32_t b;
      asm("movmatrix.sync.aligned.m8n8.trans.b16 %0, %1;" : "=r"(b) : "r"(*(const uint32_t*)(vp + nb * 8)));
      o[4 * nb] *= sc0; o[4 * nb + 1] *= sc0; o[4 * nb + 2] *= sc1; o[4 * nb + 3] *= sc1;
      asm volatile("mma.sync.aligned.m16n8k8.row.col.f32.bf16.bf16.f32 {%0, %1, %2, %3}, {%4, %5}, {%6}, {%0, %1, %2, %3};"
                   : "+f"(o[4 * nb]), "+f"(o[4 * nb + 1]), "+f"(o[4 * nb + 2]), "+f"(o[4 * nb + 3]) : "r"(p0), "r"(p1), "r"(b));
    }
  }
}
__device__ __forceinline__ bool inv_sums(float l0, float l1, float& i0, float& i1) {
  l0 += __shfl_xor_sync(0xffffffffu, l0, 1); l1 += __shfl_xor_sync(0xffffffffu, l1, 1);
  l0 += __shfl_xor_sync(0xffffffffu, l0, 2); l1 += __shfl_xor_sync(0xffffffffu, l1, 2);
  i0 = rcp(l0);
  i1 = rcp(l1);
  return !(l0 + l1 <= SUM_HI) | (fminf(l0, l1) < SUM_LO);
}
template <int LO, int HI, int N>
__device__ __forceinline__ void park(uint32_t a, const float (&o)[N], float i0, float i1, bool on = true) {
#pragma unroll
  for (int i = LO; i < HI; i++)
    asm volatile("{\n.reg .pred p;\nsetp.ne.u32 p, %5, 0;\n@p stmatrix.sync.aligned.m8n8.x4.shared.b16 [%0], {%1, %2, %3, %4};\n}"
                 ::"r"(a + i * 2048), "r"(pack2(o[8 * i] * i0, o[8 * i + 1] * i0)), "r"(pack2(o[8 * i + 2] * i1, o[8 * i + 3] * i1)),
                 "r"(pack2(o[8 * i + 4] * i0, o[8 * i + 5] * i0)), "r"(pack2(o[8 * i + 6] * i1, o[8 * i + 7] * i1)), "r"((uint32_t)on) : "memory");
}

template <int I, int NP, int E0, int N, int NS>
__device__ __forceinline__ void exp_park(float (&s)[NS], uint32_t a, const float (&o)[64], float i0, float i1, bool on, int id) {
  if constexpr (I < NP) {
    constexpr int E1 = E0 + (N - E0) * X_PG / (NP - I);
    softmax_exp<E0, E1>(s);
    park<I, I + X_PG>(a, o, i0, i1, on);
    if (I + X_PG < NP) {
#pragma unroll
      for (int i = E0; i < E1; i++) asm volatile("" : "+f"(s[i])::"memory");
      block_fence(id + I);
    }
    exp_park<I + X_PG, NP, E1, N>(s, a, o, i0, i1, on, id);
  }
}

__device__ __forceinline__ void attn_consumer(const Ctx& cx, bool hlp, int qb, int hs, int wg, int cw, int lane, const __nv_bfloat16* x,
                                              const __nv_bfloat16* kc, const __nv_bfloat16* vc, __nv_bfloat16* out) {
  const uint32_t full = cx.sb + SM_FULL;
  const uint32_t ring = cx.sb + SM_RING;
  const uint32_t qwg = ring + wg * 16384;
  auto qlane = [&](int l) { return qwg + (cw & 3) * 256 + (l >> 4) * 1024 + (l & 15) * 16; };
  const bool signaller = lane == 0 && (cw & 3) < 2;
  const int my_turn = 1 + wg, other_turn = 2 - wg;
  const uint32_t empty_c = mapa(cx.sb + SM_EMPTY, cw & 1);

  float oA[64], oB[64], i0, i1;
  uint32_t xl[32];
  {
    const int r = lane >> 2, c = lane & 3;
    const int lr0 = cw * 16 + r;
    uint32_t xa[144];
    uint32_t mm0, mm1;
    float rstd0, rstd1, sq0 = 0.f, sq1 = 0.f;
    const uint32_t xf = cx.sb + SM_XFULL + wg * 32, xs = cx.sb + SM_SLOT + wg * 49152;
    auto lo_of = [&](int l) { return ((cw & 3) * 16 + (l & 15)) * 128 + (((l >> 4) ^ (l & 7)) << 4); };
    prof(wg, 0);
    {
      const uint32_t lo = lo_of(lane);
      const uint32_t xb = cx.sb + SM_X + wg * 73728;
      float sm[X_NS][4] = {};
      const uint32_t ws = (lane & 7) == 1 ? 64 : 0;
      uint32_t wb = cx.sb + (ws ? SM_WR + (lane >> 3) * 16 : SM_ONES);
      uint32_t b0[24], b1[24], b2[24];
      TS4(1)
      mbar_wait(cx.sb + SM_BAR_W, 0);
      if (X_LN == 0) {
        ln_fetch_b(b0, wb, ws);
        ln_fetch_b(b1, wb, ws);
        ln_fetch_b(b2, wb, ws);
      }
      mbar_wait(xf, 0);
      TS4(2)
      ln_fetch<0, 12>(xa, xb, lo);
      if (X_LN == 1) {
        ln_fetch_b(b0, wb, ws);
        ln_fetch_b(b1, wb, ws);
        ln_fetch_b(b2, wb, ws);
      }
      ln_sums<0, 12>(xa, sm, b0);
      mbar_wait(xf + 8, 0);
      TS4(3)
      ln_fetch<12, 24>(xa, xb, lo);
      if (wg == 0) {
        bar_arrive(BAR_XREL + (xa[95] & blockIdx.y), 224);
      }
      ln_sums<12, 24>(xa, sm, b1);

      mbar_wait(xf + 16, 0);
      TS4(4)
      prof(wg, 1);
      ln_fetch<24, 36>(xa, xb, lo);
      ln_sums<24, 36>(xa, sm, b2);
#pragma unroll
      for (int i = 0; i < 4; i++) sm[0][i] = X_NS == 2 ? sm[0][i] + sm[1][i] : X_NS == 3 ? sm[0][i] + sm[1][i] + sm[2][i] : (sm[0][i] + sm[1][i]) + (sm[2][i] + sm[X_NS - 1][i]);
      if (cw == hs && c == 0) {
        *(float*)(cx.sp + SM_RAW + 4 * r) = sm[0][1];
        *(float*)(cx.sp + SM_RAW + 4 * r + 32) = sm[0][3];
      }
      rstd0 = sm[0][0];
      rstd1 = sm[0][2];
      mm0 = pack2(rstd0 * (1.0f / DM), rstd0 * (1.0f / DM));
      mm1 = pack2(rstd1 * (1.0f / DM), rstd1 * (1.0f / DM));
    }
#pragma unroll
    for (int i = 0; i < 16; i++) { xa[2 * i] = sub2(xa[2 * i], mm0); xa[2 * i + 1] = sub2(xa[2 * i + 1], mm1); }
    pin(xa);
    prof(wg, 2);
    TS4(5)

    float (&acc)[64] = oB;
    int st0 = 0;
#pragma unroll 1
    for (int n = 0; n < 16; n++) {
      const int p = n & 3, rb = n >> 2;
      const bool last = p == 3 && !hlp;
#pragma unroll
      for (int i = 0; i < 5; i++) {
        if (i == 4 && last) {
          wg_wait<1>();
          if (signaller && wg) mbar_arrive_cluster(empty_c + 8 * 3);
          wg_wait<0>();
          pin(acc);
          prof(wg, 6);
#pragma unroll
          for (int j = 0; j < 32; j++) xl[j] = xa[112 + j];
          i0 = rstd0;
          i1 = rstd1;
          goto attention;
        }
        const int st = st0 + i;
        const uint32_t sl = st & 3, slp = (st - 1) & 3;
        mbar_wait(full + 8 * sl, (st >> 2) & 1);
        TS4(8 + 2 * (p * 5 + i))
        const bool join = wg && last;
        if ((X_P0 ? (i || st0 + wg) : st0) && i != (wg ? 4 : 1) && !(join && i == 3)) bar_sync(my_turn, 256);
        wg_fence();
        const uint64_t db = mkdesc(ring + sl * STAGE, 16384);
        const int kb0 = i < 3 ? 8 * i : 8 * i - 4;
#pragma unroll
        for (int k = 0; k < (i == 2 ? 4 : 8); k++) {
          const int kb = kb0 + k;
          mma_n128t(acc, xa[4 * kb], xa[4 * kb + 1], xa[4 * kb + 2], xa[4 * kb + 3], db + k * 128, kb > 0);
        }
        wg_commit();
        TS4(9 + 2 * (p * 5 + i))
        if (wg ? (i == 4 ? st0 < 75 : ((X_P0 || st0) && (i < 2 || i == (join ? 3 : 2)))) : ((X_P0 || st0) && i)) bar_arrive(other_turn, 256);
        if (p == 0 && i < 4) {
          if (i == 1 && rb) {
            mbar_wait(xf + 8, rb & 1);
            mbar_wait(xf + 16, rb & 1);
            ln_fetch<16, 36>(xa, xs - 32768, lo_of(fresh_lane()));
          }
#pragma unroll
          for (int j = 0; j < 72; j++)
            if (j >= 2 * (i < 2 ? 8 * i + 8 : 8 * i + 4) && j < 2 * (i == 0 ? 16 : 8 * i + 12)) {
              xa[2 * j] = sub2(xa[2 * j], mm0);
              xa[2 * j + 1] = sub2(xa[2 * j + 1], mm1);
            }
          pin(xa);
        }
        if (i == X_SQI && n == 0) {
          mbar_wait(cx.sb + SM_BAR_SQ, 0);
          float2* sp = (float2*)(cx.sp + SM_STATS) + lr0;
          float mean0, mean1;
          ln_row(rstd0, sp[0].y, mean0, rstd0);
          ln_row(rstd1, sp[8].y, mean1, rstd1);
          __syncwarp();
          if (c == 0) {
            sp[0] = make_float2(mean0, rstd0);
            sp[8] = make_float2(mean1, rstd1);
          }
          *((uint32_t*)(cx.sp + SM_COLD) + wg) = 0;
          if (!hlp) bar_arrive(BAR_GATE, 352);
          rstd0 *= SM_SCALE_LOG2;
          rstd1 *= SM_SCALE_LOG2;
        }
        if (i == 4 && p == 3 && rb < 3) {
          const float2* sp = (const float2*)(cx.sp + SM_STATS) + cw * 16 + (fresh_lane() >> 2);
          mm0 = pack2(sp[0].x, sp[0].x);
          mm1 = pack2(sp[8].x, sp[8].x);
          sq0 = sp[0].y * SM_SCALE_LOG2;
          sq1 = sp[8].y * SM_SCALE_LOG2;
#pragma unroll
          for (int j = 0; j < 16; j++) { xa[2 * j] = sub2(xa[2 * j], mm0); xa[2 * j + 1] = sub2(xa[2 * j + 1], mm1); }
          pin(xa);
        }
        if (i == 0) {
          if (wg) {
            wg_wait<0>();
            if (signaller) mbar_arrive_cluster(empty_c + 8 * sl);
          }
        } else if (i == 2) {
          if (!join) {
            wg_wait<0>();
            if (signaller) mbar_arrive_cluster(empty_c + 8 * sl);
          }
          if (hlp && p == 3 && rb < 3) {
            mbar_wait(xf, ~rb & 1);
            ln_fetch<0, 16>(xa, xs, lo_of(fresh_lane()));
            pin(xa);
          }
        } else if (i != 3) {
          wg_wait<1>();
          if (signaller && (i == 4 || !wg)) mbar_arrive_cluster(empty_c + 8 * slp);
          wg_wait<0>();
          if (signaller) mbar_arrive_cluster(empty_c + 8 * sl);
        }
      }
      pin(acc);
      prof(wg, 3 + p);
      TS4(50 + 2 * p)
      st0 += 5;
      if (hlp && st0 > 5) bar_sync(BAR_QF + wg, 160);
      park<0, 8>(qlane(lane) + (hlp ? 5 + wg : 4 + p) * STAGE, acc, rstd0, rstd1);
      if (p || hlp) asm volatile("fence.proxy.async.shared::cta;" ::: "memory");
      if (hlp) bar_arrive(BAR_QS + wg, 160);
      if (p == 3) { rstd0 = sq0; rstd1 = sq1; }
      TS4(51 + 2 * p)
      if (p == 1 && !hlp) {
        float (&ah)[32] = *(float (*)[32])&acc[0];
#pragma unroll
        for (int i = 0; i < 3; i++) {
          const uint32_t sl = (10 + i) & 3;
          mbar_wait(full + 8 * sl, ((10 + i) >> 2) & 1);
          TS4(28 + 2 * i)
          if (i == 0 || i == 2 - wg) bar_sync(my_turn, 256);
          wg_fence();
          const uint64_t db = mkdesc(ring + sl * STAGE, 16);
#pragma unroll
          for (int k = 0; k < 12; k++) {
            const int kb = 12 * i + k;
            if (kb) mma_n64t(ah, xa[4 * kb], xa[4 * kb + 1], xa[4 * kb + 2], xa[4 * kb + 3], db + k * 128, true);
            else mma_n64t_dyn(ah, xa[0], xa[1], xa[2], xa[3], db, blockIdx.y);
          }
          wg_commit();
          TS4(29 + 2 * i)
          if (i == 2 || i != wg) {
            bar_arrive(other_turn, 256);
            if (i) {
              wg_wait<1>();
              if (signaller && i == wg + 1) mbar_arrive_cluster(empty_c + 8 * ((9 + i) & 3));
            }
            wg_wait<0>();
            if (signaller) mbar_arrive_cluster(empty_c + 8 * sl);
          }
        }
        pin(ah);
        TS4(54)
        park<0, 4>(qlane(lane) + 6 * STAGE, ah, rstd0, rstd1);
        TS4(55)
        st0 = 13;
        n = 2;
      }
    }
    TS_DUMP()
    ffn_consumer(cx, blockIdx.x & 3, wg, cw, fresh_lane(), x);
    return;
  }

attention:
  uint32_t oa[128];
  float acc[32];
  {
    uint32_t pf[28];
    uint32_t bad = 0;
    float lA0 = 0.f, lA1 = 0.f, lB0 = 0.f, lB1 = 0.f;
    int t = 0;
    uint32_t ra = 2 * 2048, rb = 2048, rc = 2 * 2048, par = 0;
    const uint64_t dk0 = mkdesc(ring, 16), dv0 = mkdesc(ring, 16384);
    uint64_t dqA = mkdesc_q(qwg + 4 * STAGE), dqB = dqA + 2048;
    auto turn = [&](auto kc_, auto bc_) {
      constexpr int KIND = decltype(kc_)::value, BIG = decltype(bc_)::value;
      constexpr int HB = KIND == 1, ID = 10 * KIND + 30 * BIG, T0 = BIG ? 38 : 0;
      constexpr int NS = BIG ? 56 : 48, SPLIT = BIG ? (HB ? X_SPLIT : X_SPLITA) : (HB ? X_SPLITS : X_SPLITSA);
      float s[NS];
      float (&op)[64] = HB ? oA : oB;
      uint32_t h0 = 0, h1 = 0;
      TS2(0)
      bar_sync(my_turn, 256);
      TS2(1)
      if (KIND) { pin(pf); pin(op); }
      mma_qk(s, HB ? dqB : dqA, dk0 + (HB ? ra : rc));
      TS2(2)
      if (KIND) {
        const bool bigp = HB ? BIG : BIG ? t != 10 : t == 66;
        if (X_BF2) block_fence(ID + 9);
        pin(pf);
        sum_tree(pf, bigp, h0, h1);
        asm volatile("" : "+r"(h0), "+r"(h1)::"memory");
        if (HB) mbar_wait(full + (rb >> 8), par);
        mma_pv(op, pf, dv0 + rb, t != T0 + 2 - HB, bigp);
      } else {
        mbar_wait(full + (rb >> 8), (NST_Q - 1) >> 2 & 1);
#pragma unroll
        for (int k = 0; k < 8; k++) mma_n128t(op, xl[4 * k], xl[4 * k + 1], xl[4 * k + 2], xl[4 * k + 3], dv0 + rb + k * 128, 1);
        wg_commit();
      }
      TS2(3)
      bar_arrive(other_turn, 256);
      (HB ? lA0 : lB0) += bf_lo(h0) + bf_hi(h0);
      (HB ? lA1 : lB1) += bf_lo(h1) + bf_hi(h1);
      wg_wait<1>();
      pin(s);
      TS1(t)
      TS2(4)
      if (KIND == 1) mbar_arrive_cluster_now<ID + 3>(empty_c + (ra >> 8), signaller);
      if (BIG && t == T0 + HB) {
        const uint32_t a = qlane(fresh_lane()) + (4 + HB) * STAGE;
        const bool ok = !__any_sync(0xffffffffu, inv_sums(HB ? lB0 : lA0, HB ? lB1 : lA1, i0, i1));
        bad = (HB ? bad : 0) | (ok ? 0 : 1 << HB);
        (HB ? lB0 : lA0) = 0.f;
        (HB ? lB1 : lA1) = 0.f;
        softmax_exp<0, X_E0>(s);
#pragma unroll
        for (int i = 0; i < X_E0; i++) asm volatile("" : "+f"(s[i])::"memory");
        block_fence(ID + 7);
        exp_park<0, X_PA, X_E0, SPLIT>(s, a, HB ? oB : oA, i0, i1, ok, 200 + ID);
        if (!HB) dqB += 2048;
        prof(wg, 8 + HB);
      } else {
        if (HB && !BIG) bad = (bad & 3) | (inv_sums(lA0, lA1, i0, i1) ? 4 : 0);
        softmax_exp<0, SPLIT>(s);
      }
      pin(s);
      if (!BIG) block_fence(ID + 4);
      TS2(5)
      wg_wait<0>();
      TS2(6)
      pin(op);
      if (KIND) pin(pf); else pin(xl);
      if (HB) {
        par ^= rc == 2048;
        if (BIG && t == 37) dqA -= 4 * 2048;
        if (BIG && t == X_WAKE && cw == 0) bar_arrive(BAR_HELPER, 64);
      } else {
        mbar_arrive_cluster_now<ID + 5>(empty_c + (rb >> 8), signaller);
        if (KIND) {
          par ^= ra == 2048;
          const uint32_t x = ra;
          ra = rc; rc = rb; rb = x;
        }
      }
      softmax_exp<SPLIT, NS>(s);
#pragma unroll
      for (int i = 0; i < NS / 2; i++) pf[i] = pack2(s[2 * i], s[2 * i + 1]);
      pin(pf);
      if (KIND == 0) {
        block_fence(ID + 6);
        park<0, 8>(qlane(fresh_lane()), oB, i0, i1);
        asm volatile("fence.proxy.async.shared::cta;" ::: "memory");
        prof(wg, 7);
      }
      if (BIG && X_PA < 8 && t == T0 + HB) park<X_PA, 8>(qlane(fresh_lane()) + (4 + HB) * STAGE, HB ? oB : oA, i0, i1, !(bad >> HB));
      if (BIG && !HB && t == T0) mbar_wait(cx.sb + SM_BAR_Q + 8 * wg, 0);
      if (HB) mbar_wait(full + (rc >> 8), par);
      t++;
    };
#pragma unroll
    for (int i = 24; i < 28; i++) asm volatile("" : "=r"(pf[i]));
    mbar_wait(full + 8 * 2, 0);
    turn(IC<0>(), IC<0>());
    rb = 3 * 2048; rc = 2048;
    kill(oA);
    const bool never = blockIdx.y == 1;
#pragma unroll 1
    while (true) {
      turn(IC<1>(), IC<0>());
      if (t == 76) break;
      if (t == 10) {
#pragma unroll 1
        do {
#pragma unroll 1
          do turn(IC<2>(), IC<1>()); while (never);
          turn(IC<1>(), IC<1>());
        } while (t != 66);
      }
#pragma unroll 1
      do turn(IC<2>(), IC<0>()); while (never);
    }
    const uint32_t ql = qlane(fresh_lane());
    auto scale = [&](auto lo, auto hi) {
#pragma unroll
      for (int i = decltype(lo)::value; i < decltype(hi)::value; i++) {
        oa[32 + 2 * i] = pack2(oA[4 * i] * i0, oA[4 * i + 1] * i0);
        oa[32 + 2 * i + 1] = pack2(oA[4 * i + 2] * i1, oA[4 * i + 3] * i1);
        asm volatile("" : "+r"(oa[32 + 2 * i]), "+r"(oa[32 + 2 * i + 1])::"memory");
      }
    };
    TS3(1)
    if (X_LD == 0) {
#pragma unroll
      for (int i = 0; i < 8; i++) ldsm4(ql + 4 * STAGE + i * 2048, oa[4 * i], oa[4 * i + 1], oa[4 * i + 2], oa[4 * i + 3]);
    }
    {
      uint32_t h0, h1;
      sum_tree(pf, false, h0, h1);
      if (inv_sums(lB0 + (bf_lo(h0) + bf_hi(h0)), lB1 + (bf_lo(h1) + bf_hi(h1)), lB0, lB1)) bad |= 8;
    }
    scale(IC<0>(), IC<X_F1>());
    volatile uint32_t* const cold = (volatile uint32_t*)(cx.sp + SM_COLD) + wg;
    if (bad) *cold = 1;
    block_fence(93);
    TS3(2)
    bar_sync(my_turn, 256);
    const uint32_t is_cold = *cold;
    TS3(3)
    pin(pf); pin(oB);
    mma_pv(oB, pf, dv0 + 2 * 2048, true, false);
    mbar_arrive_cluster_now<91>(empty_c, signaller && !is_cold);
    TS3(4)
    if (X_LD == 1) {
#pragma unroll
      for (int i = 0; i < 8; i++) ldsm4(ql + 4 * STAGE + i * 2048, oa[4 * i], oa[4 * i + 1], oa[4 * i + 2], oa[4 * i + 3]);
    }
    const uint64_t db = mkdesc(ring + 3 * STAGE, 16);
    scale(IC<X_F1>(), IC<X_F2>());
    block_fence(94);
#pragma unroll
    for (int i = 0; i < 32; i++) asm volatile("" : "+r"(oa[i])::"memory");
    wg_fence();
#pragma unroll
    for (int k = 0; k < 8; k++) mma_n64t(acc, oa[4 * k], oa[4 * k + 1], oa[4 * k + 2], oa[4 * k + 3], db + k * 128, k > 0);
    if (X_F2 < 16) {
      wg_commit();
      block_fence(95);
      scale(IC<X_F2>(), IC<16>());
      TS3(5)
      wg_fence();
    }
#pragma unroll
    for (int k = 8; k < 16; k++) mma_n64t(acc, oa[4 * k], oa[4 * k + 1], oa[4 * k + 2], oa[4 * k + 3], db + k * 128, 1);
    wg_commit();
    bar_arrive(other_turn, 256);
    wg_wait<(X_F2 < 16 ? 2 : 1)>();
    pin(oB); pin(pf);
    TS(76)
    TS3(6)
    if (signaller) mbar_arrive_cluster(empty_c + 8 * 2);
#pragma unroll
    for (int i = 16; i < 24; i++) ldsm4(ql + 5 * STAGE + (i & 7) * 2048, oa[4 * i], oa[4 * i + 1], oa[4 * i + 2], oa[4 * i + 3]);
#pragma unroll
    for (int i = 0; i < 16; i++) {
      oa[96 + 2 * i] = pack2(oB[4 * i] * lB0, oB[4 * i + 1] * lB0);
      oa[96 + 2 * i + 1] = pack2(oB[4 * i + 2] * lB1, oB[4 * i + 3] * lB1);
    }
    TS3(7)
    mbar_wait(full + 8 * 1, 0);
    TS3(8)
    wg_wait<0>();
    pin(acc); pin(oa);
    if (__any_sync(0xffffffffu, is_cold)) {
      bad = __reduce_or_sync(0xffffffffu, bad);
      if (!(bad & 8)) {
#pragma unroll
        for (int i = 24; i < 32; i++) stsm4(ql + 6 * STAGE + (i & 7) * 2048, oa[4 * i], oa[4 * i + 1], oa[4 * i + 2], oa[4 * i + 3]);
      }
#pragma unroll 1
      for (int h = 0; h < 4; h++) {
        if (bad >> h & 1) {
          const uint32_t a = ql + ((0x6054 >> (4 * h)) & 7) * STAGE;
          const int l = fresh_lane(), o = (hs * 2 + (h >> 1)) * SEQ * DH + (l >> 2) * DH + (l & 3) * 2;
          uint32_t q[32];
#pragma unroll
          for (int i = 0; i < 8; i++) ldsm4(a + i * 2048, q[4 * i], q[4 * i + 1], q[4 * i + 2], q[4 * i + 3]);
#pragma unroll 1
          for (int i = 0; i < 4; i++) {
            float ox[16], l0, l1;
            exact_attention(ox, l0, l1, q, kc + o, vc + o + i * 32);
            inv_sums(l0, l1, l0, l1);
            park<0, 2>(a + i * 4096, ox, l0, l1);
          }
        }
      }
      __syncwarp();
#pragma unroll
      for (int i = 0; i < 32; i++)
        if ((i >> 3) != 1 || (bad & 4))
          ldsm4(ql + ((0x6504 >> (4 * (i >> 3))) & 7) * STAGE + (i & 7) * 2048, oa[4 * i], oa[4 * i + 1], oa[4 * i + 2], oa[4 * i + 3]);
      pin(oa);
      asm volatile("fence.proxy.async.shared::cta;" ::: "memory");
      bar_sync(4 + wg, 128);
      if (signaller) mbar_arrive_cluster(empty_c);
      wg_fence();
#pragma unroll
      for (int k = 0; k < 16; k++) mma_n64t(acc, oa[4 * k], oa[4 * k + 1], oa[4 * k + 2], oa[4 * k + 3], db + k * 128, k > 0);
      wg_commit();
      wg_wait<0>();
      pin(acc);
    }
    if (signaller) mbar_arrive_cluster(empty_c + 8 * 3);
  }

  prof(wg, 10);
  TS3(9)
  {
    lane = fresh_lane();
    const int tw = (cw & 3) * 32 + lane;
    float red[32];
    kill(red);
    const uint32_t tag = *(const uint32_t*)(cx.sp + SM_TAG);
    uint4* const xch = cx.g->part + (size_t)(qb * 64 * 2 + wg) * 4 * 128 + tw;
    int nrx = 1;
    auto region = [](int s, int h) { return h ? 1 + (s & 1) : (s & 1) ? 0 : 3; };
    auto half_step = [&](int s, auto hc, bool arrive) {
      constexpr int h = decltype(hc)::value;
      const uint64_t db = mkdesc(ring + region(s, h) * STAGE, 16);
      bar_sync(my_turn, 256);
      pin(oa);
      wg_fence();
#pragma unroll
      for (int k = 0; k < 16; k++) {
        const int kb = h * 16 + k;
        mma_n64t(acc, oa[4 * kb], oa[4 * kb + 1], oa[4 * kb + 2], oa[4 * kb + 3], db + k * 128, kb > 0);
      }
      wg_commit();
      if (arrive) bar_arrive(other_turn, 256);
    };
    auto await = [&](int s, int h) { mbar_wait(full + 8 * region(s, h), ((s >> 1) ^ h ^ 1) & 1); };
    auto fetch = [&](uint32_t (&g)[16], int n) {
      const uint4* p = xch + (hs * 7 + n - 1) * (2 * 4 * 128);
#pragma unroll
      for (int i = 0; i < 4; i++) ld_gran(p + i * 128, g[4 * i], g[4 * i + 1], g[4 * i + 2], g[4 * i + 3]);
    };
    uint32_t g[16];
#pragma unroll 1
    for (int s = 0; s < 8; s++) {
      const bool pend = nrx < s - 1;
      if (pend) fetch(g, nrx);
      half_step(s, IC<1>(), true);
      TS3(s < 3 ? 16 + 8 * s : 75)
      if (s == 0) {
        bar_arrive(BAR_OA, 352);
#pragma unroll
        for (int i = 0; i < 32; i++) red[i] = 0.f;
      }
      await(s + 1, 0);
      TS3(s < 3 ? 17 + 8 * s : 75)
      wg_wait<0>();
      TS3(s < 3 ? 18 + 8 * s : 75)
      if (signaller && s < 7) mbar_arrive_cluster(empty_c + 8 * region(s, 1));
      pin(acc);
      TS(77 + s)
      prof(wg, 12 + s);
      uint4* p = xch + (s == 0 ? 56 + hs : ((hs + s) & 7) * 7 + s - 1) * (2 * 4 * 128);
#pragma unroll
      for (int i = 0; i < 4; i++)
        st_gran(p + i * 128, (pack2(acc[8 * i], acc[8 * i + 1]) & ~TAG) | tag, pack2(acc[8 * i + 2], acc[8 * i + 3]),
                pack2(acc[8 * i + 4], acc[8 * i + 5]), pack2(acc[8 * i + 6], acc[8 * i + 7]));
      TS3(s < 3 ? 19 + 8 * s : 75)
      half_step(s + 1, IC<0>(), true);
      TS3(s < 3 ? 20 + 8 * s : 75)
      await(s + 1, 1);
      TS3(s < 3 ? 21 + 8 * s : 75)
      if (pend && granules_ok(g, tag)) { add_granules(red, g); nrx++; }
      wg_wait<0>();
      TS3(s < 3 ? 22 + 8 * s : 75)
      if (signaller && s < 6) mbar_arrive_cluster(empty_c + 8 * region(s + 1, 0));
    }
    uint32_t xv[16], gt[16], g2[16];
    fetch(g, nrx);
    mbar_wait(cx.sb + SM_BAR_XG, 0);
    {
      const uint64_t db = mkdesc(ring + STAGE, 16);
      bar_sync(my_turn, 256);
#pragma unroll
      for (int i = 64; i < 128; i++) asm volatile("" : "+r"(oa[i])::"memory");
      wg_fence();
#pragma unroll
      for (int k = 16; k < 32; k++) mma_n64t(acc, oa[4 * k], oa[4 * k + 1], oa[4 * k + 2], oa[4 * k + 3], db + (k - 16) * 128, 1);
      wg_commit();
      if (wg == 0) bar_arrive(other_turn, 256);
    }
    const bool ok = granules_ok(g, tag);
    nrx += ok;
    fetch(g2, nrx);
    const uint32_t frag = (cw * 16 + (lane & 15)) * 128 + (((lane >> 4) ^ (lane & 7)) << 4);
#pragma unroll
    for (int i = 0; i < 4; i++) {
      ldsm4(cx.sb + SM_XO + (frag ^ (i << 5)), xv[4 * i], xv[4 * i + 1], xv[4 * i + 2], xv[4 * i + 3]);
      ldsm4(cx.sb + SM_GO + (frag ^ (i << 5)), gt[4 * i], gt[4 * i + 1], gt[4 * i + 2], gt[4 * i + 3]);
    }
    if (ok) add_granules(red, g);
    wg_wait<0>();
    pin(acc);
    TS(85)
#pragma unroll
    for (int i = 0; i < 32; i++) red[i] += acc[i];
    pin(red);
#pragma unroll 1
    for (int spins = 0; spins < (1 << 16); spins++) {
      if (granules_ok(g2, tag)) {
        add_granules(red, g2);
        if (++nrx == 8) break;
      }
      fetch(g2, nrx);
    }
    prof(wg, 20);
    TS(86)
    uint32_t ow[16];
#pragma unroll
    for (int i = 0; i < 16; i++) ow[i] = fma2(pack2(red[2 * i], red[2 * i + 1]), gt[i], xv[i]);
#pragma unroll
    for (int i = 0; i < 4; i++) stsm4(cx.sb + SM_XO + (frag ^ (i << 5)), ow[4 * i], ow[4 * i + 1], ow[4 * i + 2], ow[4 * i + 3]);
    __syncwarp();
#pragma unroll
    for (int i = 0; i < 4; i++) {
      uint4 v;
      const int row = cw * 16 + i * 4 + (lane >> 3);
      lds128(cx.sb + SM_XO + row * 128 + (((lane ^ row) & 7) << 4), v.x, v.y, v.z, v.w);
      asm volatile("st.global.v4.b32 [%0], {%1, %2, %3, %4};" ::"l"(out + (size_t)(qb * 128 + row) * DM + hs * 64 + (lane & 7) * 8),
                   "r"(v.x), "r"(v.y), "r"(v.z), "r"(v.w) : "memory");
    }
    prof(wg, 22);
    TS(87)
    TS_DUMP()
  }
}

struct KvMaps { CUtensorMap m[4]; };
__global__ void __cluster_dims__(2, 1, 1) __launch_bounds__(THREADS, 1)
fused_kernel(const __nv_bfloat16* __restrict__ x, const __nv_bfloat16* __restrict__ w_r, const __nv_bfloat16* __restrict__ kc,
             const __nv_bfloat16* __restrict__ vc, __nv_bfloat16* __restrict__ out, Scratch* scratch,
             const __grid_constant__ CUtensorMap tmX, const __grid_constant__ CUtensorMap tmWq,
             const __grid_constant__ KvMaps tmKV, const __grid_constant__ CUtensorMap tmWo,
             const __grid_constant__ CUtensorMap tmG, const __grid_constant__ CUtensorMap tmU,
             const __grid_constant__ CUtensorMap tmD, const __grid_constant__ CUtensorMap tmX16,
             const __grid_constant__ CUtensorMap tmWq96, const __grid_constant__ CUtensorMap tmX64) {
  extern __shared__ __align__(1024) uint8_t smem_raw[];
  prof(0, 23, 511);
  if (X_PFX && threadIdx.x == 192) { prefetch_tmap(&tmX); prefetch_tmap(&tmWq); }
  Ctx cx;
  cx.sb = smem_u32(smem_raw);
  cx.sp = smem_raw;
  cx.g = scratch;
  cx.rank = blockIdx.x & 1;
  const int warp = __shfl_sync(0xffffffffu, threadIdx.x >> 5, 0);
  const int cluster = blockIdx.x >> 1;
  const bool is_ffn = blockIdx.x >= N_ATT_CTA;
  const int c7 = ((cluster - 36) * 37) >> 8;
  const int hs = cluster < 4 ? 4 + cluster : cluster < 36 ? (cluster - 4) >> 3 : 4 + c7;
  const int qb = (cluster < 4 ? 0 : cluster < 36 ? (cluster - 4) & 7 : cluster - (is_ffn ? 36 : 35) - 7 * c7) * 2 + cx.rank;

  auto load_x = [&](int w, int i0, int i1) {
#pragma unroll
    for (int i = i0; i < i1; i++) {
      mbar_expect_tx(cx.sb + SM_XFULL + 32 * w + 8 * i, 24576);
      tma3d(cx.sb + SM_X + (3 * w + i) * 24576, &tmX, qb * 128 + w * 64, i * 3, cx.sb + SM_XFULL + 32 * w + 8 * i);
    }
  };
  if (warp < 4) {
    asm volatile("setmaxnreg.dec.sync.aligned.u32 24;");
    if (elect_one()) {
      if (warp == 0) {
        TSP(64)
#pragma unroll
        for (int i = 0; i < 4; i++) mbar_init(cx.sb + SM_FULL + 8 * i, 1);

      } else if (warp == 1) {
#pragma unroll
        for (int i = 0; i < 4; i++) mbar_init(cx.sb + SM_EMPTY + 8 * i, 4);
        mbar_init(cx.sb + SM_BAR_MISC, 1);
        mbar_init(cx.sb + SM_BAR_XG, 1);
        mbar_init(cx.sb + SM_BAR_SQ, 1);
        mbar_init(cx.sb + SM_BAR_Q, 1);
        mbar_init(cx.sb + SM_BAR_Q + 8, 1);
      } else if (is_ffn) {
#pragma unroll
        for (int i = 0; i < 8; i++) mbar_init(cx.sb + (warp == 2 ? SM_FFULL : SM_FEMPTY) + 8 * i, 1);
      }
      asm volatile("fence.mbarrier_init.release.cluster;" ::: "memory");
    }
    __syncwarp();
    cluster_arrive();
    if (warp == 0) TSP(70)
    cluster_wait();
    if (warp == 0) TSP(71)
    prof(0, 24, 511);
    if (warp == 0) {
      if (is_ffn) ffn_producer(cx, qb, &tmWq, &tmG, &tmU, &tmD);
      else attn_producer(cx, qb, hs, tmKV.m, &tmWq, &tmWq96, &tmWo);
      prof(0, 25, 511);
    } else {
      sq_publish(cx, qb, hs, warp - 1, read_lane());
      if (warp == 3) sq_collect(cx, qb, read_lane());
      if (!is_ffn) {
        attn_gate(cx, qb, hs, threadIdx.x - 32, x);
        if (warp == 1) TSP(65)
        asm volatile("fence.proxy.async.global;" ::: "memory");
        if (warp == 1) attn_helper(cx, qb, hs, read_lane(), &tmX16);
        else bar_arrive(BAR_OA, 352);
        attn_finish8(cx, qb, hs, warp - 1, read_lane(), out);
      } else if (warp < 3) {
        ffn_publish(cx, qb, warp - 1, read_lane(), &tmX64);
      }
    }
    __syncwarp();
    cluster_arrive();
    cluster_wait();
  } else {
    if (warp == 4 && elect_one()) {
#pragma unroll
      for (int i = 0; i < 3; i++) mbar_init(cx.sb + SM_XFULL + 8 * i, 1);
      TSP(66)
      load_x(0, 0, 3);
#pragma unroll
      for (int i = 4; i < 7; i++) mbar_init(cx.sb + SM_XFULL + 8 * i, 1);
      asm volatile("fence.mbarrier_init.release.cluster;" ::: "memory");
    }
    if (warp == 5 && elect_one()) {
      mbar_init(cx.sb + SM_BAR_W, 1);
      asm volatile("fence.mbarrier_init.release.cluster;" ::: "memory");
      *(uint4*)(cx.sp + SM_ONES) = make_uint4(0x3F803F80u, 0x3F803F80u, 0x3F803F80u, 0x3F803F80u);
      mbar_expect_tx(cx.sb + SM_BAR_W, DM * 2);
      bulk_load(cx.sb + SM_WR, w_r, DM * 2, cx.sb + SM_BAR_W);
    }
    __syncwarp();
    cluster_arrive();
    if (warp == 4 && elect_one()) {
      load_x(1, 0, X_ORD);
      TSP(67)
    }
    __syncwarp();
    asm volatile("setmaxnreg.inc.sync.aligned.u32 240;");
    const int cw = warp - 4, wg = cw >> 2;
    cluster_wait();
    if (warp == 8 && elect_one()) {
      const uint64_t pol = policy_evict_first();
#pragma unroll
      for (int i = 0; i < 4; i++) {
        if (!(i & 1)) mbar_expect_tx(cx.sb + SM_FULL + 4 * i, 32768);
        tma2d_mc(cx.sb + SM_RING + (i >> 1) * STAGE + cx.rank * 16384 + (i & 1) * 8192, &tmWq,
                 is_ffn ? (cx.rank * 4 + 3) * DH + 64 : hs * 512 + cx.rank * 64, i * 64, cx.sb + SM_FULL + 8 * (i >> 1), pol);
        if (i == 1) load_x(1, X_ORD, 3);
      }
      TSP(72)
    }
    __syncwarp();
    attn_consumer(cx, is_ffn, qb, hs, wg, cw, read_lane(), x, kc, vc, out);
  }
}

typedef CUresult (*EncodeFn)(CUtensorMap*, CUtensorMapDataType, cuuint32_t, void*, const cuuint64_t*, const cuuint64_t*,
                             const cuuint32_t*, const cuuint32_t*, CUtensorMapInterleave, CUtensorMapSwizzle,
                             CUtensorMapL2promotion, CUtensorMapFloatOOBfill);

void encode(EncodeFn fn, CUtensorMap* m, const void* p, int rank, const cuuint64_t* dims, const cuuint64_t* strides,
            const cuuint32_t* box) {
  const cuuint32_t es[5] = {1, 1, 1, 1, 1};
  fn(m, CU_TENSOR_MAP_DATA_TYPE_BFLOAT16, rank, const_cast<void*>(p), dims, strides, box, es, CU_TENSOR_MAP_INTERLEAVE_NONE,
     CU_TENSOR_MAP_SWIZZLE_128B, CU_TENSOR_MAP_L2_PROMOTION_L2_128B, CU_TENSOR_MAP_FLOAT_OOB_FILL_NONE);
}
void encode2d(EncodeFn fn, CUtensorMap* m, const void* p, uint64_t rows, uint64_t cols, uint32_t box_rows) {
  const cuuint64_t dims[2] = {cols, rows}, strides[1] = {cols * 2};
  const cuuint32_t box[2] = {64, box_rows};
  encode(fn, m, p, 2, dims, strides, box);
}

}

extern "C" void kernel_launch(void* const* d_in, const int* in_sizes, int n_in, void* d_out, int out_size) {
  (void)in_sizes; (void)n_in; (void)out_size;
  void* fnp = nullptr;
  cudaDriverEntryPointQueryResult qr;
  cudaGetDriverEntryPoint("cuTensorMapEncodeTiled", &fnp, cudaEnableDefault, &qr);
  EncodeFn fn = (EncodeFn)fnp;
  CUtensorMap tmWq, tmWo, tmG, tmU, tmD, tmX, tmX16, tmWq96, tmX64;
  encode2d(fn, &tmX64, d_in[0], SEQ, DM, 64);
  encode2d(fn, &tmWq96, d_in[3], DM, 4096, 96);
  encode2d(fn, &tmX16, d_in[0], SEQ, DM, 16);
  KvMaps tmKV;
  for (int i = 0; i < 4; i++) encode2d(fn, &tmKV.m[i], d_in[1 + (i & 1)], 16 * SEQ, DH, i < 2 ? 112 : 96);
  encode2d(fn, &tmWq, d_in[3], DM, 4096, 64);
  {
    const cuuint64_t dims[3] = {64, SEQ, 9}, strides[2] = {DM * 2, 128};
    const cuuint32_t box[3] = {64, 64, 3};
    encode(fn, &tmX, d_in[0], 3, dims, strides, box);
  }
  encode2d(fn, &tmWo, d_in[4], 4096, DM, 128);
  encode2d(fn, &tmG, d_in[7], DM, FF, 192);
  encode2d(fn, &tmU, d_in[8], DM, FF, 192);
  encode2d(fn, &tmD, d_in[9], FF, DM, 192);
  cudaFuncSetAttribute(fused_kernel, cudaFuncAttributeMaxDynamicSharedMemorySize, SM_TOTAL);
  void* scratch = nullptr;
  cudaGetSymbolAddress(&scratch, g_scratch);
  fused_kernel<<<N_CTA, THREADS, SM_TOTAL>>>((const __nv_bfloat16*)d_in[0], (const __nv_bfloat16*)d_in[6], (const __nv_bfloat16*)d_in[1],
                                            (const __nv_bfloat16*)d_in[2], (__nv_bfloat16*)d_out, (Scratch*)scratch, tmX, tmWq, tmKV,
                                            tmWo, tmG, tmU, tmD, tmX16, tmWq96, tmX64);
}
```

```cpp
#include <cuda_runtime.h>
#include <cuda_bf16.h>
#include <cuda.h>
#include <stdint.h>

#define X_PFW 1
#define X_SPLIT 38
#define X_SPLITA 36
#define X_SPLITS 32
#define X_SPLITSA 30
#define X_PA 8
#define X_PG 2
#define X_E0 10
#define X_F2 10
#define X_LD 0
#define X_LN 0
#define X_WAKE 31
#define X_PFX 1
#define X_F1 0
#define X_BF2 1
#define X_SQI 4
#define X_SQS 300
#define X_ORD 3
#define X_NS 4
namespace {

constexpr int SEQ = 2048, DM = 576, DH = 128, FF = 4608, TOPC = 8;
constexpr int N_ATT_CTA = 128, N_CTA = 132;
constexpr int THREADS = 384;

constexpr uint32_t SM_RING = 0;
constexpr uint32_t STAGE = 32768;
constexpr uint32_t SM_SLOT = 131072;
constexpr uint32_t FSTAGE = 24576;
constexpr uint32_t SM_XSEL = 196608;
constexpr uint32_t SM_H = 205824;
constexpr uint32_t SM_MISC = 229376;
constexpr uint32_t SM_FULL = SM_MISC, SM_EMPTY = SM_MISC + 32, SM_FFULL = SM_MISC + 64, SM_BAR_MISC = SM_MISC + 128,
                   SM_COLD = SM_MISC + 136, SM_TAG = SM_MISC + 144, SM_BAR_W = SM_MISC + 152, SM_ONES = SM_MISC + 160,
                   SM_BAR_Q = SM_MISC + 176, SM_XFULL = SM_MISC + 192, SM_BAR_XG = SM_MISC + 304, SM_BAR_SQ = SM_MISC + 312,
                   SM_STATS = SM_MISC + 320, SM_FEMPTY = SM_MISC + 1344, SM_RAW = SM_FEMPTY, SM_WR = SM_MISC + 1408, SM_TOPK = SM_WR;
constexpr uint32_t SM_TOTAL = SM_MISC + 2560;
constexpr uint32_t SM_X = SM_MISC - 147456;

constexpr int BAR_GATE = 6, BAR_HELPER = 7, BAR_OA = 8, BAR_XREL = 13, BAR_QS = 9, BAR_QF = 11;
constexpr int NST_Q = 18, NST_KV = 76, NST_O = 18;
constexpr float SM_SCALE_LOG2 = 0.08838834764831845f * 1.4426950408889634f;

struct Scratch {
  uint4 part[16 * 64 * 2 * 4 * 128];
  uint4 gate[N_ATT_CTA * 1152];
  uint4 q[16 * 8 * 2 * 512];
  uint2 sq[SEQ];
  uint4 stats[SEQ];
  float ypart[4 * TOPC * DM];
  int2 sel[16];
  unsigned launch[160];
  unsigned pad0, ycnt, pad[30];
  unsigned qflag[128];
};
__device__ __align__(1024) Scratch g_scratch;

__device__ __forceinline__ void prof(int, int, int = 0) {}

#define TS(id) {}
#define TS_DUMP() {}
#define TS4(k) {}
#define TSP(k) {}
#define TS1(id) TS(id)
#define TS2(k) {}
#define TS3(k) {}

__device__ __forceinline__ uint32_t smem_u32(const void* p) { return (uint32_t)__cvta_generic_to_shared(p); }
__device__ __forceinline__ void mbar_init(uint32_t bar, uint32_t cnt) {
  asm volatile("mbarrier.init.shared::cta.b64 [%0], %1;" ::"r"(bar), "r"(cnt) : "memory");
}
__device__ __forceinline__ void mbar_expect_tx(uint32_t bar, uint32_t bytes) {
  asm volatile("mbarrier.arrive.expect_tx.shared::cta.b64 _, [%0], %1;" ::"r"(bar), "r"(bytes) : "memory");
}
__device__ __forceinline__ void mbar_arrive(uint32_t bar) {
  asm volatile("mbarrier.arrive.shared::cta.b64 _, [%0];" ::"r"(bar) : "memory");
}
__device__ __forceinline__ void mbar_arrive_cluster(uint32_t bar_cluster_addr) {
  asm volatile("mbarrier.arrive.shared::cluster.b64 _, [%0];" ::"r"(bar_cluster_addr) : "memory");
}
template <int ID>
__device__ __forceinline__ void mbar_arrive_cluster_now(uint32_t bar_cluster_addr, bool pred) {
  asm volatile("{\n.reg .pred p, q;\nsetp.ne.u32 p, %1, 0;\nsetp.eq.u32 q, %2, %3;\n"
               "ARR_LOOP:\n@p mbarrier.arrive.shared::cluster.b64 _, [%0];\n@q bra.uni ARR_LOOP;\n}"
               ::"r"(bar_cluster_addr), "r"((uint32_t)pred), "r"(blockIdx.y), "n"(ID) : "memory");
}
__device__ __forceinline__ void block_fence(int id) {
  asm volatile("{\n.reg .pred q;\nsetp.eq.u32 q, %0, %1;\nBF_LOOP:\n@q st.volatile.shared.u32 [%0], %0;\n@q bra.uni BF_LOOP;\n}"
               ::"r"(blockIdx.y), "r"(id) : "memory");
}
__device__ __forceinline__ void mbar_wait(uint32_t bar, uint32_t parity) {
  asm volatile("{\n.reg .pred p, q;\n.reg .u32 n;\nmov.u32 n, 0;\n"
               "WAIT_LOOP:\nmbarrier.try_wait.parity.shared::cta.b64 p, [%0], %1;\n"
               "add.u32 n, n, 1;\nsetp.lt.u32 q, n, 4194304;\nand.pred q, q, !p;\n@q bra WAIT_LOOP;\n}"
               ::"r"(bar), "r"(parity) : "memory");
}
__device__ __forceinline__ uint32_t mapa(uint32_t addr, uint32_t rank) {
  uint32_t r;
  asm volatile("mapa.shared::cluster.u32 %0, %1, %2;" : "=r"(r) : "r"(addr), "r"(rank));
  return r;
}
__device__ __forceinline__ void cluster_arrive() { asm volatile("barrier.cluster.arrive.relaxed.aligned;" ::: "memory"); }
__device__ __forceinline__ bool elect_one() {
  uint32_t p;
  asm volatile("{\n.reg .pred p;\nelect.sync _|p, 0xffffffff;\nselp.u32 %0, 1, 0, p;\n}" : "=r"(p));
  return p;
}
__device__ __forceinline__ int read_lane() { return threadIdx.x & 31; }
__device__ __forceinline__ int fresh_lane() {
  int l;
  asm volatile("mov.u32 %0, %%laneid;" : "=r"(l));
  return l;
}
__device__ __forceinline__ void cluster_wait() { asm volatile("barrier.cluster.wait.acquire.aligned;" ::: "memory"); }
__device__ __forceinline__ void bar_sync(int id, int n) { asm volatile("barrier.cta.sync %0, %1;" ::"r"(id), "r"(n) : "memory"); }
__device__ __forceinline__ void bar_arrive(int id, int n) { asm volatile("barrier.cta.arrive %0, %1;" ::"r"(id), "r"(n) : "memory"); }

__device__ __forceinline__ uint64_t policy_evict_first() {
  uint64_t p;
  asm("createpolicy.fractional.L2::evict_first.b64 %0, 1.0;" : "=l"(p));
  return p;
}
__device__ __forceinline__ void tma2d_mc(uint32_t dst, const CUtensorMap* tm, int c0, int c1, uint32_t bar, uint64_t pol) {
  asm volatile("cp.async.bulk.tensor.2d.shared::cluster.global.mbarrier::complete_tx::bytes.multicast::cluster.L2::cache_hint"
               " [%0], [%1, {%2, %3}], [%4], %5, %6;"
               ::"r"(dst), "l"(tm), "r"(c0), "r"(c1), "r"(bar), "h"((uint16_t)3), "l"(pol) : "memory");
}
__device__ __forceinline__ void tma3d(uint32_t dst, const CUtensorMap* tm, int c1, int c2, uint32_t bar) {
  asm volatile("cp.async.bulk.tensor.3d.shared::cluster.global.mbarrier::complete_tx::bytes [%0], [%1, {%2, %3, %4}], [%5];"
               ::"r"(dst), "l"(tm), "r"(0), "r"(c1), "r"(c2), "r"(bar) : "memory");
}
__device__ __forceinline__ void tma2d(uint32_t dst, const CUtensorMap* tm, int c0, int c1, uint32_t bar) {
  asm volatile("cp.async.bulk.tensor.2d.shared::cluster.global.mbarrier::complete_tx::bytes [%0], [%1, {%2, %3}], [%4];"
               ::"r"(dst), "l"(tm), "r"(c0), "r"(c1), "r"(bar) : "memory");
}
__device__ __forceinline__ void tma2d_stream(uint32_t dst, const CUtensorMap* tm, int c0, int c1, uint32_t bar) {
  asm volatile("{\n.reg .b64 pol;\ncreatepolicy.fractional.L2::evict_first.b64 pol, 1.0;\n"
               "cp.async.bulk.tensor.2d.shared::cluster.global.mbarrier::complete_tx::bytes.L2::cache_hint [%0], [%1, {%2, %3}], [%4], pol;\n}"
               ::"r"(dst), "l"(tm), "r"(c0), "r"(c1), "r"(bar) : "memory");
}
__device__ __forceinline__ void bulk_load(uint32_t dst, const void* src, uint32_t bytes, uint32_t bar) {
  asm volatile("cp.async.bulk.shared::cluster.global.mbarrier::complete_tx::bytes [%0], [%1], %2, [%3];"
               ::"r"(dst), "l"(src), "r"(bytes), "r"(bar) : "memory");
}
__device__ __forceinline__ void tma2d_prefetch(const CUtensorMap* tm, int c0, int c1) {
  asm volatile("cp.async.bulk.prefetch.tensor.2d.L2.global [%0, {%1, %2}];" ::"l"(tm), "r"(c0), "r"(c1) : "memory");
}
__device__ __forceinline__ void prefetch_tmap(const CUtensorMap* tm) {
  asm volatile("prefetch.tensormap [%0];" ::"l"(tm) : "memory");
}

__device__ __forceinline__ void wg_fence() { asm volatile("wgmma.fence.sync.aligned;" ::: "memory"); }
__device__ __forceinline__ void wg_commit() { asm volatile("wgmma.commit_group.sync.aligned;" ::: "memory"); }
template <int N> __device__ __forceinline__ void wg_wait() { asm volatile("wgmma.wait_group.sync.aligned %0;" ::"n"(N) : "memory"); }

__device__ __forceinline__ uint64_t mkdesc(uint32_t addr, uint32_t lbo_bytes) {
  return (uint64_t)(((addr & 0x3FFFF) >> 4) | ((lbo_bytes >> 4) << 16)) | ((uint64_t)0x40000040u << 32);
}
__device__ __forceinline__ uint64_t mkdesc_q(uint32_t addr) {
  return (uint64_t)(((addr & 0x3FFFF) >> 4) | (64u << 16)) | ((uint64_t)8 << 32);
}
template <int N> __device__ __forceinline__ void pin(float (&a)[N]) {
#pragma unroll
  for (int i = 0; i < N; i++) asm volatile("" : "+f"(a[i])::"memory");
}
template <int N> __device__ __forceinline__ void kill(float (&a)[N]) {
#pragma unroll
  for (int i = 0; i < N; i++) asm volatile("" : "=f"(a[i]));
}
template <int N> __device__ __forceinline__ void pin(uint32_t (&a)[N]) {
#pragma unroll
  for (int i = 0; i < N; i++) asm volatile("" : "+r"(a[i])::"memory");
}

#define F8(d, o) "+f"(d[o]), "+f"(d[o + 1]), "+f"(d[o + 2]), "+f"(d[o + 3]), "+f"(d[o + 4]), "+f"(d[o + 5]), "+f"(d[o + 6]), "+f"(d[o + 7])
#define R32A "%0, %1, %2, %3, %4, %5, %6, %7, %8, %9, %10, %11, %12, %13, %14, %15, %16, %17, %18, %19, %20, %21, %22, %23, %24, %25, %26, %27, %28, %29, %30, %31"
#define R32B "%32, %33, %34, %35, %36, %37, %38, %39, %40, %41, %42, %43, %44, %45, %46, %47, %48, %49, %50, %51, %52, %53, %54, %55, %56, %57, %58, %59, %60, %61, %62, %63"

#define O8(d, o) "=f"(d[o]), "=f"(d[o + 1]), "=f"(d[o + 2]), "=f"(d[o + 3]), "=f"(d[o + 4]), "=f"(d[o + 5]), "=f"(d[o + 6]), "=f"(d[o + 7])

__device__ __forceinline__ void mma_n128t(float (&d)[64], uint32_t a0, uint32_t a1, uint32_t a2, uint32_t a3, uint64_t db, bool acc) {
  if (acc)
    asm volatile("wgmma.mma_async.sync.aligned.m64n128k16.f32.bf16.bf16 {" R32A ", " R32B "}, {%64, %65, %66, %67}, %68, 1, 1, 1, 1;\n"
                 : F8(d, 0), F8(d, 8), F8(d, 16), F8(d, 24), F8(d, 32), F8(d, 40), F8(d, 48), F8(d, 56)
                 : "r"(a0), "r"(a1), "r"(a2), "r"(a3), "l"(db));
  else
    asm volatile("wgmma.mma_async.sync.aligned.m64n128k16.f32.bf16.bf16 {" R32A ", " R32B "}, {%64, %65, %66, %67}, %68, 0, 1, 1, 1;\n"
                 : O8(d, 0), O8(d, 8), O8(d, 16), O8(d, 24), O8(d, 32), O8(d, 40), O8(d, 48), O8(d, 56)
                 : "r"(a0), "r"(a1), "r"(a2), "r"(a3), "l"(db));
}
#define PV1(a0, a1, a2, a3, ob, acc) "add.s64 b, %92, " #ob ";\n" \
  "wgmma.mma_async.sync.aligned.m64n128k16.f32.bf16.bf16 {" R32A ", " R32B "}, {%" #a0 ", %" #a1 ", %" #a2 ", %" #a3 "}, b, " #acc ", 1, 1, 1;\n"
#define PV6 "wgmma.fence.sync.aligned;\n" PV1(64, 65, 66, 67, 0, p) PV1(68, 69, 70, 71, 128, 1) PV1(72, 73, 74, 75, 256, 1) \
  PV1(76, 77, 78, 79, 384, 1) PV1(80, 81, 82, 83, 512, 1) PV1(84, 85, 86, 87, 640, 1)
#define U4(a, o) "r"(a[o]), "r"(a[o + 1]), "r"(a[o + 2]), "r"(a[o + 3])
__device__ __forceinline__ void mma_pv(float (&d)[64], const uint32_t (&a)[28], uint64_t dv, bool acc, bool big) {
  asm volatile("{\n.reg .pred p, q;\n.reg .b64 b;\nsetp.ne.b32 p, %93, 0;\nsetp.eq.b32 q, %94, 0;\n@q bra.uni PV_SMALL;\n"
               PV6 PV1(88, 89, 90, 91, 768, 1) "wgmma.commit_group.sync.aligned;\nbra.uni PV_DONE;\n"
               "PV_SMALL:\n" PV6 "wgmma.commit_group.sync.aligned;\nPV_DONE:\n}\n"
               : F8(d, 0), F8(d, 8), F8(d, 16), F8(d, 24), F8(d, 32), F8(d, 40), F8(d, 48), F8(d, 56)
               : U4(a, 0), U4(a, 4), U4(a, 8), U4(a, 12), U4(a, 16), U4(a, 20), U4(a, 24), "l"(dv), "r"((int)acc), "r"((int)big) : "memory");
}
#define R48 R32A ", %32, %33, %34, %35, %36, %37, %38, %39, %40, %41, %42, %43, %44, %45, %46, %47"
#define R56 R48 ", %48, %49, %50, %51, %52, %53, %54, %55"
#define QK1(N, R, A, B, oa, ob, acc) "add.s64 a, " A ", " #oa ";\nadd.s64 b, " B ", " #ob ";\n" \
  "wgmma.mma_async.sync.aligned.m64n" #N "k16.f32.bf16.bf16 {" R "}, a, b, " #acc ", 1, 1, 0, 0;\n"
#define QK8(N, R, A, B) "{\n.reg .b64 a, b;\nwgmma.fence.sync.aligned;\n" QK1(N, R, A, B, 0, 0, 0) QK1(N, R, A, B, 128, 2, 1) \
  QK1(N, R, A, B, 256, 4, 1) QK1(N, R, A, B, 384, 6, 1) QK1(N, R, A, B, 512, 1024, 1) QK1(N, R, A, B, 640, 1026, 1) \
  QK1(N, R, A, B, 768, 1028, 1) QK1(N, R, A, B, 896, 1030, 1) "wgmma.commit_group.sync.aligned;\n}\n"
__device__ __forceinline__ void mma_qk(float (&d)[56], uint64_t dq, uint64_t dk) {
  asm volatile(QK8(112, R56, "%56", "%57")
               : O8(d, 0), O8(d, 8), O8(d, 16), O8(d, 24), O8(d, 32), O8(d, 40), O8(d, 48) : "l"(dq), "l"(dk) : "memory");
}
__device__ __forceinline__ void mma_qk(float (&d)[48], uint64_t dq, uint64_t dk) {
  asm volatile(QK8(96, R48, "%48", "%49")
               : O8(d, 0), O8(d, 8), O8(d, 16), O8(d, 24), O8(d, 32), O8(d, 40) : "l"(dq), "l"(dk) : "memory");
}
__device__ __forceinline__ void mma_n64t(float (&d)[32], uint32_t a0, uint32_t a1, uint32_t a2, uint32_t a3, uint64_t db, bool acc) {
  if (acc)
    asm volatile("wgmma.mma_async.sync.aligned.m64n64k16.f32.bf16.bf16 {" R32A "}, {%32, %33, %34, %35}, %36, 1, 1, 1, 1;\n"
                 : F8(d, 0), F8(d, 8), F8(d, 16), F8(d, 24) : "r"(a0), "r"(a1), "r"(a2), "r"(a3), "l"(db));
  else
    asm volatile("wgmma.mma_async.sync.aligned.m64n64k16.f32.bf16.bf16 {" R32A "}, {%32, %33, %34, %35}, %36, 0, 1, 1, 1;\n"
                 : O8(d, 0), O8(d, 8), O8(d, 16), O8(d, 24) : "r"(a0), "r"(a1), "r"(a2), "r"(a3), "l"(db));
}
__device__ __forceinline__ void mma_n64t_dyn(float (&d)[32], uint32_t a0, uint32_t a1, uint32_t a2, uint32_t a3, uint64_t db, int acc) {
  asm volatile("{\n.reg .pred p;\nsetp.ne.b32 p, %37, 0;\n"
               "wgmma.mma_async.sync.aligned.m64n64k16.f32.bf16.bf16 {" R32A "}, {%32, %33, %34, %35}, %36, p, 1, 1, 1;\n}\n"
               : F8(d, 0), F8(d, 8), F8(d, 16), F8(d, 24) : "r"(a0), "r"(a1), "r"(a2), "r"(a3), "l"(db), "r"(acc));
}
__device__ __forceinline__ void mma_n8(float (&d)[4], uint64_t da, uint64_t db, int acc) {
  asm volatile("{\n.reg .pred p;\nsetp.ne.b32 p, %6, 0;\n"
               "wgmma.mma_async.sync.aligned.m64n8k16.f32.bf16.bf16 {%0, %1, %2, %3}, %4, %5, p, 1, 1, 1, 0;\n}\n"
               : "+f"(d[0]), "+f"(d[1]), "+f"(d[2]), "+f"(d[3])
               : "l"(da), "l"(db), "r"(acc));
}
__device__ __forceinline__ void hmma_k16(float (&d)[4], uint32_t a0, uint32_t a1, uint32_t a2, uint32_t a3, uint32_t b0, uint32_t b1) {
  asm volatile("mma.sync.aligned.m16n8k16.row.col.f32.bf16.bf16.f32 {%0, %1, %2, %3}, {%4, %5, %6, %7}, {%8, %9}, {%0, %1, %2, %3};"
               : "+f"(d[0]), "+f"(d[1]), "+f"(d[2]), "+f"(d[3]) : "r"(a0), "r"(a1), "r"(a2), "r"(a3), "r"(b0), "r"(b1));
}

__device__ __forceinline__ uint32_t pack2(float lo, float hi) {
  uint32_t r;
  asm("cvt.rn.bf16x2.f32 %0, %1, %2;" : "=r"(r) : "f"(hi), "f"(lo));
  return r;
}
__device__ __forceinline__ float bf_lo(uint32_t w) { return __uint_as_float(w << 16); }
__device__ __forceinline__ float bf_hi(uint32_t w) { return __uint_as_float(w & 0xFFFF0000u); }
__device__ __forceinline__ float bfr(float x) { return __bfloat162float(__float2bfloat16_rn(x)); }
__device__ __forceinline__ uint32_t sub2(uint32_t a, uint32_t b) {
  uint32_t r;
  asm("sub.rn.bf16x2 %0, %1, %2;" : "=r"(r) : "r"(a), "r"(b));
  return r;
}
__device__ __forceinline__ uint32_t add2(uint32_t a, uint32_t b) {
  uint32_t r;
  asm("add.rn.bf16x2 %0, %1, %2;" : "=r"(r) : "r"(a), "r"(b));
  return r;
}
__device__ __forceinline__ uint32_t fma2(uint32_t a, uint32_t b, uint32_t c) {
  uint32_t r;
  asm("fma.rn.bf16x2 %0, %1, %2, %3;" : "=r"(r) : "r"(a), "r"(b), "r"(c));
  return r;
}
__device__ __forceinline__ float ex2(float x) {
  float r;
  asm("ex2.approx.ftz.f32 %0, %1;" : "=f"(r) : "f"(x));
  return r;
}
__device__ __forceinline__ float rcp(float x) {
  float r;
  asm("rcp.approx.ftz.f32 %0, %1;" : "=f"(r) : "f"(x));
  return r;
}
__device__ __forceinline__ float silu_f(float t) { return t * rcp(1.0f + ex2(-1.4426950408889634f * t)); }
__device__ __forceinline__ void lds128(uint32_t a, uint32_t& x, uint32_t& y, uint32_t& z, uint32_t& w) {
  asm volatile("ld.shared.v4.u32 {%0, %1, %2, %3}, [%4];" : "=r"(x), "=r"(y), "=r"(z), "=r"(w) : "r"(a) : "memory");
}
__device__ __forceinline__ void ldsm4(uint32_t a, uint32_t& x, uint32_t& y, uint32_t& z, uint32_t& w) {
  asm volatile("ldmatrix.sync.aligned.m8n8.x4.shared.b16 {%0, %1, %2, %3}, [%4];" : "=r"(x), "=r"(y), "=r"(z), "=r"(w) : "r"(a) : "memory");
}
constexpr uint32_t TAG = 0x10000;
__device__ __forceinline__ void st_gran(uint4* p, uint32_t x, uint32_t y, uint32_t z, uint32_t w) {
  asm volatile("st.relaxed.gpu.global.v4.b32 [%0], {%1, %2, %3, %4};" ::"l"(p), "r"(x), "r"(y), "r"(z), "r"(w) : "memory");
}
__device__ __forceinline__ void ld_gran(const uint4* p, uint32_t& x, uint32_t& y, uint32_t& z, uint32_t& w) {
  asm volatile("ld.relaxed.gpu.global.v4.b32 {%0, %1, %2, %3}, [%4];" : "=r"(x), "=r"(y), "=r"(z), "=r"(w) : "l"(p) : "memory");
}
__device__ __forceinline__ void stsm4(uint32_t a, uint32_t x, uint32_t y, uint32_t z, uint32_t w) {
  asm volatile("stmatrix.sync.aligned.m8n8.x4.shared.b16 [%0], {%1, %2, %3, %4};" ::"r"(a), "r"(x), "r"(y), "r"(z), "r"(w) : "memory");
}
__device__ __forceinline__ void cp16(uint32_t dst, const void* src) {
  asm volatile("cp.async.cg.shared.global [%0], [%1], 16;" ::"r"(dst), "l"(src) : "memory");
}
__device__ __forceinline__ void cp_wait_all() { asm volatile("cp.async.wait_all;" ::: "memory"); }
__device__ __forceinline__ void add_granules(float (&red)[32], const uint32_t (&g)[16]) {
#pragma unroll
  for (int i = 0; i < 16; i++) { red[2 * i] += bf_lo(g[i]); red[2 * i + 1] += bf_hi((i & 3) ? g[i] : g[i] & ~TAG); }
}
__device__ __forceinline__ bool granules_ok(const uint32_t (&g)[16], uint32_t tag) {
  uint32_t a, b;
  asm("lop3.b32 %0, %1, %2, %3, 0x7E;" : "=r"(a) : "r"(g[0]), "r"(g[4]), "r"(tag));
  asm("lop3.b32 %0, %1, %2, %3, 0x7E;" : "=r"(b) : "r"(g[8]), "r"(g[12]), "r"(tag));
  return __all_sync(0xffffffffu, ((a | b) & TAG) == 0);
}
__device__ __forceinline__ unsigned ld_acquire(const unsigned* p) {
  unsigned v;
  asm volatile("ld.acquire.gpu.global.u32 %0, [%1];" : "=r"(v) : "l"(p) : "memory");
  return v;
}
__device__ __forceinline__ unsigned atom_add_acq_rel(unsigned* p) {
  unsigned v;
  asm volatile("atom.acq_rel.gpu.global.add.u32 %0, [%1], 1;" : "=r"(v) : "l"(p) : "memory");
  return v;
}

template <int K0, int K1>
__device__ __forceinline__ void ln_fetch(uint32_t (&xa)[144], uint32_t boxes, uint32_t lo) {
#pragma unroll
  for (int k = K0; k < K1; k++) ldsm4(boxes + (k >> 2) * 8192 + (lo ^ ((k & 3) << 5)), xa[4 * k], xa[4 * k + 1], xa[4 * k + 2], xa[4 * k + 3]);
}
__device__ __forceinline__ void ln_fetch_b(uint32_t (&b)[24], uint32_t& wb, uint32_t ws) {
#pragma unroll
  for (int j = 0; j < 6; j++, wb += ws) ldsm4(wb, b[4 * j], b[4 * j + 1], b[4 * j + 2], b[4 * j + 3]);
}
template <int K0, int K1>
__device__ __forceinline__ void ln_sums(const uint32_t (&xa)[144], float (&sm)[X_NS][4], const uint32_t (&b)[24]) {
#pragma unroll
  for (int k = K0; k < K1; k++)
    hmma_k16(sm[k % X_NS], xa[4 * k], xa[4 * k + 1], xa[4 * k + 2], xa[4 * k + 3], b[2 * (k % 12)], b[2 * (k % 12) + 1]);
}
__device__ __forceinline__ void ln_row(float sum, float sq, float& mean_b, float& rstd) {
  const float mean = sum * (1.0f / DM);
  const uint32_t mv = pack2(mean, fmaxf(sq * (1.0f / DM) - mean * mean, 0.0f));
  mean_b = bf_lo(mv);
  float sd;
  asm("sqrt.approx.f32 %0, %1;" : "=f"(sd) : "f"(bf_lo(pack2(bf_hi(mv) + 1e-5f, 0.f))));
  rstd = rcp(bf_lo(pack2(sd, 0.f)));
}

template <bool ROUTED>
__device__ __forceinline__ uint32_t gate2(uint32_t xc, float rstd, float2 upd = make_float2(0.f, 0.f)) {
  uint32_t t = pack2(bf_lo(xc) * rstd, bf_hi(xc) * rstd);
  if (ROUTED) t = pack2(bf_lo(t) + upd.x, bf_hi(t) + upd.y);
  return pack2(silu_f(bf_lo(t)), silu_f(bf_hi(t)));
}

template <int V> struct IC { static constexpr int value = V; };

struct Ctx {
  uint32_t sb;
  uint8_t* sp;
  uint32_t rank;
  Scratch* g;
};

__device__ __forceinline__ bool acquire(const Ctx& cx, uint32_t r, uint32_t n, uint32_t bytes) {
  mbar_wait(cx.sb + SM_EMPTY + 8 * r, (n ^ (r >> 1) ^ 1) & 1);
  __syncwarp();
  const bool e = elect_one();
  if (e) mbar_expect_tx(cx.sb + SM_FULL + 8 * r, bytes);
  return e;
}
__device__ __forceinline__ void load_wq(const Ctx& cx, const CUtensorMap* tmWq, int st, int i, int n0, uint64_t pol) {
  const uint32_t r = st & 3, dst = cx.sb + SM_RING + r * STAGE + cx.rank * 16384, bar = cx.sb + SM_FULL + 8 * r;
  const int k0 = i < 3 ? 128 * i : 128 * i - 64;
  if (acquire(cx, r, st >> 2, i == 2 ? 16384 : 32768)) {
    tma2d_mc(dst, tmWq, n0, k0, bar, pol);
    if (i != 2) tma2d_mc(dst + 8192, tmWq, n0, k0 + 64, bar, pol);
  }
}
__device__ __forceinline__ void attn_producer(const Ctx& cx, int qb, int hs, const CUtensorMap* tmKV, const CUtensorMap* tmWq,
                                              const CUtensorMap* tmWq96, const CUtensorMap* tmWo) {
  const uint32_t full = cx.sb + SM_FULL, ring = cx.sb + SM_RING + cx.rank * 16384;
  const uint64_t last_use = policy_evict_first();
  int st = 0;
#pragma unroll 1
  for (int p = 0; p < 4; p++) {
#pragma unroll 1
    for (int i = 0; i < (p == 2 ? 3 : 5); i++, st++) {
      if (p == 2) {
        if (acquire(cx, st & 3, st >> 2, 24576))
          tma2d_mc(cx.sb + SM_RING + (st & 3) * STAGE + cx.rank * 12288, tmWq96, (hs * 4 + 3) * DH, 192 * i + 96 * cx.rank, full + 8 * (st & 3), last_use);
      } else {
        if (st > 1) load_wq(cx, tmWq, st, i, (hs * 4 + (p ^ (p >> 1))) * DH + cx.rank * 64, last_use);
      }
      if (st == 1 || st == 2) TSP(72 + st)
      if (st == X_PFW) {
#pragma unroll 1
        for (int b = qb < 8; b < 5 - (qb >> 3); b++)
          if (elect_one()) tma2d_prefetch(tmWq, hs * 512 + (b < 4 ? (b ^ (b >> 1)) * DH + (qb & 1) * 64 : qb * 64), b < 4 ? (qb >> 1) * 64 : 512);
      }
      if (st == 8 && qb < 8 && elect_one()) tma2d_prefetch(tmKV + ((qb >> 1) & 1), cx.rank * 64, hs * 2 * SEQ + (qb >> 2) * 96);
    }
  }
  uint32_t r = 2, n = 4;
  int row = hs * 2 * SEQ, rows = 96;
  const CUtensorMap* tm = tmKV + 2;
#pragma unroll 1
  for (int u = 0; u < NST_KV; u++) {
    if (acquire(cx, r, n, rows * 256)) {
      tma2d_mc(ring + r * STAGE, tm, cx.rank * 64, row, full + 8 * r, last_use);
      if (((u ^ (qb >> 1)) & 7) == 0 && u < NST_KV - 4) tma2d_prefetch(tmKV + (u & 1), cx.rank * 64, row + 208);
      if ((unsigned)(u - 32) < 36 && (u & 15) == qb) tma2d_prefetch(tmWo, ((u - 32) >> 2) * 64, hs * 512 + (u & 3) * 128);
    }
    if (++r == 4) { r = 1; n++; }
    if (u & 1) row += rows;
    const bool big = (unsigned)(u - 9) < 56;
    rows = big ? 112 : 96;
    tm = tmKV + (~u & 1) + (big ? 0 : 2);
  }
#pragma unroll 1
  for (int u = 0; u < NST_O; u++) {
    const int s = u >> 1;
    const int blk = s == 0 ? 8 : ((hs + s) & 7);
    r = (0x87 >> (2 * (u & 3))) & 3;
    if (acquire(cx, r, (u >> 2) ^ ~u, 32768))
      tma2d_mc(ring + r * STAGE, tmWo, blk * 64, hs * 512 + ((u & 1) + cx.rank * 2) * 128, full + 8 * r, last_use);
  }
}

__device__ __forceinline__ void sq_publish(const Ctx& cx, int qb, int hs, int j, int lane) {
  if (j == 2 && lane == 0) {
    const unsigned e = cx.g->launch[hs * 16 + qb]++;
    *(uint2*)(cx.sp + SM_TAG) = make_uint2((~e & 1) * TAG, e);
  }
  const int row = (hs & 3) * 16 + (lane >> 1);
  uint32_t a = cx.sb + SM_X + (hs >> 2) * 73728 + j * 8192 + row * 128 + (((lane & 1) ^ (row & 7)) << 4);
  float s0 = 0.f, s1 = 0.f;
#pragma unroll 1
  for (int b = 0; b < 6; b++) {
    if (b == (hs < 4 ? 4 : 0)) {
      const int n = 224 + (__float_as_uint(s1) & blockIdx.y);
      if (j == 1) {
        bar_sync(BAR_XREL, n);
        if (lane < 4) asm volatile("mbarrier.arrive.shared::cluster.b64 _, [%0], 2;" ::"r"(mapa(cx.sb + SM_EMPTY + 16 + 8 * (lane >> 1), lane & 1)) : "memory");
      } else {
        bar_arrive(BAR_XREL, n);
      }
      __syncwarp();
      if (hs == 8) return;
    }
    if (!(b & 1)) mbar_wait(cx.sb + SM_XFULL + 32 * (hs >> 2) + 4 * b, 0);
    uint32_t v[8];
    lds128(a, v[0], v[1], v[2], v[3]);
    lds128(a ^ 32, v[4], v[5], v[6], v[7]);
    a = (a ^ 64) + (b & 1) * 24576;
#pragma unroll
    for (int i = 0; i < 8; i++) { s0 = fmaf(bf_lo(v[i]), bf_lo(v[i]), s0); s1 = fmaf(bf_hi(v[i]), bf_hi(v[i]), s1); }
  }
  s0 += s1;
  s0 += __shfl_xor_sync(0xffffffffu, s0, 1);
  float* part = (float*)(cx.sp + SM_STATS) + (lane >> 1) * 2;
  if (j < 2) {
    part[32 * j] = s0;
    bar_arrive(BAR_HELPER, 96);
  } else {
    bar_sync(BAR_HELPER, 96);
    TSP(68)
    if (!(lane & 1))
      asm volatile("st.relaxed.gpu.global.v2.b32 [%0], {%1, %2};" ::"l"(cx.g->sq + qb * 128 + hs * 16 + (lane >> 1)),
                   "r"(__float_as_uint((part[0] + part[32]) + s0)), "r"(*(const uint32_t*)(cx.sp + SM_TAG + 4) + 1) : "memory");
  }
}
__device__ __forceinline__ void sq_collect(const Ctx& cx, int qb, int lane) {
  const uint32_t e1 = *(const uint32_t*)(cx.sp + SM_TAG + 4) + 1;
#pragma unroll 1
  for (int n = 0; n < (1 << 16); n++) {
    __nanosleep(X_SQS);
    uint32_t bad = 0;
#pragma unroll
    for (int i = 0; i < 2; i++) {
      uint32_t a, t0, b, t1;
      ld_gran((const uint4*)(cx.g->sq + qb * 128) + i * 32 + lane, a, t0, b, t1);
      *(uint32_t*)(cx.sp + SM_STATS + (i * 32 + lane) * 16 + 4) = a;
      *(uint32_t*)(cx.sp + SM_STATS + (i * 32 + lane) * 16 + 12) = b;
      bad |= (t0 ^ e1) | (t1 ^ e1);
    }
    if (__all_sync(0xffffffffu, bad == 0)) break;
  }
  __syncwarp();
  if (lane == 0) mbar_arrive(cx.sb + SM_BAR_SQ);
  TSP(69)
}
__device__ __forceinline__ void attn_gate(const Ctx& cx, int qb, int hs, int j, int t, const __nv_bfloat16* x) {
  const uint4* xp = (const uint4*)(x + qb * 128 * DM) + (t >> 3) * 72 + hs * 8 + (t & 7);
  uint4 nx = *xp;
  float wsum = 0.f;
  if (j == 0) {
    mbar_wait(cx.sb + SM_BAR_W, 0);
#pragma unroll 3
    for (int i = 0; i < 9; i++) {
      const uint32_t w = *(const uint32_t*)(cx.sp + SM_WR + i * 128 + t * 4);
      wsum += bf_lo(w) + bf_hi(w);
    }
#pragma unroll
    for (int i = 1; i < 32; i *= 2) wsum += __shfl_xor_sync(0xffffffffu, wsum, i);
  }
  bar_sync(BAR_GATE, 352);
  if (t < 16) {
    const float2 st = *(const float2*)(cx.sp + SM_STATS + 8 * (hs * 16 + t));
    const int row = qb * 128 + hs * 16 + t;
    const uint32_t b = pack2(0.f, fmaf(-st.x, wsum, *(const float*)(cx.sp + SM_RAW + 4 * t)) * st.y);
    st_gran(cx.g->stats + row, __float_as_uint(st.x), __float_as_uint(st.y), (b ^ ((int)b < 0 ? 0xFFFF0000u : 0x80000000u)) | (0xFFFF - row),
            *(const uint32_t*)(cx.sp + SM_TAG + 4) + 1);
  }
  __syncwarp();
  uint32_t sa = cx.sb + SM_STATS + (t & ~7);
  uint4* gp = cx.g->gate + blockIdx.x * 1152 + (t ^ ((t >> 3) & 7));
  const int cross = t < 64 ? 10 : 9;
#pragma unroll 1
  for (int i = 0; i < 12; i++) {
    float2 st;
    asm volatile("ld.shared.v2.f32 {%0, %1}, [%2];" : "=f"(st.x), "=f"(st.y) : "r"(sa));
    const uint32_t mm = pack2(st.x, st.x);
    const uint4 v = make_uint4(sub2(nx.x, mm), sub2(nx.y, mm), sub2(nx.z, mm), sub2(nx.w, mm));
    xp += 12 * 72;
    sa += 96;
    if (i == cross) { xp += (hs * 16 - 128) * 72 + 64 - hs * 8; sa += (hs * 16 - 128) * 8; }
    if (i < 11) nx = *xp;
    *gp = make_uint4(gate2<false>(v.x, st.y), gate2<false>(v.y, st.y), gate2<false>(v.z, st.y), gate2<false>(v.w, st.y));
    gp = (uint4*)((size_t)(gp + 96) ^ 64);
  }
}

constexpr uint32_t SM_XO = SM_SLOT, SM_GO = SM_SLOT + STAGE, SM_P8 = SM_SLOT + 2 * STAGE;
__device__ __forceinline__ void attn_helper(const Ctx& cx, int qb, int hs, int lane, const CUtensorMap* tmX16) {
  const unsigned e = *(const uint32_t*)(cx.sp + SM_TAG + 4);
  bar_sync(BAR_HELPER, 64);
  bool todo = lane < 2;
#pragma unroll 1
  for (int n = 0; __any_sync(0xffffffffu, todo); n++) {
    if (todo && (ld_acquire(&cx.g->qflag[(qb * 4 + (hs >> 1)) * 2 + lane]) == e + 1 || n == (1 << 16))) {
      asm volatile("fence.proxy.async.global;" ::: "memory");
      mbar_expect_tx(cx.sb + SM_BAR_Q + 8 * lane, 8192);
      bulk_load(cx.sb + SM_SLOT + 2 * STAGE + lane * 16384 + 8192, cx.g->q + ((qb * 8 + hs) * 2 + lane) * 512, 8192, cx.sb + SM_BAR_Q + 8 * lane);
      todo = false;
    }
  }
  const uint32_t tag = (~e & 1) * TAG;
  const uint4* src = cx.g->part + (size_t)((qb * 64 + 56) * 2 + (hs >> 2)) * 4 * 128 + (hs & 3) * 32 + lane;
  const uint32_t stg = cx.sb + SM_P8 + lane * 16;
  bar_sync(BAR_OA, 352);
  asm volatile("fence.proxy.async.global;" ::: "memory");
  if (lane == 0) {
    mbar_expect_tx(cx.sb + SM_BAR_MISC, 2 * 18432);
    bulk_load(cx.sb + SM_GO, cx.g->gate + blockIdx.x * 1152, 18432, cx.sb + SM_BAR_MISC);
#pragma unroll 1
    for (int i = 0; i < 9; i++)
      tma2d(cx.sb + SM_XO + i * 2048, tmX16, i < 8 ? hs * 64 : 512, qb * 128 + (i < 8 ? i : hs) * 16, cx.sb + SM_BAR_MISC);
  }
#pragma unroll 1
  for (int n = 0; n < (1 << 16); n++) {
    __nanosleep(n ? 500 : 2000);
    uint32_t a, b, d, t;
    ld_gran(src - lane + (lane & 7) * (2 * 4 * 128) + 3 * 128 + 31, a, b, d, t);
    if (__all_sync(0xffffffffu, (a & TAG) == tag)) break;
  }
#pragma unroll 1
  for (int n = 0; n < (1 << 16); n++) {
#pragma unroll 1
    for (int i = 0; i < 8; i++) {
#pragma unroll
      for (int g = 0; g < 4; g++) cp16(stg + (i * 4 + g) * 512, src + i * (2 * 4 * 128) + g * 128);
    }
    cp_wait_all();
    uint32_t bad = 0;
#pragma unroll 4
    for (int i = 0; i < 32; i++) bad |= *(const volatile uint32_t*)(cx.sp + SM_P8 + lane * 16 + i * 512) ^ tag;
    if (__all_sync(0xffffffffu, (bad & TAG) == 0)) break;
  }
#pragma unroll 1
  for (int n = 0; n < (1 << 16) && ld_acquire(&cx.g->ycnt) != 4 * (e + 1); n++) __nanosleep(200);
  const int2 sel = __ldcg(&cx.g->sel[lane & 7]);
  const int lr = sel.x - qb * 128;
  uint32_t m = __ballot_sync(0xffffffffu, lane < 16 && ((lane & 8) ? (lr >> 4) == hs : (lr >> 7) == 0));
  mbar_wait(cx.sb + SM_BAR_MISC, 0);
#pragma unroll 1
  for (; m; m &= m - 1) {
    const int i = __ffs(m) - 1, row = __shfl_sync(0xffffffffu, lr, i);
    const float rs = __int_as_float(__shfl_sync(0xffffffffu, sel.y, i));
    const float* p = cx.g->ypart + (i & 7) * DM + (i < 8 ? hs * 64 : 512) + 2 * lane;
    const float2 a = __ldcg((const float2*)p), b = __ldcg((const float2*)(p + TOPC * DM)), c = __ldcg((const float2*)(p + 2 * TOPC * DM)),
                 d = __ldcg((const float2*)(p + 3 * TOPC * DM));
    const uint32_t y = pack2((a.x + b.x) + (c.x + d.x), (a.y + b.y) + (c.y + d.y));
    const uint32_t u = pack2(bf_lo(y) * rs, bf_hi(y) * rs);
    const float2 st = *(const float2*)(cx.sp + SM_STATS + 8 * row);
    const int o = (i < 8 ? row : 128 + (row & 15)) * 128 + ((lane * 4) ^ ((row & 7) << 4));
    *(uint32_t*)(cx.sp + SM_GO + o) = gate2<true>(sub2(*(const uint32_t*)(cx.sp + SM_XO + o), pack2(st.x, st.x)), st.y, make_float2(bf_lo(u), bf_hi(u)));
  }
  __syncwarp();
  if (lane == 0) mbar_arrive(cx.sb + SM_BAR_XG);
}
__device__ __forceinline__ void attn_finish8(const Ctx& cx, int qb, int hs, int hw, int lane, __nv_bfloat16* out) {
  bar_sync(BAR_GATE, 96);
#pragma unroll 1
  for (int g = hw; g < 4; g += 3) {
    float acc[8] = {0.f, 0.f, 0.f, 0.f, 0.f, 0.f, 0.f, 0.f};
#pragma unroll 2
    for (int sidx = 0; sidx < 8; sidx++) {
      uint32_t a, b, d, t;
      lds128(cx.sb + SM_P8 + lane * 16 + (sidx * 4 + g) * 512, a, b, d, t);
      acc[0] += bf_lo(a); acc[1] += bf_hi(a & ~TAG); acc[2] += bf_lo(b); acc[3] += bf_hi(b);
      acc[4] += bf_lo(d); acc[5] += bf_hi(d); acc[6] += bf_lo(t); acc[7] += bf_hi(t);
    }
#pragma unroll
    for (int j = 0; j < 4; j++) {
      const int o = (128 + (lane >> 2) + (j & 1) * 8) * 128 + (((2 * g + (j >> 1)) ^ (lane >> 2)) << 4) + (lane & 3) * 4;
      uint32_t* xp = (uint32_t*)(cx.sp + SM_XO + o);
      *xp = fma2(pack2(acc[2 * j], acc[2 * j + 1]), *(const uint32_t*)(cx.sp + SM_GO + o), *xp);
    }
  }
  bar_sync(BAR_GATE, 96);
#pragma unroll 1
  for (int ch = threadIdx.x - 32; ch < 128; ch += 96)
    *(uint4*)(out + (size_t)(qb * 128 + hs * 16 + (ch >> 3)) * DM + 512 + (ch & 7) * 8) =
        *(const uint4*)(cx.sp + SM_XO + 16384 + (ch ^ ((ch >> 3) & 7)) * 16);
}

__device__ __forceinline__ void ffn_producer(const Ctx& cx, int f, const CUtensorMap* tmWq, const CUtensorMap* tmG,
                                             const CUtensorMap* tmU, const CUtensorMap* tmD) {
  uint64_t keep;
  asm("createpolicy.fractional.L2::evict_normal.b64 %0, 1.0;" : "=l"(keep));
  int st = 0;
#pragma unroll 1
  for (int p = 0; p < 16; p++) {
#pragma unroll 1
    for (int i = 0; i < 5; i++, st++) if (st > 1) load_wq(cx, tmWq, st, i, ((2 * (p & 3) + cx.rank) * 4 + 3) * DH + 64, keep);
  }
  const uint32_t full = cx.sb + SM_FFULL, empty = cx.sb + SM_FEMPTY;
  int pair = 0, u = 0;
#pragma unroll 1
  for (st = 0; st < 14 * 12; st++) {
    const uint32_t sl = st & 7;
    const int unit = pair * 2 + (u & 1), k = u >> 1, k3 = k >= 3 ? k - 3 : k;
    if (unit < 27) {
      mbar_wait(empty + 8 * sl, (st >> 3) & 1);
      __syncwarp();
      if (elect_one()) {
        mbar_expect_tx(full + 8 * sl, FSTAGE);
        if (pair < 9) tma2d_stream(cx.sb + sl * FSTAGE, k < 3 ? tmG : tmU, f * 1152 + unit * 64, k3 * 192, full + 8 * sl);
        else tma2d_stream(cx.sb + sl * FSTAGE, tmD, (unit - 18) * 64, f * 1152 + k * 192, full + 8 * sl);
      }
    }
    if (++u == 12) { u = 0; pair++; }
  }
}
__device__ __forceinline__ void load_x1(uint32_t dst, const CUtensorMap* tmX64, int row, int box, int n, uint32_t bar) {
  mbar_expect_tx(bar, n * 8192);
#pragma unroll 1
  for (int i = 0; i < n; i++) tma2d(dst + i * 8192, tmX64, (box + i) * 64, row, bar);
}
__device__ __forceinline__ void ffn_publish(const Ctx& cx, int f, int w, int lane, const CUtensorMap* tmX64) {
  const uint32_t xs = cx.sb + SM_SLOT + w * 49152, xf = cx.sb + SM_XFULL + w * 32;
#pragma unroll 1
  for (int n = 0; n < 16; n++) {
    const int p = n & 3, row = (f + (n & 12) + 4) * 128 + w * 64;
    bar_sync(BAR_QS + w, 160);
    const uint32_t e1 = *(const uint32_t*)(cx.sp + SM_TAG + 4) + 1;
    if (lane == 0) {
#pragma unroll
      for (int i = 0; i < 2; i++)
        asm volatile("cp.async.bulk.global.shared::cta.bulk_group [%0], [%1], 8192;"
                     ::"l"(cx.g->q + (((f + (n & 12)) * 8 + 2 * p + i) * 2 + w) * 512), "r"(xs + 32768 + i * 8192) : "memory");
      asm volatile("cp.async.bulk.commit_group;" ::: "memory");
      if (n < 12 && (p == 0 || p == 3)) load_x1(xs, tmX64, row, p ? 4 : 0, 4, xf + (p ? 8 : 0));
      asm volatile("cp.async.bulk.wait_group.read 0;" ::: "memory");
      if (n < 12 && p == 3) load_x1(xs + 32768, tmX64, row, 8, 1, xf + 16);
      asm volatile("cp.async.bulk.wait_group 0;\nfence.proxy.async.global;" ::: "memory");
      asm volatile("st.release.gpu.global.u32 [%0], %1;" ::"l"(&cx.g->qflag[((f + (n & 12)) * 4 + p) * 2 + w]), "r"(e1) : "memory");
    }
    __syncwarp();
    if (n < 12 && p == 1) {
#pragma unroll 1
      for (int i = 0, k = 0; i < 64 && k < (1 << 16); k++) {
        uint32_t m, r, z, t;
        ld_gran(cx.g->stats + row + i + lane, m, r, z, t);
        *(uint2*)(cx.sp + SM_STATS + 8 * (w * 64 + i + lane)) = make_uint2(m, r);
        if (__all_sync(0xffffffffu, t == e1)) i += 32;
      }
    }
    bar_arrive(BAR_QF + w, 160);
  }
}

__device__ __forceinline__ void ffn_consumer(const Ctx& cx, int f, int wg, int cw, int lane, const __nv_bfloat16* x) {
  const int r = lane >> 2, c = lane & 3, tid = cw * 32 + lane;
  const uint32_t full = cx.sb + SM_FFULL, empty = cx.sb + SM_FEMPTY;
  const bool signaller = (tid & 127) == 0;
  prof(wg, 8);
  const unsigned e = *(const uint32_t*)(cx.sp + SM_TAG + 4);
  uint32_t key[8];
#pragma unroll 1
  for (int n = 0; n < (1 << 16); n++) {
    uint32_t bad = 0;
#pragma unroll
    for (int i = 0; i < 8; i++) {
      uint32_t t;
      asm volatile("ld.relaxed.gpu.global.v2.b32 {%0, %1}, [%2];" : "=r"(key[i]), "=r"(t) : "l"(&cx.g->stats[i * 256 + tid].z) : "memory");
      bad |= t ^ (e + 1);
    }
    if (__all_sync(0xffffffffu, bad == 0)) break;
  }
  bar_sync(BAR_QF + wg, 160);
  bar_sync(3, 256);
  if (tid < 8) mbar_arrive(empty + 8 * tid);
  prof(wg, 9);
  int mysel = 0;
#pragma unroll 1
  for (int k = 0; k < TOPC; k++) {
    uint32_t m = key[0];
#pragma unroll
    for (int i = 1; i < 8; i++) m = max(m, key[i]);
    m = __reduce_max_sync(0xffffffffu, m);
    uint32_t* tk = (uint32_t*)(cx.sp + SM_TOPK) + (k & 1) * 8;
    if (lane == 0) tk[cw] = m;
    bar_sync(3, 256);
    m = __reduce_max_sync(0xffffffffu, tk[lane & 7]);
#pragma unroll
    for (int i = 0; i < 8; i++) if (key[i] == m) key[i] = 0;
    if (k == cw) mysel = 0xFFFF - (int)(m & 0xFFFF);
  }
  {
    const float4 st = __ldcg((const float4*)&cx.g->stats[mysel]);
    const uint32_t mm = pack2(st.x, st.x);
#pragma unroll 3
    for (int i = 0; i < 9; i++) {
      const uint32_t t = sub2(*(const uint32_t*)(x + (size_t)mysel * DM + i * 64 + 2 * lane), mm);
      *(uint32_t*)(cx.sp + SM_XSEL + i * 1024 + cw * 128 + (((lane >> 2) ^ cw) << 4) + (lane & 3) * 4) =
          pack2(bf_lo(t) * st.y, bf_hi(t) * st.y);
    }
    const uint32_t k = __float_as_uint(st.z);
    const float score = bf_hi(k ^ ((int)k < 0 ? 0x80000000u : 0xFFFF0000u));
    if (lane == 0 && f == 0) cx.g->sel[cw] = make_int2(mysel, __float_as_int(bfr(rcp(1.0f + ex2(-1.4426950408889634f * score)))));
  }
  asm volatile("fence.proxy.async.shared::cta;" ::: "memory");
  bar_sync(3, 256);
  prof(wg, 10);
  auto run = [&](float (&acc)[4], int st, int n, uint32_t b) {
#pragma unroll 1
    for (int u = 0; u < n; u++, st += 2, b += 3072) {
      const uint32_t sl = st & 7;
      mbar_wait(full + 8 * sl, (st >> 3) & 1);
      wg_fence();
      const uint64_t da = mkdesc(cx.sb + sl * FSTAGE, 16), db = mkdesc(b, 16);
#pragma unroll
      for (int k = 0; k < 12; k++) mma_n8(acc, da + k * 128, db + (k >> 2) * 64 + (k & 3) * 2, u > 0 || k > 0);
      wg_commit();
      wg_wait<0>();
      if (signaller) mbar_arrive(empty + 8 * sl);
    }
    pin(acc);
  };
#pragma unroll 1
  for (int unit = wg; unit < 27; unit += 2) {
    if (unit >> 1 == 9) {
      asm volatile("fence.proxy.async.shared::cta;" ::: "memory");
      bar_sync(3, 256);
      prof(wg, 11);
    }
    const bool gu = unit < 18;
    float a0[4], a1[4];
#pragma unroll 1
    for (int m = 0; m < (gu ? 2 : 1); m++) {
      run(a1, (unit >> 1) * 12 + m * 6 + wg, gu ? 3 : 6, cx.sb + (gu ? SM_XSEL : SM_H));
      if (m == 0) { a0[0] = a1[0]; a0[1] = a1[1]; a0[2] = a1[2]; a0[3] = a1[3]; }
    }
    float u0 = a1[0], u1 = a1[1];
#pragma unroll 1
    for (int i = 0; i < 2; i++) {
      const int fl = (cw & 3) * 16 + r + i * 8;
      if (gu) {
        const uint32_t g = pack2(a0[0], a0[1]);
        const uint32_t h = fma2(pack2(silu_f(bf_lo(g)), silu_f(bf_hi(g))), pack2(u0, u1), 0x80008000u);
        uint8_t* hp = cx.sp + SM_H + unit * 1024 + c * 256 + (fl & 7) * 2;
        *(uint16_t*)(hp + (((fl >> 3) ^ (2 * c)) << 4)) = (uint16_t)h;
        *(uint16_t*)(hp + 128 + (((fl >> 3) ^ (2 * c + 1)) << 4)) = (uint16_t)(h >> 16);
      } else {
        float* yp = cx.g->ypart + (f * TOPC + 2 * c) * DM + (unit - 18) * 64 + fl;
        yp[0] = u0;
        yp[DM] = u1;
      }
      a0[0] = a0[2]; a0[1] = a0[3]; u0 = a1[2]; u1 = a1[3];
    }
  }
  prof(wg, 12);
  bar_sync(3, 256);
  if (tid == 0) atom_add_acq_rel(&cx.g->ycnt);
  prof(wg, 13);
}

constexpr float SUM_HI = 1.8446744e19f, SUM_LO = 9.0949470e-13f;

template <int LO, int HI, int N>
__device__ __forceinline__ void softmax_exp(float (&s)[N]) {
#pragma unroll
  for (int i = LO; i < HI; i++) s[i] = ex2(s[i]);
}
__device__ __forceinline__ void sum_tree(const uint32_t (&pf)[28], bool big, uint32_t& h0, uint32_t& h1) {
  uint32_t t0 = add2(add2(pf[16], pf[18]), add2(pf[20], pf[22])), t1 = add2(add2(pf[17], pf[19]), add2(pf[21], pf[23]));
  if (big) { t0 = add2(t0, add2(pf[24], pf[26])); t1 = add2(t1, add2(pf[25], pf[27])); }
  h0 = add2(add2(add2(add2(pf[0], pf[2]), add2(pf[4], pf[6])), add2(add2(pf[8], pf[10]), add2(pf[12], pf[14]))), t0);
  h1 = add2(add2(add2(add2(pf[1], pf[3]), add2(pf[5], pf[7])), add2(add2(pf[9], pf[11]), add2(pf[13], pf[15]))), t1);
}
__device__ __forceinline__ void exact_attention(float (&o)[16], float& l0, float& l1, const uint32_t (&q)[32], const __nv_bfloat16* kp,
                                                const __nv_bfloat16* vp) {
  float m0 = -3.0e38f, m1 = -3.0e38f;
  l0 = l1 = 0.f;
#pragma unroll
  for (int i = 0; i < 16; i++) o[i] = 0.f;
#pragma unroll 1
  for (int key = 0; key < SEQ; key += 8, kp += 8 * DH, vp += 8 * DH) {
    float d[4] = {0.f, 0.f, 0.f, 0.f};
#pragma unroll
    for (int k = 0; k < 8; k++)
      hmma_k16(d, q[4 * k], q[4 * k + 1], q[4 * k + 2], q[4 * k + 3], *(const uint32_t*)(kp + k * 16), *(const uint32_t*)(kp + k * 16 + 8));
    float x0 = fmaxf(d[0], d[1]), x1 = fmaxf(d[2], d[3]);
    x0 = fmaxf(x0, __shfl_xor_sync(0xffffffffu, x0, 1));
    x1 = fmaxf(x1, __shfl_xor_sync(0xffffffffu, x1, 1));
    x0 = fmaxf(fmaxf(x0, __shfl_xor_sync(0xffffffffu, x0, 2)), m0);
    x1 = fmaxf(fmaxf(x1, __shfl_xor_sync(0xffffffffu, x1, 2)), m1);
    const float sc0 = ex2(m0 - x0), sc1 = ex2(m1 - x1);
    m0 = x0; m1 = x1;
    const uint32_t p0 = pack2(ex2(d[0] - m0), ex2(d[1] - m0)), p1 = pack2(ex2(d[2] - m1), ex2(d[3] - m1));
    l0 = fmaf(l0, sc0, bf_lo(p0) + bf_hi(p0));
    l1 = fmaf(l1, sc1, bf_lo(p1) + bf_hi(p1));
#pragma unroll
    for (int nb = 0; nb < 4; nb++) {
      uint32_t b;
      asm("movmatrix.sync.aligned.m8n8.trans.b16 %0, %1;" : "=r"(b) : "r"(*(const uint32_t*)(vp + nb * 8)));
      o[4 * nb] *= sc0; o[4 * nb + 1] *= sc0; o[4 * nb + 2] *= sc1; o[4 * nb + 3] *= sc1;
      asm volatile("mma.sync.aligned.m16n8k8.row.col.f32.bf16.bf16.f32 {%0, %1, %2, %3}, {%4, %5}, {%6}, {%0, %1, %2, %3};"
                   : "+f"(o[4 * nb]), "+f"(o[4 * nb + 1]), "+f"(o[4 * nb + 2]), "+f"(o[4 * nb + 3]) : "r"(p0), "r"(p1), "r"(b));
    }
  }
}
__device__ __forceinline__ bool inv_sums(float l0, float l1, float& i0, float& i1) {
  l0 += __shfl_xor_sync(0xffffffffu, l0, 1); l1 += __shfl_xor_sync(0xffffffffu, l1, 1);
  l0 += __shfl_xor_sync(0xffffffffu, l0, 2); l1 += __shfl_xor_sync(0xffffffffu, l1, 2);
  i0 = rcp(l0);
  i1 = rcp(l1);
  return !(l0 + l1 <= SUM_HI) | (fminf(l0, l1) < SUM_LO);
}
template <int LO, int HI, int N>
__device__ __forceinline__ void park(uint32_t a, const float (&o)[N], float i0, float i1, bool on = true) {
#pragma unroll
  for (int i = LO; i < HI; i++)
    asm volatile("{\n.reg .pred p;\nsetp.ne.u32 p, %5, 0;\n@p stmatrix.sync.aligned.m8n8.x4.shared.b16 [%0], {%1, %2, %3, %4};\n}"
                 ::"r"(a + i * 2048), "r"(pack2(o[8 * i] * i0, o[8 * i + 1] * i0)), "r"(pack2(o[8 * i + 2] * i1, o[8 * i + 3] * i1)),
                 "r"(pack2(o[8 * i + 4] * i0, o[8 * i + 5] * i0)), "r"(pack2(o[8 * i + 6] * i1, o[8 * i + 7] * i1)), "r"((uint32_t)on) : "memory");
}

template <int I, int NP, int E0, int N, int NS>
__device__ __forceinline__ void exp_park(float (&s)[NS], uint32_t a, const float (&o)[64], float i0, float i1, bool on, int id) {
  if constexpr (I < NP) {
    constexpr int E1 = E0 + (N - E0) * X_PG / (NP - I);
    softmax_exp<E0, E1>(s);
    park<I, I + X_PG>(a, o, i0, i1, on);
    if (I + X_PG < NP) {
#pragma unroll
      for (int i = E0; i < E1; i++) asm volatile("" : "+f"(s[i])::"memory");
      block_fence(id + I);
    }
    exp_park<I + X_PG, NP, E1, N>(s, a, o, i0, i1, on, id);
  }
}

__device__ __forceinline__ void attn_consumer(const Ctx& cx, bool hlp, int qb, int hs, int wg, int cw, int lane, const __nv_bfloat16* x,
                                              const __nv_bfloat16* kc, const __nv_bfloat16* vc, __nv_bfloat16* out) {
  const uint32_t full = cx.sb + SM_FULL;
  const uint32_t ring = cx.sb + SM_RING;
  const uint32_t qwg = ring + wg * 16384;
  auto qlane = [&](int l) { return qwg + (cw & 3) * 256 + (l >> 4) * 1024 + (l & 15) * 16; };
  const bool signaller = lane == 0 && (cw & 3) < 2;
  const int my_turn = 1 + wg, other_turn = 2 - wg;
  const uint32_t empty_c = mapa(cx.sb + SM_EMPTY, cw & 1);

  float oA[64], oB[64], i0, i1;
  uint32_t xl[32];
  {
    const int r = lane >> 2, c = lane & 3;
    const int lr0 = cw * 16 + r;
    uint32_t xa[144];
    uint32_t mm0, mm1;
    float rstd0, rstd1, sq0 = 0.f, sq1 = 0.f;
    const uint32_t xf = cx.sb + SM_XFULL + wg * 32, xs = cx.sb + SM_SLOT + wg * 49152;
    auto lo_of = [&](int l) { return ((cw & 3) * 16 + (l & 15)) * 128 + (((l >> 4) ^ (l & 7)) << 4); };
    prof(wg, 0);
    {
      const uint32_t lo = lo_of(lane);
      const uint32_t xb = cx.sb + SM_X + wg * 73728;
      float sm[X_NS][4] = {};
      const uint32_t ws = (lane & 7) == 1 ? 64 : 0;
      uint32_t wb = cx.sb + (ws ? SM_WR + (lane >> 3) * 16 : SM_ONES);
      uint32_t b0[24], b1[24], b2[24];
      TS4(1)
      mbar_wait(cx.sb + SM_BAR_W, 0);
      if (X_LN == 0) {
        ln_fetch_b(b0, wb, ws);
        ln_fetch_b(b1, wb, ws);
        ln_fetch_b(b2, wb, ws);
      }
      mbar_wait(xf, 0);
      TS4(2)
      ln_fetch<0, 12>(xa, xb, lo);
      if (X_LN == 1) {
        ln_fetch_b(b0, wb, ws);
        ln_fetch_b(b1, wb, ws);
        ln_fetch_b(b2, wb, ws);
      }
      ln_sums<0, 12>(xa, sm, b0);
      mbar_wait(xf + 8, 0);
      TS4(3)
      ln_fetch<12, 24>(xa, xb, lo);
      if (wg == 0) {
        bar_arrive(BAR_XREL + (xa[95] & blockIdx.y), 224);
      }
      ln_sums<12, 24>(xa, sm, b1);

      mbar_wait(xf + 16, 0);
      TS4(4)
      prof(wg, 1);
      ln_fetch<24, 36>(xa, xb, lo);
      ln_sums<24, 36>(xa, sm, b2);
#pragma unroll
      for (int i = 0; i < 4; i++) sm[0][i] = X_NS == 2 ? sm[0][i] + sm[1][i] : X_NS == 3 ? sm[0][i] + sm[1][i] + sm[2][i] : (sm[0][i] + sm[1][i]) + (sm[2][i] + sm[X_NS - 1][i]);
      if (cw == hs && c == 0) {
        *(float*)(cx.sp + SM_RAW + 4 * r) = sm[0][1];
        *(float*)(cx.sp + SM_RAW + 4 * r + 32) = sm[0][3];
      }
      rstd0 = sm[0][0];
      rstd1 = sm[0][2];
      mm0 = pack2(rstd0 * (1.0f / DM), rstd0 * (1.0f / DM));
      mm1 = pack2(rstd1 * (1.0f / DM), rstd1 * (1.0f / DM));
    }
#pragma unroll
    for (int i = 0; i < 16; i++) { xa[2 * i] = sub2(xa[2 * i], mm0); xa[2 * i + 1] = sub2(xa[2 * i + 1], mm1); }
    pin(xa);
    prof(wg, 2);
    TS4(5)

    float (&acc)[64] = oB;
    int st0 = 0;
#pragma unroll 1
    for (int n = 0; n < 16; n++) {
      const int p = n & 3, rb = n >> 2;
      const bool last = p == 3 && !hlp;
#pragma unroll
      for (int i = 0; i < 5; i++) {
        if (i == 4 && last) {
          wg_wait<1>();
          if (signaller && wg) mbar_arrive_cluster(empty_c + 8 * 3);
          wg_wait<0>();
          pin(acc);
          prof(wg, 6);
#pragma unroll
          for (int j = 0; j < 32; j++) xl[j] = xa[112 + j];
          i0 = rstd0;
          i1 = rstd1;
          goto attention;
        }
        const int st = st0 + i;
        const uint32_t sl = st & 3, slp = (st - 1) & 3;
        if (!wg) mbar_wait(full + 8 * sl, (st >> 2) & 1);
        TS4(8 + 2 * (p * 5 + i))
        const bool join = wg && last;
        if ((i || st0 + wg) && i != (wg ? 4 : 1) && !(join && i == 3)) bar_sync(my_turn, 256);
        wg_fence();
        const uint64_t db = mkdesc(ring + sl * STAGE, 16384);
        const int kb0 = i < 3 ? 8 * i : 8 * i - 4;
#pragma unroll
        for (int k = 0; k < (i == 2 ? 4 : 8); k++) {
          const int kb = kb0 + k;
          mma_n128t(acc, xa[4 * kb], xa[4 * kb + 1], xa[4 * kb + 2], xa[4 * kb + 3], db + k * 128, kb > 0);
        }
        wg_commit();
        TS4(9 + 2 * (p * 5 + i))
        if (wg ? (i == 4 ? st0 < 75 : (i < 2 || i == (join ? 3 : 2))) : i) bar_arrive(other_turn, 256);
        if (p == 0 && i < 4) {
          if (i == 1 && rb) {
            mbar_wait(xf + 8, rb & 1);
            mbar_wait(xf + 16, rb & 1);
            ln_fetch<16, 36>(xa, xs - 32768, lo_of(fresh_lane()));
          }
#pragma unroll
          for (int j = 0; j < 72; j++)
            if (j >= 2 * (i < 2 ? 8 * i + 8 : 8 * i + 4) && j < 2 * (i == 0 ? 16 : 8 * i + 12)) {
              xa[2 * j] = sub2(xa[2 * j], mm0);
              xa[2 * j + 1] = sub2(xa[2 * j + 1], mm1);
            }
          pin(xa);
        }
        if (i == X_SQI && n == 0) {
          mbar_wait(cx.sb + SM_BAR_SQ, 0);
          float2* sp = (float2*)(cx.sp + SM_STATS) + lr0;
          float mean0, mean1;
          ln_row(rstd0, sp[0].y, mean0, rstd0);
          ln_row(rstd1, sp[8].y, mean1, rstd1);
          __syncwarp();
          if (c == 0) {
            sp[0] = make_float2(mean0, rstd0);
            sp[8] = make_float2(mean1, rstd1);
          }
          *((uint32_t*)(cx.sp + SM_COLD) + wg) = 0;
          if (!hlp) bar_arrive(BAR_GATE, 352);
          rstd0 *= SM_SCALE_LOG2;
          rstd1 *= SM_SCALE_LOG2;
        }
        if (i == 4 && p == 3 && rb < 3) {
          const float2* sp = (const float2*)(cx.sp + SM_STATS) + cw * 16 + (fresh_lane() >> 2);
          mm0 = pack2(sp[0].x, sp[0].x);
          mm1 = pack2(sp[8].x, sp[8].x);
          sq0 = sp[0].y * SM_SCALE_LOG2;
          sq1 = sp[8].y * SM_SCALE_LOG2;
#pragma unroll
          for (int j = 0; j < 16; j++) { xa[2 * j] = sub2(xa[2 * j], mm0); xa[2 * j + 1] = sub2(xa[2 * j + 1], mm1); }
          pin(xa);
        }
        if (i == 0) {
          if (wg) {
            wg_wait<0>();
            if (signaller) mbar_arrive_cluster(empty_c + 8 * sl);
          }
        } else if (i == 2) {
          if (!join) {
            wg_wait<0>();
            if (signaller) mbar_arrive_cluster(empty_c + 8 * sl);
          }
          if (hlp && p == 3 && rb < 3) {
            mbar_wait(xf, ~rb & 1);
            ln_fetch<0, 16>(xa, xs, lo_of(fresh_lane()));
            pin(xa);
          }
        } else if (i != 3) {
          wg_wait<1>();
          if (signaller && (i == 4 || !wg)) mbar_arrive_cluster(empty_c + 8 * slp);
          wg_wait<0>();
          if (signaller) mbar_arrive_cluster(empty_c + 8 * sl);
        }
      }
      pin(acc);
      prof(wg, 3 + p);
      TS4(50 + 2 * p)
      st0 += 5;
      if (hlp && st0 > 5) bar_sync(BAR_QF + wg, 160);
      park<0, 8>(qlane(lane) + (hlp ? 5 + wg : 4 + p) * STAGE, acc, rstd0, rstd1);
      if (p || hlp) asm volatile("fence.proxy.async.shared::cta;" ::: "memory");
      if (hlp) bar_arrive(BAR_QS + wg, 160);
      if (p == 3) { rstd0 = sq0; rstd1 = sq1; }
      TS4(51 + 2 * p)
      if (p == 1 && !hlp) {
        float (&ah)[32] = *(float (*)[32])&acc[0];
#pragma unroll
        for (int i = 0; i < 3; i++) {
          const uint32_t sl = (10 + i) & 3;
          if (!wg) mbar_wait(full + 8 * sl, ((10 + i) >> 2) & 1);
          TS4(28 + 2 * i)
          if (i == 0 || i == 2 - wg) bar_sync(my_turn, 256);
          wg_fence();
          const uint64_t db = mkdesc(ring + sl * STAGE, 16);
#pragma unroll
          for (int k = 0; k < 12; k++) {
            const int kb = 12 * i + k;
            if (kb) mma_n64t(ah, xa[4 * kb], xa[4 * kb + 1], xa[4 * kb + 2], xa[4 * kb + 3], db + k * 128, true);
            else mma_n64t_dyn(ah, xa[0], xa[1], xa[2], xa[3], db, blockIdx.y);
          }
          wg_commit();
          TS4(29 + 2 * i)
          if (i == 2 || i != wg) {
            bar_arrive(other_turn, 256);
            if (i) {
              wg_wait<1>();
              if (signaller && i == wg + 1) mbar_arrive_cluster(empty_c + 8 * ((9 + i) & 3));
            }
            wg_wait<0>();
            if (signaller) mbar_arrive_cluster(empty_c + 8 * sl);
          }
        }
        pin(ah);
        TS4(54)
        park<0, 4>(qlane(lane) + 6 * STAGE, ah, rstd0, rstd1);
        TS4(55)
        st0 = 13;
        n = 2;
      }
    }
    TS_DUMP()
    ffn_consumer(cx, blockIdx.x & 3, wg, cw, fresh_lane(), x);
    return;
  }

attention:
  uint32_t oa[128];
  float acc[32];
  {
    uint32_t pf[28];
    uint32_t bad = 0;
    float lA0 = 0.f, lA1 = 0.f, lB0 = 0.f, lB1 = 0.f;
    int t = 0;
    uint32_t ra = 2 * 2048, rb = 2048, rc = 2 * 2048, par = 0;
    const uint64_t dk0 = mkdesc(ring, 16), dv0 = mkdesc(ring, 16384);
    uint64_t dqA = mkdesc_q(qwg + 4 * STAGE), dqB = dqA + 2048;
    auto turn = [&](auto kc_, auto bc_) {
      constexpr int KIND = decltype(kc_)::value, BIG = decltype(bc_)::value;
      constexpr int HB = KIND == 1, ID = 10 * KIND + 30 * BIG, T0 = BIG ? 38 : 0;
      constexpr int NS = BIG ? 56 : 48, SPLIT = BIG ? (HB ? X_SPLIT : X_SPLITA) : (HB ? X_SPLITS : X_SPLITSA);
      float s[NS];
      float (&op)[64] = HB ? oA : oB;
      uint32_t h0 = 0, h1 = 0;
      TS2(0)
      bar_sync(my_turn, 256);
      TS2(1)
      if (KIND) { pin(pf); pin(op); }
      mma_qk(s, HB ? dqB : dqA, dk0 + (HB ? ra : rc));
      TS2(2)
      if (KIND) {
        const bool bigp = HB ? BIG : BIG ? t != 10 : t == 66;
        if (X_BF2) block_fence(ID + 9);
        pin(pf);
        sum_tree(pf, bigp, h0, h1);
        asm volatile("" : "+r"(h0), "+r"(h1)::"memory");
        if (HB) mbar_wait(full + (rb >> 8), par);
        mma_pv(op, pf, dv0 + rb, t != T0 + 2 - HB, bigp);
      } else {
        mbar_wait(full + (rb >> 8), (NST_Q - 1) >> 2 & 1);
#pragma unroll
        for (int k = 0; k < 8; k++) mma_n128t(op, xl[4 * k], xl[4 * k + 1], xl[4 * k + 2], xl[4 * k + 3], dv0 + rb + k * 128, 1);
        wg_commit();
      }
      TS2(3)
      bar_arrive(other_turn, 256);
      (HB ? lA0 : lB0) += bf_lo(h0) + bf_hi(h0);
      (HB ? lA1 : lB1) += bf_lo(h1) + bf_hi(h1);
      wg_wait<1>();
      pin(s);
      TS1(t)
      TS2(4)
      if (KIND == 1) mbar_arrive_cluster_now<ID + 3>(empty_c + (ra >> 8), signaller);
      if (BIG && t == T0 + HB) {
        const uint32_t a = qlane(fresh_lane()) + (4 + HB) * STAGE;
        const bool ok = !__any_sync(0xffffffffu, inv_sums(HB ? lB0 : lA0, HB ? lB1 : lA1, i0, i1));
        bad = (HB ? bad : 0) | (ok ? 0 : 1 << HB);
        (HB ? lB0 : lA0) = 0.f;
        (HB ? lB1 : lA1) = 0.f;
        softmax_exp<0, X_E0>(s);
#pragma unroll
        for (int i = 0; i < X_E0; i++) asm volatile("" : "+f"(s[i])::"memory");
        block_fence(ID + 7);
        exp_park<0, X_PA, X_E0, SPLIT>(s, a, HB ? oB : oA, i0, i1, ok, 200 + ID);
        if (!HB) dqB += 2048;
        prof(wg, 8 + HB);
      } else {
        if (HB && !BIG) bad = (bad & 3) | (inv_sums(lA0, lA1, i0, i1) ? 4 : 0);
        softmax_exp<0, SPLIT>(s);
      }
      pin(s);
      if (!BIG) block_fence(ID + 4);
      TS2(5)
      wg_wait<0>();
      TS2(6)
      pin(op);
      if (KIND) pin(pf); else pin(xl);
      if (HB) {
        par ^= rc == 2048;
        if (BIG && t == 37) dqA -= 4 * 2048;
        if (BIG && t == X_WAKE && cw == 0) bar_arrive(BAR_HELPER, 64);
      } else {
        mbar_arrive_cluster_now<ID + 5>(empty_c + (rb >> 8), signaller);
        if (KIND) {
          par ^= ra == 2048;
          const uint32_t x = ra;
          ra = rc; rc = rb; rb = x;
        }
      }
      softmax_exp<SPLIT, NS>(s);
#pragma unroll
      for (int i = 0; i < NS / 2; i++) pf[i] = pack2(s[2 * i], s[2 * i + 1]);
      pin(pf);
      if (KIND == 0) {
        block_fence(ID + 6);
        park<0, 8>(qlane(fresh_lane()), oB, i0, i1);
        asm volatile("fence.proxy.async.shared::cta;" ::: "memory");
        prof(wg, 7);
      }
      if (BIG && X_PA < 8 && t == T0 + HB) park<X_PA, 8>(qlane(fresh_lane()) + (4 + HB) * STAGE, HB ? oB : oA, i0, i1, !(bad >> HB));
      if (BIG && !HB && t == T0) mbar_wait(cx.sb + SM_BAR_Q + 8 * wg, 0);
      if (HB) mbar_wait(full + (rc >> 8), par);
      t++;
    };
#pragma unroll
    for (int i = 24; i < 28; i++) asm volatile("" : "=r"(pf[i]));
    mbar_wait(full + 8 * 2, 0);
    turn(IC<0>(), IC<0>());
    rb = 3 * 2048; rc = 2048;
    kill(oA);
    const bool never = blockIdx.y == 1;
#pragma unroll 1
    while (true) {
      turn(IC<1>(), IC<0>());
      if (t == 76) break;
      if (t == 10) {
#pragma unroll 1
        do {
#pragma unroll 1
          do turn(IC<2>(), IC<1>()); while (never);
          turn(IC<1>(), IC<1>());
        } while (t != 66);
      }
#pragma unroll 1
      do turn(IC<2>(), IC<0>()); while (never);
    }
    const uint32_t ql = qlane(fresh_lane());
    auto scale = [&](auto lo, auto hi) {
#pragma unroll
      for (int i = decltype(lo)::value; i < decltype(hi)::value; i++) {
        oa[32 + 2 * i] = pack2(oA[4 * i] * i0, oA[4 * i + 1] * i0);
        oa[32 + 2 * i + 1] = pack2(oA[4 * i + 2] * i1, oA[4 * i + 3] * i1);
        asm volatile("" : "+r"(oa[32 + 2 * i]), "+r"(oa[32 + 2 * i + 1])::"memory");
      }
    };
    TS3(1)
    if (X_LD == 0) {
#pragma unroll
      for (int i = 0; i < 8; i++) ldsm4(ql + 4 * STAGE + i * 2048, oa[4 * i], oa[4 * i + 1], oa[4 * i + 2], oa[4 * i + 3]);
    }
    {
      uint32_t h0, h1;
      sum_tree(pf, false, h0, h1);
      if (inv_sums(lB0 + (bf_lo(h0) + bf_hi(h0)), lB1 + (bf_lo(h1) + bf_hi(h1)), lB0, lB1)) bad |= 8;
    }
    scale(IC<0>(), IC<X_F1>());
    volatile uint32_t* const cold = (volatile uint32_t*)(cx.sp + SM_COLD) + wg;
    if (bad) *cold = 1;
    block_fence(93);
    TS3(2)
    bar_sync(my_turn, 256);
    const uint32_t is_cold = *cold;
    TS3(3)
    pin(pf); pin(oB);
    mma_pv(oB, pf, dv0 + 2 * 2048, true, false);
    mbar_arrive_cluster_now<91>(empty_c, signaller && !is_cold);
    TS3(4)
    if (X_LD == 1) {
#pragma unroll
      for (int i = 0; i < 8; i++) ldsm4(ql + 4 * STAGE + i * 2048, oa[4 * i], oa[4 * i + 1], oa[4 * i + 2], oa[4 * i + 3]);
    }
    const uint64_t db = mkdesc(ring + 3 * STAGE, 16);
    scale(IC<X_F1>(), IC<X_F2>());
    block_fence(94);
#pragma unroll
    for (int i = 0; i < 32; i++) asm volatile("" : "+r"(oa[i])::"memory");
    wg_fence();
#pragma unroll
    for (int k = 0; k < 8; k++) mma_n64t(acc, oa[4 * k], oa[4 * k + 1], oa[4 * k + 2], oa[4 * k + 3], db + k * 128, k > 0);
    if (X_F2 < 16) {
      wg_commit();
      block_fence(95);
      scale(IC<X_F2>(), IC<16>());
      TS3(5)
      wg_fence();
    }
#pragma unroll
    for (int k = 8; k < 16; k++) mma_n64t(acc, oa[4 * k], oa[4 * k + 1], oa[4 * k + 2], oa[4 * k + 3], db + k * 128, 1);
    wg_commit();
    bar_arrive(other_turn, 256);
    wg_wait<(X_F2 < 16 ? 2 : 1)>();
    pin(oB); pin(pf);
    TS(76)
    TS3(6)
    if (signaller) mbar_arrive_cluster(empty_c + 8 * 2);
#pragma unroll
    for (int i = 16; i < 24; i++) ldsm4(ql + 5 * STAGE + (i & 7) * 2048, oa[4 * i], oa[4 * i + 1], oa[4 * i + 2], oa[4 * i + 3]);
#pragma unroll
    for (int i = 0; i < 16; i++) {
      oa[96 + 2 * i] = pack2(oB[4 * i] * lB0, oB[4 * i + 1] * lB0);
      oa[96 + 2 * i + 1] = pack2(oB[4 * i + 2] * lB1, oB[4 * i + 3] * lB1);
    }
    TS3(7)
    mbar_wait(full + 8 * 1, 0);
    TS3(8)
    wg_wait<0>();
    pin(acc); pin(oa);
    if (__any_sync(0xffffffffu, is_cold)) {
      bad = __reduce_or_sync(0xffffffffu, bad);
      if (!(bad & 8)) {
#pragma unroll
        for (int i = 24; i < 32; i++) stsm4(ql + 6 * STAGE + (i & 7) * 2048, oa[4 * i], oa[4 * i + 1], oa[4 * i + 2], oa[4 * i + 3]);
      }
#pragma unroll 1
      for (int h = 0; h < 4; h++) {
        if (bad >> h & 1) {
          const uint32_t a = ql + ((0x6054 >> (4 * h)) & 7) * STAGE;
          const int l = fresh_lane(), o = (hs * 2 + (h >> 1)) * SEQ * DH + (l >> 2) * DH + (l & 3) * 2;
          uint32_t q[32];
#pragma unroll
          for (int i = 0; i < 8; i++) ldsm4(a + i * 2048, q[4 * i], q[4 * i + 1], q[4 * i + 2], q[4 * i + 3]);
#pragma unroll 1
          for (int i = 0; i < 4; i++) {
            float ox[16], l0, l1;
            exact_attention(ox, l0, l1, q, kc + o, vc + o + i * 32);
            inv_sums(l0, l1, l0, l1);
            park<0, 2>(a + i * 4096, ox, l0, l1);
          }
        }
      }
      __syncwarp();
#pragma unroll
      for (int i = 0; i < 32; i++)
        if ((i >> 3) != 1 || (bad & 4))
          ldsm4(ql + ((0x6504 >> (4 * (i >> 3))) & 7) * STAGE + (i & 7) * 2048, oa[4 * i], oa[4 * i + 1], oa[4 * i + 2], oa[4 * i + 3]);
      pin(oa);
      asm volatile("fence.proxy.async.shared::cta;" ::: "memory");
      bar_sync(4 + wg, 128);
      if (signaller) mbar_arrive_cluster(empty_c);
      wg_fence();
#pragma unroll
      for (int k = 0; k < 16; k++) mma_n64t(acc, oa[4 * k], oa[4 * k + 1], oa[4 * k + 2], oa[4 * k + 3], db + k * 128, k > 0);
      wg_commit();
      wg_wait<0>();
      pin(acc);
    }
    if (signaller) mbar_arrive_cluster(empty_c + 8 * 3);
  }

  prof(wg, 10);
  TS3(9)
  {
    lane = fresh_lane();
    const int tw = (cw & 3) * 32 + lane;
    float red[32];
    kill(red);
    const uint32_t tag = *(const uint32_t*)(cx.sp + SM_TAG);
    uint4* const xch = cx.g->part + (size_t)(qb * 64 * 2 + wg) * 4 * 128 + tw;
    int nrx = 1;
    auto region = [](int s, int h) { return h ? 1 + (s & 1) : (s & 1) ? 0 : 3; };
    auto half_step = [&](int s, auto hc, bool arrive) {
      constexpr int h = decltype(hc)::value;
      const uint64_t db = mkdesc(ring + region(s, h) * STAGE, 16);
      bar_sync(my_turn, 256);
      pin(oa);
      wg_fence();
#pragma unroll
      for (int k = 0; k < 16; k++) {
        const int kb = h * 16 + k;
        mma_n64t(acc, oa[4 * kb], oa[4 * kb + 1], oa[4 * kb + 2], oa[4 * kb + 3], db + k * 128, kb > 0);
      }
      wg_commit();
      if (arrive) bar_arrive(other_turn, 256);
    };
    auto await = [&](int s, int h) { mbar_wait(full + 8 * region(s, h), ((s >> 1) ^ h ^ 1) & 1); };
    auto fetch = [&](uint32_t (&g)[16], int n) {
      const uint4* p = xch + (hs * 7 + n - 1) * (2 * 4 * 128);
#pragma unroll
      for (int i = 0; i < 4; i++) ld_gran(p + i * 128, g[4 * i], g[4 * i + 1], g[4 * i + 2], g[4 * i + 3]);
    };
    uint32_t g[16];
#pragma unroll 1
    for (int s = 0; s < 8; s++) {
      const bool pend = nrx < s - 1;
      if (pend) fetch(g, nrx);
      half_step(s, IC<1>(), true);
      TS3(s < 3 ? 16 + 8 * s : 75)
      if (s == 0) {
        bar_arrive(BAR_OA, 352);
#pragma unroll
        for (int i = 0; i < 32; i++) red[i] = 0.f;
      }
      await(s + 1, 0);
      TS3(s < 3 ? 17 + 8 * s : 75)
      wg_wait<0>();
      TS3(s < 3 ? 18 + 8 * s : 75)
      if (signaller && s < 7) mbar_arrive_cluster(empty_c + 8 * region(s, 1));
      pin(acc);
      TS(77 + s)
      prof(wg, 12 + s);
      uint4* p = xch + (s == 0 ? 56 + hs : ((hs + s) & 7) * 7 + s - 1) * (2 * 4 * 128);
#pragma unroll
      for (int i = 0; i < 4; i++)
        st_gran(p + i * 128, (pack2(acc[8 * i], acc[8 * i + 1]) & ~TAG) | tag, pack2(acc[8 * i + 2], acc[8 * i + 3]),
                pack2(acc[8 * i + 4], acc[8 * i + 5]), pack2(acc[8 * i + 6], acc[8 * i + 7]));
      TS3(s < 3 ? 19 + 8 * s : 75)
      half_step(s + 1, IC<0>(), true);
      TS3(s < 3 ? 20 + 8 * s : 75)
      await(s + 1, 1);
      TS3(s < 3 ? 21 + 8 * s : 75)
      if (pend && granules_ok(g, tag)) { add_granules(red, g); nrx++; }
      wg_wait<0>();
      TS3(s < 3 ? 22 + 8 * s : 75)
      if (signaller && s < 6) mbar_arrive_cluster(empty_c + 8 * region(s + 1, 0));
    }
    uint32_t xv[16], gt[16], g2[16];
    fetch(g, nrx);
    mbar_wait(cx.sb + SM_BAR_XG, 0);
    {
      const uint64_t db = mkdesc(ring + STAGE, 16);
      bar_sync(my_turn, 256);
#pragma unroll
      for (int i = 64; i < 128; i++) asm volatile("" : "+r"(oa[i])::"memory");
      wg_fence();
#pragma unroll
      for (int k = 16; k < 32; k++) mma_n64t(acc, oa[4 * k], oa[4 * k + 1], oa[4 * k + 2], oa[4 * k + 3], db + (k - 16) * 128, 1);
      wg_commit();
      if (wg == 0) bar_arrive(other_turn, 256);
    }
    const bool ok = granules_ok(g, tag);
    nrx += ok;
    fetch(g2, nrx);
    const uint32_t frag = (cw * 16 + (lane & 15)) * 128 + (((lane >> 4) ^ (lane & 7)) << 4);
#pragma unroll
    for (int i = 0; i < 4; i++) {
      ldsm4(cx.sb + SM_XO + (frag ^ (i << 5)), xv[4 * i], xv[4 * i + 1], xv[4 * i + 2], xv[4 * i + 3]);
      ldsm4(cx.sb + SM_GO + (frag ^ (i << 5)), gt[4 * i], gt[4 * i + 1], gt[4 * i + 2], gt[4 * i + 3]);
    }
    if (ok) add_granules(red, g);
    wg_wait<0>();
    pin(acc);
    TS(85)
#pragma unroll
    for (int i = 0; i < 32; i++) red[i] += acc[i];
    pin(red);
#pragma unroll 1
    for (int spins = 0; spins < (1 << 16); spins++) {
      if (granules_ok(g2, tag)) {
        add_granules(red, g2);
        if (++nrx == 8) break;
      }
      fetch(g2, nrx);
    }
    prof(wg, 20);
    TS(86)
    uint32_t ow[16];
#pragma unroll
    for (int i = 0; i < 16; i++) ow[i] = fma2(pack2(red[2 * i], red[2 * i + 1]), gt[i], xv[i]);
#pragma unroll
    for (int i = 0; i < 4; i++) stsm4(cx.sb + SM_XO + (frag ^ (i << 5)), ow[4 * i], ow[4 * i + 1], ow[4 * i + 2], ow[4 * i + 3]);
    __syncwarp();
#pragma unroll
    for (int i = 0; i < 4; i++) {
      uint4 v;
      const int row = cw * 16 + i * 4 + (lane >> 3);
      lds128(cx.sb + SM_XO + row * 128 + (((lane ^ row) & 7) << 4), v.x, v.y, v.z, v.w);
      asm volatile("st.global.v4.b32 [%0], {%1, %2, %3, %4};" ::"l"(out + (size_t)(qb * 128 + row) * DM + hs * 64 + (lane & 7) * 8),
                   "r"(v.x), "r"(v.y), "r"(v.z), "r"(v.w) : "memory");
    }
    prof(wg, 22);
    TS(87)
    TS_DUMP()
  }
}

struct KvMaps { CUtensorMap m[4]; };
__global__ void __cluster_dims__(2, 1, 1) __launch_bounds__(THREADS, 1)
fused_kernel(const __nv_bfloat16* __restrict__ x, const __nv_bfloat16* __restrict__ w_r, const __nv_bfloat16* __restrict__ kc,
             const __nv_bfloat16* __restrict__ vc, __nv_bfloat16* __restrict__ out, Scratch* scratch,
             const __grid_constant__ CUtensorMap tmX, const __grid_constant__ CUtensorMap tmWq,
             const __grid_constant__ KvMaps tmKV, const __grid_constant__ CUtensorMap tmWo,
             const __grid_constant__ CUtensorMap tmG, const __grid_constant__ CUtensorMap tmU,
             const __grid_constant__ CUtensorMap tmD, const __grid_constant__ CUtensorMap tmX16,
             const __grid_constant__ CUtensorMap tmWq96, const __grid_constant__ CUtensorMap tmX64) {
  extern __shared__ __align__(1024) uint8_t smem_raw[];
  prof(0, 23, 511);
  if (X_PFX && threadIdx.x == 192) { prefetch_tmap(&tmX); prefetch_tmap(&tmWq); }
  Ctx cx;
  cx.sb = smem_u32(smem_raw);
  cx.sp = smem_raw;
  cx.g = scratch;
  cx.rank = blockIdx.x & 1;
  const int warp = __shfl_sync(0xffffffffu, threadIdx.x >> 5, 0);
  const int cluster = blockIdx.x >> 1;
  const bool is_ffn = blockIdx.x >= N_ATT_CTA;
  const int c7 = ((cluster - 36) * 37) >> 8;
  const int hs = cluster < 4 ? 4 + cluster : cluster < 36 ? (cluster - 4) >> 3 : 4 + c7;
  const int qb = (cluster < 4 ? 0 : cluster < 36 ? (cluster - 4) & 7 : cluster - (is_ffn ? 36 : 35) - 7 * c7) * 2 + cx.rank;

  auto load_x = [&](int w, int i0, int i1) {
#pragma unroll
    for (int i = i0; i < i1; i++) {
      mbar_expect_tx(cx.sb + SM_XFULL + 32 * w + 8 * i, 24576);
      tma3d(cx.sb + SM_X + (3 * w + i) * 24576, &tmX, qb * 128 + w * 64, i * 3, cx.sb + SM_XFULL + 32 * w + 8 * i);
    }
  };
  if (warp < 4) {
    asm volatile("setmaxnreg.dec.sync.aligned.u32 24;");
    if (elect_one()) {
      if (warp == 0) {
        TSP(64)
#pragma unroll
        for (int i = 0; i < 4; i++) mbar_init(cx.sb + SM_FULL + 8 * i, 1);

      } else if (warp == 1) {
#pragma unroll
        for (int i = 0; i < 4; i++) mbar_init(cx.sb + SM_EMPTY + 8 * i, 4);
        mbar_init(cx.sb + SM_BAR_MISC, 1);
        mbar_init(cx.sb + SM_BAR_XG, 1);
        mbar_init(cx.sb + SM_BAR_SQ, 1);
        mbar_init(cx.sb + SM_BAR_Q, 1);
        mbar_init(cx.sb + SM_BAR_Q + 8, 1);
      } else if (is_ffn) {
#pragma unroll
        for (int i = 0; i < 8; i++) mbar_init(cx.sb + (warp == 2 ? SM_FFULL : SM_FEMPTY) + 8 * i, 1);
      }
      asm volatile("fence.mbarrier_init.release.cluster;" ::: "memory");
    }
    __syncwarp();
    cluster_arrive();
    if (warp == 0) TSP(70)
    cluster_wait();
    if (warp == 0) TSP(71)
    prof(0, 24, 511);
    if (warp == 0) {
      if (is_ffn) ffn_producer(cx, qb, &tmWq, &tmG, &tmU, &tmD);
      else attn_producer(cx, qb, hs, tmKV.m, &tmWq, &tmWq96, &tmWo);
      prof(0, 25, 511);
    } else {
      sq_publish(cx, qb, hs, warp - 1, read_lane());
      if (warp == 3) sq_collect(cx, qb, read_lane());
      if (!is_ffn) {
        attn_gate(cx, qb, hs, warp - 1, threadIdx.x - 32, x);
        if (warp == 1) TSP(65)
        asm volatile("fence.proxy.async.global;" ::: "memory");
        if (warp == 1) attn_helper(cx, qb, hs, fresh_lane(), &tmX16);
        else bar_arrive(BAR_OA, 352);
        attn_finish8(cx, qb, hs, warp - 1, fresh_lane(), out);
      } else if (warp < 3) {
        ffn_publish(cx, qb, warp - 1, fresh_lane(), &tmX64);
      }
    }
    __syncwarp();
    cluster_arrive();
    cluster_wait();
  } else {
    if (warp == 4 && elect_one()) {
#pragma unroll
      for (int i = 0; i < 3; i++) mbar_init(cx.sb + SM_XFULL + 8 * i, 1);
      TSP(66)
      load_x(0, 0, 3);
#pragma unroll
      for (int i = 4; i < 7; i++) mbar_init(cx.sb + SM_XFULL + 8 * i, 1);
      asm volatile("fence.mbarrier_init.release.cluster;" ::: "memory");
    }
    if (warp == 5 && elect_one()) {
      mbar_init(cx.sb + SM_BAR_W, 1);
      asm volatile("fence.mbarrier_init.release.cluster;" ::: "memory");
      *(uint4*)(cx.sp + SM_ONES) = make_uint4(0x3F803F80u, 0x3F803F80u, 0x3F803F80u, 0x3F803F80u);
      mbar_expect_tx(cx.sb + SM_BAR_W, DM * 2);
      bulk_load(cx.sb + SM_WR, w_r, DM * 2, cx.sb + SM_BAR_W);
    }
    __syncwarp();
    cluster_arrive();
    if (warp == 4 && elect_one()) {
      load_x(1, 0, X_ORD);
      TSP(67)
    }
    __syncwarp();
    asm volatile("setmaxnreg.inc.sync.aligned.u32 240;");
    const int cw = warp - 4, wg = cw >> 2;
    cluster_wait();
    if (warp == 8 && elect_one()) {
      const uint64_t pol = policy_evict_first();
#pragma unroll
      for (int i = 0; i < 4; i++) {
        if (!(i & 1)) mbar_expect_tx(cx.sb + SM_FULL + 4 * i, 32768);
        tma2d_mc(cx.sb + SM_RING + (i >> 1) * STAGE + cx.rank * 16384 + (i & 1) * 8192, &tmWq,
                 is_ffn ? (cx.rank * 4 + 3) * DH + 64 : hs * 512 + cx.rank * 64, i * 64, cx.sb + SM_FULL + 8 * (i >> 1), pol);
        if (i == 1) load_x(1, X_ORD, 3);
      }
      TSP(72)
    }
    __syncwarp();
    attn_consumer(cx, is_ffn, qb, hs, wg, cw, read_lane(), x, kc, vc, out);
  }
}

typedef CUresult (*EncodeFn)(CUtensorMap*, CUtensorMapDataType, cuuint32_t, void*, const cuuint64_t*, const cuuint64_t*,
                             const cuuint32_t*, const cuuint32_t*, CUtensorMapInterleave, CUtensorMapSwizzle,
                             CUtensorMapL2promotion, CUtensorMapFloatOOBfill);

void encode(EncodeFn fn, CUtensorMap* m, const void* p, int rank, const cuuint64_t* dims, const cuuint64_t* strides,
            const cuuint32_t* box) {
  const cuuint32_t es[5] = {1, 1, 1, 1, 1};
  fn(m, CU_TENSOR_MAP_DATA_TYPE_BFLOAT16, rank, const_cast<void*>(p), dims, strides, box, es, CU_TENSOR_MAP_INTERLEAVE_NONE,
     CU_TENSOR_MAP_SWIZZLE_128B, CU_TENSOR_MAP_L2_PROMOTION_L2_128B, CU_TENSOR_MAP_FLOAT_OOB_FILL_NONE);
}
void encode2d(EncodeFn fn, CUtensorMap* m, const void* p, uint64_t rows, uint64_t cols, uint32_t box_rows) {
  const cuuint64_t dims[2] = {cols, rows}, strides[1] = {cols * 2};
  const cuuint32_t box[2] = {64, box_rows};
  encode(fn, m, p, 2, dims, strides, box);
}

}

extern "C" void kernel_launch(void* const* d_in, const int* in_sizes, int n_in, void* d_out, int out_size) {
  (void)in_sizes; (void)n_in; (void)out_size;
  void* fnp = nullptr;
  cudaDriverEntryPointQueryResult qr;
  cudaGetDriverEntryPoint("cuTensorMapEncodeTiled", &fnp, cudaEnableDefault, &qr);
  EncodeFn fn = (EncodeFn)fnp;
  CUtensorMap tmWq, tmWo, tmG, tmU, tmD, tmX, tmX16, tmWq96, tmX64;
  encode2d(fn, &tmX64, d_in[0], SEQ, DM, 64);
  encode2d(fn, &tmWq96, d_in[3], DM, 4096, 96);
  encode2d(fn, &tmX16, d_in[0], SEQ, DM, 16);
  KvMaps tmKV;
  for (int i = 0; i < 4; i++) encode2d(fn, &tmKV.m[i], d_in[1 + (i & 1)], 16 * SEQ, DH, i < 2 ? 112 : 96);
  encode2d(fn, &tmWq, d_in[3], DM, 4096, 64);
  {
    const cuuint64_t dims[3] = {64, SEQ, 9}, strides[2] = {DM * 2, 128};
    const cuuint32_t box[3] = {64, 64, 3};
    encode(fn, &tmX, d_in[0], 3, dims, strides, box);
  }
  encode2d(fn, &tmWo, d_in[4], 4096, DM, 128);
  encode2d(fn, &tmG, d_in[7], DM, FF, 192);
  encode2d(fn, &tmU, d_in[8], DM, FF, 192);
  encode2d(fn, &tmD, d_in[9], FF, DM, 192);
  cudaFuncSetAttribute(fused_kernel, cudaFuncAttributeMaxDynamicSharedMemorySize, SM_TOTAL);
  void* scratch = nullptr;
  cudaGetSymbolAddress(&scratch, g_scratch);
  fused_kernel<<<N_CTA, THREADS, SM_TOTAL>>>((const __nv_bfloat16*)d_in[0], (const __nv_bfloat16*)d_in[6], (const __nv_bfloat16*)d_in[1],
                                            (const __nv_bfloat16*)d_in[2], (__nv_bfloat16*)d_out, (Scratch*)scratch, tmX, tmWq, tmKV,
                                            tmWo, tmG, tmU, tmD, tmX16, tmWq96, tmX64);
}
```

```cpp
#include <cuda_runtime.h>
#include <cuda_bf16.h>
#include <cuda.h>
#include <stdint.h>

#define X_PFW 1
#define X_SPLIT 38
#define X_SPLITA 36
#define X_SPLITS 32
#define X_SPLITSA 30
#define X_PA 8
#define X_PG 2
#define X_E0 10
#define X_F2 10
#define X_LD 0
#define X_LN 0
#define X_WAKE 31
#define X_PFX 1
#define X_F1 0
#define X_BF2 1
#define X_SQI 4
#define X_SQS 300
#define X_ORD 3
#define X_NS 4
namespace {

constexpr int SEQ = 2048, DM = 576, DH = 128, FF = 4608, TOPC = 8;
constexpr int N_ATT_CTA = 128, N_CTA = 132;
constexpr int THREADS = 384;

constexpr uint32_t SM_RING = 0;
constexpr uint32_t STAGE = 32768;
constexpr uint32_t SM_SLOT = 131072;
constexpr uint32_t FSTAGE = 24576;
constexpr uint32_t SM_XSEL = 196608;
constexpr uint32_t SM_H = 205824;
constexpr uint32_t SM_MISC = 229376;
constexpr uint32_t SM_FULL = SM_MISC, SM_EMPTY = SM_MISC + 32, SM_FFULL = SM_MISC + 64, SM_BAR_MISC = SM_MISC + 128,
                   SM_COLD = SM_MISC + 136, SM_TAG = SM_MISC + 144, SM_BAR_W = SM_MISC + 152, SM_ONES = SM_MISC + 160,
                   SM_BAR_Q = SM_MISC + 176, SM_XFULL = SM_MISC + 192, SM_BAR_XG = SM_MISC + 304, SM_BAR_SQ = SM_MISC + 312,
                   SM_STATS = SM_MISC + 320, SM_FEMPTY = SM_MISC + 1344, SM_RAW = SM_FEMPTY, SM_WR = SM_MISC + 1408, SM_TOPK = SM_WR;
constexpr uint32_t SM_TOTAL = SM_MISC + 2560;
constexpr uint32_t SM_X = SM_MISC - 147456;

constexpr int BAR_GATE = 6, BAR_HELPER = 7, BAR_OA = 8, BAR_XREL = 13, BAR_QS = 9, BAR_QF = 11;
constexpr int NST_Q = 18, NST_KV = 76, NST_O = 18;
constexpr float SM_SCALE_LOG2 = 0.08838834764831845f * 1.4426950408889634f;

struct Scratch {
  uint4 part[16 * 64 * 2 * 4 * 128];
  uint4 gate[N_ATT_CTA * 1152];
  uint4 q[16 * 8 * 2 * 512];
  uint2 sq[SEQ];
  uint4 stats[SEQ];
  float ypart[4 * TOPC * DM];
  int2 sel[16];
  unsigned launch[160];
  unsigned pad0, ycnt, pad[30];
  unsigned qflag[128];
};
__device__ __align__(1024) Scratch g_scratch;

__device__ __forceinline__ void prof(int, int, int = 0) {}

#define TS(id) {}
#define TS_DUMP() {}
#define TS4(k) {}
#define TSP(k) {}
#define TS1(id) TS(id)
#define TS2(k) {}
#define TS3(k) {}

__device__ __forceinline__ uint32_t smem_u32(const void* p) { return (uint32_t)__cvta_generic_to_shared(p); }
__device__ __forceinline__ void mbar_init(uint32_t bar, uint32_t cnt) {
  asm volatile("mbarrier.init.shared::cta.b64 [%0], %1;" ::"r"(bar), "r"(cnt) : "memory");
}
__device__ __forceinline__ void mbar_expect_tx(uint32_t bar, uint32_t bytes) {
  asm volatile("mbarrier.arrive.expect_tx.shared::cta.b64 _, [%0], %1;" ::"r"(bar), "r"(bytes) : "memory");
}
__device__ __forceinline__ void mbar_arrive(uint32_t bar) {
  asm volatile("mbarrier.arrive.shared::cta.b64 _, [%0];" ::"r"(bar) : "memory");
}
__device__ __forceinline__ void mbar_arrive_cluster(uint32_t bar_cluster_addr) {
  asm volatile("mbarrier.arrive.shared::cluster.b64 _, [%0];" ::"r"(bar_cluster_addr) : "memory");
}
template <int ID>
__device__ __forceinline__ void mbar_arrive_cluster_now(uint32_t bar_cluster_addr, bool pred) {
  asm volatile("{\n.reg .pred p, q;\nsetp.ne.u32 p, %1, 0;\nsetp.eq.u32 q, %2, %3;\n"
               "ARR_LOOP:\n@p mbarrier.arrive.shared::cluster.b64 _, [%0];\n@q bra.uni ARR_LOOP;\n}"
               ::"r"(bar_cluster_addr), "r"((uint32_t)pred), "r"(blockIdx.y), "n"(ID) : "memory");
}
__device__ __forceinline__ void block_fence(int id) {
  asm volatile("{\n.reg .pred q;\nsetp.eq.u32 q, %0, %1;\nBF_LOOP:\n@q st.volatile.shared.u32 [%0], %0;\n@q bra.uni BF_LOOP;\n}"
               ::"r"(blockIdx.y), "r"(id) : "memory");
}
__device__ __forceinline__ void mbar_wait(uint32_t bar, uint32_t parity) {
  asm volatile("{\n.reg .pred p, q;\n.reg .u32 n;\nmov.u32 n, 0;\n"
               "WAIT_LOOP:\nmbarrier.try_wait.parity.shared::cta.b64 p, [%0], %1;\n"
               "add.u32 n, n, 1;\nsetp.lt.u32 q, n, 4194304;\nand.pred q, q, !p;\n@q bra WAIT_LOOP;\n}"
               ::"r"(bar), "r"(parity) : "memory");
}
__device__ __forceinline__ uint32_t mapa(uint32_t addr, uint32_t rank) {
  uint32_t r;
  asm volatile("mapa.shared::cluster.u32 %0, %1, %2;" : "=r"(r) : "r"(addr), "r"(rank));
  return r;
}
__device__ __forceinline__ void cluster_arrive() { asm volatile("barrier.cluster.arrive.relaxed.aligned;" ::: "memory"); }
__device__ __forceinline__ bool elect_one() {
  uint32_t p;
  asm volatile("{\n.reg .pred p;\nelect.sync _|p, 0xffffffff;\nselp.u32 %0, 1, 0, p;\n}" : "=r"(p));
  return p;
}
__device__ __forceinline__ int read_lane() { return threadIdx.x & 31; }
__device__ __forceinline__ int fresh_lane() {
  int l;
  asm volatile("mov.u32 %0, %%laneid;" : "=r"(l));
  return l;
}
template <class T> __device__ __forceinline__ T* at(T* p, uint32_t bytes) {
  asm("" : "+r"(bytes));
  return (T*)((const char*)p + bytes);
}
__device__ __forceinline__ void cluster_wait() { asm volatile("barrier.cluster.wait.acquire.aligned;" ::: "memory"); }
__device__ __forceinline__ void bar_sync(int id, int n) { asm volatile("barrier.cta.sync %0, %1;" ::"r"(id), "r"(n) : "memory"); }
__device__ __forceinline__ void bar_arrive(int id, int n) { asm volatile("barrier.cta.arrive %0, %1;" ::"r"(id), "r"(n) : "memory"); }

__device__ __forceinline__ uint64_t policy_evict_first() {
  uint64_t p;
  asm("createpolicy.fractional.L2::evict_first.b64 %0, 1.0;" : "=l"(p));
  return p;
}
__device__ __forceinline__ void tma2d_mc(uint32_t dst, const CUtensorMap* tm, int c0, int c1, uint32_t bar, uint64_t pol) {
  asm volatile("cp.async.bulk.tensor.2d.shared::cluster.global.mbarrier::complete_tx::bytes.multicast::cluster.L2::cache_hint"
               " [%0], [%1, {%2, %3}], [%4], %5, %6;"
               ::"r"(dst), "l"(tm), "r"(c0), "r"(c1), "r"(bar), "h"((uint16_t)3), "l"(pol) : "memory");
}
__device__ __forceinline__ void tma3d(uint32_t dst, const CUtensorMap* tm, int c1, int c2, uint32_t bar) {
  asm volatile("cp.async.bulk.tensor.3d.shared::cluster.global.mbarrier::complete_tx::bytes [%0], [%1, {%2, %3, %4}], [%5];"
               ::"r"(dst), "l"(tm), "r"(0), "r"(c1), "r"(c2), "r"(bar) : "memory");
}
__device__ __forceinline__ void tma2d(uint32_t dst, const CUtensorMap* tm, int c0, int c1, uint32_t bar) {
  asm volatile("cp.async.bulk.tensor.2d.shared::cluster.global.mbarrier::complete_tx::bytes [%0], [%1, {%2, %3}], [%4];"
               ::"r"(dst), "l"(tm), "r"(c0), "r"(c1), "r"(bar) : "memory");
}
__device__ __forceinline__ void tma2d_stream(uint32_t dst, const CUtensorMap* tm, int c0, int c1, uint32_t bar) {
  asm volatile("{\n.reg .b64 pol;\ncreatepolicy.fractional.L2::evict_first.b64 pol, 1.0;\n"
               "cp.async.bulk.tensor.2d.shared::cluster.global.mbarrier::complete_tx::bytes.L2::cache_hint [%0], [%1, {%2, %3}], [%4], pol;\n}"
               ::"r"(dst), "l"(tm), "r"(c0), "r"(c1), "r"(bar) : "memory");
}
__device__ __forceinline__ void bulk_load(uint32_t dst, const void* src, uint32_t bytes, uint32_t bar) {
  asm volatile("cp.async.bulk.shared::cluster.global.mbarrier::complete_tx::bytes [%0], [%1], %2, [%3];"
               ::"r"(dst), "l"(src), "r"(bytes), "r"(bar) : "memory");
}
__device__ __forceinline__ void tma2d_prefetch(const CUtensorMap* tm, int c0, int c1) {
  asm volatile("cp.async.bulk.prefetch.tensor.2d.L2.global [%0, {%1, %2}];" ::"l"(tm), "r"(c0), "r"(c1) : "memory");
}
__device__ __forceinline__ void prefetch_tmap(const CUtensorMap* tm) {
  asm volatile("prefetch.tensormap [%0];" ::"l"(tm) : "memory");
}

__device__ __forceinline__ void wg_fence() { asm volatile("wgmma.fence.sync.aligned;" ::: "memory"); }
__device__ __forceinline__ void wg_commit() { asm volatile("wgmma.commit_group.sync.aligned;" ::: "memory"); }
template <int N> __device__ __forceinline__ void wg_wait() { asm volatile("wgmma.wait_group.sync.aligned %0;" ::"n"(N) : "memory"); }

__device__ __forceinline__ uint64_t mkdesc(uint32_t addr, uint32_t lbo_bytes) {
  return (uint64_t)(((addr & 0x3FFFF) >> 4) | ((lbo_bytes >> 4) << 16)) | ((uint64_t)0x40000040u << 32);
}
__device__ __forceinline__ uint64_t mkdesc_q(uint32_t addr) {
  return (uint64_t)(((addr & 0x3FFFF) >> 4) | (64u << 16)) | ((uint64_t)8 << 32);
}
template <int N> __device__ __forceinline__ void pin(float (&a)[N]) {
#pragma unroll
  for (int i = 0; i < N; i++) asm volatile("" : "+f"(a[i])::"memory");
}
template <int N> __device__ __forceinline__ void kill(float (&a)[N]) {
#pragma unroll
  for (int i = 0; i < N; i++) asm volatile("" : "=f"(a[i]));
}
template <int N> __device__ __forceinline__ void pin(uint32_t (&a)[N]) {
#pragma unroll
  for (int i = 0; i < N; i++) asm volatile("" : "+r"(a[i])::"memory");
}

#define F8(d, o) "+f"(d[o]), "+f"(d[o + 1]), "+f"(d[o + 2]), "+f"(d[o + 3]), "+f"(d[o + 4]), "+f"(d[o + 5]), "+f"(d[o + 6]), "+f"(d[o + 7])
#define R32A "%0, %1, %2, %3, %4, %5, %6, %7, %8, %9, %10, %11, %12, %13, %14, %15, %16, %17, %18, %19, %20, %21, %22, %23, %24, %25, %26, %27, %28, %29, %30, %31"
#define R32B "%32, %33, %34, %35, %36, %37, %38, %39, %40, %41, %42, %43, %44, %45, %46, %47, %48, %49, %50, %51, %52, %53, %54, %55, %56, %57, %58, %59, %60, %61, %62, %63"

#define O8(d, o) "=f"(d[o]), "=f"(d[o + 1]), "=f"(d[o + 2]), "=f"(d[o + 3]), "=f"(d[o + 4]), "=f"(d[o + 5]), "=f"(d[o + 6]), "=f"(d[o + 7])

__device__ __forceinline__ void mma_n128t(float (&d)[64], uint32_t a0, uint32_t a1, uint32_t a2, uint32_t a3, uint64_t db, bool acc) {
  if (acc)
    asm volatile("wgmma.mma_async.sync.aligned.m64n128k16.f32.bf16.bf16 {" R32A ", " R32B "}, {%64, %65, %66, %67}, %68, 1, 1, 1, 1;\n"
                 : F8(d, 0), F8(d, 8), F8(d, 16), F8(d, 24), F8(d, 32), F8(d, 40), F8(d, 48), F8(d, 56)
                 : "r"(a0), "r"(a1), "r"(a2), "r"(a3), "l"(db));
  else
    asm volatile("wgmma.mma_async.sync.aligned.m64n128k16.f32.bf16.bf16 {" R32A ", " R32B "}, {%64, %65, %66, %67}, %68, 0, 1, 1, 1;\n"
                 : O8(d, 0), O8(d, 8), O8(d, 16), O8(d, 24), O8(d, 32), O8(d, 40), O8(d, 48), O8(d, 56)
                 : "r"(a0), "r"(a1), "r"(a2), "r"(a3), "l"(db));
}
#define PV1(a0, a1, a2, a3, ob, acc) "add.s64 b, %92, " #ob ";\n" \
  "wgmma.mma_async.sync.aligned.m64n128k16.f32.bf16.bf16 {" R32A ", " R32B "}, {%" #a0 ", %" #a1 ", %" #a2 ", %" #a3 "}, b, " #acc ", 1, 1, 1;\n"
#define PV6 "wgmma.fence.sync.aligned;\n" PV1(64, 65, 66, 67, 0, p) PV1(68, 69, 70, 71, 128, 1) PV1(72, 73, 74, 75, 256, 1) \
  PV1(76, 77, 78, 79, 384, 1) PV1(80, 81, 82, 83, 512, 1) PV1(84, 85, 86, 87, 640, 1)
#define U4(a, o) "r"(a[o]), "r"(a[o + 1]), "r"(a[o + 2]), "r"(a[o + 3])
__device__ __forceinline__ void mma_pv(float (&d)[64], const uint32_t (&a)[28], uint64_t dv, bool acc, bool big) {
  asm volatile("{\n.reg .pred p, q;\n.reg .b64 b;\nsetp.ne.b32 p, %93, 0;\nsetp.eq.b32 q, %94, 0;\n@q bra.uni PV_SMALL;\n"
               PV6 PV1(88, 89, 90, 91, 768, 1) "wgmma.commit_group.sync.aligned;\nbra.uni PV_DONE;\n"
               "PV_SMALL:\n" PV6 "wgmma.commit_group.sync.aligned;\nPV_DONE:\n}\n"
               : F8(d, 0), F8(d, 8), F8(d, 16), F8(d, 24), F8(d, 32), F8(d, 40), F8(d, 48), F8(d, 56)
               : U4(a, 0), U4(a, 4), U4(a, 8), U4(a, 12), U4(a, 16), U4(a, 20), U4(a, 24), "l"(dv), "r"((int)acc), "r"((int)big) : "memory");
}
#define R48 R32A ", %32, %33, %34, %35, %36, %37, %38, %39, %40, %41, %42, %43, %44, %45, %46, %47"
#define R56 R48 ", %48, %49, %50, %51, %52, %53, %54, %55"
#define QK1(N, R, A, B, oa, ob, acc) "add.s64 a, " A ", " #oa ";\nadd.s64 b, " B ", " #ob ";\n" \
  "wgmma.mma_async.sync.aligned.m64n" #N "k16.f32.bf16.bf16 {" R "}, a, b, " #acc ", 1, 1, 0, 0;\n"
#define QK8(N, R, A, B) "{\n.reg .b64 a, b;\nwgmma.fence.sync.aligned;\n" QK1(N, R, A, B, 0, 0, 0) QK1(N, R, A, B, 128, 2, 1) \
  QK1(N, R, A, B, 256, 4, 1) QK1(N, R, A, B, 384, 6, 1) QK1(N, R, A, B, 512, 1024, 1) QK1(N, R, A, B, 640, 1026, 1) \
  QK1(N, R, A, B, 768, 1028, 1) QK1(N, R, A, B, 896, 1030, 1) "wgmma.commit_group.sync.aligned;\n}\n"
__device__ __forceinline__ void mma_qk(float (&d)[56], uint64_t dq, uint64_t dk) {
  asm volatile(QK8(112, R56, "%56", "%57")
               : O8(d, 0), O8(d, 8), O8(d, 16), O8(d, 24), O8(d, 32), O8(d, 40), O8(d, 48) : "l"(dq), "l"(dk) : "memory");
}
__device__ __forceinline__ void mma_qk(float (&d)[48], uint64_t dq, uint64_t dk) {
  asm volatile(QK8(96, R48, "%48", "%49")
               : O8(d, 0), O8(d, 8), O8(d, 16), O8(d, 24), O8(d, 32), O8(d, 40) : "l"(dq), "l"(dk) : "memory");
}
__device__ __forceinline__ void mma_n64t(float (&d)[32], uint32_t a0, uint32_t a1, uint32_t a2, uint32_t a3, uint64_t db, bool acc) {
  if (acc)
    asm volatile("wgmma.mma_async.sync.aligned.m64n64k16.f32.bf16.bf16 {" R32A "}, {%32, %33, %34, %35}, %36, 1, 1, 1, 1;\n"
                 : F8(d, 0), F8(d, 8), F8(d, 16), F8(d, 24) : "r"(a0), "r"(a1), "r"(a2), "r"(a3), "l"(db));
  else
    asm volatile("wgmma.mma_async.sync.aligned.m64n64k16.f32.bf16.bf16 {" R32A "}, {%32, %33, %34, %35}, %36, 0, 1, 1, 1;\n"
                 : O8(d, 0), O8(d, 8), O8(d, 16), O8(d, 24) : "r"(a0), "r"(a1), "r"(a2), "r"(a3), "l"(db));
}
__device__ __forceinline__ void mma_n64t_dyn(float (&d)[32], uint32_t a0, uint32_t a1, uint32_t a2, uint32_t a3, uint64_t db, int acc) {
  asm volatile("{\n.reg .pred p;\nsetp.ne.b32 p, %37, 0;\n"
               "wgmma.mma_async.sync.aligned.m64n64k16.f32.bf16.bf16 {" R32A "}, {%32, %33, %34, %35}, %36, p, 1, 1, 1;\n}\n"
               : F8(d, 0), F8(d, 8), F8(d, 16), F8(d, 24) : "r"(a0), "r"(a1), "r"(a2), "r"(a3), "l"(db), "r"(acc));
}
__device__ __forceinline__ void mma_n8(float (&d)[4], uint64_t da, uint64_t db, int acc) {
  asm volatile("{\n.reg .pred p;\nsetp.ne.b32 p, %6, 0;\n"
               "wgmma.mma_async.sync.aligned.m64n8k16.f32.bf16.bf16 {%0, %1, %2, %3}, %4, %5, p, 1, 1, 1, 0;\n}\n"
               : "+f"(d[0]), "+f"(d[1]), "+f"(d[2]), "+f"(d[3])
               : "l"(da), "l"(db), "r"(acc));
}
__device__ __forceinline__ void hmma_k16(float (&d)[4], uint32_t a0, uint32_t a1, uint32_t a2, uint32_t a3, uint32_t b0, uint32_t b1) {
  asm volatile("mma.sync.aligned.m16n8k16.row.col.f32.bf16.bf16.f32 {%0, %1, %2, %3}, {%4, %5, %6, %7}, {%8, %9}, {%0, %1, %2, %3};"
               : "+f"(d[0]), "+f"(d[1]), "+f"(d[2]), "+f"(d[3]) : "r"(a0), "r"(a1), "r"(a2), "r"(a3), "r"(b0), "r"(b1));
}

__device__ __forceinline__ uint32_t pack2(float lo, float hi) {
  uint32_t r;
  asm("cvt.rn.bf16x2.f32 %0, %1, %2;" : "=r"(r) : "f"(hi), "f"(lo));
  return r;
}
__device__ __forceinline__ float bf_lo(uint32_t w) { return __uint_as_float(w << 16); }
__device__ __forceinline__ float bf_hi(uint32_t w) { return __uint_as_float(w & 0xFFFF0000u); }
__device__ __forceinline__ float bfr(float x) { return __bfloat162float(__float2bfloat16_rn(x)); }
__device__ __forceinline__ uint32_t sub2(uint32_t a, uint32_t b) {
  uint32_t r;
  asm("sub.rn.bf16x2 %0, %1, %2;" : "=r"(r) : "r"(a), "r"(b));
  return r;
}
__device__ __forceinline__ uint32_t add2(uint32_t a, uint32_t b) {
  uint32_t r;
  asm("add.rn.bf16x2 %0, %1, %2;" : "=r"(r) : "r"(a), "r"(b));
  return r;
}
__device__ __forceinline__ uint32_t fma2(uint32_t a, uint32_t b, uint32_t c) {
  uint32_t r;
  asm("fma.rn.bf16x2 %0, %1, %2, %3;" : "=r"(r) : "r"(a), "r"(b), "r"(c));
  return r;
}
__device__ __forceinline__ float ex2(float x) {
  float r;
  asm("ex2.approx.ftz.f32 %0, %1;" : "=f"(r) : "f"(x));
  return r;
}
__device__ __forceinline__ float rcp(float x) {
  float r;
  asm("rcp.approx.ftz.f32 %0, %1;" : "=f"(r) : "f"(x));
  return r;
}
__device__ __forceinline__ float silu_f(float t) { return t * rcp(1.0f + ex2(-1.4426950408889634f * t)); }
__device__ __forceinline__ void lds128(uint32_t a, uint32_t& x, uint32_t& y, uint32_t& z, uint32_t& w) {
  asm volatile("ld.shared.v4.u32 {%0, %1, %2, %3}, [%4];" : "=r"(x), "=r"(y), "=r"(z), "=r"(w) : "r"(a) : "memory");
}
__device__ __forceinline__ void ldsm4(uint32_t a, uint32_t& x, uint32_t& y, uint32_t& z, uint32_t& w) {
  asm volatile("ldmatrix.sync.aligned.m8n8.x4.shared.b16 {%0, %1, %2, %3}, [%4];" : "=r"(x), "=r"(y), "=r"(z), "=r"(w) : "r"(a) : "memory");
}
constexpr uint32_t TAG = 0x10000;
__device__ __forceinline__ void st_gran(uint4* p, uint32_t x, uint32_t y, uint32_t z, uint32_t w) {
  asm volatile("st.relaxed.gpu.global.v4.b32 [%0], {%1, %2, %3, %4};" ::"l"(p), "r"(x), "r"(y), "r"(z), "r"(w) : "memory");
}
__device__ __forceinline__ void ld_gran(const uint4* p, uint32_t& x, uint32_t& y, uint32_t& z, uint32_t& w) {
  asm volatile("ld.relaxed.gpu.global.v4.b32 {%0, %1, %2, %3}, [%4];" : "=r"(x), "=r"(y), "=r"(z), "=r"(w) : "l"(p) : "memory");
}
__device__ __forceinline__ void stsm4(uint32_t a, uint32_t x, uint32_t y, uint32_t z, uint32_t w) {
  asm volatile("stmatrix.sync.aligned.m8n8.x4.shared.b16 [%0], {%1, %2, %3, %4};" ::"r"(a), "r"(x), "r"(y), "r"(z), "r"(w) : "memory");
}
__device__ __forceinline__ void cp16(uint32_t dst, const void* src) {
  asm volatile("cp.async.cg.shared.global [%0], [%1], 16;" ::"r"(dst), "l"(src) : "memory");
}
__device__ __forceinline__ void cp_wait_all() { asm volatile("cp.async.wait_all;" ::: "memory"); }
__device__ __forceinline__ void add_granules(float (&red)[32], const uint32_t (&g)[16]) {
#pragma unroll
  for (int i = 0; i < 16; i++) { red[2 * i] += bf_lo(g[i]); red[2 * i + 1] += bf_hi((i & 3) ? g[i] : g[i] & ~TAG); }
}
__device__ __forceinline__ bool granules_ok(const uint32_t (&g)[16], uint32_t tag) {
  uint32_t a, b;
  asm("lop3.b32 %0, %1, %2, %3, 0x7E;" : "=r"(a) : "r"(g[0]), "r"(g[4]), "r"(tag));
  asm("lop3.b32 %0, %1, %2, %3, 0x7E;" : "=r"(b) : "r"(g[8]), "r"(g[12]), "r"(tag));
  return __all_sync(0xffffffffu, ((a | b) & TAG) == 0);
}
__device__ __forceinline__ unsigned ld_acquire(const unsigned* p) {
  unsigned v;
  asm volatile("ld.acquire.gpu.global.u32 %0, [%1];" : "=r"(v) : "l"(p) : "memory");
  return v;
}
__device__ __forceinline__ unsigned atom_add_acq_rel(unsigned* p) {
  unsigned v;
  asm volatile("atom.acq_rel.gpu.global.add.u32 %0, [%1], 1;" : "=r"(v) : "l"(p) : "memory");
  return v;
}

template <int K0, int K1>
__device__ __forceinline__ void ln_fetch(uint32_t (&xa)[144], uint32_t boxes, uint32_t lo) {
#pragma unroll
  for (int k = K0; k < K1; k++) ldsm4(boxes + (k >> 2) * 8192 + (lo ^ ((k & 3) << 5)), xa[4 * k], xa[4 * k + 1], xa[4 * k + 2], xa[4 * k + 3]);
}
__device__ __forceinline__ void ln_fetch_b(uint32_t (&b)[24], uint32_t& wb, uint32_t ws) {
#pragma unroll
  for (int j = 0; j < 6; j++, wb += ws) ldsm4(wb, b[4 * j], b[4 * j + 1], b[4 * j + 2], b[4 * j + 3]);
}
template <int K0, int K1>
__device__ __forceinline__ void ln_sums(const uint32_t (&xa)[144], float (&sm)[X_NS][4], const uint32_t (&b)[24]) {
#pragma unroll
  for (int k = K0; k < K1; k++)
    hmma_k16(sm[k % X_NS], xa[4 * k], xa[4 * k + 1], xa[4 * k + 2], xa[4 * k + 3], b[2 * (k % 12)], b[2 * (k % 12) + 1]);
}
__device__ __forceinline__ void ln_row(float sum, float sq, float& mean_b, float& rstd) {
  const float mean = sum * (1.0f / DM);
  const uint32_t mv = pack2(mean, fmaxf(sq * (1.0f / DM) - mean * mean, 0.0f));
  mean_b = bf_lo(mv);
  float sd;
  asm("sqrt.approx.f32 %0, %1;" : "=f"(sd) : "f"(bf_lo(pack2(bf_hi(mv) + 1e-5f, 0.f))));
  rstd = rcp(bf_lo(pack2(sd, 0.f)));
}

template <bool ROUTED>
__device__ __forceinline__ uint32_t gate2(uint32_t xc, float rstd, float2 upd = make_float2(0.f, 0.f)) {
  uint32_t t = pack2(bf_lo(xc) * rstd, bf_hi(xc) * rstd);
  if (ROUTED) t = pack2(bf_lo(t) + upd.x, bf_hi(t) + upd.y);
  return pack2(silu_f(bf_lo(t)), silu_f(bf_hi(t)));
}

template <int V> struct IC { static constexpr int value = V; };

struct Ctx {
  uint32_t sb;
  uint8_t* sp;
  uint32_t rank;
  Scratch* g;
};

__device__ __forceinline__ bool acquire(const Ctx& cx, uint32_t r, uint32_t n, uint32_t bytes) {
  mbar_wait(cx.sb + SM_EMPTY + 8 * r, (n ^ (r >> 1) ^ 1) & 1);
  __syncwarp();
  const bool e = elect_one();
  if (e) mbar_expect_tx(cx.sb + SM_FULL + 8 * r, bytes);
  return e;
}
__device__ __forceinline__ void load_wq(const Ctx& cx, const CUtensorMap* tmWq, int st, int i, int n0, uint64_t pol) {
  const uint32_t r = st & 3, dst = cx.sb + SM_RING + r * STAGE + cx.rank * 16384, bar = cx.sb + SM_FULL + 8 * r;
  const int k0 = i < 3 ? 128 * i : 128 * i - 64;
  if (acquire(cx, r, st >> 2, i == 2 ? 16384 : 32768)) {
    tma2d_mc(dst, tmWq, n0, k0, bar, pol);
    if (i != 2) tma2d_mc(dst + 8192, tmWq, n0, k0 + 64, bar, pol);
  }
}
__device__ __forceinline__ void attn_producer(const Ctx& cx, int qb, int hs, const CUtensorMap* tmKV, const CUtensorMap* tmWq,
                                              const CUtensorMap* tmWq96, const CUtensorMap* tmWo) {
  const uint32_t full = cx.sb + SM_FULL, ring = cx.sb + SM_RING + cx.rank * 16384;
  const uint64_t last_use = policy_evict_first();
  int st = 0;
#pragma unroll 1
  for (int p = 0; p < 4; p++) {
#pragma unroll 1
    for (int i = 0; i < (p == 2 ? 3 : 5); i++, st++) {
      if (p == 2) {
        if (acquire(cx, st & 3, st >> 2, 24576))
          tma2d_mc(cx.sb + SM_RING + (st & 3) * STAGE + cx.rank * 12288, tmWq96, (hs * 4 + 3) * DH, 192 * i + 96 * cx.rank, full + 8 * (st & 3), last_use);
      } else {
        if (st > 1) load_wq(cx, tmWq, st, i, (hs * 4 + (p ^ (p >> 1))) * DH + cx.rank * 64, last_use);
      }
      if (st == 1 || st == 2) TSP(72 + st)
      if (st == X_PFW) {
#pragma unroll 1
        for (int b = qb < 8; b < 5 - (qb >> 3); b++)
          if (elect_one()) tma2d_prefetch(tmWq, hs * 512 + (b < 4 ? (b ^ (b >> 1)) * DH + (qb & 1) * 64 : qb * 64), b < 4 ? (qb >> 1) * 64 : 512);
      }
      if (st == 8 && qb < 8 && elect_one()) tma2d_prefetch(tmKV + ((qb >> 1) & 1), cx.rank * 64, hs * 2 * SEQ + (qb >> 2) * 96);
    }
  }
  uint32_t r = 2, n = 4;
  int row = hs * 2 * SEQ, rows = 96;
  const CUtensorMap* tm = tmKV + 2;
#pragma unroll 1
  for (int u = 0; u < NST_KV; u++) {
    if (acquire(cx, r, n, rows * 256)) {
      tma2d_mc(ring + r * STAGE, tm, cx.rank * 64, row, full + 8 * r, last_use);
      if (((u ^ (qb >> 1)) & 7) == 0 && u < NST_KV - 4) tma2d_prefetch(tmKV + (u & 1), cx.rank * 64, row + 208);
      if ((unsigned)(u - 32) < 36 && (u & 15) == qb) tma2d_prefetch(tmWo, ((u - 32) >> 2) * 64, hs * 512 + (u & 3) * 128);
    }
    if (++r == 4) { r = 1; n++; }
    if (u & 1) row += rows;
    const bool big = (unsigned)(u - 9) < 56;
    rows = big ? 112 : 96;
    tm = tmKV + (~u & 1) + (big ? 0 : 2);
  }
#pragma unroll 1
  for (int u = 0; u < NST_O; u++) {
    const int s = u >> 1;
    const int blk = s == 0 ? 8 : ((hs + s) & 7);
    r = (0x87 >> (2 * (u & 3))) & 3;
    if (acquire(cx, r, (u >> 2) ^ ~u, 32768))
      tma2d_mc(ring + r * STAGE, tmWo, blk * 64, hs * 512 + ((u & 1) + cx.rank * 2) * 128, full + 8 * r, last_use);
  }
}

__device__ __forceinline__ void sq_publish(const Ctx& cx, int qb, int hs, int j, int lane) {
  if (j == 2 && lane == 0) {
    const unsigned e = cx.g->launch[hs * 16 + qb]++;
    *(uint2*)(cx.sp + SM_TAG) = make_uint2((~e & 1) * TAG, e);
  }
  const int row = (hs & 3) * 16 + (lane >> 1);
  uint32_t a = cx.sb + SM_X + (hs >> 2) * 73728 + j * 8192 + row * 128 + (((lane & 1) ^ (row & 7)) << 4);
  float s0 = 0.f, s1 = 0.f;
#pragma unroll 1
  for (int b = 0; b < 6; b++) {
    if (b == (hs < 4 ? 4 : 0)) {
      const int n = 224 + (__float_as_uint(s1) & blockIdx.y);
      if (j == 1) {
        bar_sync(BAR_XREL, n);
        if (lane < 4) asm volatile("mbarrier.arrive.shared::cluster.b64 _, [%0], 2;" ::"r"(mapa(cx.sb + SM_EMPTY + 16 + 8 * (lane >> 1), lane & 1)) : "memory");
      } else {
        bar_arrive(BAR_XREL, n);
      }
      __syncwarp();
      if (hs == 8) return;
    }
    if (!(b & 1)) mbar_wait(cx.sb + SM_XFULL + 32 * (hs >> 2) + 4 * b, 0);
    uint32_t v[8];
    lds128(a, v[0], v[1], v[2], v[3]);
    lds128(a ^ 32, v[4], v[5], v[6], v[7]);
    a = (a ^ 64) + (b & 1) * 24576;
#pragma unroll
    for (int i = 0; i < 8; i++) { s0 = fmaf(bf_lo(v[i]), bf_lo(v[i]), s0); s1 = fmaf(bf_hi(v[i]), bf_hi(v[i]), s1); }
  }
  s0 += s1;
  s0 += __shfl_xor_sync(0xffffffffu, s0, 1);
  float* part = (float*)(cx.sp + SM_STATS) + (lane >> 1) * 2;
  if (j < 2) {
    part[32 * j] = s0;
    bar_arrive(BAR_HELPER, 96);
  } else {
    bar_sync(BAR_HELPER, 96);
    TSP(68)
    if (!(lane & 1))
      asm volatile("st.relaxed.gpu.global.v2.b32 [%0], {%1, %2};" ::"l"(cx.g->sq + qb * 128 + hs * 16 + (lane >> 1)),
                   "r"(__float_as_uint((part[0] + part[32]) + s0)), "r"(*(const uint32_t*)(cx.sp + SM_TAG + 4) + 1) : "memory");
  }
}
__device__ __forceinline__ void sq_collect(const Ctx& cx, int qb, int lane) {
  const uint32_t e1 = *(const uint32_t*)(cx.sp + SM_TAG + 4) + 1;
#pragma unroll 1
  for (int n = 0; n < (1 << 16); n++) {
    __nanosleep(X_SQS);
    uint32_t bad = 0;
#pragma unroll
    for (int i = 0; i < 2; i++) {
      uint32_t a, t0, b, t1;
      ld_gran((const uint4*)at(cx.g->sq, qb * 1024 + lane * 16) + i * 32, a, t0, b, t1);
      *(uint32_t*)(cx.sp + SM_STATS + (i * 32 + lane) * 16 + 4) = a;
      *(uint32_t*)(cx.sp + SM_STATS + (i * 32 + lane) * 16 + 12) = b;
      bad |= (t0 ^ e1) | (t1 ^ e1);
    }
    if (__all_sync(0xffffffffu, bad == 0)) break;
  }
  __syncwarp();
  if (lane == 0) mbar_arrive(cx.sb + SM_BAR_SQ);
  TSP(69)
}
__device__ __forceinline__ void attn_gate(const Ctx& cx, int qb, int hs, int j, int t, const __nv_bfloat16* x) {
  const uint4* xp = (const uint4*)(x + qb * 128 * DM) + (t >> 3) * 72 + hs * 8 + (t & 7);
  uint4 nx = *xp;
  float wsum = 0.f;
  if (j == 0) {
    mbar_wait(cx.sb + SM_BAR_W, 0);
#pragma unroll 3
    for (int i = 0; i < 9; i++) {
      const uint32_t w = *(const uint32_t*)(cx.sp + SM_WR + i * 128 + t * 4);
      wsum += bf_lo(w) + bf_hi(w);
    }
#pragma unroll
    for (int i = 1; i < 32; i *= 2) wsum += __shfl_xor_sync(0xffffffffu, wsum, i);
  }
  bar_sync(BAR_GATE, 352);
  if (t < 16) {
    const float2 st = *(const float2*)(cx.sp + SM_STATS + 8 * (hs * 16 + t));
    const int row = qb * 128 + hs * 16 + t;
    const uint32_t b = pack2(0.f, fmaf(-st.x, wsum, *(const float*)(cx.sp + SM_RAW + 4 * t)) * st.y);
    st_gran(at(cx.g->stats, row * 16), __float_as_uint(st.x), __float_as_uint(st.y), (b ^ ((int)b < 0 ? 0xFFFF0000u : 0x80000000u)) | (0xFFFF - row),
            *(const uint32_t*)(cx.sp + SM_TAG + 4) + 1);
  }
  __syncwarp();
  uint32_t sa = cx.sb + SM_STATS + (t & ~7);
  uint4* gp = cx.g->gate + blockIdx.x * 1152 + (t ^ ((t >> 3) & 7));
  const int cross = t < 64 ? 10 : 9;
#pragma unroll 1
  for (int i = 0; i < 12; i++) {
    float2 st;
    asm volatile("ld.shared.v2.f32 {%0, %1}, [%2];" : "=f"(st.x), "=f"(st.y) : "r"(sa));
    const uint32_t mm = pack2(st.x, st.x);
    const uint4 v = make_uint4(sub2(nx.x, mm), sub2(nx.y, mm), sub2(nx.z, mm), sub2(nx.w, mm));
    xp += 12 * 72;
    sa += 96;
    if (i == cross) { xp += (hs * 16 - 128) * 72 + 64 - hs * 8; sa += (hs * 16 - 128) * 8; }
    if (i < 11) nx = *xp;
    *gp = make_uint4(gate2<false>(v.x, st.y), gate2<false>(v.y, st.y), gate2<false>(v.z, st.y), gate2<false>(v.w, st.y));
    gp = (uint4*)((size_t)(gp + 96) ^ 64);
  }
}

constexpr uint32_t SM_XO = SM_SLOT, SM_GO = SM_SLOT + STAGE, SM_P8 = SM_SLOT + 2 * STAGE;
__device__ __forceinline__ void attn_helper(const Ctx& cx, int qb, int hs, int lane, const CUtensorMap* tmX16) {
  const unsigned e = *(const uint32_t*)(cx.sp + SM_TAG + 4);
  bar_sync(BAR_HELPER, 64);
  bool todo = lane < 2;
#pragma unroll 1
  for (int n = 0; __any_sync(0xffffffffu, todo); n++) {
    if (todo && (ld_acquire(at(cx.g->qflag, ((qb * 4 + (hs >> 1)) * 2 + lane) * 4)) == e + 1 || n == (1 << 16))) {
      asm volatile("fence.proxy.async.global;" ::: "memory");
      mbar_expect_tx(cx.sb + SM_BAR_Q + 8 * lane, 8192);
      bulk_load(cx.sb + SM_SLOT + 2 * STAGE + lane * 16384 + 8192, at(cx.g->q, ((qb * 8 + hs) * 2 + lane) * 8192), 8192, cx.sb + SM_BAR_Q + 8 * lane);
      todo = false;
    }
  }
  const uint32_t tag = (~e & 1) * TAG;
  const uint4* src = cx.g->part + (size_t)((qb * 64 + 56) * 2 + (hs >> 2)) * 4 * 128 + (hs & 3) * 32 + lane;
  const uint32_t stg = cx.sb + SM_P8 + lane * 16;
  bar_sync(BAR_OA, 352);
  asm volatile("fence.proxy.async.global;" ::: "memory");
  if (lane == 0) {
    mbar_expect_tx(cx.sb + SM_BAR_MISC, 2 * 18432);
    bulk_load(cx.sb + SM_GO, cx.g->gate + blockIdx.x * 1152, 18432, cx.sb + SM_BAR_MISC);
#pragma unroll 1
    for (int i = 0; i < 9; i++)
      tma2d(cx.sb + SM_XO + i * 2048, tmX16, i < 8 ? hs * 64 : 512, qb * 128 + (i < 8 ? i : hs) * 16, cx.sb + SM_BAR_MISC);
  }
#pragma unroll 1
  for (int n = 0; n < (1 << 16); n++) {
    __nanosleep(n ? 500 : 2000);
    uint32_t a, b, d, t;
    ld_gran(src - lane + (lane & 7) * (2 * 4 * 128) + 3 * 128 + 31, a, b, d, t);
    if (__all_sync(0xffffffffu, (a & TAG) == tag)) break;
  }
#pragma unroll 1
  for (int n = 0; n < (1 << 16); n++) {
#pragma unroll 1
    for (int i = 0; i < 8; i++) {
#pragma unroll
      for (int g = 0; g < 4; g++) cp16(stg + (i * 4 + g) * 512, src + i * (2 * 4 * 128) + g * 128);
    }
    cp_wait_all();
    uint32_t bad = 0;
#pragma unroll 4
    for (int i = 0; i < 32; i++) bad |= *(const volatile uint32_t*)(cx.sp + SM_P8 + lane * 16 + i * 512) ^ tag;
    if (__all_sync(0xffffffffu, (bad & TAG) == 0)) break;
  }
#pragma unroll 1
  for (int n = 0; n < (1 << 16) && ld_acquire(&cx.g->ycnt) != 4 * (e + 1); n++) __nanosleep(200);
  const int2 sel = __ldcg(at(cx.g->sel, (lane & 7) * 8));
  const int lr = sel.x - qb * 128;
  uint32_t m = __ballot_sync(0xffffffffu, lane < 16 && ((lane & 8) ? (lr >> 4) == hs : (lr >> 7) == 0));
  mbar_wait(cx.sb + SM_BAR_MISC, 0);
#pragma unroll 1
  for (; m; m &= m - 1) {
    const int i = __ffs(m) - 1, row = __shfl_sync(0xffffffffu, lr, i);
    const float rs = __int_as_float(__shfl_sync(0xffffffffu, sel.y, i));
    const float* p = cx.g->ypart + (i & 7) * DM + (i < 8 ? hs * 64 : 512) + 2 * lane;
    const float2 a = __ldcg((const float2*)p), b = __ldcg((const float2*)(p + TOPC * DM)), c = __ldcg((const float2*)(p + 2 * TOPC * DM)),
                 d = __ldcg((const float2*)(p + 3 * TOPC * DM));
    const uint32_t y = pack2((a.x + b.x) + (c.x + d.x), (a.y + b.y) + (c.y + d.y));
    const uint32_t u = pack2(bf_lo(y) * rs, bf_hi(y) * rs);
    const float2 st = *(const float2*)(cx.sp + SM_STATS + 8 * row);
    const int o = (i < 8 ? row : 128 + (row & 15)) * 128 + ((lane * 4) ^ ((row & 7) << 4));
    *(uint32_t*)(cx.sp + SM_GO + o) = gate2<true>(sub2(*(const uint32_t*)(cx.sp + SM_XO + o), pack2(st.x, st.x)), st.y, make_float2(bf_lo(u), bf_hi(u)));
  }
  __syncwarp();
  if (lane == 0) mbar_arrive(cx.sb + SM_BAR_XG);
}
__device__ __forceinline__ void attn_finish8(const Ctx& cx, int qb, int hs, int hw, int lane, __nv_bfloat16* out) {
  bar_sync(BAR_GATE, 96);
#pragma unroll 1
  for (int g = hw; g < 4; g += 3) {
    float acc[8] = {0.f, 0.f, 0.f, 0.f, 0.f, 0.f, 0.f, 0.f};
#pragma unroll 2
    for (int sidx = 0; sidx < 8; sidx++) {
      uint32_t a, b, d, t;
      lds128(cx.sb + SM_P8 + lane * 16 + (sidx * 4 + g) * 512, a, b, d, t);
      acc[0] += bf_lo(a); acc[1] += bf_hi(a & ~TAG); acc[2] += bf_lo(b); acc[3] += bf_hi(b);
      acc[4] += bf_lo(d); acc[5] += bf_hi(d); acc[6] += bf_lo(t); acc[7] += bf_hi(t);
    }
#pragma unroll
    for (int j = 0; j < 4; j++) {
      const int o = (128 + (lane >> 2) + (j & 1) * 8) * 128 + (((2 * g + (j >> 1)) ^ (lane >> 2)) << 4) + (lane & 3) * 4;
      uint32_t* xp = (uint32_t*)(cx.sp + SM_XO + o);
      *xp = fma2(pack2(acc[2 * j], acc[2 * j + 1]), *(const uint32_t*)(cx.sp + SM_GO + o), *xp);
    }
  }
  bar_sync(BAR_GATE, 96);
#pragma unroll 1
  for (int ch = threadIdx.x - 32; ch < 128; ch += 96)
    *(uint4*)at(out, ((qb * 128 + hs * 16 + (ch >> 3)) * DM + 512 + (ch & 7) * 8) * 2) =
        *(const uint4*)(cx.sp + SM_XO + 16384 + (ch ^ ((ch >> 3) & 7)) * 16);
}

__device__ __forceinline__ void ffn_producer(const Ctx& cx, int f, const CUtensorMap* tmWq, const CUtensorMap* tmG,
                                             const CUtensorMap* tmU, const CUtensorMap* tmD) {
  uint64_t keep;
  asm("createpolicy.fractional.L2::evict_normal.b64 %0, 1.0;" : "=l"(keep));
  int st = 0;
#pragma unroll 1
  for (int p = 0; p < 16; p++) {
#pragma unroll 1
    for (int i = 0; i < 5; i++, st++) if (st > 1) load_wq(cx, tmWq, st, i, ((2 * (p & 3) + cx.rank) * 4 + 3) * DH + 64, keep);
  }
  const uint32_t full = cx.sb + SM_FFULL, empty = cx.sb + SM_FEMPTY;
  int pair = 0, u = 0;
#pragma unroll 1
  for (st = 0; st < 14 * 12; st++) {
    const uint32_t sl = st & 7;
    const int unit = pair * 2 + (u & 1), k = u >> 1, k3 = k >= 3 ? k - 3 : k;
    if (unit < 27) {
      mbar_wait(empty + 8 * sl, (st >> 3) & 1);
      __syncwarp();
      if (elect_one()) {
        mbar_expect_tx(full + 8 * sl, FSTAGE);
        if (pair < 9) tma2d_stream(cx.sb + sl * FSTAGE, k < 3 ? tmG : tmU, f * 1152 + unit * 64, k3 * 192, full + 8 * sl);
        else tma2d_stream(cx.sb + sl * FSTAGE, tmD, (unit - 18) * 64, f * 1152 + k * 192, full + 8 * sl);
      }
    }
    if (++u == 12) { u = 0; pair++; }
  }
}
__device__ __forceinline__ void load_x1(uint32_t dst, const CUtensorMap* tmX64, int row, int box, int n, uint32_t bar) {
  mbar_expect_tx(bar, n * 8192);
#pragma unroll 1
  for (int i = 0; i < n; i++) tma2d(dst + i * 8192, tmX64, (box + i) * 64, row, bar);
}
__device__ __forceinline__ void ffn_publish(const Ctx& cx, int f, int w, int lane, const CUtensorMap* tmX64) {
  const uint32_t xs = cx.sb + SM_SLOT + w * 49152, xf = cx.sb + SM_XFULL + w * 32;
#pragma unroll 1
  for (int n = 0; n < 16; n++) {
    const int p = n & 3, row = (f + (n & 12) + 4) * 128 + w * 64;
    bar_sync(BAR_QS + w, 160);
    const uint32_t e1 = *(const uint32_t*)(cx.sp + SM_TAG + 4) + 1;
    if (lane == 0) {
#pragma unroll
      for (int i = 0; i < 2; i++)
        asm volatile("cp.async.bulk.global.shared::cta.bulk_group [%0], [%1], 8192;"
                     ::"l"(cx.g->q + (((f + (n & 12)) * 8 + 2 * p + i) * 2 + w) * 512), "r"(xs + 32768 + i * 8192) : "memory");
      asm volatile("cp.async.bulk.commit_group;" ::: "memory");
      if (n < 12 && (p == 0 || p == 3)) load_x1(xs, tmX64, row, p ? 4 : 0, 4, xf + (p ? 8 : 0));
      asm volatile("cp.async.bulk.wait_group.read 0;" ::: "memory");
      if (n < 12 && p == 3) load_x1(xs + 32768, tmX64, row, 8, 1, xf + 16);
      asm volatile("cp.async.bulk.wait_group 0;\nfence.proxy.async.global;" ::: "memory");
      asm volatile("st.release.gpu.global.u32 [%0], %1;" ::"l"(&cx.g->qflag[((f + (n & 12)) * 4 + p) * 2 + w]), "r"(e1) : "memory");
    }
    __syncwarp();
    if (n < 12 && p == 1) {
#pragma unroll 1
      for (int i = 0, k = 0; i < 64 && k < (1 << 16); k++) {
        uint32_t m, r, z, t;
        ld_gran(cx.g->stats + row + i + lane, m, r, z, t);
        *(uint2*)(cx.sp + SM_STATS + 8 * (w * 64 + i + lane)) = make_uint2(m, r);
        if (__all_sync(0xffffffffu, t == e1)) i += 32;
      }
    }
    bar_arrive(BAR_QF + w, 160);
  }
}

__device__ __forceinline__ void ffn_consumer(const Ctx& cx, int f, int wg, int cw, int lane, const __nv_bfloat16* x) {
  const int r = lane >> 2, c = lane & 3, tid = cw * 32 + lane;
  const uint32_t full = cx.sb + SM_FFULL, empty = cx.sb + SM_FEMPTY;
  const bool signaller = (tid & 127) == 0;
  prof(wg, 8);
  const unsigned e = *(const uint32_t*)(cx.sp + SM_TAG + 4);
  uint32_t key[8];
#pragma unroll 1
  for (int n = 0; n < (1 << 16); n++) {
    uint32_t bad = 0;
#pragma unroll
    for (int i = 0; i < 8; i++) {
      uint32_t t;
      asm volatile("ld.relaxed.gpu.global.v2.b32 {%0, %1}, [%2];" : "=r"(key[i]), "=r"(t) : "l"(&cx.g->stats[i * 256 + tid].z) : "memory");
      bad |= t ^ (e + 1);
    }
    if (__all_sync(0xffffffffu, bad == 0)) break;
  }
  bar_sync(BAR_QF + wg, 160);
  bar_sync(3, 256);
  if (tid < 8) mbar_arrive(empty + 8 * tid);
  prof(wg, 9);
  int mysel = 0;
#pragma unroll 1
  for (int k = 0; k < TOPC; k++) {
    uint32_t m = key[0];
#pragma unroll
    for (int i = 1; i < 8; i++) m = max(m, key[i]);
    m = __reduce_max_sync(0xffffffffu, m);
    uint32_t* tk = (uint32_t*)(cx.sp + SM_TOPK) + (k & 1) * 8;
    if (lane == 0) tk[cw] = m;
    bar_sync(3, 256);
    m = __reduce_max_sync(0xffffffffu, tk[lane & 7]);
#pragma unroll
    for (int i = 0; i < 8; i++) if (key[i] == m) key[i] = 0;
    if (k == cw) mysel = 0xFFFF - (int)(m & 0xFFFF);
  }
  {
    const float4 st = __ldcg((const float4*)&cx.g->stats[mysel]);
    const uint32_t mm = pack2(st.x, st.x);
#pragma unroll 3
    for (int i = 0; i < 9; i++) {
      const uint32_t t = sub2(*(const uint32_t*)(x + (size_t)mysel * DM + i * 64 + 2 * lane), mm);
      *(uint32_t*)(cx.sp + SM_XSEL + i * 1024 + cw * 128 + (((lane >> 2) ^ cw) << 4) + (lane & 3) * 4) =
          pack2(bf_lo(t) * st.y, bf_hi(t) * st.y);
    }
    const uint32_t k = __float_as_uint(st.z);
    const float score = bf_hi(k ^ ((int)k < 0 ? 0x80000000u : 0xFFFF0000u));
    if (lane == 0 && f == 0) cx.g->sel[cw] = make_int2(mysel, __float_as_int(bfr(rcp(1.0f + ex2(-1.4426950408889634f * score)))));
  }
  asm volatile("fence.proxy.async.shared::cta;" ::: "memory");
  bar_sync(3, 256);
  prof(wg, 10);
  auto run = [&](float (&acc)[4], int st, int n, uint32_t b) {
#pragma unroll 1
    for (int u = 0; u < n; u++, st += 2, b += 3072) {
      const uint32_t sl = st & 7;
      mbar_wait(full + 8 * sl, (st >> 3) & 1);
      wg_fence();
      const uint64_t da = mkdesc(cx.sb + sl * FSTAGE, 16), db = mkdesc(b, 16);
#pragma unroll
      for (int k = 0; k < 12; k++) mma_n8(acc, da + k * 128, db + (k >> 2) * 64 + (k & 3) * 2, u > 0 || k > 0);
      wg_commit();
      wg_wait<0>();
      if (signaller) mbar_arrive(empty + 8 * sl);
    }
    pin(acc);
  };
#pragma unroll 1
  for (int unit = wg; unit < 27; unit += 2) {
    if (unit >> 1 == 9) {
      asm volatile("fence.proxy.async.shared::cta;" ::: "memory");
      bar_sync(3, 256);
      prof(wg, 11);
    }
    const bool gu = unit < 18;
    float a0[4], a1[4];
#pragma unroll 1
    for (int m = 0; m < (gu ? 2 : 1); m++) {
      run(a1, (unit >> 1) * 12 + m * 6 + wg, gu ? 3 : 6, cx.sb + (gu ? SM_XSEL : SM_H));
      if (m == 0) { a0[0] = a1[0]; a0[1] = a1[1]; a0[2] = a1[2]; a0[3] = a1[3]; }
    }
    float u0 = a1[0], u1 = a1[1];
#pragma unroll 1
    for (int i = 0; i < 2; i++) {
      const int fl = (cw & 3) * 16 + r + i * 8;
      if (gu) {
        const uint32_t g = pack2(a0[0], a0[1]);
        const uint32_t h = fma2(pack2(silu_f(bf_lo(g)), silu_f(bf_hi(g))), pack2(u0, u1), 0x80008000u);
        uint8_t* hp = cx.sp + SM_H + unit * 1024 + c * 256 + (fl & 7) * 2;
        *(uint16_t*)(hp + (((fl >> 3) ^ (2 * c)) << 4)) = (uint16_t)h;
        *(uint16_t*)(hp + 128 + (((fl >> 3) ^ (2 * c + 1)) << 4)) = (uint16_t)(h >> 16);
      } else {
        float* yp = cx.g->ypart + (f * TOPC + 2 * c) * DM + (unit - 18) * 64 + fl;
        yp[0] = u0;
        yp[DM] = u1;
      }
      a0[0] = a0[2]; a0[1] = a0[3]; u0 = a1[2]; u1 = a1[3];
    }
  }
  prof(wg, 12);
  bar_sync(3, 256);
  if (tid == 0) atom_add_acq_rel(&cx.g->ycnt);
  prof(wg, 13);
}

constexpr float SUM_HI = 1.8446744e19f, SUM_LO = 9.0949470e-13f;

template <int LO, int HI, int N>
__device__ __forceinline__ void softmax_exp(float (&s)[N]) {
#pragma unroll
  for (int i = LO; i < HI; i++) s[i] = ex2(s[i]);
}
__device__ __forceinline__ void sum_tree(const uint32_t (&pf)[28], bool big, uint32_t& h0, uint32_t& h1) {
  uint32_t t0 = add2(add2(pf[16], pf[18]), add2(pf[20], pf[22])), t1 = add2(add2(pf[17], pf[19]), add2(pf[21], pf[23]));
  if (big) { t0 = add2(t0, add2(pf[24], pf[26])); t1 = add2(t1, add2(pf[25], pf[27])); }
  h0 = add2(add2(add2(add2(pf[0], pf[2]), add2(pf[4], pf[6])), add2(add2(pf[8], pf[10]), add2(pf[12], pf[14]))), t0);
  h1 = add2(add2(add2(add2(pf[1], pf[3]), add2(pf[5], pf[7])), add2(add2(pf[9], pf[11]), add2(pf[13], pf[15]))), t1);
}
__device__ __forceinline__ void exact_attention(float (&o)[16], float& l0, float& l1, const uint32_t (&q)[32], const __nv_bfloat16* kp,
                                                const __nv_bfloat16* vp) {
  float m0 = -3.0e38f, m1 = -3.0e38f;
  l0 = l1 = 0.f;
#pragma unroll
  for (int i = 0; i < 16; i++) o[i] = 0.f;
#pragma unroll 1
  for (int key = 0; key < SEQ; key += 8, kp += 8 * DH, vp += 8 * DH) {
    float d[4] = {0.f, 0.f, 0.f, 0.f};
#pragma unroll
    for (int k = 0; k < 8; k++)
      hmma_k16(d, q[4 * k], q[4 * k + 1], q[4 * k + 2], q[4 * k + 3], *(const uint32_t*)(kp + k * 16), *(const uint32_t*)(kp + k * 16 + 8));
    float x0 = fmaxf(d[0], d[1]), x1 = fmaxf(d[2], d[3]);
    x0 = fmaxf(x0, __shfl_xor_sync(0xffffffffu, x0, 1));
    x1 = fmaxf(x1, __shfl_xor_sync(0xffffffffu, x1, 1));
    x0 = fmaxf(fmaxf(x0, __shfl_xor_sync(0xffffffffu, x0, 2)), m0);
    x1 = fmaxf(fmaxf(x1, __shfl_xor_sync(0xffffffffu, x1, 2)), m1);
    const float sc0 = ex2(m0 - x0), sc1 = ex2(m1 - x1);
    m0 = x0; m1 = x1;
    const uint32_t p0 = pack2(ex2(d[0] - m0), ex2(d[1] - m0)), p1 = pack2(ex2(d[2] - m1), ex2(d[3] - m1));
    l0 = fmaf(l0, sc0, bf_lo(p0) + bf_hi(p0));
    l1 = fmaf(l1, sc1, bf_lo(p1) + bf_hi(p1));
#pragma unroll
    for (int nb = 0; nb < 4; nb++) {
      uint32_t b;
      asm("movmatrix.sync.aligned.m8n8.trans.b16 %0, %1;" : "=r"(b) : "r"(*(const uint32_t*)(vp + nb * 8)));
      o[4 * nb] *= sc0; o[4 * nb + 1] *= sc0; o[4 * nb + 2] *= sc1; o[4 * nb + 3] *= sc1;
      asm volatile("mma.sync.aligned.m16n8k8.row.col.f32.bf16.bf16.f32 {%0, %1, %2, %3}, {%4, %5}, {%6}, {%0, %1, %2, %3};"
                   : "+f"(o[4 * nb]), "+f"(o[4 * nb + 1]), "+f"(o[4 * nb + 2]), "+f"(o[4 * nb + 3]) : "r"(p0), "r"(p1), "r"(b));
    }
  }
}
__device__ __forceinline__ bool inv_sums(float l0, float l1, float& i0, float& i1) {
  l0 += __shfl_xor_sync(0xffffffffu, l0, 1); l1 += __shfl_xor_sync(0xffffffffu, l1, 1);
  l0 += __shfl_xor_sync(0xffffffffu, l0, 2); l1 += __shfl_xor_sync(0xffffffffu, l1, 2);
  i0 = rcp(l0);
  i1 = rcp(l1);
  return !(l0 + l1 <= SUM_HI) | (fminf(l0, l1) < SUM_LO);
}
template <int LO, int HI, int N>
__device__ __forceinline__ void park(uint32_t a, const float (&o)[N], float i0, float i1, bool on = true) {
#pragma unroll
  for (int i = LO; i < HI; i++)
    asm volatile("{\n.reg .pred p;\nsetp.ne.u32 p, %5, 0;\n@p stmatrix.sync.aligned.m8n8.x4.shared.b16 [%0], {%1, %2, %3, %4};\n}"
                 ::"r"(a + i * 2048), "r"(pack2(o[8 * i] * i0, o[8 * i + 1] * i0)), "r"(pack2(o[8 * i + 2] * i1, o[8 * i + 3] * i1)),
                 "r"(pack2(o[8 * i + 4] * i0, o[8 * i + 5] * i0)), "r"(pack2(o[8 * i + 6] * i1, o[8 * i + 7] * i1)), "r"((uint32_t)on) : "memory");
}

template <int I, int NP, int E0, int N, int NS>
__device__ __forceinline__ void exp_park(float (&s)[NS], uint32_t a, const float (&o)[64], float i0, float i1, bool on, int id) {
  if constexpr (I < NP) {
    constexpr int E1 = E0 + (N - E0) * X_PG / (NP - I);
    softmax_exp<E0, E1>(s);
    park<I, I + X_PG>(a, o, i0, i1, on);
    if (I + X_PG < NP) {
#pragma unroll
      for (int i = E0; i < E1; i++) asm volatile("" : "+f"(s[i])::"memory");
      block_fence(id + I);
    }
    exp_park<I + X_PG, NP, E1, N>(s, a, o, i0, i1, on, id);
  }
}

__device__ __forceinline__ void attn_consumer(const Ctx& cx, bool hlp, int qb, int hs, int wg, int cw, int lane, const __nv_bfloat16* x,
                                              const __nv_bfloat16* kc, const __nv_bfloat16* vc, __nv_bfloat16* out) {
  const uint32_t full = cx.sb + SM_FULL;
  const uint32_t ring = cx.sb + SM_RING;
  const uint32_t qwg = ring + wg * 16384;
  auto qlane = [&](int l) { return qwg + (cw & 3) * 256 + (l >> 4) * 1024 + (l & 15) * 16; };
  const bool signaller = lane == 0 && (cw & 3) < 2;
  const int my_turn = 1 + wg, other_turn = 2 - wg;
  const uint32_t empty_c = mapa(cx.sb + SM_EMPTY, cw & 1);

  float oA[64], oB[64], i0, i1;
  uint32_t xl[32];
  {
    const int r = lane >> 2, c = lane & 3;
    const int lr0 = cw * 16 + r;
    uint32_t xa[144];
    uint32_t mm0, mm1;
    float rstd0, rstd1, sq0 = 0.f, sq1 = 0.f;
    const uint32_t xf = cx.sb + SM_XFULL + wg * 32, xs = cx.sb + SM_SLOT + wg * 49152;
    auto lo_of = [&](int l) { return ((cw & 3) * 16 + (l & 15)) * 128 + (((l >> 4) ^ (l & 7)) << 4); };
    prof(wg, 0);
    {
      const uint32_t lo = lo_of(lane);
      const uint32_t xb = cx.sb + SM_X + wg * 73728;
      float sm[X_NS][4] = {};
      const uint32_t ws = (lane & 7) == 1 ? 64 : 0;
      uint32_t wb = cx.sb + (ws ? SM_WR + (lane >> 3) * 16 : SM_ONES);
      uint32_t b0[24], b1[24], b2[24];
      TS4(1)
      mbar_wait(cx.sb + SM_BAR_W, 0);
      if (X_LN == 0) {
        ln_fetch_b(b0, wb, ws);
        ln_fetch_b(b1, wb, ws);
        ln_fetch_b(b2, wb, ws);
      }
      mbar_wait(xf, 0);
      TS4(2)
      ln_fetch<0, 12>(xa, xb, lo);
      if (X_LN == 1) {
        ln_fetch_b(b0, wb, ws);
        ln_fetch_b(b1, wb, ws);
        ln_fetch_b(b2, wb, ws);
      }
      ln_sums<0, 12>(xa, sm, b0);
      mbar_wait(xf + 8, 0);
      TS4(3)
      ln_fetch<12, 24>(xa, xb, lo);
      if (wg == 0) {
        bar_arrive(BAR_XREL + (xa[95] & blockIdx.y), 224);
      }
      ln_sums<12, 24>(xa, sm, b1);

      mbar_wait(xf + 16, 0);
      TS4(4)
      prof(wg, 1);
      ln_fetch<24, 36>(xa, xb, lo);
      ln_sums<24, 36>(xa, sm, b2);
#pragma unroll
      for (int i = 0; i < 4; i++) sm[0][i] = X_NS == 2 ? sm[0][i] + sm[1][i] : X_NS == 3 ? sm[0][i] + sm[1][i] + sm[2][i] : (sm[0][i] + sm[1][i]) + (sm[2][i] + sm[X_NS - 1][i]);
      if (cw == hs && c == 0) {
        *(float*)(cx.sp + SM_RAW + 4 * r) = sm[0][1];
        *(float*)(cx.sp + SM_RAW + 4 * r + 32) = sm[0][3];
      }
      rstd0 = sm[0][0];
      rstd1 = sm[0][2];
      mm0 = pack2(rstd0 * (1.0f / DM), rstd0 * (1.0f / DM));
      mm1 = pack2(rstd1 * (1.0f / DM), rstd1 * (1.0f / DM));
    }
#pragma unroll
    for (int i = 0; i < 16; i++) { xa[2 * i] = sub2(xa[2 * i], mm0); xa[2 * i + 1] = sub2(xa[2 * i + 1], mm1); }
    pin(xa);
    prof(wg, 2);
    TS4(5)

    float (&acc)[64] = oB;
    int st0 = 0;
#pragma unroll 1
    for (int n = 0; n < 16; n++) {
      const int p = n & 3, rb = n >> 2;
      const bool last = p == 3 && !hlp;
#pragma unroll
      for (int i = 0; i < 5; i++) {
        if (i == 4 && last) {
          wg_wait<1>();
          if (signaller && wg) mbar_arrive_cluster(empty_c + 8 * 3);
          wg_wait<0>();
          pin(acc);
          prof(wg, 6);
#pragma unroll
          for (int j = 0; j < 32; j++) xl[j] = xa[112 + j];
          i0 = rstd0;
          i1 = rstd1;
          goto attention;
        }
        const int st = st0 + i;
        const uint32_t sl = st & 3, slp = (st - 1) & 3;
        if (!wg) mbar_wait(full + 8 * sl, (st >> 2) & 1);
        TS4(8 + 2 * (p * 5 + i))
        const bool join = wg && last;
        if ((i || st0 + wg) && i != (wg ? 4 : 1) && !(join && i == 3)) bar_sync(my_turn, 256);
        wg_fence();
        const uint64_t db = mkdesc(ring + sl * STAGE, 16384);
        const int kb0 = i < 3 ? 8 * i : 8 * i - 4;
#pragma unroll
        for (int k = 0; k < (i == 2 ? 4 : 8); k++) {
          const int kb = kb0 + k;
          mma_n128t(acc, xa[4 * kb], xa[4 * kb + 1], xa[4 * kb + 2], xa[4 * kb + 3], db + k * 128, kb > 0);
        }
        wg_commit();
        TS4(9 + 2 * (p * 5 + i))
        if (wg ? (i == 4 ? st0 < 75 : (i < 2 || i == (join ? 3 : 2))) : i) bar_arrive(other_turn, 256);
        if (p == 0 && i < 4) {
          if (i == 1 && rb) {
            mbar_wait(xf + 8, rb & 1);
            mbar_wait(xf + 16, rb & 1);
            ln_fetch<16, 36>(xa, xs - 32768, lo_of(fresh_lane()));
          }
#pragma unroll
          for (int j = 0; j < 72; j++)
            if (j >= 2 * (i < 2 ? 8 * i + 8 : 8 * i + 4) && j < 2 * (i == 0 ? 16 : 8 * i + 12)) {
              xa[2 * j] = sub2(xa[2 * j], mm0);
              xa[2 * j + 1] = sub2(xa[2 * j + 1], mm1);
            }
          pin(xa);
        }
        if (i == X_SQI && n == 0) {
          mbar_wait(cx.sb + SM_BAR_SQ, 0);
          float2* sp = (float2*)(cx.sp + SM_STATS) + lr0;
          float mean0, mean1;
          ln_row(rstd0, sp[0].y, mean0, rstd0);
          ln_row(rstd1, sp[8].y, mean1, rstd1);
          __syncwarp();
          if (c == 0) {
            sp[0] = make_float2(mean0, rstd0);
            sp[8] = make_float2(mean1, rstd1);
          }
          *((uint32_t*)(cx.sp + SM_COLD) + wg) = 0;
          if (!hlp) bar_arrive(BAR_GATE, 352);
          rstd0 *= SM_SCALE_LOG2;
          rstd1 *= SM_SCALE_LOG2;
        }
        if (i == 4 && p == 3 && rb < 3) {
          const float2* sp = (const float2*)(cx.sp + SM_STATS) + cw * 16 + (fresh_lane() >> 2);
          mm0 = pack2(sp[0].x, sp[0].x);
          mm1 = pack2(sp[8].x, sp[8].x);
          sq0 = sp[0].y * SM_SCALE_LOG2;
          sq1 = sp[8].y * SM_SCALE_LOG2;
#pragma unroll
          for (int j = 0; j < 16; j++) { xa[2 * j] = sub2(xa[2 * j], mm0); xa[2 * j + 1] = sub2(xa[2 * j + 1], mm1); }
          pin(xa);
        }
        if (i == 0) {
          if (wg) {
            wg_wait<0>();
            if (signaller) mbar_arrive_cluster(empty_c + 8 * sl);
          }
        } else if (i == 2) {
          if (!join) {
            wg_wait<0>();
            if (signaller) mbar_arrive_cluster(empty_c + 8 * sl);
          }
          if (hlp && p == 3 && rb < 3) {
            mbar_wait(xf, ~rb & 1);
            ln_fetch<0, 16>(xa, xs, lo_of(fresh_lane()));
            pin(xa);
          }
        } else if (i != 3) {
          wg_wait<1>();
          if (signaller && (i == 4 || !wg)) mbar_arrive_cluster(empty_c + 8 * slp);
          wg_wait<0>();
          if (signaller) mbar_arrive_cluster(empty_c + 8 * sl);
        }
      }
      pin(acc);
      prof(wg, 3 + p);
      TS4(50 + 2 * p)
      st0 += 5;
      if (hlp && st0 > 5) bar_sync(BAR_QF + wg, 160);
      park<0, 8>(qlane(lane) + (hlp ? 5 + wg : 4 + p) * STAGE, acc, rstd0, rstd1);
      if (p || hlp) asm volatile("fence.proxy.async.shared::cta;" ::: "memory");
      if (hlp) bar_arrive(BAR_QS + wg, 160);
      if (p == 3) { rstd0 = sq0; rstd1 = sq1; }
      TS4(51 + 2 * p)
      if (p == 1 && !hlp) {
        float (&ah)[32] = *(float (*)[32])&acc[0];
#pragma unroll
        for (int i = 0; i < 3; i++) {
          const uint32_t sl = (10 + i) & 3;
          if (!wg) mbar_wait(full + 8 * sl, ((10 + i) >> 2) & 1);
          TS4(28 + 2 * i)
          if (i == 0 || i == 2 - wg) bar_sync(my_turn, 256);
          wg_fence();
          const uint64_t db = mkdesc(ring + sl * STAGE, 16);
#pragma unroll
          for (int k = 0; k < 12; k++) {
            const int kb = 12 * i + k;
            if (kb) mma_n64t(ah, xa[4 * kb], xa[4 * kb + 1], xa[4 * kb + 2], xa[4 * kb + 3], db + k * 128, true);
            else mma_n64t_dyn(ah, xa[0], xa[1], xa[2], xa[3], db, blockIdx.y);
          }
          wg_commit();
          TS4(29 + 2 * i)
          if (i == 2 || i != wg) {
            bar_arrive(other_turn, 256);
            if (i) {
              wg_wait<1>();
              if (signaller && i == wg + 1) mbar_arrive_cluster(empty_c + 8 * ((9 + i) & 3));
            }
            wg_wait<0>();
            if (signaller) mbar_arrive_cluster(empty_c + 8 * sl);
          }
        }
        pin(ah);
        TS4(54)
        park<0, 4>(qlane(lane) + 6 * STAGE, ah, rstd0, rstd1);
        TS4(55)
        st0 = 13;
        n = 2;
      }
    }
    TS_DUMP()
    ffn_consumer(cx, blockIdx.x & 3, wg, cw, fresh_lane(), x);
    return;
  }

attention:
  uint32_t oa[128];
  float acc[32];
  {
    uint32_t pf[28];
    uint32_t bad = 0;
    float lA0 = 0.f, lA1 = 0.f, lB0 = 0.f, lB1 = 0.f;
    int t = 0;
    uint32_t ra = 2 * 2048, rb = 2048, rc = 2 * 2048, par = 0;
    const uint64_t dk0 = mkdesc(ring, 16), dv0 = mkdesc(ring, 16384);
    uint64_t dqA = mkdesc_q(qwg + 4 * STAGE), dqB = dqA + 2048;
    auto turn = [&](auto kc_, auto bc_) {
      constexpr int KIND = decltype(kc_)::value, BIG = decltype(bc_)::value;
      constexpr int HB = KIND == 1, ID = 10 * KIND + 30 * BIG, T0 = BIG ? 38 : 0;
      constexpr int NS = BIG ? 56 : 48, SPLIT = BIG ? (HB ? X_SPLIT : X_SPLITA) : (HB ? X_SPLITS : X_SPLITSA);
      float s[NS];
      float (&op)[64] = HB ? oA : oB;
      uint32_t h0 = 0, h1 = 0;
      TS2(0)
      bar_sync(my_turn, 256);
      TS2(1)
      if (KIND) { pin(pf); pin(op); }
      mma_qk(s, HB ? dqB : dqA, dk0 + (HB ? ra : rc));
      TS2(2)
      if (KIND) {
        const bool bigp = HB ? BIG : BIG ? t != 10 : t == 66;
        if (X_BF2) block_fence(ID + 9);
        pin(pf);
        sum_tree(pf, bigp, h0, h1);
        asm volatile("" : "+r"(h0), "+r"(h1)::"memory");
        if (HB) mbar_wait(full + (rb >> 8), par);
        mma_pv(op, pf, dv0 + rb, t != T0 + 2 - HB, bigp);
      } else {
        mbar_wait(full + (rb >> 8), (NST_Q - 1) >> 2 & 1);
#pragma unroll
        for (int k = 0; k < 8; k++) mma_n128t(op, xl[4 * k], xl[4 * k + 1], xl[4 * k + 2], xl[4 * k + 3], dv0 + rb + k * 128, 1);
        wg_commit();
      }
      TS2(3)
      bar_arrive(other_turn, 256);
      (HB ? lA0 : lB0) += bf_lo(h0) + bf_hi(h0);
      (HB ? lA1 : lB1) += bf_lo(h1) + bf_hi(h1);
      wg_wait<1>();
      pin(s);
      TS1(t)
      TS2(4)
      if (KIND == 1) mbar_arrive_cluster_now<ID + 3>(empty_c + (ra >> 8), signaller);
      if (BIG && t == T0 + HB) {
        const uint32_t a = qlane(fresh_lane()) + (4 + HB) * STAGE;
        const bool ok = !__any_sync(0xffffffffu, inv_sums(HB ? lB0 : lA0, HB ? lB1 : lA1, i0, i1));
        bad = (HB ? bad : 0) | (ok ? 0 : 1 << HB);
        (HB ? lB0 : lA0) = 0.f;
        (HB ? lB1 : lA1) = 0.f;
        softmax_exp<0, X_E0>(s);
#pragma unroll
        for (int i = 0; i < X_E0; i++) asm volatile("" : "+f"(s[i])::"memory");
        block_fence(ID + 7);
        exp_park<0, X_PA, X_E0, SPLIT>(s, a, HB ? oB : oA, i0, i1, ok, 200 + ID);
        if (!HB) dqB += 2048;
        prof(wg, 8 + HB);
      } else {
        if (HB && !BIG) bad = (bad & 3) | (inv_sums(lA0, lA1, i0, i1) ? 4 : 0);
        softmax_exp<0, SPLIT>(s);
      }
      pin(s);
      if (!BIG) block_fence(ID + 4);
      TS2(5)
      wg_wait<0>();
      TS2(6)
      pin(op);
      if (KIND) pin(pf); else pin(xl);
      if (HB) {
        par ^= rc == 2048;
        if (BIG && t == 37) dqA -= 4 * 2048;
        if (BIG && t == X_WAKE && cw == 0) bar_arrive(BAR_HELPER, 64);
      } else {
        mbar_arrive_cluster_now<ID + 5>(empty_c + (rb >> 8), signaller);
        if (KIND) {
          par ^= ra == 2048;
          const uint32_t x = ra;
          ra = rc; rc = rb; rb = x;
        }
      }
      softmax_exp<SPLIT, NS>(s);
#pragma unroll
      for (int i = 0; i < NS / 2; i++) pf[i] = pack2(s[2 * i], s[2 * i + 1]);
      pin(pf);
      if (KIND == 0) {
        block_fence(ID + 6);
        park<0, 8>(qlane(fresh_lane()), oB, i0, i1);
        asm volatile("fence.proxy.async.shared::cta;" ::: "memory");
        prof(wg, 7);
      }
      if (BIG && X_PA < 8 && t == T0 + HB) park<X_PA, 8>(qlane(fresh_lane()) + (4 + HB) * STAGE, HB ? oB : oA, i0, i1, !(bad >> HB));
      if (BIG && !HB && t == T0) mbar_wait(cx.sb + SM_BAR_Q + 8 * wg, 0);
      if (HB) mbar_wait(full + (rc >> 8), par);
      t++;
    };
#pragma unroll
    for (int i = 24; i < 28; i++) asm volatile("" : "=r"(pf[i]));
    mbar_wait(full + 8 * 2, 0);
    turn(IC<0>(), IC<0>());
    rb = 3 * 2048; rc = 2048;
    kill(oA);
    const bool never = blockIdx.y == 1;
#pragma unroll 1
    while (true) {
      turn(IC<1>(), IC<0>());
      if (t == 76) break;
      if (t == 10) {
#pragma unroll 1
        do {
#pragma unroll 1
          do turn(IC<2>(), IC<1>()); while (never);
          turn(IC<1>(), IC<1>());
        } while (t != 66);
      }
#pragma unroll 1
      do turn(IC<2>(), IC<0>()); while (never);
    }
    const uint32_t ql = qlane(fresh_lane());
    auto scale = [&](auto lo, auto hi) {
#pragma unroll
      for (int i = decltype(lo)::value; i < decltype(hi)::value; i++) {
        oa[32 + 2 * i] = pack2(oA[4 * i] * i0, oA[4 * i + 1] * i0);
        oa[32 + 2 * i + 1] = pack2(oA[4 * i + 2] * i1, oA[4 * i + 3] * i1);
        asm volatile("" : "+r"(oa[32 + 2 * i]), "+r"(oa[32 + 2 * i + 1])::"memory");
      }
    };
    TS3(1)
    if (X_LD == 0) {
#pragma unroll
      for (int i = 0; i < 8; i++) ldsm4(ql + 4 * STAGE + i * 2048, oa[4 * i], oa[4 * i + 1], oa[4 * i + 2], oa[4 * i + 3]);
    }
    {
      uint32_t h0, h1;
      sum_tree(pf, false, h0, h1);
      if (inv_sums(lB0 + (bf_lo(h0) + bf_hi(h0)), lB1 + (bf_lo(h1) + bf_hi(h1)), lB0, lB1)) bad |= 8;
    }
    scale(IC<0>(), IC<X_F1>());
    volatile uint32_t* const cold = (volatile uint32_t*)(cx.sp + SM_COLD) + wg;
    if (bad) *cold = 1;
    block_fence(93);
    TS3(2)
    bar_sync(my_turn, 256);
    const uint32_t is_cold = *cold;
    TS3(3)
    pin(pf); pin(oB);
    mma_pv(oB, pf, dv0 + 2 * 2048, true, false);
    mbar_arrive_cluster_now<91>(empty_c, signaller && !is_cold);
    TS3(4)
    if (X_LD == 1) {
#pragma unroll
      for (int i = 0; i < 8; i++) ldsm4(ql + 4 * STAGE + i * 2048, oa[4 * i], oa[4 * i + 1], oa[4 * i + 2], oa[4 * i + 3]);
    }
    const uint64_t db = mkdesc(ring + 3 * STAGE, 16);
    scale(IC<X_F1>(), IC<X_F2>());
    block_fence(94);
#pragma unroll
    for (int i = 0; i < 32; i++) asm volatile("" : "+r"(oa[i])::"memory");
    wg_fence();
#pragma unroll
    for (int k = 0; k < 8; k++) mma_n64t(acc, oa[4 * k], oa[4 * k + 1], oa[4 * k + 2], oa[4 * k + 3], db + k * 128, k > 0);
    if (X_F2 < 16) {
      wg_commit();
      block_fence(95);
      scale(IC<X_F2>(), IC<16>());
      TS3(5)
      wg_fence();
    }
#pragma unroll
    for (int k = 8; k < 16; k++) mma_n64t(acc, oa[4 * k], oa[4 * k + 1], oa[4 * k + 2], oa[4 * k + 3], db + k * 128, 1);
    wg_commit();
    bar_arrive(other_turn, 256);
    wg_wait<(X_F2 < 16 ? 2 : 1)>();
    pin(oB); pin(pf);
    TS(76)
    TS3(6)
    if (signaller) mbar_arrive_cluster(empty_c + 8 * 2);
#pragma unroll
    for (int i = 16; i < 24; i++) ldsm4(ql + 5 * STAGE + (i & 7) * 2048, oa[4 * i], oa[4 * i + 1], oa[4 * i + 2], oa[4 * i + 3]);
#pragma unroll
    for (int i = 0; i < 16; i++) {
      oa[96 + 2 * i] = pack2(oB[4 * i] * lB0, oB[4 * i + 1] * lB0);
      oa[96 + 2 * i + 1] = pack2(oB[4 * i + 2] * lB1, oB[4 * i + 3] * lB1);
    }
    TS3(7)
    mbar_wait(full + 8 * 1, 0);
    TS3(8)
    wg_wait<0>();
    pin(acc); pin(oa);
    if (__any_sync(0xffffffffu, is_cold)) {
      bad = __reduce_or_sync(0xffffffffu, bad);
      if (!(bad & 8)) {
#pragma unroll
        for (int i = 24; i < 32; i++) stsm4(ql + 6 * STAGE + (i & 7) * 2048, oa[4 * i], oa[4 * i + 1], oa[4 * i + 2], oa[4 * i + 3]);
      }
#pragma unroll 1
      for (int h = 0; h < 4; h++) {
        if (bad >> h & 1) {
          const uint32_t a = ql + ((0x6054 >> (4 * h)) & 7) * STAGE;
          const int l = fresh_lane(), o = (hs * 2 + (h >> 1)) * SEQ * DH + (l >> 2) * DH + (l & 3) * 2;
          uint32_t q[32];
#pragma unroll
          for (int i = 0; i < 8; i++) ldsm4(a + i * 2048, q[4 * i], q[4 * i + 1], q[4 * i + 2], q[4 * i + 3]);
#pragma unroll 1
          for (int i = 0; i < 4; i++) {
            float ox[16], l0, l1;
            exact_attention(ox, l0, l1, q, kc + o, vc + o + i * 32);
            inv_sums(l0, l1, l0, l1);
            park<0, 2>(a + i * 4096, ox, l0, l1);
          }
        }
      }
      __syncwarp();
#pragma unroll
      for (int i = 0; i < 32; i++)
        if ((i >> 3) != 1 || (bad & 4))
          ldsm4(ql + ((0x6504 >> (4 * (i >> 3))) & 7) * STAGE + (i & 7) * 2048, oa[4 * i], oa[4 * i + 1], oa[4 * i + 2], oa[4 * i + 3]);
      pin(oa);
      asm volatile("fence.proxy.async.shared::cta;" ::: "memory");
      bar_sync(4 + wg, 128);
      if (signaller) mbar_arrive_cluster(empty_c);
      wg_fence();
#pragma unroll
      for (int k = 0; k < 16; k++) mma_n64t(acc, oa[4 * k], oa[4 * k + 1], oa[4 * k + 2], oa[4 * k + 3], db + k * 128, k > 0);
      wg_commit();
      wg_wait<0>();
      pin(acc);
    }
    if (signaller) mbar_arrive_cluster(empty_c + 8 * 3);
  }

  prof(wg, 10);
  TS3(9)
  {
    lane = fresh_lane();
    const int tw = (cw & 3) * 32 + lane;
    float red[32];
    kill(red);
    const uint32_t tag = *(const uint32_t*)(cx.sp + SM_TAG);
    uint4* const xch = at(cx.g->part, ((qb * 64 * 2 + wg) * 4 * 128 + tw) * 16);
    int nrx = 1;
    auto region = [](int s, int h) { return h ? 1 + (s & 1) : (s & 1) ? 0 : 3; };
    auto half_step = [&](int s, auto hc, bool arrive) {
      constexpr int h = decltype(hc)::value;
      const uint64_t db = mkdesc(ring + region(s, h) * STAGE, 16);
      bar_sync(my_turn, 256);
      pin(oa);
      wg_fence();
#pragma unroll
      for (int k = 0; k < 16; k++) {
        const int kb = h * 16 + k;
        mma_n64t(acc, oa[4 * kb], oa[4 * kb + 1], oa[4 * kb + 2], oa[4 * kb + 3], db + k * 128, kb > 0);
      }
      wg_commit();
      if (arrive) bar_arrive(other_turn, 256);
    };
    auto await = [&](int s, int h) { mbar_wait(full + 8 * region(s, h), ((s >> 1) ^ h ^ 1) & 1); };
    auto fetch = [&](uint32_t (&g)[16], int n) {
      const uint4* p = at(xch, (hs * 7 + n - 1) * 16384);
#pragma unroll
      for (int i = 0; i < 4; i++) ld_gran(p + i * 128, g[4 * i], g[4 * i + 1], g[4 * i + 2], g[4 * i + 3]);
    };
    uint32_t g[16];
#pragma unroll 1
    for (int s = 0; s < 8; s++) {
      const bool pend = nrx < s - 1;
      if (pend) fetch(g, nrx);
      half_step(s, IC<1>(), true);
      TS3(s < 3 ? 16 + 8 * s : 75)
      if (s == 0) {
        bar_arrive(BAR_OA, 352);
#pragma unroll
        for (int i = 0; i < 32; i++) red[i] = 0.f;
      }
      await(s + 1, 0);
      TS3(s < 3 ? 17 + 8 * s : 75)
      wg_wait<0>();
      TS3(s < 3 ? 18 + 8 * s : 75)
      if (signaller && s < 7) mbar_arrive_cluster(empty_c + 8 * region(s, 1));
      pin(acc);
      TS(77 + s)
      prof(wg, 12 + s);
      uint4* p = at(xch, (s == 0 ? 56 + hs : ((hs + s) & 7) * 7 + s - 1) * 16384);
#pragma unroll
      for (int i = 0; i < 4; i++)
        st_gran(p + i * 128, (pack2(acc[8 * i], acc[8 * i + 1]) & ~TAG) | tag, pack2(acc[8 * i + 2], acc[8 * i + 3]),
                pack2(acc[8 * i + 4], acc[8 * i + 5]), pack2(acc[8 * i + 6], acc[8 * i + 7]));
      TS3(s < 3 ? 19 + 8 * s : 75)
      half_step(s + 1, IC<0>(), true);
      TS3(s < 3 ? 20 + 8 * s : 75)
      await(s + 1, 1);
      TS3(s < 3 ? 21 + 8 * s : 75)
      if (pend && granules_ok(g, tag)) { add_granules(red, g); nrx++; }
      wg_wait<0>();
      TS3(s < 3 ? 22 + 8 * s : 75)
      if (signaller && s < 6) mbar_arrive_cluster(empty_c + 8 * region(s + 1, 0));
    }
    uint32_t xv[16], gt[16], g2[16];
    fetch(g, nrx);
    mbar_wait(cx.sb + SM_BAR_XG, 0);
    {
      const uint64_t db = mkdesc(ring + STAGE, 16);
      bar_sync(my_turn, 256);
#pragma unroll
      for (int i = 64; i < 128; i++) asm volatile("" : "+r"(oa[i])::"memory");
      wg_fence();
#pragma unroll
      for (int k = 16; k < 32; k++) mma_n64t(acc, oa[4 * k], oa[4 * k + 1], oa[4 * k + 2], oa[4 * k + 3], db + (k - 16) * 128, 1);
      wg_commit();
      if (wg == 0) bar_arrive(other_turn, 256);
    }
    const bool ok = granules_ok(g, tag);
    nrx += ok;
    fetch(g2, nrx);
    const uint32_t frag = (cw * 16 + (lane & 15)) * 128 + (((lane >> 4) ^ (lane & 7)) << 4);
#pragma unroll
    for (int i = 0; i < 4; i++) {
      ldsm4(cx.sb + SM_XO + (frag ^ (i << 5)), xv[4 * i], xv[4 * i + 1], xv[4 * i + 2], xv[4 * i + 3]);
      ldsm4(cx.sb + SM_GO + (frag ^ (i << 5)), gt[4 * i], gt[4 * i + 1], gt[4 * i + 2], gt[4 * i + 3]);
    }
    if (ok) add_granules(red, g);
    wg_wait<0>();
    pin(acc);
    TS(85)
#pragma unroll
    for (int i = 0; i < 32; i++) red[i] += acc[i];
    pin(red);
#pragma unroll 1
    for (int spins = 0; spins < (1 << 16); spins++) {
      if (granules_ok(g2, tag)) {
        add_granules(red, g2);
        if (++nrx == 8) break;
      }
      fetch(g2, nrx);
    }
    prof(wg, 20);
    TS(86)
    uint32_t ow[16];
#pragma unroll
    for (int i = 0; i < 16; i++) ow[i] = fma2(pack2(red[2 * i], red[2 * i + 1]), gt[i], xv[i]);
#pragma unroll
    for (int i = 0; i < 4; i++) stsm4(cx.sb + SM_XO + (frag ^ (i << 5)), ow[4 * i], ow[4 * i + 1], ow[4 * i + 2], ow[4 * i + 3]);
    __syncwarp();
    __nv_bfloat16* const op = at(out, ((qb * 128 + cw * 16 + (lane >> 3)) * DM + hs * 64 + (lane & 7) * 8) * 2);
#pragma unroll
    for (int i = 0; i < 4; i++) {
      uint4 v;
      const int row = cw * 16 + i * 4 + (lane >> 3);
      lds128(cx.sb + SM_XO + row * 128 + (((lane ^ row) & 7) << 4), v.x, v.y, v.z, v.w);
      asm volatile("st.global.v4.b32 [%0], {%1, %2, %3, %4};" ::"l"(op + i * 4 * DM),
                   "r"(v.x), "r"(v.y), "r"(v.z), "r"(v.w) : "memory");
    }
    prof(wg, 22);
    TS(87)
    TS_DUMP()
  }
}

struct KvMaps { CUtensorMap m[4]; };
__global__ void __cluster_dims__(2, 1, 1) __launch_bounds__(THREADS, 1)
fused_kernel(const __nv_bfloat16* __restrict__ x, const __nv_bfloat16* __restrict__ w_r, const __nv_bfloat16* __restrict__ kc,
             const __nv_bfloat16* __restrict__ vc, __nv_bfloat16* __restrict__ out, Scratch* scratch,
             const __grid_constant__ CUtensorMap tmX, const __grid_constant__ CUtensorMap tmWq,
             const __grid_constant__ KvMaps tmKV, const __grid_constant__ CUtensorMap tmWo,
             const __grid_constant__ CUtensorMap tmG, const __grid_constant__ CUtensorMap tmU,
             const __grid_constant__ CUtensorMap tmD, const __grid_constant__ CUtensorMap tmX16,
             const __grid_constant__ CUtensorMap tmWq96, const __grid_constant__ CUtensorMap tmX64) {
  extern __shared__ __align__(1024) uint8_t smem_raw[];
  prof(0, 23, 511);
  if (X_PFX && threadIdx.x == 192) { prefetch_tmap(&tmX); prefetch_tmap(&tmWq); }
  Ctx cx;
  cx.sb = smem_u32(smem_raw);
  cx.sp = smem_raw;
  cx.g = scratch;
  cx.rank = blockIdx.x & 1;
  const int warp = __shfl_sync(0xffffffffu, threadIdx.x >> 5, 0);
  const int cluster = blockIdx.x >> 1;
  const bool is_ffn = blockIdx.x >= N_ATT_CTA;
  const int c7 = ((cluster - 36) * 37) >> 8;
  const int hs = cluster < 4 ? 4 + cluster : cluster < 36 ? (cluster - 4) >> 3 : 4 + c7;
  const int qb = (cluster < 4 ? 0 : cluster < 36 ? (cluster - 4) & 7 : cluster - (is_ffn ? 36 : 35) - 7 * c7) * 2 + cx.rank;

  auto load_x = [&](int w, int i0, int i1) {
#pragma unroll
    for (int i = i0; i < i1; i++) {
      mbar_expect_tx(cx.sb + SM_XFULL + 32 * w + 8 * i, 24576);
      tma3d(cx.sb + SM_X + (3 * w + i) * 24576, &tmX, qb * 128 + w * 64, i * 3, cx.sb + SM_XFULL + 32 * w + 8 * i);
    }
  };
  if (warp < 4) {
    asm volatile("setmaxnreg.dec.sync.aligned.u32 24;");
    if (elect_one()) {
      if (warp == 0) TSP(64)
      if (warp < 2) {
#pragma unroll
        for (int i = 0; i < 4; i++) mbar_init(cx.sb + SM_FULL + 32 * warp + 8 * i, 1 + 3 * warp);
        mbar_init(cx.sb + SM_BAR_XG + 8 * warp, 1);
        mbar_init(cx.sb + SM_BAR_Q + 8 * warp, 1);
        if (warp) mbar_init(cx.sb + SM_BAR_MISC, 1);
      } else if (is_ffn) {
#pragma unroll
        for (int i = 0; i < 8; i++) mbar_init(cx.sb + (warp == 2 ? SM_FFULL : SM_FEMPTY) + 8 * i, 1);
      }
      asm volatile("fence.mbarrier_init.release.cluster;" ::: "memory");
    }
    __syncwarp();
    cluster_arrive();
    if (warp == 0) TSP(70)
    cluster_wait();
    if (warp == 0) TSP(71)
    prof(0, 24, 511);
    if (warp == 0) {
      if (is_ffn) ffn_producer(cx, qb, &tmWq, &tmG, &tmU, &tmD);
      else attn_producer(cx, qb, hs, tmKV.m, &tmWq, &tmWq96, &tmWo);
      prof(0, 25, 511);
    } else {
      sq_publish(cx, qb, hs, warp - 1, read_lane());
      if (warp == 3) sq_collect(cx, qb, read_lane());
      if (!is_ffn) {
        attn_gate(cx, qb, hs, warp - 1, threadIdx.x - 32, x);
        if (warp == 1) TSP(65)
        asm volatile("fence.proxy.async.global;" ::: "memory");
        if (warp == 1) attn_helper(cx, qb, hs, fresh_lane(), &tmX16);
        else bar_arrive(BAR_OA, 352);
        attn_finish8(cx, qb, hs, warp - 1, fresh_lane(), out);
      } else if (warp < 3) {
        ffn_publish(cx, qb, warp - 1, fresh_lane(), &tmX64);
      }
    }
    __syncwarp();
    cluster_arrive();
    cluster_wait();
  } else {
    if (warp == 4 && elect_one()) {
#pragma unroll
      for (int i = 0; i < 3; i++) mbar_init(cx.sb + SM_XFULL + 8 * i, 1);
      TSP(66)
      load_x(0, 0, 3);
#pragma unroll
      for (int i = 4; i < 7; i++) mbar_init(cx.sb + SM_XFULL + 8 * i, 1);
      asm volatile("fence.mbarrier_init.release.cluster;" ::: "memory");
    }
    if (warp == 5 && elect_one()) {
      mbar_init(cx.sb + SM_BAR_W, 1);
      asm volatile("fence.mbarrier_init.release.cluster;" ::: "memory");
      *(uint4*)(cx.sp + SM_ONES) = make_uint4(0x3F803F80u, 0x3F803F80u, 0x3F803F80u, 0x3F803F80u);
      mbar_expect_tx(cx.sb + SM_BAR_W, DM * 2);
      bulk_load(cx.sb + SM_WR, w_r, DM * 2, cx.sb + SM_BAR_W);
    }
    __syncwarp();
    cluster_arrive();
    if (warp == 4 && elect_one()) {
      load_x(1, 0, X_ORD);
      TSP(67)
    }
    __syncwarp();
    asm volatile("setmaxnreg.inc.sync.aligned.u32 240;");
    const int cw = warp - 4, wg = cw >> 2;
    cluster_wait();
    if (warp == 8 && elect_one()) {
      const uint64_t pol = policy_evict_first();
#pragma unroll
      for (int i = 0; i < 4; i++) {
        if (!(i & 1)) mbar_expect_tx(cx.sb + SM_FULL + 4 * i, 32768);
        tma2d_mc(cx.sb + SM_RING + (i >> 1) * STAGE + cx.rank * 16384 + (i & 1) * 8192, &tmWq,
                 is_ffn ? (cx.rank * 4 + 3) * DH + 64 : hs * 512 + cx.rank * 64, i * 64, cx.sb + SM_FULL + 8 * (i >> 1), pol);
        if (i == 1) load_x(1, X_ORD, 3);
      }
      TSP(72)
    }
    __syncwarp();
    attn_consumer(cx, is_ffn, qb, hs, wg, cw, read_lane(), x, kc, vc, out);
  }
}

typedef CUresult (*EncodeFn)(CUtensorMap*, CUtensorMapDataType, cuuint32_t, void*, const cuuint64_t*, const cuuint64_t*,
                             const cuuint32_t*, const cuuint32_t*, CUtensorMapInterleave, CUtensorMapSwizzle,
                             CUtensorMapL2promotion, CUtensorMapFloatOOBfill);

void encode(EncodeFn fn, CUtensorMap* m, const void* p, int rank, const cuuint64_t* dims, const cuuint64_t* strides,
            const cuuint32_t* box) {
  const cuuint32_t es[5] = {1, 1, 1, 1, 1};
  fn(m, CU_TENSOR_MAP_DATA_TYPE_BFLOAT16, rank, const_cast<void*>(p), dims, strides, box, es, CU_TENSOR_MAP_INTERLEAVE_NONE,
     CU_TENSOR_MAP_SWIZZLE_128B, CU_TENSOR_MAP_L2_PROMOTION_L2_128B, CU_TENSOR_MAP_FLOAT_OOB_FILL_NONE);
}
void encode2d(EncodeFn fn, CUtensorMap* m, const void* p, uint64_t rows, uint64_t cols, uint32_t box_rows) {
  const cuuint64_t dims[2] = {cols, rows}, strides[1] = {cols * 2};
  const cuuint32_t box[2] = {64, box_rows};
  encode(fn, m, p, 2, dims, strides, box);
}

}

extern "C" void kernel_launch(void* const* d_in, const int* in_sizes, int n_in, void* d_out, int out_size) {
  (void)in_sizes; (void)n_in; (void)out_size;
  void* fnp = nullptr;
  cudaDriverEntryPointQueryResult qr;
  cudaGetDriverEntryPoint("cuTensorMapEncodeTiled", &fnp, cudaEnableDefault, &qr);
  EncodeFn fn = (EncodeFn)fnp;
  CUtensorMap tmWq, tmWo, tmG, tmU, tmD, tmX, tmX16, tmWq96, tmX64;
  encode2d(fn, &tmX64, d_in[0], SEQ, DM, 64);
  encode2d(fn, &tmWq96, d_in[3], DM, 4096, 96);
  encode2d(fn, &tmX16, d_in[0], SEQ, DM, 16);
  KvMaps tmKV;
  for (int i = 0; i < 4; i++) encode2d(fn, &tmKV.m[i], d_in[1 + (i & 1)], 16 * SEQ, DH, i < 2 ? 112 : 96);
  encode2d(fn, &tmWq, d_in[3], DM, 4096, 64);
  {
    const cuuint64_t dims[3] = {64, SEQ, 9}, strides[2] = {DM * 2, 128};
    const cuuint32_t box[3] = {64, 64, 3};
    encode(fn, &tmX, d_in[0], 3, dims, strides, box);
  }
  encode2d(fn, &tmWo, d_in[4], 4096, DM, 128);
  encode2d(fn, &tmG, d_in[7], DM, FF, 192);
  encode2d(fn, &tmU, d_in[8], DM, FF, 192);
  encode2d(fn, &tmD, d_in[9], FF, DM, 192);
  cudaFuncSetAttribute(fused_kernel, cudaFuncAttributeMaxDynamicSharedMemorySize, SM_TOTAL);
  void* scratch = nullptr;
  cudaGetSymbolAddress(&scratch, g_scratch);
  fused_kernel<<<N_CTA, THREADS, SM_TOTAL>>>((const __nv_bfloat16*)d_in[0], (const __nv_bfloat16*)d_in[6], (const __nv_bfloat16*)d_in[1],
                                            (const __nv_bfloat16*)d_in[2], (__nv_bfloat16*)d_out, (Scratch*)scratch, tmX, tmWq, tmKV,
                                            tmWo, tmG, tmU, tmD, tmX16, tmWq96, tmX64);
}
```

```cpp
#include <cuda_runtime.h>
#include <cuda_bf16.h>
#include <cuda.h>
#include <stdint.h>

#define X_PFW 1
#define X_SPLIT 38
#define X_SPLITA 36
#define X_SPLITS 32
#define X_SPLITSA 30
#define X_PA 8
#define X_PG 4
#define X_E0 10
#define X_F2 10
#define X_LD 0
#define X_LN 0
#define X_WAKE 31
#define X_PFX 1
#define X_F1 0
#define X_BF2 1
#define X_SQI 4
#define X_SQS 300
#define X_ORD 3
#define X_NS 4
namespace {

constexpr int SEQ = 2048, DM = 576, DH = 128, FF = 4608, TOPC = 8;
constexpr int N_ATT_CTA = 128, N_CTA = 132;
constexpr int THREADS = 384;

constexpr uint32_t SM_RING = 0;
constexpr uint32_t STAGE = 32768;
constexpr uint32_t SM_SLOT = 131072;
constexpr uint32_t FSTAGE = 24576;
constexpr uint32_t SM_XSEL = 196608;
constexpr uint32_t SM_H = 205824;
constexpr uint32_t SM_MISC = 229376;
constexpr uint32_t SM_FULL = SM_MISC, SM_EMPTY = SM_MISC + 32, SM_FFULL = SM_MISC + 64, SM_BAR_MISC = SM_MISC + 128,
                   SM_COLD = SM_MISC + 136, SM_TAG = SM_MISC + 144, SM_BAR_W = SM_MISC + 152, SM_ONES = SM_MISC + 160,
                   SM_BAR_Q = SM_MISC + 176, SM_XFULL = SM_MISC + 192, SM_BAR_XG = SM_MISC + 304, SM_BAR_SQ = SM_MISC + 312,
                   SM_STATS = SM_MISC + 320, SM_FEMPTY = SM_MISC + 1344, SM_RAW = SM_FEMPTY, SM_WR = SM_MISC + 1408, SM_TOPK = SM_WR;
constexpr uint32_t SM_TOTAL = SM_MISC + 2560;
constexpr uint32_t SM_X = SM_MISC - 147456;

constexpr int BAR_GATE = 6, BAR_HELPER = 7, BAR_OA = 8, BAR_XREL = 13, BAR_QS = 9, BAR_QF = 11;
constexpr int NST_Q = 18, NST_KV = 76, NST_O = 18;
constexpr float SM_SCALE_LOG2 = 0.08838834764831845f * 1.4426950408889634f;

struct Scratch {
  uint4 part[16 * 64 * 2 * 4 * 128];
  uint4 gate[N_ATT_CTA * 1152];
  uint4 q[16 * 8 * 2 * 512];
  uint2 sq[SEQ];
  uint4 stats[SEQ];
  float ypart[4 * TOPC * DM];
  int2 sel[16];
  unsigned launch[160];
  unsigned pad0, ycnt, pad[30];
  unsigned qflag[128];
};
__device__ __align__(1024) Scratch g_scratch;

__device__ __forceinline__ void prof(int, int, int = 0) {}

#define TS(id) {}
#define TS_DUMP() {}
#define TSH(k) {}
#define TS4(k) {}
#define TSP(k) {}
#define TS1(id) TS(id)
#define TS2(k) {}
#define TS3(k) {}

__device__ __forceinline__ uint32_t smem_u32(const void* p) { return (uint32_t)__cvta_generic_to_shared(p); }
__device__ __forceinline__ void mbar_init(uint32_t bar, uint32_t cnt) {
  asm volatile("mbarrier.init.shared::cta.b64 [%0], %1;" ::"r"(bar), "r"(cnt) : "memory");
}
__device__ __forceinline__ void mbar_expect_tx(uint32_t bar, uint32_t bytes) {
  asm volatile("mbarrier.arrive.expect_tx.shared::cta.b64 _, [%0], %1;" ::"r"(bar), "r"(bytes) : "memory");
}
__device__ __forceinline__ void mbar_arrive(uint32_t bar) {
  asm volatile("mbarrier.arrive.shared::cta.b64 _, [%0];" ::"r"(bar) : "memory");
}
__device__ __forceinline__ void mbar_arrive_cluster(uint32_t bar_cluster_addr, bool pred) {
  asm volatile("{\n.reg .pred p;\nsetp.ne.u32 p, %1, 0;\n@p mbarrier.arrive.shared::cluster.b64 _, [%0];\n}"
               ::"r"(bar_cluster_addr), "r"((uint32_t)pred) : "memory");
}
template <int ID>
__device__ __forceinline__ void mbar_arrive_cluster_now(uint32_t bar_cluster_addr, bool pred) {
  asm volatile("{\n.reg .pred p, q;\nsetp.ne.u32 p, %1, 0;\nsetp.eq.u32 q, %2, %3;\n"
               "ARR_LOOP:\n@p mbarrier.arrive.shared::cluster.b64 _, [%0];\n@q bra.uni ARR_LOOP;\n}"
               ::"r"(bar_cluster_addr), "r"((uint32_t)pred), "r"(blockIdx.y), "n"(ID) : "memory");
}
__device__ __forceinline__ void block_fence(int id) {
  asm volatile("{\n.reg .pred q;\nsetp.eq.u32 q, %0, %1;\nBF_LOOP:\n@q st.volatile.shared.u32 [%0], %0;\n@q bra.uni BF_LOOP;\n}"
               ::"r"(blockIdx.y), "r"(id) : "memory");
}
__device__ __forceinline__ void mbar_wait(uint32_t bar, uint32_t parity) {
  asm volatile("{\n.reg .pred p, q;\n.reg .u32 n;\nmov.u32 n, 0;\n"
               "WAIT_LOOP:\nmbarrier.try_wait.parity.shared::cta.b64 p, [%0], %1;\n"
               "add.u32 n, n, 1;\nsetp.lt.u32 q, n, 4194304;\nand.pred q, q, !p;\n@q bra WAIT_LOOP;\n}"
               ::"r"(bar), "r"(parity) : "memory");
}
__device__ __forceinline__ uint32_t mapa(uint32_t addr, uint32_t rank) {
  uint32_t r;
  asm volatile("mapa.shared::cluster.u32 %0, %1, %2;" : "=r"(r) : "r"(addr), "r"(rank));
  return r;
}
__device__ __forceinline__ void cluster_arrive() { asm volatile("barrier.cluster.arrive.relaxed.aligned;" ::: "memory"); }
__device__ __forceinline__ bool elect_one() {
  uint32_t p;
  asm volatile("{\n.reg .pred p;\nelect.sync _|p, 0xffffffff;\nselp.u32 %0, 1, 0, p;\n}" : "=r"(p));
  return p;
}
__device__ __forceinline__ int read_lane() { return threadIdx.x & 31; }
__device__ __forceinline__ int fresh_lane() {
  int l;
  asm volatile("mov.u32 %0, %%laneid;" : "=r"(l));
  return l;
}
template <class T> __device__ __forceinline__ T* at(T* p, uint32_t bytes) {
  asm("" : "+r"(bytes));
  return (T*)((const char*)p + bytes);
}
__device__ __forceinline__ void cluster_wait() { asm volatile("barrier.cluster.wait.acquire.aligned;" ::: "memory"); }
__device__ __forceinline__ void bar_sync(int id, int n) { asm volatile("barrier.cta.sync %0, %1;" ::"r"(id), "r"(n) : "memory"); }
__device__ __forceinline__ void bar_arrive(int id, int n) { asm volatile("barrier.cta.arrive %0, %1;" ::"r"(id), "r"(n) : "memory"); }

__device__ __forceinline__ uint64_t policy_evict_first() {
  uint64_t p;
  asm("createpolicy.fractional.L2::evict_first.b64 %0, 1.0;" : "=l"(p));
  return p;
}
__device__ __forceinline__ void tma2d_mc(uint32_t dst, const CUtensorMap* tm, int c0, int c1, uint32_t bar, uint64_t pol) {
  asm volatile("cp.async.bulk.tensor.2d.shared::cluster.global.mbarrier::complete_tx::bytes.multicast::cluster.L2::cache_hint"
               " [%0], [%1, {%2, %3}], [%4], %5, %6;"
               ::"r"(dst), "l"(tm), "r"(c0), "r"(c1), "r"(bar), "h"((uint16_t)3), "l"(pol) : "memory");
}
__device__ __forceinline__ void tma3d(uint32_t dst, const CUtensorMap* tm, int c1, int c2, uint32_t bar) {
  asm volatile("cp.async.bulk.tensor.3d.shared::cluster.global.mbarrier::complete_tx::bytes [%0], [%1, {%2, %3, %4}], [%5];"
               ::"r"(dst), "l"(tm), "r"(0), "r"(c1), "r"(c2), "r"(bar) : "memory");
}
__device__ __forceinline__ void tma2d(uint32_t dst, const CUtensorMap* tm, int c0, int c1, uint32_t bar) {
  asm volatile("cp.async.bulk.tensor.2d.shared::cluster.global.mbarrier::complete_tx::bytes [%0], [%1, {%2, %3}], [%4];"
               ::"r"(dst), "l"(tm), "r"(c0), "r"(c1), "r"(bar) : "memory");
}
__device__ __forceinline__ void tma2d_stream(uint32_t dst, const CUtensorMap* tm, int c0, int c1, uint32_t bar) {
  asm volatile("{\n.reg .b64 pol;\ncreatepolicy.fractional.L2::evict_first.b64 pol, 1.0;\n"
               "cp.async.bulk.tensor.2d.shared::cluster.global.mbarrier::complete_tx::bytes.L2::cache_hint [%0], [%1, {%2, %3}], [%4], pol;\n}"
               ::"r"(dst), "l"(tm), "r"(c0), "r"(c1), "r"(bar) : "memory");
}
__device__ __forceinline__ void bulk_load(uint32_t dst, const void* src, uint32_t bytes, uint32_t bar) {
  asm volatile("cp.async.bulk.shared::cluster.global.mbarrier::complete_tx::bytes [%0], [%1], %2, [%3];"
               ::"r"(dst), "l"(src), "r"(bytes), "r"(bar) : "memory");
}
__device__ __forceinline__ void tma2d_prefetch(const CUtensorMap* tm, int c0, int c1) {
  asm volatile("cp.async.bulk.prefetch.tensor.2d.L2.global [%0, {%1, %2}];" ::"l"(tm), "r"(c0), "r"(c1) : "memory");
}
__device__ __forceinline__ void prefetch_tmap(const CUtensorMap* tm) {
  asm volatile("prefetch.tensormap [%0];" ::"l"(tm) : "memory");
}

__device__ __forceinline__ void wg_fence() { asm volatile("wgmma.fence.sync.aligned;" ::: "memory"); }
__device__ __forceinline__ void wg_commit() { asm volatile("wgmma.commit_group.sync.aligned;" ::: "memory"); }
template <int N> __device__ __forceinline__ void wg_wait() { asm volatile("wgmma.wait_group.sync.aligned %0;" ::"n"(N) : "memory"); }

__device__ __forceinline__ uint64_t mkdesc(uint32_t addr, uint32_t lbo_bytes) {
  return (uint64_t)(((addr & 0x3FFFF) >> 4) | ((lbo_bytes >> 4) << 16)) | ((uint64_t)0x40000040u << 32);
}
__device__ __forceinline__ uint64_t mkdesc_q(uint32_t addr) {
  return (uint64_t)(((addr & 0x3FFFF) >> 4) | (64u << 16)) | ((uint64_t)8 << 32);
}
template <int N> __device__ __forceinline__ void pin(float (&a)[N]) {
#pragma unroll
  for (int i = 0; i < N; i++) asm volatile("" : "+f"(a[i])::"memory");
}
template <int N> __device__ __forceinline__ void kill(float (&a)[N]) {
#pragma unroll
  for (int i = 0; i < N; i++) asm volatile("" : "=f"(a[i]));
}
template <int N> __device__ __forceinline__ void pin(uint32_t (&a)[N]) {
#pragma unroll
  for (int i = 0; i < N; i++) asm volatile("" : "+r"(a[i])::"memory");
}

#define F8(d, o) "+f"(d[o]), "+f"(d[o + 1]), "+f"(d[o + 2]), "+f"(d[o + 3]), "+f"(d[o + 4]), "+f"(d[o + 5]), "+f"(d[o + 6]), "+f"(d[o + 7])
#define R32A "%0, %1, %2, %3, %4, %5, %6, %7, %8, %9, %10, %11, %12, %13, %14, %15, %16, %17, %18, %19, %20, %21, %22, %23, %24, %25, %26, %27, %28, %29, %30, %31"
#define R32B "%32, %33, %34, %35, %36, %37, %38, %39, %40, %41, %42, %43, %44, %45, %46, %47, %48, %49, %50, %51, %52, %53, %54, %55, %56, %57, %58, %59, %60, %61, %62, %63"

#define O8(d, o) "=f"(d[o]), "=f"(d[o + 1]), "=f"(d[o + 2]), "=f"(d[o + 3]), "=f"(d[o + 4]), "=f"(d[o + 5]), "=f"(d[o + 6]), "=f"(d[o + 7])

__device__ __forceinline__ void mma_n128t(float (&d)[64], uint32_t a0, uint32_t a1, uint32_t a2, uint32_t a3, uint64_t db, bool acc) {
  if (acc)
    asm volatile("wgmma.mma_async.sync.aligned.m64n128k16.f32.bf16.bf16 {" R32A ", " R32B "}, {%64, %65, %66, %67}, %68, 1, 1, 1, 1;\n"
                 : F8(d, 0), F8(d, 8), F8(d, 16), F8(d, 24), F8(d, 32), F8(d, 40), F8(d, 48), F8(d, 56)
                 : "r"(a0), "r"(a1), "r"(a2), "r"(a3), "l"(db));
  else
    asm volatile("wgmma.mma_async.sync.aligned.m64n128k16.f32.bf16.bf16 {" R32A ", " R32B "}, {%64, %65, %66, %67}, %68, 0, 1, 1, 1;\n"
                 : O8(d, 0), O8(d, 8), O8(d, 16), O8(d, 24), O8(d, 32), O8(d, 40), O8(d, 48), O8(d, 56)
                 : "r"(a0), "r"(a1), "r"(a2), "r"(a3), "l"(db));
}
#define PV1(a0, a1, a2, a3, ob, acc) "add.s64 b, %92, " #ob ";\n" \
  "wgmma.mma_async.sync.aligned.m64n128k16.f32.bf16.bf16 {" R32A ", " R32B "}, {%" #a0 ", %" #a1 ", %" #a2 ", %" #a3 "}, b, " #acc ", 1, 1, 1;\n"
#define PV6 "wgmma.fence.sync.aligned;\n" PV1(64, 65, 66, 67, 0, p) PV1(68, 69, 70, 71, 128, 1) PV1(72, 73, 74, 75, 256, 1) \
  PV1(76, 77, 78, 79, 384, 1) PV1(80, 81, 82, 83, 512, 1) PV1(84, 85, 86, 87, 640, 1)
#define U4(a, o) "r"(a[o]), "r"(a[o + 1]), "r"(a[o + 2]), "r"(a[o + 3])
__device__ __forceinline__ void mma_pv(float (&d)[64], const uint32_t (&a)[28], uint64_t dv, bool acc, bool big) {
  asm volatile("{\n.reg .pred p, q;\n.reg .b64 b;\nsetp.ne.b32 p, %93, 0;\nsetp.eq.b32 q, %94, 0;\n@q bra.uni PV_SMALL;\n"
               PV6 PV1(88, 89, 90, 91, 768, 1) "wgmma.commit_group.sync.aligned;\nbra.uni PV_DONE;\n"
               "PV_SMALL:\n" PV6 "wgmma.commit_group.sync.aligned;\nPV_DONE:\n}\n"
               : F8(d, 0), F8(d, 8), F8(d, 16), F8(d, 24), F8(d, 32), F8(d, 40), F8(d, 48), F8(d, 56)
               : U4(a, 0), U4(a, 4), U4(a, 8), U4(a, 12), U4(a, 16), U4(a, 20), U4(a, 24), "l"(dv), "r"((int)acc), "r"((int)big) : "memory");
}
#define R48 R32A ", %32, %33, %34, %35, %36, %37, %38, %39, %40, %41, %42, %43, %44, %45, %46, %47"
#define R56 R48 ", %48, %49, %50, %51, %52, %53, %54, %55"
#define QK1(N, R, A, B, oa, ob, acc) "add.s64 a, " A ", " #oa ";\nadd.s64 b, " B ", " #ob ";\n" \
  "wgmma.mma_async.sync.aligned.m64n" #N "k16.f32.bf16.bf16 {" R "}, a, b, " #acc ", 1, 1, 0, 0;\n"
#define QK8(N, R, A, B) "{\n.reg .b64 a, b;\nwgmma.fence.sync.aligned;\n" QK1(N, R, A, B, 0, 0, 0) QK1(N, R, A, B, 128, 2, 1) \
  QK1(N, R, A, B, 256, 4, 1) QK1(N, R, A, B, 384, 6, 1) QK1(N, R, A, B, 512, 1024, 1) QK1(N, R, A, B, 640, 1026, 1) \
  QK1(N, R, A, B, 768, 1028, 1) QK1(N, R, A, B, 896, 1030, 1) "wgmma.commit_group.sync.aligned;\n}\n"
__device__ __forceinline__ void mma_qk(float (&d)[56], uint64_t dq, uint64_t dk) {
  asm volatile(QK8(112, R56, "%56", "%57")
               : O8(d, 0), O8(d, 8), O8(d, 16), O8(d, 24), O8(d, 32), O8(d, 40), O8(d, 48) : "l"(dq), "l"(dk) : "memory");
}
__device__ __forceinline__ void mma_qk(float (&d)[48], uint64_t dq, uint64_t dk) {
  asm volatile(QK8(96, R48, "%48", "%49")
               : O8(d, 0), O8(d, 8), O8(d, 16), O8(d, 24), O8(d, 32), O8(d, 40) : "l"(dq), "l"(dk) : "memory");
}
__device__ __forceinline__ void mma_n64t(float (&d)[32], uint32_t a0, uint32_t a1, uint32_t a2, uint32_t a3, uint64_t db, bool acc) {
  if (acc)
    asm volatile("wgmma.mma_async.sync.aligned.m64n64k16.f32.bf16.bf16 {" R32A "}, {%32, %33, %34, %35}, %36, 1, 1, 1, 1;\n"
                 : F8(d, 0), F8(d, 8), F8(d, 16), F8(d, 24) : "r"(a0), "r"(a1), "r"(a2), "r"(a3), "l"(db));
  else
    asm volatile("wgmma.mma_async.sync.aligned.m64n64k16.f32.bf16.bf16 {" R32A "}, {%32, %33, %34, %35}, %36, 0, 1, 1, 1;\n"
                 : O8(d, 0), O8(d, 8), O8(d, 16), O8(d, 24) : "r"(a0), "r"(a1), "r"(a2), "r"(a3), "l"(db));
}
__device__ __forceinline__ void mma_n64t_dyn(float (&d)[32], uint32_t a0, uint32_t a1, uint32_t a2, uint32_t a3, uint64_t db, int acc) {
  asm volatile("{\n.reg .pred p;\nsetp.ne.b32 p, %37, 0;\n"
               "wgmma.mma_async.sync.aligned.m64n64k16.f32.bf16.bf16 {" R32A "}, {%32, %33, %34, %35}, %36, p, 1, 1, 1;\n}\n"
               : F8(d, 0), F8(d, 8), F8(d, 16), F8(d, 24) : "r"(a0), "r"(a1), "r"(a2), "r"(a3), "l"(db), "r"(acc));
}
__device__ __forceinline__ void mma_n8(float (&d)[4], uint64_t da, uint64_t db, int acc) {
  asm volatile("{\n.reg .pred p;\nsetp.ne.b32 p, %6, 0;\n"
               "wgmma.mma_async.sync.aligned.m64n8k16.f32.bf16.bf16 {%0, %1, %2, %3}, %4, %5, p, 1, 1, 1, 0;\n}\n"
               : "+f"(d[0]), "+f"(d[1]), "+f"(d[2]), "+f"(d[3])
               : "l"(da), "l"(db), "r"(acc));
}
__device__ __forceinline__ void hmma_k16(float (&d)[4], uint32_t a0, uint32_t a1, uint32_t a2, uint32_t a3, uint32_t b0, uint32_t b1) {
  asm volatile("mma.sync.aligned.m16n8k16.row.col.f32.bf16.bf16.f32 {%0, %1, %2, %3}, {%4, %5, %6, %7}, {%8, %9}, {%0, %1, %2, %3};"
               : "+f"(d[0]), "+f"(d[1]), "+f"(d[2]), "+f"(d[3]) : "r"(a0), "r"(a1), "r"(a2), "r"(a3), "r"(b0), "r"(b1));
}

__device__ __forceinline__ uint32_t pack2(float lo, float hi) {
  uint32_t r;
  asm("cvt.rn.bf16x2.f32 %0, %1, %2;" : "=r"(r) : "f"(hi), "f"(lo));
  return r;
}
__device__ __forceinline__ float bf_lo(uint32_t w) { return __uint_as_float(w << 16); }
__device__ __forceinline__ float bf_hi(uint32_t w) { return __uint_as_float(w & 0xFFFF0000u); }
__device__ __forceinline__ float bfr(float x) { return __bfloat162float(__float2bfloat16_rn(x)); }
__device__ __forceinline__ uint32_t sub2(uint32_t a, uint32_t b) {
  uint32_t r;
  asm("sub.rn.bf16x2 %0, %1, %2;" : "=r"(r) : "r"(a), "r"(b));
  return r;
}
__device__ __forceinline__ uint32_t add2(uint32_t a, uint32_t b) {
  uint32_t r;
  asm("add.rn.bf16x2 %0, %1, %2;" : "=r"(r) : "r"(a), "r"(b));
  return r;
}
__device__ __forceinline__ uint32_t fma2(uint32_t a, uint32_t b, uint32_t c) {
  uint32_t r;
  asm("fma.rn.bf16x2 %0, %1, %2, %3;" : "=r"(r) : "r"(a), "r"(b), "r"(c));
  return r;
}
__device__ __forceinline__ float ex2(float x) {
  float r;
  asm("ex2.approx.ftz.f32 %0, %1;" : "=f"(r) : "f"(x));
  return r;
}
__device__ __forceinline__ float rcp(float x) {
  float r;
  asm("rcp.approx.ftz.f32 %0, %1;" : "=f"(r) : "f"(x));
  return r;
}
__device__ __forceinline__ float silu_f(float t) { return t * rcp(1.0f + ex2(-1.4426950408889634f * t)); }
__device__ __forceinline__ void lds128(uint32_t a, uint32_t& x, uint32_t& y, uint32_t& z, uint32_t& w) {
  asm volatile("ld.shared.v4.u32 {%0, %1, %2, %3}, [%4];" : "=r"(x), "=r"(y), "=r"(z), "=r"(w) : "r"(a) : "memory");
}
__device__ __forceinline__ void ldsm4(uint32_t a, uint32_t& x, uint32_t& y, uint32_t& z, uint32_t& w) {
  asm volatile("ldmatrix.sync.aligned.m8n8.x4.shared.b16 {%0, %1, %2, %3}, [%4];" : "=r"(x), "=r"(y), "=r"(z), "=r"(w) : "r"(a) : "memory");
}
constexpr uint32_t TAG = 0x10000;
__device__ __forceinline__ void st_gran(uint4* p, uint32_t x, uint32_t y, uint32_t z, uint32_t w) {
  asm volatile("st.relaxed.gpu.global.v4.b32 [%0], {%1, %2, %3, %4};" ::"l"(p), "r"(x), "r"(y), "r"(z), "r"(w) : "memory");
}
__device__ __forceinline__ void ld_gran(const uint4* p, uint32_t& x, uint32_t& y, uint32_t& z, uint32_t& w) {
  asm volatile("ld.relaxed.gpu.global.v4.b32 {%0, %1, %2, %3}, [%4];" : "=r"(x), "=r"(y), "=r"(z), "=r"(w) : "l"(p) : "memory");
}
__device__ __forceinline__ void stsm4(uint32_t a, uint32_t x, uint32_t y, uint32_t z, uint32_t w) {
  asm volatile("stmatrix.sync.aligned.m8n8.x4.shared.b16 [%0], {%1, %2, %3, %4};" ::"r"(a), "r"(x), "r"(y), "r"(z), "r"(w) : "memory");
}
__device__ __forceinline__ void cp16(uint32_t dst, const void* src) {
  asm volatile("cp.async.cg.shared.global [%0], [%1], 16;" ::"r"(dst), "l"(src) : "memory");
}
__device__ __forceinline__ void cp_wait_all() { asm volatile("cp.async.wait_all;" ::: "memory"); }
__device__ __forceinline__ void add_granules(float (&red)[32], const uint32_t (&g)[16]) {
#pragma unroll
  for (int i = 0; i < 16; i++) { red[2 * i] += bf_lo(g[i]); red[2 * i + 1] += bf_hi((i & 3) ? g[i] : g[i] & ~TAG); }
}
__device__ __forceinline__ bool granules_ok(const uint32_t (&g)[16], uint32_t tag) {
  uint32_t a, b;
  asm("lop3.b32 %0, %1, %2, %3, 0x7E;" : "=r"(a) : "r"(g[0]), "r"(g[4]), "r"(tag));
  asm("lop3.b32 %0, %1, %2, %3, 0x7E;" : "=r"(b) : "r"(g[8]), "r"(g[12]), "r"(tag));
  return __all_sync(0xffffffffu, ((a | b) & TAG) == 0);
}
__device__ __forceinline__ unsigned ld_acquire(const unsigned* p) {
  unsigned v;
  asm volatile("ld.acquire.gpu.global.u32 %0, [%1];" : "=r"(v) : "l"(p) : "memory");
  return v;
}
__device__ __forceinline__ unsigned atom_add_acq_rel(unsigned* p) {
  unsigned v;
  asm volatile("atom.acq_rel.gpu.global.add.u32 %0, [%1], 1;" : "=r"(v) : "l"(p) : "memory");
  return v;
}

template <int K0, int K1>
__device__ __forceinline__ void ln_fetch(uint32_t (&xa)[144], uint32_t boxes, uint32_t lo) {
#pragma unroll
  for (int k = K0; k < K1; k++) ldsm4(boxes + (k >> 2) * 8192 + (lo ^ ((k & 3) << 5)), xa[4 * k], xa[4 * k + 1], xa[4 * k + 2], xa[4 * k + 3]);
}
__device__ __forceinline__ void ln_fetch_b(uint32_t (&b)[24], uint32_t& wb, uint32_t ws) {
#pragma unroll
  for (int j = 0; j < 6; j++, wb += ws) ldsm4(wb, b[4 * j], b[4 * j + 1], b[4 * j + 2], b[4 * j + 3]);
}
template <int K0, int K1>
__device__ __forceinline__ void ln_sums(const uint32_t (&xa)[144], float (&sm)[X_NS][4], const uint32_t (&b)[24]) {
#pragma unroll
  for (int k = K0; k < K1; k++)
    hmma_k16(sm[k % X_NS], xa[4 * k], xa[4 * k + 1], xa[4 * k + 2], xa[4 * k + 3], b[2 * (k % 12)], b[2 * (k % 12) + 1]);
}
__device__ __forceinline__ void ln_row(float sum, float sq, float& mean_b, float& rstd) {
  const float mean = sum * (1.0f / DM);
  const uint32_t mv = pack2(mean, fmaxf(sq * (1.0f / DM) - mean * mean, 0.0f));
  mean_b = bf_lo(mv);
  float sd;
  asm("sqrt.approx.f32 %0, %1;" : "=f"(sd) : "f"(bf_lo(pack2(bf_hi(mv) + 1e-5f, 0.f))));
  rstd = rcp(bf_lo(pack2(sd, 0.f)));
}

template <bool ROUTED>
__device__ __forceinline__ uint32_t gate2(uint32_t xc, float rstd, float2 upd = make_float2(0.f, 0.f)) {
  uint32_t t = pack2(bf_lo(xc) * rstd, bf_hi(xc) * rstd);
  if (ROUTED) t = pack2(bf_lo(t) + upd.x, bf_hi(t) + upd.y);
  return pack2(silu_f(bf_lo(t)), silu_f(bf_hi(t)));
}

template <int V> struct IC { static constexpr int value = V; };

struct Ctx {
  uint32_t sb;
  uint8_t* sp;
  uint32_t rank;
  Scratch* g;
};

__device__ __forceinline__ bool acquire(const Ctx& cx, uint32_t r, uint32_t n, uint32_t bytes) {
  mbar_wait(cx.sb + SM_EMPTY + 8 * r, (n ^ (r >> 1) ^ 1) & 1);
  __syncwarp();
  const bool e = elect_one();
  if (e) mbar_expect_tx(cx.sb + SM_FULL + 8 * r, bytes);
  return e;
}
__device__ __forceinline__ void load_wq(const Ctx& cx, const CUtensorMap* tmWq, int st, int i, int n0, uint64_t pol) {
  const uint32_t r = st & 3, dst = cx.sb + SM_RING + r * STAGE + cx.rank * 16384, bar = cx.sb + SM_FULL + 8 * r;
  const int k0 = i < 3 ? 128 * i : 128 * i - 64;
  if (acquire(cx, r, st >> 2, i == 2 ? 16384 : 32768)) {
    tma2d_mc(dst, tmWq, n0, k0, bar, pol);
    if (i != 2) tma2d_mc(dst + 8192, tmWq, n0, k0 + 64, bar, pol);
  }
}
__device__ __forceinline__ void attn_producer(const Ctx& cx, int qb, int hs, const CUtensorMap* tmKV, const CUtensorMap* tmWq,
                                              const CUtensorMap* tmWq96, const CUtensorMap* tmWo) {
  const uint32_t full = cx.sb + SM_FULL, ring = cx.sb + SM_RING + cx.rank * 16384;
  const uint64_t last_use = policy_evict_first();
  int st = 0;
#pragma unroll 1
  for (int p = 0; p < 4; p++) {
#pragma unroll 1
    for (int i = 0; i < (p == 2 ? 3 : 5); i++, st++) {
      if (p == 2) {
        if (acquire(cx, st & 3, st >> 2, 24576))
          tma2d_mc(cx.sb + SM_RING + (st & 3) * STAGE + cx.rank * 12288, tmWq96, (hs * 4 + 3) * DH, 192 * i + 96 * cx.rank, full + 8 * (st & 3), last_use);
      } else {
        if (st > 1) load_wq(cx, tmWq, st, i, (hs * 4 + (p ^ (p >> 1))) * DH + cx.rank * 64, last_use);
      }
      if (st == 1 || st == 2) TSP(72 + st)
      if (st == X_PFW) {
#pragma unroll 1
        for (int b = qb < 8; b < 5 - (qb >> 3); b++)
          if (elect_one()) tma2d_prefetch(tmWq, hs * 512 + (b < 4 ? (b ^ (b >> 1)) * DH + (qb & 1) * 64 : qb * 64), b < 4 ? (qb >> 1) * 64 : 512);
      }
      if (st == 8 && qb < 8 && elect_one()) tma2d_prefetch(tmKV + ((qb >> 1) & 1), cx.rank * 64, hs * 2 * SEQ + (qb >> 2) * 96);
    }
  }
  uint32_t r = 2, n = 4;
  int row = hs * 2 * SEQ, rows = 96;
  const CUtensorMap* tm = tmKV + 2;
#pragma unroll 1
  for (int u = 0; u < NST_KV; u++) {
    if (acquire(cx, r, n, rows * 256)) {
      tma2d_mc(ring + r * STAGE, tm, cx.rank * 64, row, full + 8 * r, last_use);
      if (((u ^ (qb >> 1)) & 7) == 0 && u < NST_KV - 4) tma2d_prefetch(tmKV + (u & 1), cx.rank * 64, row + 208);
      if ((unsigned)(u - 32) < 36 && (u & 15) == qb) tma2d_prefetch(tmWo, ((u - 32) >> 2) * 64, hs * 512 + (u & 3) * 128);
    }
    if (++r == 4) { r = 1; n++; }
    if (u & 1) row += rows;
    const bool big = (unsigned)(u - 9) < 56;
    rows = big ? 112 : 96;
    tm = tmKV + (~u & 1) + (big ? 0 : 2);
  }
#pragma unroll 1
  for (int u = 0; u < NST_O; u++) {
    const int s = u >> 1;
    const int blk = s == 0 ? 8 : ((hs + s) & 7);
    r = (0x87 >> (2 * (u & 3))) & 3;
    if (acquire(cx, r, (u >> 2) ^ ~u, 32768))
      tma2d_mc(ring + r * STAGE, tmWo, blk * 64, hs * 512 + ((u & 1) + cx.rank * 2) * 128, full + 8 * r, last_use);
  }
}

__device__ __forceinline__ void sq_publish(const Ctx& cx, int qb, int hs, int j, int lane) {
  if (j == 2 && lane == 0) {
    const unsigned e = cx.g->launch[hs * 16 + qb]++;
    *(uint2*)(cx.sp + SM_TAG) = make_uint2((~e & 1) * TAG, e);
  }
  const int row = (hs & 3) * 16 + (lane >> 1);
  uint32_t a = cx.sb + SM_X + (hs >> 2) * 73728 + j * 8192 + row * 128 + (((lane & 1) ^ (row & 7)) << 4);
  float s0 = 0.f, s1 = 0.f;
#pragma unroll 1
  for (int b = 0; b < 6; b++) {
    if (b == (hs < 4 ? 4 : 0)) {
      const int n = 224 + (__float_as_uint(s1) & blockIdx.y);
      if (j == 1) {
        bar_sync(BAR_XREL, n);
        if (lane < 4) asm volatile("mbarrier.arrive.shared::cluster.b64 _, [%0], 2;" ::"r"(mapa(cx.sb + SM_EMPTY + 16 + 8 * (lane >> 1), lane & 1)) : "memory");
      } else {
        bar_arrive(BAR_XREL, n);
      }
      __syncwarp();
      if (hs == 8) return;
    }
    if (!(b & 1)) mbar_wait(cx.sb + SM_XFULL + 32 * (hs >> 2) + 4 * b, 0);
    uint32_t v[8];
    lds128(a, v[0], v[1], v[2], v[3]);
    lds128(a ^ 32, v[4], v[5], v[6], v[7]);
    a = (a ^ 64) + (b & 1) * 24576;
#pragma unroll
    for (int i = 0; i < 8; i++) { s0 = fmaf(bf_lo(v[i]), bf_lo(v[i]), s0); s1 = fmaf(bf_hi(v[i]), bf_hi(v[i]), s1); }
  }
  s0 += s1;
  s0 += __shfl_xor_sync(0xffffffffu, s0, 1);
  float* part = (float*)(cx.sp + SM_STATS) + (lane >> 1) * 2;
  if (j < 2) {
    part[32 * j] = s0;
    bar_arrive(BAR_HELPER, 96);
  } else {
    bar_sync(BAR_HELPER, 96);
    TSP(68)
    if (!(lane & 1))
      asm volatile("st.relaxed.gpu.global.v2.b32 [%0], {%1, %2};" ::"l"(cx.g->sq + qb * 128 + hs * 16 + (lane >> 1)),
                   "r"(__float_as_uint((part[0] + part[32]) + s0)), "r"(*(const uint32_t*)(cx.sp + SM_TAG + 4) + 1) : "memory");
  }
}
__device__ __forceinline__ void sq_collect(const Ctx& cx, int qb, int lane) {
  const uint32_t e1 = *(const uint32_t*)(cx.sp + SM_TAG + 4) + 1;
#pragma unroll 1
  for (int n = 0; n < (1 << 16); n++) {
    __nanosleep(X_SQS);
    uint32_t bad = 0;
#pragma unroll
    for (int i = 0; i < 2; i++) {
      uint32_t a, t0, b, t1;
      ld_gran((const uint4*)at(cx.g->sq, qb * 1024 + lane * 16) + i * 32, a, t0, b, t1);
      *(uint32_t*)(cx.sp + SM_STATS + (i * 32 + lane) * 16 + 4) = a;
      *(uint32_t*)(cx.sp + SM_STATS + (i * 32 + lane) * 16 + 12) = b;
      bad |= (t0 ^ e1) | (t1 ^ e1);
    }
    if (__all_sync(0xffffffffu, bad == 0)) break;
  }
  __syncwarp();
  if (lane == 0) mbar_arrive(cx.sb + SM_BAR_SQ);
  TSP(69)
}
__device__ __forceinline__ void attn_gate(const Ctx& cx, int qb, int hs, int j, int t, const __nv_bfloat16* x) {
  const uint4* xp = (const uint4*)(x + qb * 128 * DM) + (t >> 3) * 72 + hs * 8 + (t & 7);
  uint4 nx = *xp;
  float wsum = 0.f;
  if (j == 0) {
    mbar_wait(cx.sb + SM_BAR_W, 0);
#pragma unroll 3
    for (int i = 0; i < 9; i++) {
      const uint32_t w = *(const uint32_t*)(cx.sp + SM_WR + i * 128 + t * 4);
      wsum += bf_lo(w) + bf_hi(w);
    }
#pragma unroll
    for (int i = 1; i < 32; i *= 2) wsum += __shfl_xor_sync(0xffffffffu, wsum, i);
  }
  bar_sync(BAR_GATE, 352);
  if (t < 16) {
    const float2 st = *(const float2*)(cx.sp + SM_STATS + 8 * (hs * 16 + t));
    const int row = qb * 128 + hs * 16 + t;
    const uint32_t b = pack2(0.f, fmaf(-st.x, wsum, *(const float*)(cx.sp + SM_RAW + 4 * t)) * st.y);
    st_gran(at(cx.g->stats, row * 16), __float_as_uint(st.x), __float_as_uint(st.y), (b ^ ((int)b < 0 ? 0xFFFF0000u : 0x80000000u)) | (0xFFFF - row),
            *(const uint32_t*)(cx.sp + SM_TAG + 4) + 1);
  }
  __syncwarp();
  uint32_t sa = cx.sb + SM_STATS + (t & ~7);
  uint4* gp = cx.g->gate + blockIdx.x * 1152 + (t ^ ((t >> 3) & 7));
  const int cross = t < 64 ? 10 : 9;
#pragma unroll 1
  for (int i = 0; i < 12; i++) {
    float2 st;
    asm volatile("ld.shared.v2.f32 {%0, %1}, [%2];" : "=f"(st.x), "=f"(st.y) : "r"(sa));
    const uint32_t mm = pack2(st.x, st.x);
    const uint4 v = make_uint4(sub2(nx.x, mm), sub2(nx.y, mm), sub2(nx.z, mm), sub2(nx.w, mm));
    xp += 12 * 72;
    sa += 96;
    if (i == cross) { xp += (hs * 16 - 128) * 72 + 64 - hs * 8; sa += (hs * 16 - 128) * 8; }
    if (i < 11) nx = *xp;
    *gp = make_uint4(gate2<false>(v.x, st.y), gate2<false>(v.y, st.y), gate2<false>(v.z, st.y), gate2<false>(v.w, st.y));
    gp = (uint4*)((size_t)(gp + 96) ^ 64);
  }
}

constexpr uint32_t SM_XO = SM_SLOT, SM_GO = SM_SLOT + STAGE, SM_P8 = SM_SLOT + 2 * STAGE;
__device__ __forceinline__ void attn_helper(const Ctx& cx, int qb, int hs, int lane, const CUtensorMap* tmX16) {
  const unsigned e = *(const uint32_t*)(cx.sp + SM_TAG + 4);
  bar_sync(BAR_HELPER, 64);
  bool todo = lane < 2;
#pragma unroll 1
  for (int n = 0; __any_sync(0xffffffffu, todo); n++) {
    if (todo && (ld_acquire(at(cx.g->qflag, ((qb * 4 + (hs >> 1)) * 2 + lane) * 4)) == e + 1 || n == (1 << 16))) {
      asm volatile("fence.proxy.async.global;" ::: "memory");
      mbar_expect_tx(cx.sb + SM_BAR_Q + 8 * lane, 8192);
      bulk_load(cx.sb + SM_SLOT + 2 * STAGE + lane * 16384 + 8192, at(cx.g->q, ((qb * 8 + hs) * 2 + lane) * 8192), 8192, cx.sb + SM_BAR_Q + 8 * lane);
      todo = false;
    }
  }
  const uint32_t tag = (~e & 1) * TAG;
  const uint4* src = cx.g->part + (size_t)((qb * 64 + 56) * 2 + (hs >> 2)) * 4 * 128 + (hs & 3) * 32 + lane;
  const uint32_t stg = cx.sb + SM_P8 + lane * 16;
  bar_sync(BAR_OA, 352);
  asm volatile("fence.proxy.async.global;" ::: "memory");
  if (lane == 0) {
    mbar_expect_tx(cx.sb + SM_BAR_MISC, 2 * 18432);
    bulk_load(cx.sb + SM_GO, cx.g->gate + blockIdx.x * 1152, 18432, cx.sb + SM_BAR_MISC);
#pragma unroll 1
    for (int i = 0; i < 9; i++)
      tma2d(cx.sb + SM_XO + i * 2048, tmX16, i < 8 ? hs * 64 : 512, qb * 128 + (i < 8 ? i : hs) * 16, cx.sb + SM_BAR_MISC);
  }
#pragma unroll 1
  for (int n = 0; n < (1 << 16); n++) {
    __nanosleep(n ? 500 : 2000);
    uint32_t a, b, d, t;
    ld_gran(src - lane + (lane & 7) * (2 * 4 * 128) + 3 * 128 + 31, a, b, d, t);
    if (__all_sync(0xffffffffu, (a & TAG) == tag)) break;
  }
  TSH(46)
#pragma unroll 1
  for (int n = 0; n < (1 << 16); n++) {
#pragma unroll 1
    for (int i = 0; i < 8; i++) {
#pragma unroll
      for (int g = 0; g < 4; g++) cp16(stg + (i * 4 + g) * 512, src + i * (2 * 4 * 128) + g * 128);
    }
    cp_wait_all();
    uint32_t bad = 0;
#pragma unroll 4
    for (int i = 0; i < 32; i++) bad |= *(const volatile uint32_t*)(cx.sp + SM_P8 + lane * 16 + i * 512) ^ tag;
    if (__all_sync(0xffffffffu, (bad & TAG) == 0)) break;
  }
  TSH(47)
#pragma unroll 1
  for (int n = 0; n < (1 << 16) && ld_acquire(&cx.g->ycnt) != 4 * (e + 1); n++) __nanosleep(200);
  const int2 sel = __ldcg(at(cx.g->sel, (lane & 7) * 8));
  const int lr = sel.x - qb * 128;
  uint32_t m = __ballot_sync(0xffffffffu, lane < 16 && ((lane & 8) ? (lr >> 4) == hs : (lr >> 7) == 0));
  mbar_wait(cx.sb + SM_BAR_MISC, 0);
#pragma unroll 1
  for (; m; m &= m - 1) {
    const int i = __ffs(m) - 1, row = __shfl_sync(0xffffffffu, lr, i);
    const float rs = __int_as_float(__shfl_sync(0xffffffffu, sel.y, i));
    const float* p = cx.g->ypart + (i & 7) * DM + (i < 8 ? hs * 64 : 512) + 2 * lane;
    const float2 a = __ldcg((const float2*)p), b = __ldcg((const float2*)(p + TOPC * DM)), c = __ldcg((const float2*)(p + 2 * TOPC * DM)),
                 d = __ldcg((const float2*)(p + 3 * TOPC * DM));
    const uint32_t y = pack2((a.x + b.x) + (c.x + d.x), (a.y + b.y) + (c.y + d.y));
    const uint32_t u = pack2(bf_lo(y) * rs, bf_hi(y) * rs);
    const float2 st = *(const float2*)(cx.sp + SM_STATS + 8 * row);
    const int o = (i < 8 ? row : 128 + (row & 15)) * 128 + ((lane * 4) ^ ((row & 7) << 4));
    *(uint32_t*)(cx.sp + SM_GO + o) = gate2<true>(sub2(*(const uint32_t*)(cx.sp + SM_XO + o), pack2(st.x, st.x)), st.y, make_float2(bf_lo(u), bf_hi(u)));
  }
  __syncwarp();
  if (lane == 0) mbar_arrive(cx.sb + SM_BAR_XG);
  TSH(48)
}
__device__ __forceinline__ void attn_finish8(const Ctx& cx, int qb, int hs, int hw, int lane, __nv_bfloat16* out) {
  bar_sync(BAR_GATE, 96);
#pragma unroll 1
  for (int g = hw; g < 4; g += 3) {
    float acc[8] = {0.f, 0.f, 0.f, 0.f, 0.f, 0.f, 0.f, 0.f};
#pragma unroll 2
    for (int sidx = 0; sidx < 8; sidx++) {
      uint32_t a, b, d, t;
      lds128(cx.sb + SM_P8 + lane * 16 + (sidx * 4 + g) * 512, a, b, d, t);
      acc[0] += bf_lo(a); acc[1] += bf_hi(a & ~TAG); acc[2] += bf_lo(b); acc[3] += bf_hi(b);
      acc[4] += bf_lo(d); acc[5] += bf_hi(d); acc[6] += bf_lo(t); acc[7] += bf_hi(t);
    }
#pragma unroll
    for (int j = 0; j < 4; j++) {
      const int o = (128 + (lane >> 2) + (j & 1) * 8) * 128 + (((2 * g + (j >> 1)) ^ (lane >> 2)) << 4) + (lane & 3) * 4;
      uint32_t* xp = (uint32_t*)(cx.sp + SM_XO + o);
      *xp = fma2(pack2(acc[2 * j], acc[2 * j + 1]), *(const uint32_t*)(cx.sp + SM_GO + o), *xp);
    }
  }
  bar_sync(BAR_GATE, 96);
#pragma unroll 1
  for (int ch = threadIdx.x - 32; ch < 128; ch += 96)
    *(uint4*)at(out, ((qb * 128 + hs * 16 + (ch >> 3)) * DM + 512 + (ch & 7) * 8) * 2) =
        *(const uint4*)(cx.sp + SM_XO + 16384 + (ch ^ ((ch >> 3) & 7)) * 16);
}

__device__ __forceinline__ void ffn_producer(const Ctx& cx, int f, const CUtensorMap* tmWq, const CUtensorMap* tmG,
                                             const CUtensorMap* tmU, const CUtensorMap* tmD) {
  uint64_t keep;
  asm("createpolicy.fractional.L2::evict_normal.b64 %0, 1.0;" : "=l"(keep));
  int st = 0;
#pragma unroll 1
  for (int p = 0; p < 16; p++) {
#pragma unroll 1
    for (int i = 0; i < 5; i++, st++) if (st > 1) load_wq(cx, tmWq, st, i, ((2 * (p & 3) + cx.rank) * 4 + 3) * DH + 64, keep);
  }
  const uint32_t full = cx.sb + SM_FFULL, empty = cx.sb + SM_FEMPTY;
  int pair = 0, u = 0;
#pragma unroll 1
  for (st = 0; st < 14 * 12; st++) {
    const uint32_t sl = st & 7;
    const int unit = pair * 2 + (u & 1), k = u >> 1, k3 = k >= 3 ? k - 3 : k;
    if (unit < 27) {
      mbar_wait(empty + 8 * sl, (st >> 3) & 1);
      __syncwarp();
      if (elect_one()) {
        mbar_expect_tx(full + 8 * sl, FSTAGE);
        if (pair < 9) tma2d_stream(cx.sb + sl * FSTAGE, k < 3 ? tmG : tmU, f * 1152 + unit * 64, k3 * 192, full + 8 * sl);
        else tma2d_stream(cx.sb + sl * FSTAGE, tmD, (unit - 18) * 64, f * 1152 + k * 192, full + 8 * sl);
      }
    }
    if (++u == 12) { u = 0; pair++; }
  }
}
__device__ __forceinline__ void load_x1(uint32_t dst, const CUtensorMap* tmX64, int row, int box, int n, uint32_t bar) {
  mbar_expect_tx(bar, n * 8192);
#pragma unroll 1
  for (int i = 0; i < n; i++) tma2d(dst + i * 8192, tmX64, (box + i) * 64, row, bar);
}
__device__ __forceinline__ void ffn_publish(const Ctx& cx, int f, int w, int lane, const CUtensorMap* tmX64) {
  const uint32_t xs = cx.sb + SM_SLOT + w * 49152, xf = cx.sb + SM_XFULL + w * 32;
#pragma unroll 1
  for (int n = 0; n < 16; n++) {
    const int p = n & 3, row = (f + (n & 12) + 4) * 128 + w * 64;
    if (n < 12 && p == 3) {
      bar_sync(BAR_QS + w, 160);
      if (lane == 0) load_x1(xs, tmX64, row, 4, 4, xf + 8);
      __syncwarp();
    }
    bar_sync(BAR_QS + w, 160);
    const uint32_t e1 = *(const uint32_t*)(cx.sp + SM_TAG + 4) + 1;
    if (lane == 0) {
#pragma unroll
      for (int i = 0; i < 2; i++)
        asm volatile("cp.async.bulk.global.shared::cta.bulk_group [%0], [%1], 8192;"
                     ::"l"(cx.g->q + (((f + (n & 12)) * 8 + 2 * p + i) * 2 + w) * 512), "r"(xs + 32768 + i * 8192) : "memory");
      asm volatile("cp.async.bulk.commit_group;" ::: "memory");
      asm volatile("cp.async.bulk.wait_group.read 0;" ::: "memory");
      if (n < 12 && (p == 0 || p == 3)) load_x1(xs + (p ? 32768 : 0), tmX64, row, p ? 8 : 0, p ? 1 : 4, xf + (p ? 16 : 0));
      asm volatile("cp.async.bulk.wait_group 0;\nfence.proxy.async.global;" ::: "memory");
      asm volatile("st.release.gpu.global.u32 [%0], %1;" ::"l"(&cx.g->qflag[((f + (n & 12)) * 4 + p) * 2 + w]), "r"(e1) : "memory");
    }
    __syncwarp();
    if (n < 12 && p == 1) {
#pragma unroll 1
      for (int i = 0, k = 0; i < 64 && k < (1 << 16); k++) {
        uint32_t m, r, z, t;
        ld_gran(cx.g->stats + row + i + lane, m, r, z, t);
        *(uint2*)(cx.sp + SM_STATS + 8 * (w * 64 + i + lane)) = make_uint2(m, r);
        if (__all_sync(0xffffffffu, t == e1)) i += 32;
      }
    }
    bar_arrive(BAR_QF + w, 160);
  }
}

__device__ __forceinline__ void ffn_consumer(const Ctx& cx, int f, int wg, int cw, int lane, const __nv_bfloat16* x) {
  const int r = lane >> 2, c = lane & 3, tid = cw * 32 + lane;
  const uint32_t full = cx.sb + SM_FFULL, empty = cx.sb + SM_FEMPTY;
  const bool signaller = (tid & 127) == 0;
  prof(wg, 8);
  const unsigned e = *(const uint32_t*)(cx.sp + SM_TAG + 4);
  uint32_t key[8];
#pragma unroll 1
  for (int n = 0; n < (1 << 16); n++) {
    uint32_t bad = 0;
#pragma unroll
    for (int i = 0; i < 8; i++) {
      uint32_t t;
      asm volatile("ld.relaxed.gpu.global.v2.b32 {%0, %1}, [%2];" : "=r"(key[i]), "=r"(t) : "l"(&cx.g->stats[i * 256 + tid].z) : "memory");
      bad |= t ^ (e + 1);
    }
    if (__all_sync(0xffffffffu, bad == 0)) break;
  }
  bar_sync(BAR_QF + wg, 160);
  bar_sync(3, 256);
  if (tid < 8) mbar_arrive(empty + 8 * tid);
  prof(wg, 9);
  int mysel = 0;
#pragma unroll 1
  for (int k = 0; k < TOPC; k++) {
    uint32_t m = key[0];
#pragma unroll
    for (int i = 1; i < 8; i++) m = max(m, key[i]);
    m = __reduce_max_sync(0xffffffffu, m);
    uint32_t* tk = (uint32_t*)(cx.sp + SM_TOPK) + (k & 1) * 8;
    if (lane == 0) tk[cw] = m;
    bar_sync(3, 256);
    m = __reduce_max_sync(0xffffffffu, tk[lane & 7]);
#pragma unroll
    for (int i = 0; i < 8; i++) if (key[i] == m) key[i] = 0;
    if (k == cw) mysel = 0xFFFF - (int)(m & 0xFFFF);
  }
  {
    const float4 st = __ldcg((const float4*)&cx.g->stats[mysel]);
    const uint32_t mm = pack2(st.x, st.x);
#pragma unroll 3
    for (int i = 0; i < 9; i++) {
      const uint32_t t = sub2(*(const uint32_t*)(x + (size_t)mysel * DM + i * 64 + 2 * lane), mm);
      *(uint32_t*)(cx.sp + SM_XSEL + i * 1024 + cw * 128 + (((lane >> 2) ^ cw) << 4) + (lane & 3) * 4) =
          pack2(bf_lo(t) * st.y, bf_hi(t) * st.y);
    }
    const uint32_t k = __float_as_uint(st.z);
    const float score = bf_hi(k ^ ((int)k < 0 ? 0x80000000u : 0xFFFF0000u));
    if (lane == 0 && f == 0) cx.g->sel[cw] = make_int2(mysel, __float_as_int(bfr(rcp(1.0f + ex2(-1.4426950408889634f * score)))));
  }
  asm volatile("fence.proxy.async.shared::cta;" ::: "memory");
  bar_sync(3, 256);
  prof(wg, 10);
  auto run = [&](float (&acc)[4], int st, int n, uint32_t b) {
#pragma unroll 1
    for (int u = 0; u < n; u++, st += 2, b += 3072) {
      const uint32_t sl = st & 7;
      mbar_wait(full + 8 * sl, (st >> 3) & 1);
      wg_fence();
      const uint64_t da = mkdesc(cx.sb + sl * FSTAGE, 16), db = mkdesc(b, 16);
#pragma unroll
      for (int k = 0; k < 12; k++) mma_n8(acc, da + k * 128, db + (k >> 2) * 64 + (k & 3) * 2, u > 0 || k > 0);
      wg_commit();
      wg_wait<0>();
      if (signaller) mbar_arrive(empty + 8 * sl);
    }
    pin(acc);
  };
#pragma unroll 1
  for (int unit = wg; unit < 27; unit += 2) {
    if (unit >> 1 == 9) {
      asm volatile("fence.proxy.async.shared::cta;" ::: "memory");
      bar_sync(3, 256);
      prof(wg, 11);
    }
    const bool gu = unit < 18;
    float a0[4], a1[4];
#pragma unroll 1
    for (int m = 0; m < (gu ? 2 : 1); m++) {
      run(a1, (unit >> 1) * 12 + m * 6 + wg, gu ? 3 : 6, cx.sb + (gu ? SM_XSEL : SM_H));
      if (m == 0) { a0[0] = a1[0]; a0[1] = a1[1]; a0[2] = a1[2]; a0[3] = a1[3]; }
    }
    float u0 = a1[0], u1 = a1[1];
#pragma unroll 1
    for (int i = 0; i < 2; i++) {
      const int fl = (cw & 3) * 16 + r + i * 8;
      if (gu) {
        const uint32_t g = pack2(a0[0], a0[1]);
        const uint32_t h = fma2(pack2(silu_f(bf_lo(g)), silu_f(bf_hi(g))), pack2(u0, u1), 0x80008000u);
        uint8_t* hp = cx.sp + SM_H + unit * 1024 + c * 256 + (fl & 7) * 2;
        *(uint16_t*)(hp + (((fl >> 3) ^ (2 * c)) << 4)) = (uint16_t)h;
        *(uint16_t*)(hp + 128 + (((fl >> 3) ^ (2 * c + 1)) << 4)) = (uint16_t)(h >> 16);
      } else {
        float* yp = cx.g->ypart + (f * TOPC + 2 * c) * DM + (unit - 18) * 64 + fl;
        yp[0] = u0;
        yp[DM] = u1;
      }
      a0[0] = a0[2]; a0[1] = a0[3]; u0 = a1[2]; u1 = a1[3];
    }
  }
  prof(wg, 12);
  bar_sync(3, 256);
  if (tid == 0) atom_add_acq_rel(&cx.g->ycnt);
  prof(wg, 13);
}

constexpr float SUM_HI = 1.8446744e19f, SUM_LO = 9.0949470e-13f;

template <int LO, int HI, int N>
__device__ __forceinline__ void softmax_exp(float (&s)[N]) {
#pragma unroll
  for (int i = LO; i < HI; i++) s[i] = ex2(s[i]);
}
__device__ __forceinline__ void sum_tree(const uint32_t (&pf)[28], bool big, uint32_t& h0, uint32_t& h1) {
  uint32_t t0 = add2(add2(pf[16], pf[18]), add2(pf[20], pf[22])), t1 = add2(add2(pf[17], pf[19]), add2(pf[21], pf[23]));
  if (big) { t0 = add2(t0, add2(pf[24], pf[26])); t1 = add2(t1, add2(pf[25], pf[27])); }
  h0 = add2(add2(add2(add2(pf[0], pf[2]), add2(pf[4], pf[6])), add2(add2(pf[8], pf[10]), add2(pf[12], pf[14]))), t0);
  h1 = add2(add2(add2(add2(pf[1], pf[3]), add2(pf[5], pf[7])), add2(add2(pf[9], pf[11]), add2(pf[13], pf[15]))), t1);
}
__device__ __forceinline__ void exact_attention(float (&o)[16], float& l0, float& l1, const uint32_t (&q)[32], const __nv_bfloat16* kp,
                                                const __nv_bfloat16* vp) {
  float m0 = -3.0e38f, m1 = -3.0e38f;
  l0 = l1 = 0.f;
#pragma unroll
  for (int i = 0; i < 16; i++) o[i] = 0.f;
#pragma unroll 1
  for (int key = 0; key < SEQ; key += 8, kp += 8 * DH, vp += 8 * DH) {
    float d[4] = {0.f, 0.f, 0.f, 0.f};
#pragma unroll
    for (int k = 0; k < 8; k++)
      hmma_k16(d, q[4 * k], q[4 * k + 1], q[4 * k + 2], q[4 * k + 3], *(const uint32_t*)(kp + k * 16), *(const uint32_t*)(kp + k * 16 + 8));
    float x0 = fmaxf(d[0], d[1]), x1 = fmaxf(d[2], d[3]);
    x0 = fmaxf(x0, __shfl_xor_sync(0xffffffffu, x0, 1));
    x1 = fmaxf(x1, __shfl_xor_sync(0xffffffffu, x1, 1));
    x0 = fmaxf(fmaxf(x0, __shfl_xor_sync(0xffffffffu, x0, 2)), m0);
    x1 = fmaxf(fmaxf(x1, __shfl_xor_sync(0xffffffffu, x1, 2)), m1);
    const float sc0 = ex2(m0 - x0), sc1 = ex2(m1 - x1);
    m0 = x0; m1 = x1;
    const uint32_t p0 = pack2(ex2(d[0] - m0), ex2(d[1] - m0)), p1 = pack2(ex2(d[2] - m1), ex2(d[3] - m1));
    l0 = fmaf(l0, sc0, bf_lo(p0) + bf_hi(p0));
    l1 = fmaf(l1, sc1, bf_lo(p1) + bf_hi(p1));
#pragma unroll
    for (int nb = 0; nb < 4; nb++) {
      uint32_t b;
      asm("movmatrix.sync.aligned.m8n8.trans.b16 %0, %1;" : "=r"(b) : "r"(*(const uint32_t*)(vp + nb * 8)));
      o[4 * nb] *= sc0; o[4 * nb + 1] *= sc0; o[4 * nb + 2] *= sc1; o[4 * nb + 3] *= sc1;
      asm volatile("mma.sync.aligned.m16n8k8.row.col.f32.bf16.bf16.f32 {%0, %1, %2, %3}, {%4, %5}, {%6}, {%0, %1, %2, %3};"
                   : "+f"(o[4 * nb]), "+f"(o[4 * nb + 1]), "+f"(o[4 * nb + 2]), "+f"(o[4 * nb + 3]) : "r"(p0), "r"(p1), "r"(b));
    }
  }
}
__device__ __forceinline__ bool inv_sums(float l0, float l1, float& i0, float& i1) {
  l0 += __shfl_xor_sync(0xffffffffu, l0, 1); l1 += __shfl_xor_sync(0xffffffffu, l1, 1);
  l0 += __shfl_xor_sync(0xffffffffu, l0, 2); l1 += __shfl_xor_sync(0xffffffffu, l1, 2);
  i0 = rcp(l0);
  i1 = rcp(l1);
  return !(l0 + l1 <= SUM_HI) | (fminf(l0, l1) < SUM_LO);
}
template <int LO, int HI, int N>
__device__ __forceinline__ void park(uint32_t a, const float (&o)[N], float i0, float i1, bool on = true) {
#pragma unroll
  for (int i = LO; i < HI; i++)
    asm volatile("{\n.reg .pred p;\nsetp.ne.u32 p, %5, 0;\n@p stmatrix.sync.aligned.m8n8.x4.shared.b16 [%0], {%1, %2, %3, %4};\n}"
                 ::"r"(a + i * 2048), "r"(pack2(o[8 * i] * i0, o[8 * i + 1] * i0)), "r"(pack2(o[8 * i + 2] * i1, o[8 * i + 3] * i1)),
                 "r"(pack2(o[8 * i + 4] * i0, o[8 * i + 5] * i0)), "r"(pack2(o[8 * i + 6] * i1, o[8 * i + 7] * i1)), "r"((uint32_t)on) : "memory");
}

template <int I, int NP, int E0, int N, int NS>
__device__ __forceinline__ void exp_park(float (&s)[NS], uint32_t a, const float (&o)[64], float i0, float i1, bool on, int id) {
  if constexpr (I < NP) {
    constexpr int E1 = E0 + (N - E0) * X_PG / (NP - I);
    softmax_exp<E0, E1>(s);
    park<I, I + X_PG>(a, o, i0, i1, on);
    if (I + X_PG < NP) {
#pragma unroll
      for (int i = E0; i < E1; i++) asm volatile("" : "+f"(s[i])::"memory");
      block_fence(id + I);
    }
    exp_park<I + X_PG, NP, E1, N>(s, a, o, i0, i1, on, id);
  }
}

__device__ __forceinline__ void attn_consumer(const Ctx& cx, bool hlp, int qb, int hs, int wg, int cw, int lane, const __nv_bfloat16* x,
                                              const __nv_bfloat16* kc, const __nv_bfloat16* vc, __nv_bfloat16* out) {
  const uint32_t full = cx.sb + SM_FULL;
  const uint32_t ring = cx.sb + SM_RING;
  const uint32_t qwg = ring + wg * 16384;
  auto qlane = [&](int l) { return qwg + (cw & 3) * 256 + (l >> 4) * 1024 + (l & 15) * 16; };
  const bool signaller = lane == 0 && (cw & 3) < 2;
  const int my_turn = 1 + wg, other_turn = 2 - wg;
  const uint32_t empty_c = mapa(cx.sb + SM_EMPTY, cw & 1);

  float oA[64], oB[64], i0, i1;
  uint32_t xl[32];
  {
    const int r = lane >> 2, c = lane & 3;
    const int lr0 = cw * 16 + r;
    uint32_t xa[144];
    uint32_t mm0, mm1;
    float rstd0, rstd1, sq0 = 0.f, sq1 = 0.f;
    const uint32_t xf = cx.sb + SM_XFULL + wg * 32, xs = cx.sb + SM_SLOT + wg * 49152;
    auto lo_of = [&](int l) { return ((cw & 3) * 16 + (l & 15)) * 128 + (((l >> 4) ^ (l & 7)) << 4); };
    prof(wg, 0);
    {
      const uint32_t lo = lo_of(lane);
      const uint32_t xb = cx.sb + SM_X + wg * 73728;
      float sm[X_NS][4] = {};
      const uint32_t ws = (lane & 7) == 1 ? 64 : 0;
      uint32_t wb = cx.sb + (ws ? SM_WR + (lane >> 3) * 16 : SM_ONES);
      uint32_t b0[24], b1[24], b2[24];
      TS4(1)
      mbar_wait(cx.sb + SM_BAR_W, 0);
      if (X_LN == 0) {
        ln_fetch_b(b0, wb, ws);
        ln_fetch_b(b1, wb, ws);
        ln_fetch_b(b2, wb, ws);
      }
      mbar_wait(xf, 0);
      TS4(2)
      ln_fetch<0, 12>(xa, xb, lo);
      if (X_LN == 1) {
        ln_fetch_b(b0, wb, ws);
        ln_fetch_b(b1, wb, ws);
        ln_fetch_b(b2, wb, ws);
      }
      ln_sums<0, 12>(xa, sm, b0);
      mbar_wait(xf + 8, 0);
      TS4(3)
      ln_fetch<12, 24>(xa, xb, lo);
      if (wg == 0) {
        bar_arrive(BAR_XREL + (xa[95] & blockIdx.y), 224);
      }
      ln_sums<12, 24>(xa, sm, b1);

      mbar_wait(xf + 16, 0);
      TS4(4)
      prof(wg, 1);
      ln_fetch<24, 36>(xa, xb, lo);
      ln_sums<24, 36>(xa, sm, b2);
#pragma unroll
      for (int i = 0; i < 4; i++) sm[0][i] = X_NS == 2 ? sm[0][i] + sm[1][i] : X_NS == 3 ? sm[0][i] + sm[1][i] + sm[2][i] : (sm[0][i] + sm[1][i]) + (sm[2][i] + sm[X_NS - 1][i]);
      if (cw == hs && c == 0) {
        *(float*)(cx.sp + SM_RAW + 4 * r) = sm[0][1];
        *(float*)(cx.sp + SM_RAW + 4 * r + 32) = sm[0][3];
      }
      rstd0 = sm[0][0];
      rstd1 = sm[0][2];
      mm0 = pack2(rstd0 * (1.0f / DM), rstd0 * (1.0f / DM));
      mm1 = pack2(rstd1 * (1.0f / DM), rstd1 * (1.0f / DM));
    }
#pragma unroll
    for (int i = 0; i < 16; i++) { xa[2 * i] = sub2(xa[2 * i], mm0); xa[2 * i + 1] = sub2(xa[2 * i + 1], mm1); }
    pin(xa);
    prof(wg, 2);
    TS4(5)

    float (&acc)[64] = oB;
    int st0 = 0;
#pragma unroll 1
    for (int n = 0; n < 16; n++) {
      const int p = n & 3, rb = n >> 2;
      const bool last = p == 3 && !hlp;
#pragma unroll
      for (int i = 0; i < 5; i++) {
        if (i == 4 && last) {
          wg_wait<1>();
          mbar_arrive_cluster(empty_c + 8 * 3, signaller && wg);
          wg_wait<0>();
          pin(acc);
          prof(wg, 6);
#pragma unroll
          for (int j = 0; j < 32; j++) xl[j] = xa[112 + j];
          i0 = rstd0;
          i1 = rstd1;
          goto attention;
        }
        const int st = st0 + i;
        const uint32_t sl = st & 3, slp = (st - 1) & 3;
        if (!wg) mbar_wait(full + 8 * sl, (st >> 2) & 1);
        TS4(8 + 2 * (p * 5 + i))
        const bool join = wg && last;
        if ((i || st0 + wg) && i != (wg ? 4 : 1) && !(join && i == 3)) bar_sync(my_turn, 256);
        wg_fence();
        const uint64_t db = mkdesc(ring + sl * STAGE, 16384);
        const int kb0 = i < 3 ? 8 * i : 8 * i - 4;
#pragma unroll
        for (int k = 0; k < (i == 2 ? 4 : 8); k++) {
          const int kb = kb0 + k;
          mma_n128t(acc, xa[4 * kb], xa[4 * kb + 1], xa[4 * kb + 2], xa[4 * kb + 3], db + k * 128, kb > 0);
        }
        wg_commit();
        TS4(9 + 2 * (p * 5 + i))
        if (wg ? (i == 4 ? st0 < 75 : (i < 2 || i == (join ? 3 : 2))) : i) bar_arrive(other_turn, 256);
        if (p == 0 && i < 4) {
          if (i == 1 && rb) {
            mbar_wait(xf + 8, rb & 1);
            ln_fetch<16, 32>(xa, xs - 32768, lo_of(fresh_lane()));
          }
          if (i == 2 && rb) {
            mbar_wait(xf + 16, rb & 1);
            ln_fetch<32, 36>(xa, xs - 32768, lo_of(fresh_lane()));
          }
#pragma unroll
          for (int j = 0; j < 72; j++)
            if (j >= 2 * (i < 2 ? 8 * i + 8 : 8 * i + 4) && j < 2 * (i == 0 ? 16 : 8 * i + 12)) {
              xa[2 * j] = sub2(xa[2 * j], mm0);
              xa[2 * j + 1] = sub2(xa[2 * j + 1], mm1);
            }
          pin(xa);
        }
        if (i == X_SQI && n == 0) {
          mbar_wait(cx.sb + SM_BAR_SQ, 0);
          float2* sp = (float2*)(cx.sp + SM_STATS) + lr0;
          float mean0, mean1;
          ln_row(rstd0, sp[0].y, mean0, rstd0);
          ln_row(rstd1, sp[8].y, mean1, rstd1);
          __syncwarp();
          if (c == 0) {
            sp[0] = make_float2(mean0, rstd0);
            sp[8] = make_float2(mean1, rstd1);
          }
          *((uint32_t*)(cx.sp + SM_COLD) + wg) = 0;
          if (!hlp) bar_arrive(BAR_GATE, 352);
          rstd0 *= SM_SCALE_LOG2;
          rstd1 *= SM_SCALE_LOG2;
        }
        if (i == 3 && hlp && p == 3 && rb < 3) bar_arrive(BAR_QS + wg + (xa[63] & blockIdx.y), 160);
        if (i == 4 && p == 3 && rb < 3) {
          const float2* sp = (const float2*)(cx.sp + SM_STATS) + cw * 16 + (fresh_lane() >> 2);
          mm0 = pack2(sp[0].x, sp[0].x);
          mm1 = pack2(sp[8].x, sp[8].x);
          sq0 = sp[0].y * SM_SCALE_LOG2;
          sq1 = sp[8].y * SM_SCALE_LOG2;
#pragma unroll
          for (int j = 0; j < 16; j++) { xa[2 * j] = sub2(xa[2 * j], mm0); xa[2 * j + 1] = sub2(xa[2 * j + 1], mm1); }
          pin(xa);
        }
        if (i == 0) {
          if (wg) {
            wg_wait<0>();
            mbar_arrive_cluster(empty_c + 8 * sl, signaller);
          }
        } else if (i == 2) {
          if (!join) {
            wg_wait<0>();
            mbar_arrive_cluster(empty_c + 8 * sl, signaller);
          }
          if (hlp && p == 3 && rb < 3) {
            mbar_wait(xf, ~rb & 1);
            ln_fetch<0, 16>(xa, xs, lo_of(fresh_lane()));
            pin(xa);
          }
        } else if (i != 3) {
          wg_wait<1>();
          mbar_arrive_cluster(empty_c + 8 * slp, signaller && (i == 4 || !wg));
          wg_wait<0>();
          mbar_arrive_cluster(empty_c + 8 * sl, signaller);
        }
      }
      pin(acc);
      prof(wg, 3 + p);
      TS4(50 + 2 * p)
      st0 += 5;
      if (hlp && st0 > 5) bar_sync(BAR_QF + wg, 160);
      park<0, 8>(qlane(lane) + (hlp ? 5 + wg : 4 + p) * STAGE, acc, rstd0, rstd1);
      if (p || hlp) asm volatile("fence.proxy.async.shared::cta;" ::: "memory");
      if (hlp) bar_arrive(BAR_QS + wg, 160);
      if (p == 3) { rstd0 = sq0; rstd1 = sq1; }
      TS4(51 + 2 * p)
      if (p == 1 && !hlp) {
        float (&ah)[32] = *(float (*)[32])&acc[0];
#pragma unroll
        for (int i = 0; i < 3; i++) {
          const uint32_t sl = (10 + i) & 3;
          if (!wg) mbar_wait(full + 8 * sl, ((10 + i) >> 2) & 1);
          TS4(28 + 2 * i)
          if (i == 0 || i == 2 - wg) bar_sync(my_turn, 256);
          wg_fence();
          const uint64_t db = mkdesc(ring + sl * STAGE, 16);
#pragma unroll
          for (int k = 0; k < 12; k++) {
            const int kb = 12 * i + k;
            if (kb) mma_n64t(ah, xa[4 * kb], xa[4 * kb + 1], xa[4 * kb + 2], xa[4 * kb + 3], db + k * 128, true);
            else mma_n64t_dyn(ah, xa[0], xa[1], xa[2], xa[3], db, blockIdx.y);
          }
          wg_commit();
          TS4(29 + 2 * i)
          if (i == 2 || i != wg) {
            bar_arrive(other_turn, 256);
            if (i) {
              wg_wait<1>();
              mbar_arrive_cluster(empty_c + 8 * ((9 + i) & 3), signaller && i == wg + 1);
            }
            wg_wait<0>();
            mbar_arrive_cluster(empty_c + 8 * sl, signaller);
          }
        }
        pin(ah);
        TS4(54)
        park<0, 4>(qlane(lane) + 6 * STAGE, ah, rstd0, rstd1);
        TS4(55)
        st0 = 13;
        n = 2;
      }
    }
    TS_DUMP()
    ffn_consumer(cx, blockIdx.x & 3, wg, cw, fresh_lane(), x);
    return;
  }

attention:
  uint32_t oa[128];
  float acc[32];
  {
    uint32_t pf[28];
    uint32_t bad = 0;
    float lA0 = 0.f, lA1 = 0.f, lB0 = 0.f, lB1 = 0.f;
    int t = 0;
    uint32_t ra = 2 * 2048, rb = 2048, rc = 2 * 2048, par = 0;
    const uint64_t dk0 = mkdesc(ring, 16), dv0 = mkdesc(ring, 16384);
    uint64_t dqA = mkdesc_q(qwg + 4 * STAGE), dqB = dqA + 2048;
    auto turn = [&](auto kc_, auto bc_) {
      constexpr int KIND = decltype(kc_)::value, BIG = decltype(bc_)::value;
      constexpr int HB = KIND == 1, ID = 10 * KIND + 30 * BIG, T0 = BIG ? 38 : 0;
      constexpr int NS = BIG ? 56 : 48, SPLIT = BIG ? (HB ? X_SPLIT : X_SPLITA) : (HB ? X_SPLITS : X_SPLITSA);
      float s[NS];
      float (&op)[64] = HB ? oA : oB;
      uint32_t h0 = 0, h1 = 0;
      TS2(0)
      bar_sync(my_turn, 256);
      TS2(1)
      if (KIND) { pin(pf); pin(op); }
      mma_qk(s, HB ? dqB : dqA, dk0 + (HB ? ra : rc));
      TS2(2)
      if (KIND) {
        const bool bigp = HB ? BIG : BIG ? t != 10 : t == 66;
        if (X_BF2) block_fence(ID + 9);
        pin(pf);
        sum_tree(pf, bigp, h0, h1);
        asm volatile("" : "+r"(h0), "+r"(h1)::"memory");
        if (HB) mbar_wait(full + (rb >> 8), par);
        mma_pv(op, pf, dv0 + rb, t != T0 + 2 - HB, bigp);
      } else {
        mbar_wait(full + (rb >> 8), (NST_Q - 1) >> 2 & 1);
#pragma unroll
        for (int k = 0; k < 8; k++) mma_n128t(op, xl[4 * k], xl[4 * k + 1], xl[4 * k + 2], xl[4 * k + 3], dv0 + rb + k * 128, 1);
        wg_commit();
      }
      TS2(3)
      bar_arrive(other_turn, 256);
      (HB ? lA0 : lB0) += bf_lo(h0) + bf_hi(h0);
      (HB ? lA1 : lB1) += bf_lo(h1) + bf_hi(h1);
      wg_wait<1>();
      pin(s);
      TS1(t)
      TS2(4)
      if (KIND == 1) mbar_arrive_cluster_now<ID + 3>(empty_c + (ra >> 8), signaller);
      if (BIG && t == T0 + HB) {
        const uint32_t a = qlane(fresh_lane()) + (4 + HB) * STAGE;
        const bool ok = !__any_sync(0xffffffffu, inv_sums(HB ? lB0 : lA0, HB ? lB1 : lA1, i0, i1));
        bad = (HB ? bad : 0) | (ok ? 0 : 1 << HB);
        (HB ? lB0 : lA0) = 0.f;
        (HB ? lB1 : lA1) = 0.f;
        softmax_exp<0, X_E0>(s);
#pragma unroll
        for (int i = 0; i < X_E0; i++) asm volatile("" : "+f"(s[i])::"memory");
        block_fence(ID + 7);
        exp_park<0, X_PA, X_E0, SPLIT>(s, a, HB ? oB : oA, i0, i1, ok, 200 + ID);
        if (!HB) dqB += 2048;
        prof(wg, 8 + HB);
      } else {
        if (HB && !BIG) bad = (bad & 3) | (inv_sums(lA0, lA1, i0, i1) ? 4 : 0);
        softmax_exp<0, SPLIT>(s);
      }
      pin(s);
      if (!BIG) block_fence(ID + 4);
      TS2(5)
      wg_wait<0>();
      TS2(6)
      pin(op);
      if (KIND) pin(pf); else pin(xl);
      if (HB) {
        par ^= rc == 2048;
        if (BIG && t == 37) dqA -= 4 * 2048;
        if (BIG && t == X_WAKE && cw == 0) bar_arrive(BAR_HELPER, 64);
      } else {
        mbar_arrive_cluster_now<ID + 5>(empty_c + (rb >> 8), signaller);
        if (KIND) {
          par ^= ra == 2048;
          const uint32_t x = ra;
          ra = rc; rc = rb; rb = x;
        }
      }
      softmax_exp<SPLIT, NS>(s);
#pragma unroll
      for (int i = 0; i < NS / 2; i++) pf[i] = pack2(s[2 * i], s[2 * i + 1]);
      pin(pf);
      if (KIND == 0) {
        block_fence(ID + 6);
        park<0, 8>(qlane(fresh_lane()), oB, i0, i1);
        asm volatile("fence.proxy.async.shared::cta;" ::: "memory");
        prof(wg, 7);
      }
      if (BIG && X_PA < 8 && t == T0 + HB) park<X_PA, 8>(qlane(fresh_lane()) + (4 + HB) * STAGE, HB ? oB : oA, i0, i1, !(bad >> HB));
      if (BIG && !HB && t == T0) mbar_wait(cx.sb + SM_BAR_Q + 8 * wg, 0);
      if (HB) mbar_wait(full + (rc >> 8), par);
      t++;
    };
#pragma unroll
    for (int i = 24; i < 28; i++) asm volatile("" : "=r"(pf[i]));
    mbar_wait(full + 8 * 2, 0);
    turn(IC<0>(), IC<0>());
    rb = 3 * 2048; rc = 2048;
    kill(oA);
    const bool never = blockIdx.y == 1;
#pragma unroll 1
    while (true) {
      turn(IC<1>(), IC<0>());
      if (t == 76) break;
      if (t == 10) {
#pragma unroll 1
        do {
#pragma unroll 1
          do turn(IC<2>(), IC<1>()); while (never);
          turn(IC<1>(), IC<1>());
        } while (t != 66);
      }
#pragma unroll 1
      do turn(IC<2>(), IC<0>()); while (never);
    }
    const uint32_t ql = qlane(fresh_lane());
    auto scale = [&](auto lo, auto hi) {
#pragma unroll
      for (int i = decltype(lo)::value; i < decltype(hi)::value; i++) {
        oa[32 + 2 * i] = pack2(oA[4 * i] * i0, oA[4 * i + 1] * i0);
        oa[32 + 2 * i + 1] = pack2(oA[4 * i + 2] * i1, oA[4 * i + 3] * i1);
        asm volatile("" : "+r"(oa[32 + 2 * i]), "+r"(oa[32 + 2 * i + 1])::"memory");
      }
    };
    TS3(1)
    if (X_LD == 0) {
#pragma unroll
      for (int i = 0; i < 8; i++) ldsm4(ql + 4 * STAGE + i * 2048, oa[4 * i], oa[4 * i + 1], oa[4 * i + 2], oa[4 * i + 3]);
    }
    {
      uint32_t h0, h1;
      sum_tree(pf, false, h0, h1);
      if (inv_sums(lB0 + (bf_lo(h0) + bf_hi(h0)), lB1 + (bf_lo(h1) + bf_hi(h1)), lB0, lB1)) bad |= 8;
    }
    scale(IC<0>(), IC<X_F1>());
    volatile uint32_t* const cold = (volatile uint32_t*)(cx.sp + SM_COLD) + wg;
    if (bad) *cold = 1;
    block_fence(93);
    TS3(2)
    bar_sync(my_turn, 256);
    const uint32_t is_cold = *cold;
    TS3(3)
    pin(pf); pin(oB);
    mma_pv(oB, pf, dv0 + 2 * 2048, true, false);
    mbar_arrive_cluster_now<91>(empty_c, signaller && !is_cold);
    TS3(4)
    if (X_LD == 1) {
#pragma unroll
      for (int i = 0; i < 8; i++) ldsm4(ql + 4 * STAGE + i * 2048, oa[4 * i], oa[4 * i + 1], oa[4 * i + 2], oa[4 * i + 3]);
    }
    const uint64_t db = mkdesc(ring + 3 * STAGE, 16);
    scale(IC<X_F1>(), IC<X_F2>());
    block_fence(94);
#pragma unroll
    for (int i = 0; i < 32; i++) asm volatile("" : "+r"(oa[i])::"memory");
    wg_fence();
#pragma unroll
    for (int k = 0; k < 8; k++) mma_n64t(acc, oa[4 * k], oa[4 * k + 1], oa[4 * k + 2], oa[4 * k + 3], db + k * 128, k > 0);
    if (X_F2 < 16) {
      wg_commit();
      block_fence(95);
      scale(IC<X_F2>(), IC<16>());
      TS3(5)
      wg_fence();
    }
#pragma unroll
    for (int k = 8; k < 16; k++) mma_n64t(acc, oa[4 * k], oa[4 * k + 1], oa[4 * k + 2], oa[4 * k + 3], db + k * 128, 1);
    wg_commit();
    bar_arrive(other_turn, 256);
    wg_wait<(X_F2 < 16 ? 2 : 1)>();
    pin(oB); pin(pf);
    TS(76)
    TS3(6)
    mbar_arrive_cluster(empty_c + 8 * 2, signaller);
#pragma unroll
    for (int i = 16; i < 24; i++) ldsm4(ql + 5 * STAGE + (i & 7) * 2048, oa[4 * i], oa[4 * i + 1], oa[4 * i + 2], oa[4 * i + 3]);
#pragma unroll
    for (int i = 0; i < 16; i++) {
      oa[96 + 2 * i] = pack2(oB[4 * i] * lB0, oB[4 * i + 1] * lB0);
      oa[96 + 2 * i + 1] = pack2(oB[4 * i + 2] * lB1, oB[4 * i + 3] * lB1);
    }
    TS3(7)
    mbar_wait(full + 8 * 1, 0);
    TS3(8)
    wg_wait<0>();
    pin(acc); pin(oa);
    if (__any_sync(0xffffffffu, is_cold)) {
      bad = __reduce_or_sync(0xffffffffu, bad);
      if (!(bad & 8)) {
#pragma unroll
        for (int i = 24; i < 32; i++) stsm4(ql + 6 * STAGE + (i & 7) * 2048, oa[4 * i], oa[4 * i + 1], oa[4 * i + 2], oa[4 * i + 3]);
      }
#pragma unroll 1
      for (int h = 0; h < 4; h++) {
        if (bad >> h & 1) {
          const uint32_t a = ql + ((0x6054 >> (4 * h)) & 7) * STAGE;
          const int l = fresh_lane(), o = (hs * 2 + (h >> 1)) * SEQ * DH + (l >> 2) * DH + (l & 3) * 2;
          uint32_t q[32];
#pragma unroll
          for (int i = 0; i < 8; i++) ldsm4(a + i * 2048, q[4 * i], q[4 * i + 1], q[4 * i + 2], q[4 * i + 3]);
#pragma unroll 1
          for (int i = 0; i < 4; i++) {
            float ox[16], l0, l1;
            exact_attention(ox, l0, l1, q, kc + o, vc + o + i * 32);
            inv_sums(l0, l1, l0, l1);
            park<0, 2>(a + i * 4096, ox, l0, l1);
          }
        }
      }
      __syncwarp();
#pragma unroll
      for (int i = 0; i < 32; i++)
        if ((i >> 3) != 1 || (bad & 4))
          ldsm4(ql + ((0x6504 >> (4 * (i >> 3))) & 7) * STAGE + (i & 7) * 2048, oa[4 * i], oa[4 * i + 1], oa[4 * i + 2], oa[4 * i + 3]);
      pin(oa);
      asm volatile("fence.proxy.async.shared::cta;" ::: "memory");
      bar_sync(4 + wg, 128);
      mbar_arrive_cluster(empty_c, signaller);
      wg_fence();
#pragma unroll
      for (int k = 0; k < 16; k++) mma_n64t(acc, oa[4 * k], oa[4 * k + 1], oa[4 * k + 2], oa[4 * k + 3], db + k * 128, k > 0);
      wg_commit();
      wg_wait<0>();
      pin(acc);
    }
    mbar_arrive_cluster(empty_c + 8 * 3, signaller);
  }

  prof(wg, 10);
  TS3(9)
  {
    lane = fresh_lane();
    const int tw = (cw & 3) * 32 + lane;
    float red[32];
    kill(red);
    const uint32_t tag = *(const uint32_t*)(cx.sp + SM_TAG);
    uint4* const xch = at(cx.g->part, ((qb * 64 * 2 + wg) * 4 * 128 + tw) * 16);
    int nrx = 1;
    auto region = [](int s, int h) { return h ? 1 + (s & 1) : (s & 1) ? 0 : 3; };
    auto half_step = [&](int s, auto hc, bool arrive) {
      constexpr int h = decltype(hc)::value;
      const uint64_t db = mkdesc(ring + region(s, h) * STAGE, 16);
      bar_sync(my_turn, 256);
      pin(oa);
      wg_fence();
#pragma unroll
      for (int k = 0; k < 16; k++) {
        const int kb = h * 16 + k;
        mma_n64t(acc, oa[4 * kb], oa[4 * kb + 1], oa[4 * kb + 2], oa[4 * kb + 3], db + k * 128, kb > 0);
      }
      wg_commit();
      if (arrive) bar_arrive(other_turn, 256);
    };
    auto await = [&](int s, int h) { mbar_wait(full + 8 * region(s, h), ((s >> 1) ^ h ^ 1) & 1); };
    auto fetch = [&](uint32_t (&g)[16], int n) {
      const uint4* p = at(xch, (hs * 7 + n - 1) * 16384);
#pragma unroll
      for (int i = 0; i < 4; i++) ld_gran(p + i * 128, g[4 * i], g[4 * i + 1], g[4 * i + 2], g[4 * i + 3]);
    };
    uint32_t g[16];
#pragma unroll 1
    for (int s = 0;; s++) {
      const bool pend = nrx < s - 1;
      if (pend) fetch(g, nrx);
      half_step(s, IC<1>(), s + wg < 9);
      if (s == 8) break;
      TS3(s < 3 ? 16 + 8 * s : 75)
      if (s == 0) {
        bar_arrive(BAR_OA, 352);
#pragma unroll
        for (int i = 0; i < 32; i++) red[i] = 0.f;
      }
      await(s + 1, 0);
      TS3(s < 3 ? 17 + 8 * s : 75)
      wg_wait<0>();
      TS3(s < 3 ? 18 + 8 * s : 75)
      mbar_arrive_cluster(empty_c + 8 * region(s, 1), signaller && s < 7);
      pin(acc);
      TS(77 + s)
      prof(wg, 12 + s);
      uint4* p = at(xch, (s == 0 ? 56 + hs : ((hs + s) & 7) * 7 + s - 1) * 16384);
#pragma unroll
      for (int i = 0; i < 4; i++)
        st_gran(p + i * 128, (pack2(acc[8 * i], acc[8 * i + 1]) & ~TAG) | tag, pack2(acc[8 * i + 2], acc[8 * i + 3]),
                pack2(acc[8 * i + 4], acc[8 * i + 5]), pack2(acc[8 * i + 6], acc[8 * i + 7]));
      TS3(s < 3 ? 19 + 8 * s : 75)
      half_step(s + 1, IC<0>(), true);
      TS3(s < 3 ? 20 + 8 * s : 75)
      await(s + 1, 1);
      TS3(s < 3 ? 21 + 8 * s : 75)
      if (pend && granules_ok(g, tag)) { add_granules(red, g); nrx++; }
      wg_wait<0>();
      TS3(s < 3 ? 22 + 8 * s : 75)
      mbar_arrive_cluster(empty_c + 8 * region(s + 1, 0), signaller && s < 6);
    }
    uint32_t xv[16], gt[16], g2[16];
    TS3(42)
    const bool ok = granules_ok(g, tag);
    TS3(43)
    nrx += ok;
    fetch(g2, nrx);
    mbar_wait(cx.sb + SM_BAR_XG, 0);
    const uint32_t frag = (cw * 16 + (lane & 15)) * 128 + (((lane >> 4) ^ (lane & 7)) << 4);
#pragma unroll
    for (int i = 0; i < 4; i++) {
      ldsm4(cx.sb + SM_XO + (frag ^ (i << 5)), xv[4 * i], xv[4 * i + 1], xv[4 * i + 2], xv[4 * i + 3]);
      ldsm4(cx.sb + SM_GO + (frag ^ (i << 5)), gt[4 * i], gt[4 * i + 1], gt[4 * i + 2], gt[4 * i + 3]);
    }
    if (ok) add_granules(red, g);
    TS3(44)
    wg_wait<0>();
    pin(acc);
    TS(85)
#pragma unroll
    for (int i = 0; i < 32; i++) red[i] += acc[i];
    pin(red);
#pragma unroll 1
    for (int spins = 0; spins < (1 << 16); spins++) {
      if (granules_ok(g2, tag)) {
        add_granules(red, g2);
        if (++nrx == 8) break;
      }
      fetch(g2, nrx);
    }
    prof(wg, 20);
    TS(86)
    uint32_t ow[16];
#pragma unroll
    for (int i = 0; i < 16; i++) ow[i] = fma2(pack2(red[2 * i], red[2 * i + 1]), gt[i], xv[i]);
#pragma unroll
    for (int i = 0; i < 4; i++) stsm4(cx.sb + SM_XO + (frag ^ (i << 5)), ow[4 * i], ow[4 * i + 1], ow[4 * i + 2], ow[4 * i + 3]);
    __syncwarp();
    __nv_bfloat16* const op = at(out, ((qb * 128 + cw * 16 + (lane >> 3)) * DM + hs * 64 + (lane & 7) * 8) * 2);
#pragma unroll
    for (int i = 0; i < 4; i++) {
      uint4 v;
      const int row = cw * 16 + i * 4 + (lane >> 3);
      lds128(cx.sb + SM_XO + row * 128 + (((lane ^ row) & 7) << 4), v.x, v.y, v.z, v.w);
      asm volatile("st.global.v4.b32 [%0], {%1, %2, %3, %4};" ::"l"(op + i * 4 * DM),
                   "r"(v.x), "r"(v.y), "r"(v.z), "r"(v.w) : "memory");
    }
    prof(wg, 22);
    TS(87)
    TS_DUMP()
  }
}

struct KvMaps { CUtensorMap m[4]; };
__global__ void __cluster_dims__(2, 1, 1) __launch_bounds__(THREADS, 1)
fused_kernel(const __nv_bfloat16* __restrict__ x, const __nv_bfloat16* __restrict__ w_r, const __nv_bfloat16* __restrict__ kc,
             const __nv_bfloat16* __restrict__ vc, __nv_bfloat16* __restrict__ out, Scratch* scratch,
             const __grid_constant__ CUtensorMap tmX, const __grid_constant__ CUtensorMap tmWq,
             const __grid_constant__ KvMaps tmKV, const __grid_constant__ CUtensorMap tmWo,
             const __grid_constant__ CUtensorMap tmG, const __grid_constant__ CUtensorMap tmU,
             const __grid_constant__ CUtensorMap tmD, const __grid_constant__ CUtensorMap tmX16,
             const __grid_constant__ CUtensorMap tmWq96, const __grid_constant__ CUtensorMap tmX64) {
  extern __shared__ __align__(1024) uint8_t smem_raw[];
  prof(0, 23, 511);
  if (X_PFX && threadIdx.x == 192) { prefetch_tmap(&tmX); prefetch_tmap(&tmWq); }
  Ctx cx;
  cx.sb = smem_u32(smem_raw);
  cx.sp = smem_raw;
  cx.g = scratch;
  cx.rank = blockIdx.x & 1;
  const int warp = __shfl_sync(0xffffffffu, threadIdx.x >> 5, 0);
  const int cluster = blockIdx.x >> 1;
  const bool is_ffn = blockIdx.x >= N_ATT_CTA;
  const int c7 = ((cluster - 36) * 37) >> 8;
  const int hs = cluster < 4 ? 4 + cluster : cluster < 36 ? (cluster - 4) >> 3 : 4 + c7;
  const int qb = (cluster < 4 ? 0 : cluster < 36 ? (cluster - 4) & 7 : cluster - (is_ffn ? 36 : 35) - 7 * c7) * 2 + cx.rank;

  auto load_x = [&](int w, int i0, int i1) {
#pragma unroll
    for (int i = i0; i < i1; i++) {
      mbar_expect_tx(cx.sb + SM_XFULL + 32 * w + 8 * i, 24576);
      tma3d(cx.sb + SM_X + (3 * w + i) * 24576, &tmX, qb * 128 + w * 64, i * 3, cx.sb + SM_XFULL + 32 * w + 8 * i);
    }
  };
  if (warp < 4) {
    asm volatile("setmaxnreg.dec.sync.aligned.u32 24;");
    if (elect_one()) {
      if (warp == 0) TSP(64)
      if (warp < 2) {
#pragma unroll
        for (int i = 0; i < 4; i++) mbar_init(cx.sb + SM_FULL + 32 * warp + 8 * i, 1 + 3 * warp);
        mbar_init(cx.sb + SM_BAR_XG + 8 * warp, 1);
        mbar_init(cx.sb + SM_BAR_Q + 8 * warp, 1);
        if (warp) mbar_init(cx.sb + SM_BAR_MISC, 1);
      } else if (is_ffn) {
#pragma unroll
        for (int i = 0; i < 8; i++) mbar_init(cx.sb + (warp == 2 ? SM_FFULL : SM_FEMPTY) + 8 * i, 1);
      }
      asm volatile("fence.mbarrier_init.release.cluster;" ::: "memory");
    }
    __syncwarp();
    cluster_arrive();
    if (warp == 0) TSP(70)
    cluster_wait();
    if (warp == 0) TSP(71)
    prof(0, 24, 511);
    if (warp == 0) {
      if (is_ffn) ffn_producer(cx, qb, &tmWq, &tmG, &tmU, &tmD);
      else attn_producer(cx, qb, hs, tmKV.m, &tmWq, &tmWq96, &tmWo);
      prof(0, 25, 511);
    } else {
      sq_publish(cx, qb, hs, warp - 1, read_lane());
      if (warp == 3) sq_collect(cx, qb, read_lane());
      if (!is_ffn) {
        attn_gate(cx, qb, hs, warp - 1, threadIdx.x - 32, x);
        if (warp == 1) TSP(65)
        asm volatile("fence.proxy.async.global;" ::: "memory");
        if (warp == 1) attn_helper(cx, qb, hs, fresh_lane(), &tmX16);
        else bar_arrive(BAR_OA, 352);
        attn_finish8(cx, qb, hs, warp - 1, fresh_lane(), out);
      } else if (warp < 3) {
        ffn_publish(cx, qb, warp - 1, fresh_lane(), &tmX64);
      }
    }
    __syncwarp();
    cluster_arrive();
    cluster_wait();
  } else {
    if (warp == 4 && elect_one()) {
#pragma unroll
      for (int i = 0; i < 3; i++) mbar_init(cx.sb + SM_XFULL + 8 * i, 1);
      TSP(66)
      load_x(0, 0, 3);
#pragma unroll
      for (int i = 4; i < 7; i++) mbar_init(cx.sb + SM_XFULL + 8 * i, 1);
      asm volatile("fence.mbarrier_init.release.cluster;" ::: "memory");
    }
    if (warp == 5 && elect_one()) {
      mbar_init(cx.sb + SM_BAR_W, 1);
      asm volatile("fence.mbarrier_init.release.cluster;" ::: "memory");
      *(uint4*)(cx.sp + SM_ONES) = make_uint4(0x3F803F80u, 0x3F803F80u, 0x3F803F80u, 0x3F803F80u);
      mbar_expect_tx(cx.sb + SM_BAR_W, DM * 2);
      bulk_load(cx.sb + SM_WR, w_r, DM * 2, cx.sb + SM_BAR_W);
    }
    __syncwarp();
    cluster_arrive();
    if (warp == 4 && elect_one()) {
      load_x(1, 0, X_ORD);
      TSP(67)
    }
    __syncwarp();
    asm volatile("setmaxnreg.inc.sync.aligned.u32 240;");
    const int cw = warp - 4, wg = cw >> 2;
    cluster_wait();
    if (warp == 8 && elect_one()) {
      const uint64_t pol = policy_evict_first();
#pragma unroll
      for (int i = 0; i < 4; i++) {
        if (!(i & 1)) mbar_expect_tx(cx.sb + SM_FULL + 4 * i, 32768);
        tma2d_mc(cx.sb + SM_RING + (i >> 1) * STAGE + cx.rank * 16384 + (i & 1) * 8192, &tmWq,
                 is_ffn ? (cx.rank * 4 + 3) * DH + 64 : hs * 512 + cx.rank * 64, i * 64, cx.sb + SM_FULL + 8 * (i >> 1), pol);
        if (i == 1) load_x(1, X_ORD, 3);
      }
      TSP(72)
    }
    __syncwarp();
    attn_consumer(cx, is_ffn, qb, hs, wg, cw, read_lane(), x, kc, vc, out);
  }
}

typedef CUresult (*EncodeFn)(CUtensorMap*, CUtensorMapDataType, cuuint32_t, void*, const cuuint64_t*, const cuuint64_t*,
                             const cuuint32_t*, const cuuint32_t*, CUtensorMapInterleave, CUtensorMapSwizzle,
                             CUtensorMapL2promotion, CUtensorMapFloatOOBfill);

void encode(EncodeFn fn, CUtensorMap* m, const void* p, int rank, const cuuint64_t* dims, const cuuint64_t* strides,
            const cuuint32_t* box) {
  const cuuint32_t es[5] = {1, 1, 1, 1, 1};
  fn(m, CU_TENSOR_MAP_DATA_TYPE_BFLOAT16, rank, const_cast<void*>(p), dims, strides, box, es, CU_TENSOR_MAP_INTERLEAVE_NONE,
     CU_TENSOR_MAP_SWIZZLE_128B, CU_TENSOR_MAP_L2_PROMOTION_L2_128B, CU_TENSOR_MAP_FLOAT_OOB_FILL_NONE);
}
void encode2d(EncodeFn fn, CUtensorMap* m, const void* p, uint64_t rows, uint64_t cols, uint32_t box_rows) {
  const cuuint64_t dims[2] = {cols, rows}, strides[1] = {cols * 2};
  const cuuint32_t box[2] = {64, box_rows};
  encode(fn, m, p, 2, dims, strides, box);
}

}

extern "C" void kernel_launch(void* const* d_in, const int* in_sizes, int n_in, void* d_out, int out_size) {
  (void)in_sizes; (void)n_in; (void)out_size;
  void* fnp = nullptr;
  cudaDriverEntryPointQueryResult qr;
  cudaGetDriverEntryPoint("cuTensorMapEncodeTiled", &fnp, cudaEnableDefault, &qr);
  EncodeFn fn = (EncodeFn)fnp;
  CUtensorMap tmWq, tmWo, tmG, tmU, tmD, tmX, tmX16, tmWq96, tmX64;
  encode2d(fn, &tmX64, d_in[0], SEQ, DM, 64);
  encode2d(fn, &tmWq96, d_in[3], DM, 4096, 96);
  encode2d(fn, &tmX16, d_in[0], SEQ, DM, 16);
  KvMaps tmKV;
  for (int i = 0; i < 4; i++) encode2d(fn, &tmKV.m[i], d_in[1 + (i & 1)], 16 * SEQ, DH, i < 2 ? 112 : 96);
  encode2d(fn, &tmWq, d_in[3], DM, 4096, 64);
  {
    const cuuint64_t dims[3] = {64, SEQ, 9}, strides[2] = {DM * 2, 128};
    const cuuint32_t box[3] = {64, 64, 3};
    encode(fn, &tmX, d_in[0], 3, dims, strides, box);
  }
  encode2d(fn, &tmWo, d_in[4], 4096, DM, 128);
  encode2d(fn, &tmG, d_in[7], DM, FF, 192);
  encode2d(fn, &tmU, d_in[8], DM, FF, 192);
  encode2d(fn, &tmD, d_in[9], FF, DM, 192);
  cudaFuncSetAttribute(fused_kernel, cudaFuncAttributeMaxDynamicSharedMemorySize, SM_TOTAL);
  void* scratch = nullptr;
  cudaGetSymbolAddress(&scratch, g_scratch);
  fused_kernel<<<N_CTA, THREADS, SM_TOTAL>>>((const __nv_bfloat16*)d_in[0], (const __nv_bfloat16*)d_in[6], (const __nv_bfloat16*)d_in[1],
                                            (const __nv_bfloat16*)d_in[2], (__nv_bfloat16*)d_out, (Scratch*)scratch, tmX, tmWq, tmKV,
                                            tmWo, tmG, tmU, tmD, tmX16, tmWq96, tmX64);
}
```

```cpp
#include <cuda_runtime.h>
#include <cuda_bf16.h>
#include <cuda.h>
#include <stdint.h>

#define X_PFW 1
#define X_SPLIT 38
#define X_SPLITA 36
#define X_SPLITS 32
#define X_SPLITSA 30
#define X_PA 8
#define X_PG 4
#define X_E0 10
#define X_F2 10
#define X_LD 0
#define X_LN 0
#define X_WAKE 31
#define X_PFX 1
#define X_F1 0
#define X_BF2 1
#define X_SQI 4
#define X_SQS 300
#define X_ORD 3
#define X_NS 4
namespace {

constexpr int SEQ = 2048, DM = 576, DH = 128, FF = 4608, TOPC = 8;
constexpr int N_ATT_CTA = 128, N_CTA = 132;
constexpr int THREADS = 384;

constexpr uint32_t SM_RING = 0;
constexpr uint32_t STAGE = 32768;
constexpr uint32_t SM_SLOT = 131072;
constexpr uint32_t FSTAGE = 24576;
constexpr uint32_t SM_XSEL = 196608;
constexpr uint32_t SM_H = 205824;
constexpr uint32_t SM_MISC = 229376;
constexpr uint32_t SM_FULL = SM_MISC, SM_EMPTY = SM_MISC + 32, SM_FFULL = SM_MISC + 64, SM_BAR_MISC = SM_MISC + 128,
                   SM_COLD = SM_MISC + 136, SM_TAG = SM_MISC + 144, SM_BAR_W = SM_MISC + 152, SM_ONES = SM_MISC + 160,
                   SM_BAR_Q = SM_MISC + 176, SM_XFULL = SM_MISC + 192, SM_BAR_XG = SM_MISC + 304, SM_BAR_SQ = SM_MISC + 312,
                   SM_STATS = SM_MISC + 320, SM_FEMPTY = SM_MISC + 1344, SM_RAW = SM_FEMPTY, SM_WR = SM_MISC + 1408, SM_TOPK = SM_WR;
constexpr uint32_t SM_TOTAL = SM_MISC + 2560;
constexpr uint32_t SM_X = SM_MISC - 147456;

constexpr int BAR_GATE = 6, BAR_HELPER = 7, BAR_OA = 8, BAR_XREL = 13, BAR_QS = 9, BAR_QF = 11;
constexpr int NST_Q = 18, NST_KV = 76, NST_O = 18;
constexpr float SM_SCALE_LOG2 = 0.08838834764831845f * 1.4426950408889634f;

struct Scratch {
  uint4 part[16 * 64 * 2 * 4 * 128];
  uint4 gate[N_ATT_CTA * 1152];
  uint4 q[16 * 8 * 2 * 512];
  uint2 sq[SEQ];
  uint4 stats[SEQ];
  float ypart[4 * TOPC * DM];
  int2 sel[16];
  unsigned launch[160];
  unsigned pad0, ycnt, pad[30];
  unsigned qflag[128];
};
__device__ __align__(1024) Scratch g_scratch;

__device__ __forceinline__ void prof(int, int, int = 0) {}

#define TS(id) {}
#define TS_DUMP() {}
#define TSH(k) {}
#define TS4(k) {}
#define TSP(k) {}
#define TS1(id) TS(id)
#define TS2(k) {}
#define TS3(k) {}

__device__ __forceinline__ uint32_t smem_u32(const void* p) { return (uint32_t)__cvta_generic_to_shared(p); }
__device__ __forceinline__ void mbar_init(uint32_t bar, uint32_t cnt) {
  asm volatile("mbarrier.init.shared::cta.b64 [%0], %1;" ::"r"(bar), "r"(cnt) : "memory");
}
__device__ __forceinline__ void mbar_expect_tx(uint32_t bar, uint32_t bytes) {
  asm volatile("mbarrier.arrive.expect_tx.shared::cta.b64 _, [%0], %1;" ::"r"(bar), "r"(bytes) : "memory");
}
__device__ __forceinline__ void mbar_arrive(uint32_t bar) {
  asm volatile("mbarrier.arrive.shared::cta.b64 _, [%0];" ::"r"(bar) : "memory");
}
__device__ __forceinline__ void mbar_arrive_cluster(uint32_t bar_cluster_addr, bool pred) {
  asm volatile("{\n.reg .pred p;\nsetp.ne.u32 p, %1, 0;\n@p mbarrier.arrive.shared::cluster.b64 _, [%0];\n}"
               ::"r"(bar_cluster_addr), "r"((uint32_t)pred) : "memory");
}
template <int ID>
__device__ __forceinline__ void mbar_arrive_cluster_now(uint32_t bar_cluster_addr, bool pred) {
  asm volatile("{\n.reg .pred p, q;\nsetp.ne.u32 p, %1, 0;\nsetp.eq.u32 q, %2, %3;\n"
               "ARR_LOOP:\n@p mbarrier.arrive.shared::cluster.b64 _, [%0];\n@q bra.uni ARR_LOOP;\n}"
               ::"r"(bar_cluster_addr), "r"((uint32_t)pred), "r"(blockIdx.y), "n"(ID) : "memory");
}
__device__ __forceinline__ void block_fence(int id) {
  asm volatile("{\n.reg .pred q;\nsetp.eq.u32 q, %0, %1;\nBF_LOOP:\n@q st.volatile.shared.u32 [%0], %0;\n@q bra.uni BF_LOOP;\n}"
               ::"r"(blockIdx.y), "r"(id) : "memory");
}
__device__ __forceinline__ void mbar_wait(uint32_t bar, uint32_t parity) {
  asm volatile("{\n.reg .pred p, q;\n.reg .u32 n;\nmov.u32 n, 0;\n"
               "WAIT_LOOP:\nmbarrier.try_wait.parity.shared::cta.b64 p, [%0], %1;\n"
               "add.u32 n, n, 1;\nsetp.lt.u32 q, n, 4194304;\nand.pred q, q, !p;\n@q bra WAIT_LOOP;\n}"
               ::"r"(bar), "r"(parity) : "memory");
}
__device__ __forceinline__ uint32_t mapa(uint32_t addr, uint32_t rank) {
  uint32_t r;
  asm volatile("mapa.shared::cluster.u32 %0, %1, %2;" : "=r"(r) : "r"(addr), "r"(rank));
  return r;
}
__device__ __forceinline__ void cluster_arrive() { asm volatile("barrier.cluster.arrive.relaxed.aligned;" ::: "memory"); }
__device__ __forceinline__ bool elect_one() {
  uint32_t p;
  asm volatile("{\n.reg .pred p;\nelect.sync _|p, 0xffffffff;\nselp.u32 %0, 1, 0, p;\n}" : "=r"(p));
  return p;
}
__device__ __forceinline__ int read_lane() { return threadIdx.x & 31; }
__device__ __forceinline__ int fresh_lane() {
  int l;
  asm volatile("mov.u32 %0, %%laneid;" : "=r"(l));
  return l;
}
template <class T> __device__ __forceinline__ T* at(T* p, uint32_t bytes) {
  asm("" : "+r"(bytes));
  return (T*)((const char*)p + bytes);
}
__device__ __forceinline__ void cluster_wait() { asm volatile("barrier.cluster.wait.acquire.aligned;" ::: "memory"); }
__device__ __forceinline__ void bar_sync(int id, int n) { asm volatile("barrier.cta.sync %0, %1;" ::"r"(id), "r"(n) : "memory"); }
__device__ __forceinline__ void bar_arrive(int id, int n) { asm volatile("barrier.cta.arrive %0, %1;" ::"r"(id), "r"(n) : "memory"); }

__device__ __forceinline__ uint64_t policy_evict_first() {
  uint64_t p;
  asm("createpolicy.fractional.L2::evict_first.b64 %0, 1.0;" : "=l"(p));
  return p;
}
__device__ __forceinline__ void tma2d_mc(uint32_t dst, const CUtensorMap* tm, int c0, int c1, uint32_t bar, uint64_t pol) {
  asm volatile("cp.async.bulk.tensor.2d.shared::cluster.global.mbarrier::complete_tx::bytes.multicast::cluster.L2::cache_hint"
               " [%0], [%1, {%2, %3}], [%4], %5, %6;"
               ::"r"(dst), "l"(tm), "r"(c0), "r"(c1), "r"(bar), "h"((uint16_t)3), "l"(pol) : "memory");
}
__device__ __forceinline__ void tma3d(uint32_t dst, const CUtensorMap* tm, int c1, int c2, uint32_t bar) {
  asm volatile("cp.async.bulk.tensor.3d.shared::cluster.global.mbarrier::complete_tx::bytes [%0], [%1, {%2, %3, %4}], [%5];"
               ::"r"(dst), "l"(tm), "r"(0), "r"(c1), "r"(c2), "r"(bar) : "memory");
}
__device__ __forceinline__ void tma2d(uint32_t dst, const CUtensorMap* tm, int c0, int c1, uint32_t bar) {
  asm volatile("cp.async.bulk.tensor.2d.shared::cluster.global.mbarrier::complete_tx::bytes [%0], [%1, {%2, %3}], [%4];"
               ::"r"(dst), "l"(tm), "r"(c0), "r"(c1), "r"(bar) : "memory");
}
__device__ __forceinline__ void tma2d_stream(uint32_t dst, const CUtensorMap* tm, int c0, int c1, uint32_t bar) {
  asm volatile("{\n.reg .b64 pol;\ncreatepolicy.fractional.L2::evict_first.b64 pol, 1.0;\n"
               "cp.async.bulk.tensor.2d.shared::cluster.global.mbarrier::complete_tx::bytes.L2::cache_hint [%0], [%1, {%2, %3}], [%4], pol;\n}"
               ::"r"(dst), "l"(tm), "r"(c0), "r"(c1), "r"(bar) : "memory");
}
__device__ __forceinline__ void bulk_load(uint32_t dst, const void* src, uint32_t bytes, uint32_t bar) {
  asm volatile("cp.async.bulk.shared::cluster.global.mbarrier::complete_tx::bytes [%0], [%1], %2, [%3];"
               ::"r"(dst), "l"(src), "r"(bytes), "r"(bar) : "memory");
}
__device__ __forceinline__ void tma2d_prefetch(const CUtensorMap* tm, int c0, int c1) {
  asm volatile("cp.async.bulk.prefetch.tensor.2d.L2.global [%0, {%1, %2}];" ::"l"(tm), "r"(c0), "r"(c1) : "memory");
}
__device__ __forceinline__ void prefetch_tmap(const CUtensorMap* tm) {
  asm volatile("prefetch.tensormap [%0];" ::"l"(tm) : "memory");
}

__device__ __forceinline__ void wg_fence() { asm volatile("wgmma.fence.sync.aligned;" ::: "memory"); }
__device__ __forceinline__ void wg_commit() { asm volatile("wgmma.commit_group.sync.aligned;" ::: "memory"); }
template <int N> __device__ __forceinline__ void wg_wait() { asm volatile("wgmma.wait_group.sync.aligned %0;" ::"n"(N) : "memory"); }

__device__ __forceinline__ uint64_t mkdesc(uint32_t addr, uint32_t lbo_bytes) {
  return (uint64_t)(((addr & 0x3FFFF) >> 4) | ((lbo_bytes >> 4) << 16)) | ((uint64_t)0x40000040u << 32);
}
__device__ __forceinline__ uint64_t mkdesc_q(uint32_t addr) {
  return (uint64_t)(((addr & 0x3FFFF) >> 4) | (64u << 16)) | ((uint64_t)8 << 32);
}
template <int N> __device__ __forceinline__ void pin(float (&a)[N]) {
#pragma unroll
  for (int i = 0; i < N; i++) asm volatile("" : "+f"(a[i])::"memory");
}
template <int N> __device__ __forceinline__ void kill(float (&a)[N]) {
#pragma unroll
  for (int i = 0; i < N; i++) asm volatile("" : "=f"(a[i]));
}
template <int N> __device__ __forceinline__ void pin(uint32_t (&a)[N]) {
#pragma unroll
  for (int i = 0; i < N; i++) asm volatile("" : "+r"(a[i])::"memory");
}

#define F8(d, o) "+f"(d[o]), "+f"(d[o + 1]), "+f"(d[o + 2]), "+f"(d[o + 3]), "+f"(d[o + 4]), "+f"(d[o + 5]), "+f"(d[o + 6]), "+f"(d[o + 7])
#define R32A "%0, %1, %2, %3, %4, %5, %6, %7, %8, %9, %10, %11, %12, %13, %14, %15, %16, %17, %18, %19, %20, %21, %22, %23, %24, %25, %26, %27, %28, %29, %30, %31"
#define R32B "%32, %33, %34, %35, %36, %37, %38, %39, %40, %41, %42, %43, %44, %45, %46, %47, %48, %49, %50, %51, %52, %53, %54, %55, %56, %57, %58, %59, %60, %61, %62, %63"

#define O8(d, o) "=f"(d[o]), "=f"(d[o + 1]), "=f"(d[o + 2]), "=f"(d[o + 3]), "=f"(d[o + 4]), "=f"(d[o + 5]), "=f"(d[o + 6]), "=f"(d[o + 7])

__device__ __forceinline__ void mma_n128t(float (&d)[64], uint32_t a0, uint32_t a1, uint32_t a2, uint32_t a3, uint64_t db, bool acc) {
  if (acc)
    asm volatile("wgmma.mma_async.sync.aligned.m64n128k16.f32.bf16.bf16 {" R32A ", " R32B "}, {%64, %65, %66, %67}, %68, 1, 1, 1, 1;\n"
                 : F8(d, 0), F8(d, 8), F8(d, 16), F8(d, 24), F8(d, 32), F8(d, 40), F8(d, 48), F8(d, 56)
                 : "r"(a0), "r"(a1), "r"(a2), "r"(a3), "l"(db));
  else
    asm volatile("wgmma.mma_async.sync.aligned.m64n128k16.f32.bf16.bf16 {" R32A ", " R32B "}, {%64, %65, %66, %67}, %68, 0, 1, 1, 1;\n"
                 : O8(d, 0), O8(d, 8), O8(d, 16), O8(d, 24), O8(d, 32), O8(d, 40), O8(d, 48), O8(d, 56)
                 : "r"(a0), "r"(a1), "r"(a2), "r"(a3), "l"(db));
}
#define PV1(a0, a1, a2, a3, ob, acc) "add.s64 b, %92, " #ob ";\n" \
  "wgmma.mma_async.sync.aligned.m64n128k16.f32.bf16.bf16 {" R32A ", " R32B "}, {%" #a0 ", %" #a1 ", %" #a2 ", %" #a3 "}, b, " #acc ", 1, 1, 1;\n"
#define PV6 "wgmma.fence.sync.aligned;\n" PV1(64, 65, 66, 67, 0, p) PV1(68, 69, 70, 71, 128, 1) PV1(72, 73, 74, 75, 256, 1) \
  PV1(76, 77, 78, 79, 384, 1) PV1(80, 81, 82, 83, 512, 1) PV1(84, 85, 86, 87, 640, 1)
#define U4(a, o) "r"(a[o]), "r"(a[o + 1]), "r"(a[o + 2]), "r"(a[o + 3])
__device__ __forceinline__ void mma_pv(float (&d)[64], const uint32_t (&a)[28], uint64_t dv, bool acc, bool big) {
  asm volatile("{\n.reg .pred p, q;\n.reg .b64 b;\nsetp.ne.b32 p, %93, 0;\nsetp.eq.b32 q, %94, 0;\n@q bra.uni PV_SMALL;\n"
               PV6 PV1(88, 89, 90, 91, 768, 1) "wgmma.commit_group.sync.aligned;\nbra.uni PV_DONE;\n"
               "PV_SMALL:\n" PV6 "wgmma.commit_group.sync.aligned;\nPV_DONE:\n}\n"
               : F8(d, 0), F8(d, 8), F8(d, 16), F8(d, 24), F8(d, 32), F8(d, 40), F8(d, 48), F8(d, 56)
               : U4(a, 0), U4(a, 4), U4(a, 8), U4(a, 12), U4(a, 16), U4(a, 20), U4(a, 24), "l"(dv), "r"((int)acc), "r"((int)big) : "memory");
}
#define R48 R32A ", %32, %33, %34, %35, %36, %37, %38, %39, %40, %41, %42, %43, %44, %45, %46, %47"
#define R56 R48 ", %48, %49, %50, %51, %52, %53, %54, %55"
#define QK1(N, R, A, B, oa, ob, acc) "add.s64 a, " A ", " #oa ";\nadd.s64 b, " B ", " #ob ";\n" \
  "wgmma.mma_async.sync.aligned.m64n" #N "k16.f32.bf16.bf16 {" R "}, a, b, " #acc ", 1, 1, 0, 0;\n"
#define QK8(N, R, A, B) "{\n.reg .b64 a, b;\nwgmma.fence.sync.aligned;\n" QK1(N, R, A, B, 0, 0, 0) QK1(N, R, A, B, 128, 2, 1) \
  QK1(N, R, A, B, 256, 4, 1) QK1(N, R, A, B, 384, 6, 1) QK1(N, R, A, B, 512, 1024, 1) QK1(N, R, A, B, 640, 1026, 1) \
  QK1(N, R, A, B, 768, 1028, 1) QK1(N, R, A, B, 896, 1030, 1) "wgmma.commit_group.sync.aligned;\n}\n"
__device__ __forceinline__ void mma_qk(float (&d)[56], uint64_t dq, uint64_t dk) {
  asm volatile(QK8(112, R56, "%56", "%57")
               : O8(d, 0), O8(d, 8), O8(d, 16), O8(d, 24), O8(d, 32), O8(d, 40), O8(d, 48) : "l"(dq), "l"(dk) : "memory");
}
__device__ __forceinline__ void mma_qk(float (&d)[48], uint64_t dq, uint64_t dk) {
  asm volatile(QK8(96, R48, "%48", "%49")
               : O8(d, 0), O8(d, 8), O8(d, 16), O8(d, 24), O8(d, 32), O8(d, 40) : "l"(dq), "l"(dk) : "memory");
}
__device__ __forceinline__ void mma_n64t(float (&d)[32], uint32_t a0, uint32_t a1, uint32_t a2, uint32_t a3, uint64_t db, bool acc) {
  if (acc)
    asm volatile("wgmma.mma_async.sync.aligned.m64n64k16.f32.bf16.bf16 {" R32A "}, {%32, %33, %34, %35}, %36, 1, 1, 1, 1;\n"
                 : F8(d, 0), F8(d, 8), F8(d, 16), F8(d, 24) : "r"(a0), "r"(a1), "r"(a2), "r"(a3), "l"(db));
  else
    asm volatile("wgmma.mma_async.sync.aligned.m64n64k16.f32.bf16.bf16 {" R32A "}, {%32, %33, %34, %35}, %36, 0, 1, 1, 1;\n"
                 : O8(d, 0), O8(d, 8), O8(d, 16), O8(d, 24) : "r"(a0), "r"(a1), "r"(a2), "r"(a3), "l"(db));
}
__device__ __forceinline__ void mma_n64t_dyn(float (&d)[32], uint32_t a0, uint32_t a1, uint32_t a2, uint32_t a3, uint64_t db, int acc) {
  asm volatile("{\n.reg .pred p;\nsetp.ne.b32 p, %37, 0;\n"
               "wgmma.mma_async.sync.aligned.m64n64k16.f32.bf16.bf16 {" R32A "}, {%32, %33, %34, %35}, %36, p, 1, 1, 1;\n}\n"
               : F8(d, 0), F8(d, 8), F8(d, 16), F8(d, 24) : "r"(a0), "r"(a1), "r"(a2), "r"(a3), "l"(db), "r"(acc));
}
__device__ __forceinline__ void mma_n8(float (&d)[4], uint64_t da, uint64_t db, int acc) {
  asm volatile("{\n.reg .pred p;\nsetp.ne.b32 p, %6, 0;\n"
               "wgmma.mma_async.sync.aligned.m64n8k16.f32.bf16.bf16 {%0, %1, %2, %3}, %4, %5, p, 1, 1, 1, 0;\n}\n"
               : "+f"(d[0]), "+f"(d[1]), "+f"(d[2]), "+f"(d[3])
               : "l"(da), "l"(db), "r"(acc));
}
__device__ __forceinline__ void hmma_k16(float (&d)[4], uint32_t a0, uint32_t a1, uint32_t a2, uint32_t a3, uint32_t b0, uint32_t b1) {
  asm volatile("mma.sync.aligned.m16n8k16.row.col.f32.bf16.bf16.f32 {%0, %1, %2, %3}, {%4, %5, %6, %7}, {%8, %9}, {%0, %1, %2, %3};"
               : "+f"(d[0]), "+f"(d[1]), "+f"(d[2]), "+f"(d[3]) : "r"(a0), "r"(a1), "r"(a2), "r"(a3), "r"(b0), "r"(b1));
}

__device__ __forceinline__ uint32_t pack2(float lo, float hi) {
  uint32_t r;
  asm("cvt.rn.bf16x2.f32 %0, %1, %2;" : "=r"(r) : "f"(hi), "f"(lo));
  return r;
}
__device__ __forceinline__ float bf_lo(uint32_t w) { return __uint_as_float(w << 16); }
__device__ __forceinline__ float bf_hi(uint32_t w) { return __uint_as_float(w & 0xFFFF0000u); }
__device__ __forceinline__ float bfr(float x) { return __bfloat162float(__float2bfloat16_rn(x)); }
__device__ __forceinline__ uint32_t sub2(uint32_t a, uint32_t b) {
  uint32_t r;
  asm("sub.rn.bf16x2 %0, %1, %2;" : "=r"(r) : "r"(a), "r"(b));
  return r;
}
__device__ __forceinline__ uint32_t add2(uint32_t a, uint32_t b) {
  uint32_t r;
  asm("add.rn.bf16x2 %0, %1, %2;" : "=r"(r) : "r"(a), "r"(b));
  return r;
}
__device__ __forceinline__ uint32_t fma2(uint32_t a, uint32_t b, uint32_t c) {
  uint32_t r;
  asm("fma.rn.bf16x2 %0, %1, %2, %3;" : "=r"(r) : "r"(a), "r"(b), "r"(c));
  return r;
}
__device__ __forceinline__ float ex2(float x) {
  float r;
  asm("ex2.approx.ftz.f32 %0, %1;" : "=f"(r) : "f"(x));
  return r;
}
__device__ __forceinline__ float rcp(float x) {
  float r;
  asm("rcp.approx.ftz.f32 %0, %1;" : "=f"(r) : "f"(x));
  return r;
}
__device__ __forceinline__ float silu_f(float t) { return t * rcp(1.0f + ex2(-1.4426950408889634f * t)); }
__device__ __forceinline__ void lds128(uint32_t a, uint32_t& x, uint32_t& y, uint32_t& z, uint32_t& w) {
  asm volatile("ld.shared.v4.u32 {%0, %1, %2, %3}, [%4];" : "=r"(x), "=r"(y), "=r"(z), "=r"(w) : "r"(a) : "memory");
}
__device__ __forceinline__ void ldsm4(uint32_t a, uint32_t& x, uint32_t& y, uint32_t& z, uint32_t& w) {
  asm volatile("ldmatrix.sync.aligned.m8n8.x4.shared.b16 {%0, %1, %2, %3}, [%4];" : "=r"(x), "=r"(y), "=r"(z), "=r"(w) : "r"(a) : "memory");
}
constexpr uint32_t TAG = 0x10000;
__device__ __forceinline__ void st_gran(uint4* p, uint32_t x, uint32_t y, uint32_t z, uint32_t w) {
  asm volatile("st.relaxed.gpu.global.v4.b32 [%0], {%1, %2, %3, %4};" ::"l"(p), "r"(x), "r"(y), "r"(z), "r"(w) : "memory");
}
__device__ __forceinline__ void ld_gran(const uint4* p, uint32_t& x, uint32_t& y, uint32_t& z, uint32_t& w) {
  asm volatile("ld.relaxed.gpu.global.v4.b32 {%0, %1, %2, %3}, [%4];" : "=r"(x), "=r"(y), "=r"(z), "=r"(w) : "l"(p) : "memory");
}
__device__ __forceinline__ void stsm4(uint32_t a, uint32_t x, uint32_t y, uint32_t z, uint32_t w) {
  asm volatile("stmatrix.sync.aligned.m8n8.x4.shared.b16 [%0], {%1, %2, %3, %4};" ::"r"(a), "r"(x), "r"(y), "r"(z), "r"(w) : "memory");
}
__device__ __forceinline__ void cp16(uint32_t dst, const void* src) {
  asm volatile("cp.async.cg.shared.global [%0], [%1], 16;" ::"r"(dst), "l"(src) : "memory");
}
__device__ __forceinline__ void cp_wait_all() { asm volatile("cp.async.wait_all;" ::: "memory"); }
__device__ __forceinline__ void add_granules(float (&red)[32], const uint32_t (&g)[16]) {
#pragma unroll
  for (int i = 0; i < 16; i++) { red[2 * i] += bf_lo(g[i]); red[2 * i + 1] += bf_hi((i & 3) ? g[i] : g[i] & ~TAG); }
}
__device__ __forceinline__ bool granules_ok(const uint32_t (&g)[16], uint32_t tag) {
  uint32_t a, b;
  asm("lop3.b32 %0, %1, %2, %3, 0x7E;" : "=r"(a) : "r"(g[0]), "r"(g[4]), "r"(tag));
  asm("lop3.b32 %0, %1, %2, %3, 0x7E;" : "=r"(b) : "r"(g[8]), "r"(g[12]), "r"(tag));
  return __all_sync(0xffffffffu, ((a | b) & TAG) == 0);
}
__device__ __forceinline__ unsigned ld_acquire(const unsigned* p) {
  unsigned v;
  asm volatile("ld.acquire.gpu.global.u32 %0, [%1];" : "=r"(v) : "l"(p) : "memory");
  return v;
}
__device__ __forceinline__ unsigned atom_add_acq_rel(unsigned* p) {
  unsigned v;
  asm volatile("atom.acq_rel.gpu.global.add.u32 %0, [%1], 1;" : "=r"(v) : "l"(p) : "memory");
  return v;
}

template <int K0, int K1>
__device__ __forceinline__ void ln_fetch(uint32_t (&xa)[144], uint32_t boxes, uint32_t lo) {
#pragma unroll
  for (int k = K0; k < K1; k++) ldsm4(boxes + (k >> 2) * 8192 + (lo ^ ((k & 3) << 5)), xa[4 * k], xa[4 * k + 1], xa[4 * k + 2], xa[4 * k + 3]);
}
__device__ __forceinline__ void ln_fetch_b(uint32_t (&b)[24], uint32_t& wb, uint32_t ws) {
#pragma unroll
  for (int j = 0; j < 6; j++, wb += ws) ldsm4(wb, b[4 * j], b[4 * j + 1], b[4 * j + 2], b[4 * j + 3]);
}
template <int K0, int K1>
__device__ __forceinline__ void ln_sums(const uint32_t (&xa)[144], float (&sm)[X_NS][4], const uint32_t (&b)[24]) {
#pragma unroll
  for (int k = K0; k < K1; k++)
    hmma_k16(sm[k % X_NS], xa[4 * k], xa[4 * k + 1], xa[4 * k + 2], xa[4 * k + 3], b[2 * (k % 12)], b[2 * (k % 12) + 1]);
}
__device__ __forceinline__ void ln_row(float sum, float sq, float& mean_b, float& rstd) {
  const float mean = sum * (1.0f / DM);
  const uint32_t mv = pack2(mean, fmaxf(sq * (1.0f / DM) - mean * mean, 0.0f));
  mean_b = bf_lo(mv);
  float sd;
  asm("sqrt.approx.f32 %0, %1;" : "=f"(sd) : "f"(bf_lo(pack2(bf_hi(mv) + 1e-5f, 0.f))));
  rstd = rcp(bf_lo(pack2(sd, 0.f)));
}

template <bool ROUTED>
__device__ __forceinline__ uint32_t gate2(uint32_t xc, float rstd, float2 upd = make_float2(0.f, 0.f)) {
  uint32_t t = pack2(bf_lo(xc) * rstd, bf_hi(xc) * rstd);
  if (ROUTED) t = pack2(bf_lo(t) + upd.x, bf_hi(t) + upd.y);
  return pack2(silu_f(bf_lo(t)), silu_f(bf_hi(t)));
}

template <int V> struct IC { static constexpr int value = V; };

struct Ctx {
  uint32_t sb;
  uint8_t* sp;
  uint32_t rank;
  Scratch* g;
};

__device__ __forceinline__ bool acquire(const Ctx& cx, uint32_t r, uint32_t n, uint32_t bytes) {
  mbar_wait(cx.sb + SM_EMPTY + 8 * r, (n ^ (r >> 1) ^ 1) & 1);
  __syncwarp();
  const bool e = elect_one();
  if (e) mbar_expect_tx(cx.sb + SM_FULL + 8 * r, bytes);
  return e;
}
__device__ __forceinline__ void load_wq(const Ctx& cx, const CUtensorMap* tmWq, int st, int i, int n0, uint64_t pol) {
  const uint32_t r = st & 3, dst = cx.sb + SM_RING + r * STAGE + cx.rank * 16384, bar = cx.sb + SM_FULL + 8 * r;
  const int k0 = i < 3 ? 128 * i : 128 * i - 64;
  if (acquire(cx, r, st >> 2, i == 2 ? 16384 : 32768)) {
    tma2d_mc(dst, tmWq, n0, k0, bar, pol);
    if (i != 2) tma2d_mc(dst + 8192, tmWq, n0, k0 + 64, bar, pol);
  }
}
__device__ __forceinline__ void attn_producer(const Ctx& cx, int qb, int hs, const CUtensorMap* tmKV, const CUtensorMap* tmWq,
                                              const CUtensorMap* tmWq96, const CUtensorMap* tmWo) {
  const uint32_t full = cx.sb + SM_FULL, ring = cx.sb + SM_RING + cx.rank * 16384;
  const uint64_t last_use = policy_evict_first();
  int st = 0;
#pragma unroll 1
  for (int p = 0; p < 4; p++) {
#pragma unroll 1
    for (int i = 0; i < (p == 2 ? 3 : 5); i++, st++) {
      if (p == 2) {
        if (acquire(cx, st & 3, st >> 2, 24576))
          tma2d_mc(cx.sb + SM_RING + (st & 3) * STAGE + cx.rank * 12288, tmWq96, (hs * 4 + 3) * DH, 192 * i + 96 * cx.rank, full + 8 * (st & 3), last_use);
      } else {
        if (st > 1) load_wq(cx, tmWq, st, i, (hs * 4 + (p ^ (p >> 1))) * DH + cx.rank * 64, last_use);
      }
      if (st == 1 || st == 2) TSP(72 + st)
      if (st == X_PFW) {
#pragma unroll 1
        for (int b = qb < 8; b < 5 - (qb >> 3); b++)
          if (elect_one()) tma2d_prefetch(tmWq, hs * 512 + (b < 4 ? (b ^ (b >> 1)) * DH + (qb & 1) * 64 : qb * 64), b < 4 ? (qb >> 1) * 64 : 512);
      }
      if (st == 8 && qb < 8 && elect_one()) tma2d_prefetch(tmKV + ((qb >> 1) & 1), cx.rank * 64, hs * 2 * SEQ + (qb >> 2) * 96);
    }
  }
  uint32_t r = 2, n = 4;
  int row = hs * 2 * SEQ, rows = 96;
  const CUtensorMap* tm = tmKV + 2;
#pragma unroll 1
  for (int u = 0; u < NST_KV; u++) {
    if (acquire(cx, r, n, rows * 256)) {
      tma2d_mc(ring + r * STAGE, tm, cx.rank * 64, row, full + 8 * r, last_use);
      if (((u ^ (qb >> 1)) & 7) == 0 && u < NST_KV - 4) tma2d_prefetch(tmKV + (u & 1), cx.rank * 64, row + 208);
      if ((unsigned)(u - 32) < 36 && (u & 15) == qb) tma2d_prefetch(tmWo, ((u - 32) >> 2) * 64, hs * 512 + (u & 3) * 128);
    }
    if (++r == 4) { r = 1; n++; }
    if (u & 1) row += rows;
    const bool big = (unsigned)(u - 9) < 56;
    rows = big ? 112 : 96;
    tm = tmKV + (~u & 1) + (big ? 0 : 2);
  }
#pragma unroll 1
  for (int u = 0; u < NST_O; u++) {
    const int s = u >> 1;
    const int blk = s == 0 ? 8 : ((hs + s) & 7);
    r = (0x87 >> (2 * (u & 3))) & 3;
    if (acquire(cx, r, (u >> 2) ^ ~u, 32768))
      tma2d_mc(ring + r * STAGE, tmWo, blk * 64, hs * 512 + ((u & 1) + cx.rank * 2) * 128, full + 8 * r, last_use);
  }
}

__device__ __forceinline__ void sq_publish(const Ctx& cx, int qb, int hs, int j, int lane) {
  if (j == 2 && lane == 0) {
    const unsigned e = cx.g->launch[hs * 16 + qb]++;
    *(uint2*)(cx.sp + SM_TAG) = make_uint2((~e & 1) * TAG, e);
  }
  const int row = (hs & 3) * 16 + (lane >> 1);
  uint32_t a = cx.sb + SM_X + (hs >> 2) * 73728 + j * 8192 + row * 128 + (((lane & 1) ^ (row & 7)) << 4);
  float s0 = 0.f, s1 = 0.f;
#pragma unroll 1
  for (int b = 0; b < 6; b++) {
    if (b == (hs < 4 ? 4 : 0)) {
      const int n = 224 + (__float_as_uint(s1) & blockIdx.y);
      if (j == 1) {
        bar_sync(BAR_XREL, n);
        if (lane < 4) asm volatile("mbarrier.arrive.shared::cluster.b64 _, [%0], 2;" ::"r"(mapa(cx.sb + SM_EMPTY + 16 + 8 * (lane >> 1), lane & 1)) : "memory");
      } else {
        bar_arrive(BAR_XREL, n);
      }
      __syncwarp();
      if (hs == 8) return;
    }
    if (!(b & 1)) mbar_wait(cx.sb + SM_XFULL + 32 * (hs >> 2) + 4 * b, 0);
    uint32_t v[8];
    lds128(a, v[0], v[1], v[2], v[3]);
    lds128(a ^ 32, v[4], v[5], v[6], v[7]);
    a = (a ^ 64) + (b & 1) * 24576;
#pragma unroll
    for (int i = 0; i < 8; i++) { s0 = fmaf(bf_lo(v[i]), bf_lo(v[i]), s0); s1 = fmaf(bf_hi(v[i]), bf_hi(v[i]), s1); }
  }
  s0 += s1;
  s0 += __shfl_xor_sync(0xffffffffu, s0, 1);
  float* part = (float*)(cx.sp + SM_STATS) + (lane >> 1) * 2;
  if (j < 2) {
    part[32 * j] = s0;
    bar_arrive(BAR_HELPER, 96);
  } else {
    bar_sync(BAR_HELPER, 96);
    TSP(68)
    if (!(lane & 1))
      asm volatile("st.relaxed.gpu.global.v2.b32 [%0], {%1, %2};" ::"l"(cx.g->sq + qb * 128 + hs * 16 + (lane >> 1)),
                   "r"(__float_as_uint((part[0] + part[32]) + s0)), "r"(*(const uint32_t*)(cx.sp + SM_TAG + 4) + 1) : "memory");
  }
}
__device__ __forceinline__ void sq_collect(const Ctx& cx, int qb, int lane) {
  const uint32_t e1 = *(const uint32_t*)(cx.sp + SM_TAG + 4) + 1;
#pragma unroll 1
  for (int n = 0; n < (1 << 16); n++) {
    __nanosleep(X_SQS);
    uint32_t bad = 0;
#pragma unroll
    for (int i = 0; i < 2; i++) {
      uint32_t a, t0, b, t1;
      ld_gran((const uint4*)at(cx.g->sq, qb * 1024 + lane * 16) + i * 32, a, t0, b, t1);
      *(uint32_t*)(cx.sp + SM_STATS + (i * 32 + lane) * 16 + 4) = a;
      *(uint32_t*)(cx.sp + SM_STATS + (i * 32 + lane) * 16 + 12) = b;
      bad |= (t0 ^ e1) | (t1 ^ e1);
    }
    if (__all_sync(0xffffffffu, bad == 0)) break;
  }
  __syncwarp();
  if (lane == 0) mbar_arrive(cx.sb + SM_BAR_SQ);
  TSP(69)
}
__device__ __forceinline__ void attn_gate(const Ctx& cx, int qb, int hs, int j, int t, const __nv_bfloat16* x) {
  const uint4* xp = (const uint4*)(x + qb * 128 * DM) + (t >> 3) * 72 + hs * 8 + (t & 7);
  uint4 nx = *xp;
  float wsum = 0.f;
  if (j == 0) {
    mbar_wait(cx.sb + SM_BAR_W, 0);
#pragma unroll 3
    for (int i = 0; i < 9; i++) {
      const uint32_t w = *(const uint32_t*)(cx.sp + SM_WR + i * 128 + t * 4);
      wsum += bf_lo(w) + bf_hi(w);
    }
#pragma unroll
    for (int i = 1; i < 32; i *= 2) wsum += __shfl_xor_sync(0xffffffffu, wsum, i);
  }
  bar_sync(BAR_GATE, 352);
  if (t < 16) {
    const float2 st = *(const float2*)(cx.sp + SM_STATS + 8 * (hs * 16 + t));
    const int row = qb * 128 + hs * 16 + t;
    const uint32_t b = pack2(0.f, fmaf(-st.x, wsum, *(const float*)(cx.sp + SM_RAW + 4 * t)) * st.y);
    st_gran(at(cx.g->stats, row * 16), __float_as_uint(st.x), __float_as_uint(st.y), (b ^ ((int)b < 0 ? 0xFFFF0000u : 0x80000000u)) | (0xFFFF - row),
            *(const uint32_t*)(cx.sp + SM_TAG + 4) + 1);
  }
  __syncwarp();
  uint32_t sa = cx.sb + SM_STATS + (t & ~7);
  uint4* gp = cx.g->gate + blockIdx.x * 1152 + (t ^ ((t >> 3) & 7));
  const int cross = t < 64 ? 10 : 9;
#pragma unroll 1
  for (int i = 0; i < 12; i++) {
    float2 st;
    asm volatile("ld.shared.v2.f32 {%0, %1}, [%2];" : "=f"(st.x), "=f"(st.y) : "r"(sa));
    const uint32_t mm = pack2(st.x, st.x);
    const uint4 v = make_uint4(sub2(nx.x, mm), sub2(nx.y, mm), sub2(nx.z, mm), sub2(nx.w, mm));
    xp += 12 * 72;
    sa += 96;
    if (i == cross) { xp += (hs * 16 - 128) * 72 + 64 - hs * 8; sa += (hs * 16 - 128) * 8; }
    if (i < 11) nx = *xp;
    *gp = make_uint4(gate2<false>(v.x, st.y), gate2<false>(v.y, st.y), gate2<false>(v.z, st.y), gate2<false>(v.w, st.y));
    gp = (uint4*)((size_t)(gp + 96) ^ 64);
  }
}

constexpr uint32_t SM_XO = SM_SLOT, SM_GO = SM_SLOT + STAGE, SM_P8 = SM_SLOT + 2 * STAGE;
__device__ __forceinline__ void attn_helper(const Ctx& cx, int qb, int hs, int lane, const CUtensorMap* tmX16) {
  const unsigned e = *(const uint32_t*)(cx.sp + SM_TAG + 4);
  bar_sync(BAR_HELPER, 64);
  bool todo = lane < 2;
#pragma unroll 1
  for (int n = 0; __any_sync(0xffffffffu, todo); n++) {
    if (todo && (ld_acquire(at(cx.g->qflag, ((qb * 4 + (hs >> 1)) * 2 + lane) * 4)) == e + 1 || n == (1 << 16))) {
      asm volatile("fence.proxy.async.global;" ::: "memory");
      mbar_expect_tx(cx.sb + SM_BAR_Q + 8 * lane, 8192);
      bulk_load(cx.sb + SM_SLOT + 2 * STAGE + lane * 16384 + 8192, at(cx.g->q, ((qb * 8 + hs) * 2 + lane) * 8192), 8192, cx.sb + SM_BAR_Q + 8 * lane);
      todo = false;
    }
  }
  const uint32_t tag = (~e & 1) * TAG;
  const uint4* src = cx.g->part + (size_t)((qb * 64 + 56) * 2 + (hs >> 2)) * 4 * 128 + (hs & 3) * 32 + lane;
  const uint32_t stg = cx.sb + SM_P8 + lane * 16;
  bar_sync(BAR_OA, 352);
  asm volatile("fence.proxy.async.global;" ::: "memory");
  if (lane == 0) {
    mbar_expect_tx(cx.sb + SM_BAR_MISC, 2 * 18432);
    bulk_load(cx.sb + SM_GO, cx.g->gate + blockIdx.x * 1152, 18432, cx.sb + SM_BAR_MISC);
#pragma unroll 1
    for (int i = 0; i < 9; i++)
      tma2d(cx.sb + SM_XO + i * 2048, tmX16, i < 8 ? hs * 64 : 512, qb * 128 + (i < 8 ? i : hs) * 16, cx.sb + SM_BAR_MISC);
  }
#pragma unroll 1
  for (int n = 0; n < (1 << 16); n++) {
    __nanosleep(n ? 500 : 2000);
    uint32_t a, b, d, t;
    ld_gran(src - lane + (lane & 7) * (2 * 4 * 128) + 3 * 128 + 31, a, b, d, t);
    if (__all_sync(0xffffffffu, (a & TAG) == tag)) break;
  }
  TSH(46)
#pragma unroll 1
  for (int n = 0; n < (1 << 16); n++) {
#pragma unroll 1
    for (int i = 0; i < 8; i++) {
#pragma unroll
      for (int g = 0; g < 4; g++) cp16(stg + (i * 4 + g) * 512, src + i * (2 * 4 * 128) + g * 128);
    }
    cp_wait_all();
    uint32_t bad = 0;
#pragma unroll 4
    for (int i = 0; i < 32; i++) bad |= *(const volatile uint32_t*)(cx.sp + SM_P8 + lane * 16 + i * 512) ^ tag;
    if (__all_sync(0xffffffffu, (bad & TAG) == 0)) break;
  }
  TSH(47)
#pragma unroll 1
  for (int n = 0; n < (1 << 16) && ld_acquire(&cx.g->ycnt) != 4 * (e + 1); n++) __nanosleep(200);
  const int2 sel = __ldcg(at(cx.g->sel, (lane & 7) * 8));
  const int lr = sel.x - qb * 128;
  uint32_t m = __ballot_sync(0xffffffffu, lane < 16 && ((lane & 8) ? (lr >> 4) == hs : (lr >> 7) == 0));
  mbar_wait(cx.sb + SM_BAR_MISC, 0);
#pragma unroll 1
  for (; m; m &= m - 1) {
    const int i = __ffs(m) - 1, row = __shfl_sync(0xffffffffu, lr, i);
    const float rs = __int_as_float(__shfl_sync(0xffffffffu, sel.y, i));
    const float* p = cx.g->ypart + (i & 7) * DM + (i < 8 ? hs * 64 : 512) + 2 * lane;
    const float2 a = __ldcg((const float2*)p), b = __ldcg((const float2*)(p + TOPC * DM)), c = __ldcg((const float2*)(p + 2 * TOPC * DM)),
                 d = __ldcg((const float2*)(p + 3 * TOPC * DM));
    const uint32_t y = pack2((a.x + b.x) + (c.x + d.x), (a.y + b.y) + (c.y + d.y));
    const uint32_t u = pack2(bf_lo(y) * rs, bf_hi(y) * rs);
    const float2 st = *(const float2*)(cx.sp + SM_STATS + 8 * row);
    const int o = (i < 8 ? row : 128 + (row & 15)) * 128 + ((lane * 4) ^ ((row & 7) << 4));
    *(uint32_t*)(cx.sp + SM_GO + o) = gate2<true>(sub2(*(const uint32_t*)(cx.sp + SM_XO + o), pack2(st.x, st.x)), st.y, make_float2(bf_lo(u), bf_hi(u)));
  }
  __syncwarp();
  if (lane == 0) mbar_arrive(cx.sb + SM_BAR_XG);
  TSH(48)
}
__device__ __forceinline__ void attn_finish8(const Ctx& cx, int qb, int hs, int hw, int lane, __nv_bfloat16* out) {
  bar_sync(BAR_GATE, 96);
#pragma unroll 1
  for (int g = hw; g < 4; g += 3) {
    float acc[8] = {0.f, 0.f, 0.f, 0.f, 0.f, 0.f, 0.f, 0.f};
#pragma unroll 2
    for (int sidx = 0; sidx < 8; sidx++) {
      uint32_t a, b, d, t;
      lds128(cx.sb + SM_P8 + lane * 16 + (sidx * 4 + g) * 512, a, b, d, t);
      acc[0] += bf_lo(a); acc[1] += bf_hi(a & ~TAG); acc[2] += bf_lo(b); acc[3] += bf_hi(b);
      acc[4] += bf_lo(d); acc[5] += bf_hi(d); acc[6] += bf_lo(t); acc[7] += bf_hi(t);
    }
#pragma unroll
    for (int j = 0; j < 4; j++) {
      const int o = (128 + (lane >> 2) + (j & 1) * 8) * 128 + (((2 * g + (j >> 1)) ^ (lane >> 2)) << 4) + (lane & 3) * 4;
      uint32_t* xp = (uint32_t*)(cx.sp + SM_XO + o);
      *xp = fma2(pack2(acc[2 * j], acc[2 * j + 1]), *(const uint32_t*)(cx.sp + SM_GO + o), *xp);
    }
  }
  bar_sync(BAR_GATE, 96);
#pragma unroll 1
  for (int ch = threadIdx.x - 32; ch < 128; ch += 96)
    *(uint4*)at(out, ((qb * 128 + hs * 16 + (ch >> 3)) * DM + 512 + (ch & 7) * 8) * 2) =
        *(const uint4*)(cx.sp + SM_XO + 16384 + (ch ^ ((ch >> 3) & 7)) * 16);
}

__device__ __forceinline__ void ffn_producer(const Ctx& cx, int f, const CUtensorMap* tmWq, const CUtensorMap* tmG,
                                             const CUtensorMap* tmU, const CUtensorMap* tmD) {
  uint64_t keep;
  asm("createpolicy.fractional.L2::evict_normal.b64 %0, 1.0;" : "=l"(keep));
  int st = 0;
#pragma unroll 1
  for (int p = 0; p < 16; p++) {
#pragma unroll 1
    for (int i = 0; i < 5; i++, st++) if (st > 1) load_wq(cx, tmWq, st, i, ((2 * (p & 3) + cx.rank) * 4 + 3) * DH + 64, keep);
  }
  const uint32_t full = cx.sb + SM_FFULL, empty = cx.sb + SM_FEMPTY;
  int pair = 0, u = 0;
#pragma unroll 1
  for (st = 0; st < 14 * 12; st++) {
    const uint32_t sl = st & 7;
    const int unit = pair * 2 + (u & 1), k = u >> 1, k3 = k >= 3 ? k - 3 : k;
    if (unit < 27) {
      mbar_wait(empty + 8 * sl, (st >> 3) & 1);
      __syncwarp();
      if (elect_one()) {
        mbar_expect_tx(full + 8 * sl, FSTAGE);
        if (pair < 9) tma2d_stream(cx.sb + sl * FSTAGE, k < 3 ? tmG : tmU, f * 1152 + unit * 64, k3 * 192, full + 8 * sl);
        else tma2d_stream(cx.sb + sl * FSTAGE, tmD, (unit - 18) * 64, f * 1152 + k * 192, full + 8 * sl);
      }
    }
    if (++u == 12) { u = 0; pair++; }
  }
}
__device__ __forceinline__ void load_x1(uint32_t dst, const CUtensorMap* tmX64, int row, int box, int n, uint32_t bar) {
  mbar_expect_tx(bar, n * 8192);
#pragma unroll 1
  for (int i = 0; i < n; i++) tma2d(dst + i * 8192, tmX64, (box + i) * 64, row, bar);
}
__device__ __forceinline__ void ffn_publish(const Ctx& cx, int f, int w, int lane, const CUtensorMap* tmX64) {
  const uint32_t xs = cx.sb + SM_SLOT + w * 49152, xf = cx.sb + SM_XFULL + w * 32;
#pragma unroll 1
  for (int n = 0; n < 16; n++) {
    const int p = n & 3, row = (f + (n & 12) + 4) * 128 + w * 64;
    if (n < 12 && p == 3) {
      bar_sync(BAR_QS + w, 160);
      if (lane == 0) load_x1(xs, tmX64, row, 4, 4, xf + 8);
      __syncwarp();
    }
    bar_sync(BAR_QS + w, 160);
    const uint32_t e1 = *(const uint32_t*)(cx.sp + SM_TAG + 4) + 1;
    if (lane == 0) {
#pragma unroll
      for (int i = 0; i < 2; i++)
        asm volatile("cp.async.bulk.global.shared::cta.bulk_group [%0], [%1], 8192;"
                     ::"l"(cx.g->q + (((f + (n & 12)) * 8 + 2 * p + i) * 2 + w) * 512), "r"(xs + 32768 + i * 8192) : "memory");
      asm volatile("cp.async.bulk.commit_group;" ::: "memory");
      asm volatile("cp.async.bulk.wait_group.read 0;" ::: "memory");
      if (n < 12 && (p == 0 || p == 3)) load_x1(xs + (p ? 32768 : 0), tmX64, row, p ? 8 : 0, p ? 1 : 4, xf + (p ? 16 : 0));
      asm volatile("cp.async.bulk.wait_group 0;\nfence.proxy.async.global;" ::: "memory");
      asm volatile("st.release.gpu.global.u32 [%0], %1;" ::"l"(&cx.g->qflag[((f + (n & 12)) * 4 + p) * 2 + w]), "r"(e1) : "memory");
    }
    __syncwarp();
    if (n < 12 && p == 1) {
#pragma unroll 1
      for (int i = 0, k = 0; i < 64 && k < (1 << 16); k++) {
        uint32_t m, r, z, t;
        ld_gran(cx.g->stats + row + i + lane, m, r, z, t);
        *(uint2*)(cx.sp + SM_STATS + 8 * (w * 64 + i + lane)) = make_uint2(m, r);
        if (__all_sync(0xffffffffu, t == e1)) i += 32;
      }
    }
    bar_arrive(BAR_QF + w, 160);
  }
}

__device__ __forceinline__ void ffn_consumer(const Ctx& cx, int f, int wg, int cw, int lane, const __nv_bfloat16* x) {
  const int r = lane >> 2, c = lane & 3, tid = cw * 32 + lane;
  const uint32_t full = cx.sb + SM_FFULL, empty = cx.sb + SM_FEMPTY;
  const bool signaller = (tid & 127) == 0;
  prof(wg, 8);
  const unsigned e = *(const uint32_t*)(cx.sp + SM_TAG + 4);
  uint32_t key[8];
#pragma unroll 1
  for (int n = 0; n < (1 << 16); n++) {
    uint32_t bad = 0;
#pragma unroll
    for (int i = 0; i < 8; i++) {
      uint32_t t;
      asm volatile("ld.relaxed.gpu.global.v2.b32 {%0, %1}, [%2];" : "=r"(key[i]), "=r"(t) : "l"(&cx.g->stats[i * 256 + tid].z) : "memory");
      bad |= t ^ (e + 1);
    }
    if (__all_sync(0xffffffffu, bad == 0)) break;
  }
  bar_sync(BAR_QF + wg, 160);
  bar_sync(3, 256);
  if (tid < 8) mbar_arrive(empty + 8 * tid);
  prof(wg, 9);
  int mysel = 0;
#pragma unroll 1
  for (int k = 0; k < TOPC; k++) {
    uint32_t m = key[0];
#pragma unroll
    for (int i = 1; i < 8; i++) m = max(m, key[i]);
    m = __reduce_max_sync(0xffffffffu, m);
    uint32_t* tk = (uint32_t*)(cx.sp + SM_TOPK) + (k & 1) * 8;
    if (lane == 0) tk[cw] = m;
    bar_sync(3, 256);
    m = __reduce_max_sync(0xffffffffu, tk[lane & 7]);
#pragma unroll
    for (int i = 0; i < 8; i++) if (key[i] == m) key[i] = 0;
    if (k == cw) mysel = 0xFFFF - (int)(m & 0xFFFF);
  }
  {
    const float4 st = __ldcg((const float4*)&cx.g->stats[mysel]);
    const uint32_t mm = pack2(st.x, st.x);
#pragma unroll 3
    for (int i = 0; i < 9; i++) {
      const uint32_t t = sub2(*(const uint32_t*)(x + (size_t)mysel * DM + i * 64 + 2 * lane), mm);
      *(uint32_t*)(cx.sp + SM_XSEL + i * 1024 + cw * 128 + (((lane >> 2) ^ cw) << 4) + (lane & 3) * 4) =
          pack2(bf_lo(t) * st.y, bf_hi(t) * st.y);
    }
    const uint32_t k = __float_as_uint(st.z);
    const float score = bf_hi(k ^ ((int)k < 0 ? 0x80000000u : 0xFFFF0000u));
    if (lane == 0 && f == 0) cx.g->sel[cw] = make_int2(mysel, __float_as_int(bfr(rcp(1.0f + ex2(-1.4426950408889634f * score)))));
  }
  asm volatile("fence.proxy.async.shared::cta;" ::: "memory");
  bar_sync(3, 256);
  prof(wg, 10);
  auto run = [&](float (&acc)[4], int st, int n, uint32_t b) {
#pragma unroll 1
    for (int u = 0; u < n; u++, st += 2, b += 3072) {
      const uint32_t sl = st & 7;
      mbar_wait(full + 8 * sl, (st >> 3) & 1);
      wg_fence();
      const uint64_t da = mkdesc(cx.sb + sl * FSTAGE, 16), db = mkdesc(b, 16);
#pragma unroll
      for (int k = 0; k < 12; k++) mma_n8(acc, da + k * 128, db + (k >> 2) * 64 + (k & 3) * 2, u > 0 || k > 0);
      wg_commit();
      wg_wait<0>();
      if (signaller) mbar_arrive(empty + 8 * sl);
    }
    pin(acc);
  };
#pragma unroll 1
  for (int unit = wg; unit < 27; unit += 2) {
    if (unit >> 1 == 9) {
      asm volatile("fence.proxy.async.shared::cta;" ::: "memory");
      bar_sync(3, 256);
      prof(wg, 11);
    }
    const bool gu = unit < 18;
    float a0[4], a1[4];
#pragma unroll 1
    for (int m = 0; m < (gu ? 2 : 1); m++) {
      run(a1, (unit >> 1) * 12 + m * 6 + wg, gu ? 3 : 6, cx.sb + (gu ? SM_XSEL : SM_H));
      if (m == 0) { a0[0] = a1[0]; a0[1] = a1[1]; a0[2] = a1[2]; a0[3] = a1[3]; }
    }
    float u0 = a1[0], u1 = a1[1];
#pragma unroll 1
    for (int i = 0; i < 2; i++) {
      const int fl = (cw & 3) * 16 + r + i * 8;
      if (gu) {
        const uint32_t g = pack2(a0[0], a0[1]);
        const uint32_t h = fma2(pack2(silu_f(bf_lo(g)), silu_f(bf_hi(g))), pack2(u0, u1), 0x80008000u);
        uint8_t* hp = cx.sp + SM_H + unit * 1024 + c * 256 + (fl & 7) * 2;
        *(uint16_t*)(hp + (((fl >> 3) ^ (2 * c)) << 4)) = (uint16_t)h;
        *(uint16_t*)(hp + 128 + (((fl >> 3) ^ (2 * c + 1)) << 4)) = (uint16_t)(h >> 16);
      } else {
        float* yp = cx.g->ypart + (f * TOPC + 2 * c) * DM + (unit - 18) * 64 + fl;
        yp[0] = u0;
        yp[DM] = u1;
      }
      a0[0] = a0[2]; a0[1] = a0[3]; u0 = a1[2]; u1 = a1[3];
    }
  }
  prof(wg, 12);
  bar_sync(3, 256);
  if (tid == 0) atom_add_acq_rel(&cx.g->ycnt);
  prof(wg, 13);
}

constexpr float SUM_HI = 1.8446744e19f, SUM_LO = 9.0949470e-13f;

template <int LO, int HI, int N>
__device__ __forceinline__ void softmax_exp(float (&s)[N]) {
#pragma unroll
  for (int i = LO; i < HI; i++) s[i] = ex2(s[i]);
}
__device__ __forceinline__ void sum_tree(const uint32_t (&pf)[28], bool big, uint32_t& h0, uint32_t& h1) {
  uint32_t t0 = add2(add2(pf[16], pf[18]), add2(pf[20], pf[22])), t1 = add2(add2(pf[17], pf[19]), add2(pf[21], pf[23]));
  if (big) { t0 = add2(t0, add2(pf[24], pf[26])); t1 = add2(t1, add2(pf[25], pf[27])); }
  h0 = add2(add2(add2(add2(pf[0], pf[2]), add2(pf[4], pf[6])), add2(add2(pf[8], pf[10]), add2(pf[12], pf[14]))), t0);
  h1 = add2(add2(add2(add2(pf[1], pf[3]), add2(pf[5], pf[7])), add2(add2(pf[9], pf[11]), add2(pf[13], pf[15]))), t1);
}
__device__ __forceinline__ void exact_attention(float (&o)[16], float& l0, float& l1, const uint32_t (&q)[32], const __nv_bfloat16* kp,
                                                const __nv_bfloat16* vp) {
  float m0 = -3.0e38f, m1 = -3.0e38f;
  l0 = l1 = 0.f;
#pragma unroll
  for (int i = 0; i < 16; i++) o[i] = 0.f;
#pragma unroll 1
  for (int key = 0; key < SEQ; key += 8, kp += 8 * DH, vp += 8 * DH) {
    float d[4] = {0.f, 0.f, 0.f, 0.f};
#pragma unroll
    for (int k = 0; k < 8; k++)
      hmma_k16(d, q[4 * k], q[4 * k + 1], q[4 * k + 2], q[4 * k + 3], *(const uint32_t*)(kp + k * 16), *(const uint32_t*)(kp + k * 16 + 8));
    float x0 = fmaxf(d[0], d[1]), x1 = fmaxf(d[2], d[3]);
    x0 = fmaxf(x0, __shfl_xor_sync(0xffffffffu, x0, 1));
    x1 = fmaxf(x1, __shfl_xor_sync(0xffffffffu, x1, 1));
    x0 = fmaxf(fmaxf(x0, __shfl_xor_sync(0xffffffffu, x0, 2)), m0);
    x1 = fmaxf(fmaxf(x1, __shfl_xor_sync(0xffffffffu, x1, 2)), m1);
    const float sc0 = ex2(m0 - x0), sc1 = ex2(m1 - x1);
    m0 = x0; m1 = x1;
    const uint32_t p0 = pack2(ex2(d[0] - m0), ex2(d[1] - m0)), p1 = pack2(ex2(d[2] - m1), ex2(d[3] - m1));
    l0 = fmaf(l0, sc0, bf_lo(p0) + bf_hi(p0));
    l1 = fmaf(l1, sc1, bf_lo(p1) + bf_hi(p1));
#pragma unroll
    for (int nb = 0; nb < 4; nb++) {
      uint32_t b;
      asm("movmatrix.sync.aligned.m8n8.trans.b16 %0, %1;" : "=r"(b) : "r"(*(const uint32_t*)(vp + nb * 8)));
      o[4 * nb] *= sc0; o[4 * nb + 1] *= sc0; o[4 * nb + 2] *= sc1; o[4 * nb + 3] *= sc1;
      asm volatile("mma.sync.aligned.m16n8k8.row.col.f32.bf16.bf16.f32 {%0, %1, %2, %3}, {%4, %5}, {%6}, {%0, %1, %2, %3};"
                   : "+f"(o[4 * nb]), "+f"(o[4 * nb + 1]), "+f"(o[4 * nb + 2]), "+f"(o[4 * nb + 3]) : "r"(p0), "r"(p1), "r"(b));
    }
  }
}
__device__ __forceinline__ bool inv_sums(float l0, float l1, float& i0, float& i1) {
  l0 += __shfl_xor_sync(0xffffffffu, l0, 1); l1 += __shfl_xor_sync(0xffffffffu, l1, 1);
  l0 += __shfl_xor_sync(0xffffffffu, l0, 2); l1 += __shfl_xor_sync(0xffffffffu, l1, 2);
  i0 = rcp(l0);
  i1 = rcp(l1);
  return !(l0 + l1 <= SUM_HI) | (fminf(l0, l1) < SUM_LO);
}
template <int LO, int HI, int N>
__device__ __forceinline__ void park(uint32_t a, const float (&o)[N], float i0, float i1, bool on = true) {
#pragma unroll
  for (int i = LO; i < HI; i++)
    asm volatile("{\n.reg .pred p;\nsetp.ne.u32 p, %5, 0;\n@p stmatrix.sync.aligned.m8n8.x4.shared.b16 [%0], {%1, %2, %3, %4};\n}"
                 ::"r"(a + i * 2048), "r"(pack2(o[8 * i] * i0, o[8 * i + 1] * i0)), "r"(pack2(o[8 * i + 2] * i1, o[8 * i + 3] * i1)),
                 "r"(pack2(o[8 * i + 4] * i0, o[8 * i + 5] * i0)), "r"(pack2(o[8 * i + 6] * i1, o[8 * i + 7] * i1)), "r"((uint32_t)on) : "memory");
}

template <int I, int NP, int E0, int N, int NS>
__device__ __forceinline__ void exp_park(float (&s)[NS], uint32_t a, const float (&o)[64], float i0, float i1, bool on, int id) {
  if constexpr (I < NP) {
    constexpr int E1 = E0 + (N - E0) * X_PG / (NP - I);
    softmax_exp<E0, E1>(s);
    park<I, I + X_PG>(a, o, i0, i1, on);
    if (I + X_PG < NP) {
#pragma unroll
      for (int i = E0; i < E1; i++) asm volatile("" : "+f"(s[i])::"memory");
      block_fence(id + I);
    }
    exp_park<I + X_PG, NP, E1, N>(s, a, o, i0, i1, on, id);
  }
}

__device__ __forceinline__ void attn_consumer(const Ctx& cx, bool hlp, int qb, int hs, int wg, int cw, int lane, const __nv_bfloat16* x,
                                              const __nv_bfloat16* kc, const __nv_bfloat16* vc, __nv_bfloat16* out) {
  const uint32_t full = cx.sb + SM_FULL;
  const uint32_t ring = cx.sb + SM_RING;
  const uint32_t qwg = ring + wg * 16384;
  auto qlane = [&](int l) { return qwg + (cw & 3) * 256 + (l >> 4) * 1024 + (l & 15) * 16; };
  const bool signaller = lane == 0 && (cw & 3) < 2;
  const int my_turn = 1 + wg, other_turn = 2 - wg;
  const uint32_t empty_c = mapa(cx.sb + SM_EMPTY, cw & 1);

  float oA[64], oB[64], i0, i1;
  uint32_t xl[32];
  {
    const int r = lane >> 2, c = lane & 3;
    const int lr0 = cw * 16 + r;
    uint32_t xa[144];
    uint32_t mm0, mm1;
    float rstd0, rstd1, sq0 = 0.f, sq1 = 0.f;
    const uint32_t xf = cx.sb + SM_XFULL + wg * 32, xs = cx.sb + SM_SLOT + wg * 49152;
    auto lo_of = [&](int l) { return ((cw & 3) * 16 + (l & 15)) * 128 + (((l >> 4) ^ (l & 7)) << 4); };
    prof(wg, 0);
    {
      const uint32_t lo = lo_of(lane);
      const uint32_t xb = cx.sb + SM_X + wg * 73728;
      float sm[X_NS][4] = {};
      const uint32_t ws = (lane & 7) == 1 ? 64 : 0;
      uint32_t wb = cx.sb + (ws ? SM_WR + (lane >> 3) * 16 : SM_ONES);
      uint32_t b0[24], b1[24], b2[24];
      mbar_wait(cx.sb + SM_BAR_W, 0);
      TS4(1)
      if (X_LN == 0) {
        ln_fetch_b(b0, wb, ws);
        ln_fetch_b(b1, wb, ws);
        ln_fetch_b(b2, wb, ws);
      }
      mbar_wait(xf, 0);
      TS4(2)
      ln_fetch<0, 12>(xa, xb, lo);
      if (X_LN == 1) {
        ln_fetch_b(b0, wb, ws);
        ln_fetch_b(b1, wb, ws);
        ln_fetch_b(b2, wb, ws);
      }
      ln_sums<0, 12>(xa, sm, b0);
      mbar_wait(xf + 8, 0);
      TS4(3)
      ln_fetch<12, 24>(xa, xb, lo);
      if (wg == 0) {
        bar_arrive(BAR_XREL + (xa[95] & blockIdx.y), 224);
      }
      ln_sums<12, 24>(xa, sm, b1);

      mbar_wait(xf + 16, 0);
      TS4(4)
      prof(wg, 1);
      ln_fetch<24, 36>(xa, xb, lo);
      ln_sums<24, 36>(xa, sm, b2);
#pragma unroll
      for (int i = 0; i < 4; i++) sm[0][i] = X_NS == 2 ? sm[0][i] + sm[1][i] : X_NS == 3 ? sm[0][i] + sm[1][i] + sm[2][i] : (sm[0][i] + sm[1][i]) + (sm[2][i] + sm[X_NS - 1][i]);
      if (cw == hs && c == 0) {
        *(float*)(cx.sp + SM_RAW + 4 * r) = sm[0][1];
        *(float*)(cx.sp + SM_RAW + 4 * r + 32) = sm[0][3];
      }
      rstd0 = sm[0][0];
      rstd1 = sm[0][2];
      mm0 = pack2(rstd0 * (1.0f / DM), rstd0 * (1.0f / DM));
      mm1 = pack2(rstd1 * (1.0f / DM), rstd1 * (1.0f / DM));
    }
#pragma unroll
    for (int i = 0; i < 16; i++) { xa[2 * i] = sub2(xa[2 * i], mm0); xa[2 * i + 1] = sub2(xa[2 * i + 1], mm1); }
    pin(xa);
    prof(wg, 2);
    TS4(5)

    float (&acc)[64] = oB;
    int st0 = 0;
#pragma unroll 1
    for (int n = 0; n < 16; n++) {
      const int p = n & 3, rb = n >> 2;
      const bool last = p == 3 && !hlp;
#pragma unroll
      for (int i = 0; i < 5; i++) {
        if (i == 4 && last) {
          wg_wait<1>();
          mbar_arrive_cluster(empty_c + 8 * 3, signaller && wg);
          wg_wait<0>();
          pin(acc);
          prof(wg, 6);
#pragma unroll
          for (int j = 0; j < 32; j++) xl[j] = xa[112 + j];
          i0 = rstd0;
          i1 = rstd1;
          goto attention;
        }
        const int st = st0 + i;
        const uint32_t sl = st & 3, slp = (st - 1) & 3;
        if (!wg) mbar_wait(full + 8 * sl, (st >> 2) & 1);
        TS4(8 + 2 * (p * 5 + i))
        const bool join = wg && last;
        if ((i || st0 + wg) && i != (wg ? 4 : 1) && !(join && i == 3)) bar_sync(my_turn, 256);
        wg_fence();
        const uint64_t db = mkdesc(ring + sl * STAGE, 16384);
        const int kb0 = i < 3 ? 8 * i : 8 * i - 4;
#pragma unroll
        for (int k = 0; k < (i == 2 ? 4 : 8); k++) {
          const int kb = kb0 + k;
          mma_n128t(acc, xa[4 * kb], xa[4 * kb + 1], xa[4 * kb + 2], xa[4 * kb + 3], db + k * 128, kb > 0);
        }
        wg_commit();
        TS4(9 + 2 * (p * 5 + i))
        if (wg ? (i == 4 ? st0 < 75 : (i < 2 || i == (join ? 3 : 2))) : i) bar_arrive(other_turn, 256);
        if (p == 0 && i < 4) {
          if (i == 1 && rb) {
            mbar_wait(xf + 8, rb & 1);
            ln_fetch<16, 32>(xa, xs - 32768, lo_of(fresh_lane()));
          }
          if (i == 2 && rb) {
            mbar_wait(xf + 16, rb & 1);
            ln_fetch<32, 36>(xa, xs - 32768, lo_of(fresh_lane()));
          }
#pragma unroll
          for (int j = 0; j < 72; j++)
            if (j >= 2 * (i < 2 ? 8 * i + 8 : 8 * i + 4) && j < 2 * (i == 0 ? 16 : 8 * i + 12)) {
              xa[2 * j] = sub2(xa[2 * j], mm0);
              xa[2 * j + 1] = sub2(xa[2 * j + 1], mm1);
            }
          pin(xa);
        }
        if (i == X_SQI && n == 0) {
          mbar_wait(cx.sb + SM_BAR_SQ, 0);
          float2* sp = (float2*)(cx.sp + SM_STATS) + lr0;
          float mean0, mean1;
          ln_row(rstd0, sp[0].y, mean0, rstd0);
          ln_row(rstd1, sp[8].y, mean1, rstd1);
          __syncwarp();
          if (c == 0) {
            sp[0] = make_float2(mean0, rstd0);
            sp[8] = make_float2(mean1, rstd1);
          }
          *((uint32_t*)(cx.sp + SM_COLD) + wg) = 0;
          if (!hlp) bar_arrive(BAR_GATE, 352);
          rstd0 *= SM_SCALE_LOG2;
          rstd1 *= SM_SCALE_LOG2;
        }
        if (i == 3 && hlp && p == 3 && rb < 3) bar_arrive(BAR_QS + wg + (xa[63] & blockIdx.y), 160);
        if (i == 4 && p == 3 && rb < 3) {
          const float2* sp = (const float2*)(cx.sp + SM_STATS) + cw * 16 + (fresh_lane() >> 2);
          mm0 = pack2(sp[0].x, sp[0].x);
          mm1 = pack2(sp[8].x, sp[8].x);
          sq0 = sp[0].y * SM_SCALE_LOG2;
          sq1 = sp[8].y * SM_SCALE_LOG2;
#pragma unroll
          for (int j = 0; j < 16; j++) { xa[2 * j] = sub2(xa[2 * j], mm0); xa[2 * j + 1] = sub2(xa[2 * j + 1], mm1); }
          pin(xa);
        }
        if (i == 0) {
          if (wg) {
            wg_wait<0>();
            mbar_arrive_cluster(empty_c + 8 * sl, signaller);
          }
        } else if (i == 2) {
          if (!join) {
            wg_wait<0>();
            mbar_arrive_cluster(empty_c + 8 * sl, signaller);
          }
          if (hlp && p == 3 && rb < 3) {
            mbar_wait(xf, ~rb & 1);
            ln_fetch<0, 16>(xa, xs, lo_of(fresh_lane()));
            pin(xa);
          }
        } else if (i != 3) {
          wg_wait<1>();
          mbar_arrive_cluster(empty_c + 8 * slp, signaller && (i == 4 || !wg));
          wg_wait<0>();
          mbar_arrive_cluster(empty_c + 8 * sl, signaller);
        }
      }
      pin(acc);
      prof(wg, 3 + p);
      TS4(50 + 2 * p)
      st0 += 5;
      if (hlp && st0 > 5) bar_sync(BAR_QF + wg, 160);
      park<0, 8>(qlane(lane) + (hlp ? 5 + wg : 4 + p) * STAGE, acc, rstd0, rstd1);
      if (p || hlp) asm volatile("fence.proxy.async.shared::cta;" ::: "memory");
      if (hlp) bar_arrive(BAR_QS + wg, 160);
      if (p == 3) { rstd0 = sq0; rstd1 = sq1; }
      TS4(51 + 2 * p)
      if (p == 1 && !hlp) {
        float (&ah)[32] = *(float (*)[32])&acc[0];
#pragma unroll
        for (int i = 0; i < 3; i++) {
          const uint32_t sl = (10 + i) & 3;
          if (!wg) mbar_wait(full + 8 * sl, ((10 + i) >> 2) & 1);
          TS4(28 + 2 * i)
          if (i == 0 || i == 2 - wg) bar_sync(my_turn, 256);
          wg_fence();
          const uint64_t db = mkdesc(ring + sl * STAGE, 16);
#pragma unroll
          for (int k = 0; k < 12; k++) {
            const int kb = 12 * i + k;
            if (kb) mma_n64t(ah, xa[4 * kb], xa[4 * kb + 1], xa[4 * kb + 2], xa[4 * kb + 3], db + k * 128, true);
            else mma_n64t_dyn(ah, xa[0], xa[1], xa[2], xa[3], db, blockIdx.y);
          }
          wg_commit();
          TS4(29 + 2 * i)
          if (i == 2 || i != wg) {
            bar_arrive(other_turn, 256);
            if (i) {
              wg_wait<1>();
              mbar_arrive_cluster(empty_c + 8 * ((9 + i) & 3), signaller && i == wg + 1);
            }
            wg_wait<0>();
            mbar_arrive_cluster(empty_c + 8 * sl, signaller);
          }
        }
        pin(ah);
        TS4(54)
        park<0, 4>(qlane(lane) + 6 * STAGE, ah, rstd0, rstd1);
        TS4(55)
        st0 = 13;
        n = 2;
      }
    }
    TS_DUMP()
    ffn_consumer(cx, blockIdx.x & 3, wg, cw, fresh_lane(), x);
    return;
  }

attention:
  uint32_t oa[128];
  float acc[32];
  {
    uint32_t pf[28];
    uint32_t bad = 0;
    float lA0 = 0.f, lA1 = 0.f, lB0 = 0.f, lB1 = 0.f;
    int t = 0;
    uint32_t ra = 2 * 2048, rb = 2048, rc = 2 * 2048, par = 0;
    const uint64_t dk0 = mkdesc(ring, 16), dv0 = mkdesc(ring, 16384);
    uint64_t dqA = mkdesc_q(qwg + 4 * STAGE), dqB = dqA + 2048;
    auto turn = [&](auto kc_, auto bc_) {
      constexpr int KIND = decltype(kc_)::value, BIG = decltype(bc_)::value;
      constexpr int HB = KIND == 1, ID = 10 * KIND + 30 * BIG, T0 = BIG ? 38 : 0;
      constexpr int NS = BIG ? 56 : 48, SPLIT = BIG ? (HB ? X_SPLIT : X_SPLITA) : (HB ? X_SPLITS : X_SPLITSA);
      float s[NS];
      float (&op)[64] = HB ? oA : oB;
      uint32_t h0 = 0, h1 = 0;
      TS2(0)
      bar_sync(my_turn, 256);
      TS2(1)
      if (KIND) { pin(pf); pin(op); }
      mma_qk(s, HB ? dqB : dqA, dk0 + (HB ? ra : rc));
      TS2(2)
      if (KIND) {
        const bool bigp = HB ? BIG : BIG ? t != 10 : t == 66;
        if (X_BF2) block_fence(ID + 9);
        pin(pf);
        sum_tree(pf, bigp, h0, h1);
        asm volatile("" : "+r"(h0), "+r"(h1)::"memory");
        if (HB) mbar_wait(full + (rb >> 8), par);
        mma_pv(op, pf, dv0 + rb, t != T0 + 2 - HB, bigp);
      } else {
        mbar_wait(full + (rb >> 8), (NST_Q - 1) >> 2 & 1);
#pragma unroll
        for (int k = 0; k < 8; k++) mma_n128t(op, xl[4 * k], xl[4 * k + 1], xl[4 * k + 2], xl[4 * k + 3], dv0 + rb + k * 128, 1);
        wg_commit();
      }
      TS2(3)
      bar_arrive(other_turn, 256);
      (HB ? lA0 : lB0) += bf_lo(h0) + bf_hi(h0);
      (HB ? lA1 : lB1) += bf_lo(h1) + bf_hi(h1);
      wg_wait<1>();
      pin(s);
      TS1(t)
      TS2(4)
      if (KIND == 1) mbar_arrive_cluster_now<ID + 3>(empty_c + (ra >> 8), signaller);
      if (BIG && t == T0 + HB) {
        const uint32_t a = qlane(fresh_lane()) + (4 + HB) * STAGE;
        const bool ok = !__any_sync(0xffffffffu, inv_sums(HB ? lB0 : lA0, HB ? lB1 : lA1, i0, i1));
        bad = (HB ? bad : 0) | (ok ? 0 : 1 << HB);
        (HB ? lB0 : lA0) = 0.f;
        (HB ? lB1 : lA1) = 0.f;
        softmax_exp<0, X_E0>(s);
#pragma unroll
        for (int i = 0; i < X_E0; i++) asm volatile("" : "+f"(s[i])::"memory");
        block_fence(ID + 7);
        exp_park<0, X_PA, X_E0, SPLIT>(s, a, HB ? oB : oA, i0, i1, ok, 200 + ID);
        if (!HB) dqB += 2048;
        prof(wg, 8 + HB);
      } else {
        if (HB && !BIG) bad = (bad & 3) | (inv_sums(lA0, lA1, i0, i1) ? 4 : 0);
        softmax_exp<0, SPLIT>(s);
      }
      pin(s);
      if (!BIG) block_fence(ID + 4);
      TS2(5)
      wg_wait<0>();
      TS2(6)
      pin(op);
      if (KIND) pin(pf); else pin(xl);
      if (HB) {
        par ^= rc == 2048;
        if (BIG && t == 37) dqA -= 4 * 2048;
        if (BIG && t == X_WAKE && cw == 0) bar_arrive(BAR_HELPER, 64);
      } else {
        mbar_arrive_cluster_now<ID + 5>(empty_c + (rb >> 8), signaller);
        if (KIND) {
          par ^= ra == 2048;
          const uint32_t x = ra;
          ra = rc; rc = rb; rb = x;
        }
      }
      softmax_exp<SPLIT, NS>(s);
#pragma unroll
      for (int i = 0; i < NS / 2; i++) pf[i] = pack2(s[2 * i], s[2 * i + 1]);
      pin(pf);
      if (KIND == 0) {
        block_fence(ID + 6);
        park<0, 8>(qlane(fresh_lane()), oB, i0, i1);
        asm volatile("fence.proxy.async.shared::cta;" ::: "memory");
        prof(wg, 7);
      }
      if (BIG && X_PA < 8 && t == T0 + HB) park<X_PA, 8>(qlane(fresh_lane()) + (4 + HB) * STAGE, HB ? oB : oA, i0, i1, !(bad >> HB));
      if (BIG && !HB && t == T0) mbar_wait(cx.sb + SM_BAR_Q + 8 * wg, 0);
      if (HB) mbar_wait(full + (rc >> 8), par);
      t++;
    };
#pragma unroll
    for (int i = 24; i < 28; i++) asm volatile("" : "=r"(pf[i]));
    mbar_wait(full + 8 * 2, 0);
    turn(IC<0>(), IC<0>());
    rb = 3 * 2048; rc = 2048;
    kill(oA);
    const bool never = blockIdx.y == 1;
#pragma unroll 1
    while (true) {
      turn(IC<1>(), IC<0>());
      if (t == 76) break;
      if (t == 10) {
#pragma unroll 1
        do {
#pragma unroll 1
          do turn(IC<2>(), IC<1>()); while (never);
          turn(IC<1>(), IC<1>());
        } while (t != 66);
      }
#pragma unroll 1
      do turn(IC<2>(), IC<0>()); while (never);
    }
    const uint32_t ql = qlane(fresh_lane());
    auto scale = [&](auto lo, auto hi) {
#pragma unroll
      for (int i = decltype(lo)::value; i < decltype(hi)::value; i++) {
        oa[32 + 2 * i] = pack2(oA[4 * i] * i0, oA[4 * i + 1] * i0);
        oa[32 + 2 * i + 1] = pack2(oA[4 * i + 2] * i1, oA[4 * i + 3] * i1);
        asm volatile("" : "+r"(oa[32 + 2 * i]), "+r"(oa[32 + 2 * i + 1])::"memory");
      }
    };
    TS3(1)
    if (X_LD == 0) {
#pragma unroll
      for (int i = 0; i < 8; i++) ldsm4(ql + 4 * STAGE + i * 2048, oa[4 * i], oa[4 * i + 1], oa[4 * i + 2], oa[4 * i + 3]);
    }
    {
      uint32_t h0, h1;
      sum_tree(pf, false, h0, h1);
      if (inv_sums(lB0 + (bf_lo(h0) + bf_hi(h0)), lB1 + (bf_lo(h1) + bf_hi(h1)), lB0, lB1)) bad |= 8;
    }
    scale(IC<0>(), IC<X_F1>());
    volatile uint32_t* const cold = (volatile uint32_t*)(cx.sp + SM_COLD) + wg;
    if (bad) *cold = 1;
    block_fence(93);
    TS3(2)
    bar_sync(my_turn, 256);
    const uint32_t is_cold = *cold;
    TS3(3)
    pin(pf); pin(oB);
    mma_pv(oB, pf, dv0 + 2 * 2048, true, false);
    mbar_arrive_cluster_now<91>(empty_c, signaller && !is_cold);
    TS3(4)
    if (X_LD == 1) {
#pragma unroll
      for (int i = 0; i < 8; i++) ldsm4(ql + 4 * STAGE + i * 2048, oa[4 * i], oa[4 * i + 1], oa[4 * i + 2], oa[4 * i + 3]);
    }
    const uint64_t db = mkdesc(ring + 3 * STAGE, 16);
    scale(IC<X_F1>(), IC<X_F2>());
    block_fence(94);
#pragma unroll
    for (int i = 0; i < 32; i++) asm volatile("" : "+r"(oa[i])::"memory");
    wg_fence();
#pragma unroll
    for (int k = 0; k < 8; k++) mma_n64t(acc, oa[4 * k], oa[4 * k + 1], oa[4 * k + 2], oa[4 * k + 3], db + k * 128, k > 0);
    if (X_F2 < 16) {
      wg_commit();
      block_fence(95);
      scale(IC<X_F2>(), IC<16>());
      TS3(5)
      wg_fence();
    }
#pragma unroll
    for (int k = 8; k < 16; k++) mma_n64t(acc, oa[4 * k], oa[4 * k + 1], oa[4 * k + 2], oa[4 * k + 3], db + k * 128, 1);
    wg_commit();
    bar_arrive(other_turn, 256);
    wg_wait<(X_F2 < 16 ? 2 : 1)>();
    pin(oB); pin(pf);
    TS(76)
    TS3(6)
    mbar_arrive_cluster(empty_c + 8 * 2, signaller);
#pragma unroll
    for (int i = 16; i < 24; i++) ldsm4(ql + 5 * STAGE + (i & 7) * 2048, oa[4 * i], oa[4 * i + 1], oa[4 * i + 2], oa[4 * i + 3]);
#pragma unroll
    for (int i = 0; i < 16; i++) {
      oa[96 + 2 * i] = pack2(oB[4 * i] * lB0, oB[4 * i + 1] * lB0);
      oa[96 + 2 * i + 1] = pack2(oB[4 * i + 2] * lB1, oB[4 * i + 3] * lB1);
    }
    TS3(7)
    mbar_wait(full + 8 * 1, 0);
    TS3(8)
    wg_wait<0>();
    pin(acc); pin(oa);
    if (__any_sync(0xffffffffu, is_cold)) {
      bad = __reduce_or_sync(0xffffffffu, bad);
      if (!(bad & 8)) {
#pragma unroll
        for (int i = 24; i < 32; i++) stsm4(ql + 6 * STAGE + (i & 7) * 2048, oa[4 * i], oa[4 * i + 1], oa[4 * i + 2], oa[4 * i + 3]);
      }
#pragma unroll 1
      for (int h = 0; h < 4; h++) {
        if (bad >> h & 1) {
          const uint32_t a = ql + ((0x6054 >> (4 * h)) & 7) * STAGE;
          const int l = fresh_lane(), o = (hs * 2 + (h >> 1)) * SEQ * DH + (l >> 2) * DH + (l & 3) * 2;
          uint32_t q[32];
#pragma unroll
          for (int i = 0; i < 8; i++) ldsm4(a + i * 2048, q[4 * i], q[4 * i + 1], q[4 * i + 2], q[4 * i + 3]);
#pragma unroll 1
          for (int i = 0; i < 4; i++) {
            float ox[16], l0, l1;
            exact_attention(ox, l0, l1, q, kc + o, vc + o + i * 32);
            inv_sums(l0, l1, l0, l1);
            park<0, 2>(a + i * 4096, ox, l0, l1);
          }
        }
      }
      __syncwarp();
#pragma unroll
      for (int i = 0; i < 32; i++)
        if ((i >> 3) != 1 || (bad & 4))
          ldsm4(ql + ((0x6504 >> (4 * (i >> 3))) & 7) * STAGE + (i & 7) * 2048, oa[4 * i], oa[4 * i + 1], oa[4 * i + 2], oa[4 * i + 3]);
      pin(oa);
      asm volatile("fence.proxy.async.shared::cta;" ::: "memory");
      bar_sync(4 + wg, 128);
      mbar_arrive_cluster(empty_c, signaller);
      wg_fence();
#pragma unroll
      for (int k = 0; k < 16; k++) mma_n64t(acc, oa[4 * k], oa[4 * k + 1], oa[4 * k + 2], oa[4 * k + 3], db + k * 128, k > 0);
      wg_commit();
      wg_wait<0>();
      pin(acc);
    }
    mbar_arrive_cluster(empty_c + 8 * 3, signaller);
  }

  prof(wg, 10);
  TS3(9)
  {
    lane = fresh_lane();
    const int tw = (cw & 3) * 32 + lane;
    float red[32];
    kill(red);
    const uint32_t tag = *(const uint32_t*)(cx.sp + SM_TAG);
    uint4* const xch = at(cx.g->part, ((qb * 64 * 2 + wg) * 4 * 128 + tw) * 16);
    int nrx = 1;
    auto region = [](int s, int h) { return h ? 1 + (s & 1) : (s & 1) ? 0 : 3; };
    auto half_step = [&](int s, auto hc, bool arrive) {
      constexpr int h = decltype(hc)::value;
      const uint64_t db = mkdesc(ring + region(s, h) * STAGE, 16);
      bar_sync(my_turn, 256);
      pin(oa);
      wg_fence();
#pragma unroll
      for (int k = 0; k < 16; k++) {
        const int kb = h * 16 + k;
        mma_n64t(acc, oa[4 * kb], oa[4 * kb + 1], oa[4 * kb + 2], oa[4 * kb + 3], db + k * 128, kb > 0);
      }
      wg_commit();
      if (arrive) bar_arrive(other_turn, 256);
    };
    auto await = [&](int s, int h) { mbar_wait(full + 8 * region(s, h), ((s >> 1) ^ h ^ 1) & 1); };
    auto fetch = [&](uint32_t (&g)[16], int n) {
      const uint4* p = at(xch, (hs * 7 + n - 1) * 16384);
#pragma unroll
      for (int i = 0; i < 4; i++) ld_gran(p + i * 128, g[4 * i], g[4 * i + 1], g[4 * i + 2], g[4 * i + 3]);
    };
    uint32_t g[16];
#pragma unroll 1
    for (int s = 0;; s++) {
      const bool pend = nrx < s - 1;
      if (pend && s < 8) fetch(g, nrx);
      half_step(s, IC<1>(), s + wg < 9);
      if (s == 8) break;
      TS3(s < 3 ? 16 + 8 * s : 75)
      if (s == 0) {
        bar_arrive(BAR_OA, 352);
#pragma unroll
        for (int i = 0; i < 32; i++) red[i] = 0.f;
      }
      await(s + 1, 0);
      TS3(s < 3 ? 17 + 8 * s : 75)
      wg_wait<0>();
      TS3(s < 3 ? 18 + 8 * s : 75)
      mbar_arrive_cluster(empty_c + 8 * region(s, 1), signaller && s < 7);
      pin(acc);
      TS(77 + s)
      prof(wg, 12 + s);
      uint4* p = at(xch, (s == 0 ? 56 + hs : ((hs + s) & 7) * 7 + s - 1) * 16384);
#pragma unroll
      for (int i = 0; i < 4; i++)
        st_gran(p + i * 128, (pack2(acc[8 * i], acc[8 * i + 1]) & ~TAG) | tag, pack2(acc[8 * i + 2], acc[8 * i + 3]),
                pack2(acc[8 * i + 4], acc[8 * i + 5]), pack2(acc[8 * i + 6], acc[8 * i + 7]));
      TS3(s < 3 ? 19 + 8 * s : 75)
      half_step(s + 1, IC<0>(), true);
      TS3(s < 3 ? 20 + 8 * s : 75)
      if (pend && granules_ok(g, tag)) { add_granules(red, g); nrx++; }
      if (s == 7) fetch(g, nrx);
      await(s + 1, 1);
      TS3(s < 3 ? 21 + 8 * s : 75)
      wg_wait<0>();
      TS3(s < 3 ? 22 + 8 * s : 75)
      mbar_arrive_cluster(empty_c + 8 * region(s + 1, 0), signaller && s < 6);
    }
    uint32_t xv[16], gt[16], g2[16];
    TS3(42)
    const bool ok = granules_ok(g, tag);
    TS3(43)
    nrx += ok;
    fetch(g2, nrx);
    mbar_wait(cx.sb + SM_BAR_XG, 0);
    const uint32_t frag = (cw * 16 + (lane & 15)) * 128 + (((lane >> 4) ^ (lane & 7)) << 4);
#pragma unroll
    for (int i = 0; i < 4; i++) {
      ldsm4(cx.sb + SM_XO + (frag ^ (i << 5)), xv[4 * i], xv[4 * i + 1], xv[4 * i + 2], xv[4 * i + 3]);
      ldsm4(cx.sb + SM_GO + (frag ^ (i << 5)), gt[4 * i], gt[4 * i + 1], gt[4 * i + 2], gt[4 * i + 3]);
    }
    if (ok) add_granules(red, g);
    TS3(44)
    wg_wait<0>();
    pin(acc);
    TS(85)
#pragma unroll
    for (int i = 0; i < 32; i++) red[i] += acc[i];
    pin(red);
#pragma unroll 1
    for (int spins = 0; spins < (1 << 16); spins++) {
      if (granules_ok(g2, tag)) {
        add_granules(red, g2);
        if (++nrx == 8) break;
      }
      fetch(g2, nrx);
    }
    uint32_t ow[16];
#pragma unroll
    for (int i = 0; i < 16; i++) ow[i] = pack2(red[2 * i], red[2 * i + 1]);
    prof(wg, 20);
    TS(86)
#pragma unroll
    for (int i = 0; i < 16; i++) ow[i] = fma2(ow[i], gt[i], xv[i]);
#pragma unroll
    for (int i = 0; i < 4; i++) stsm4(cx.sb + SM_XO + (frag ^ (i << 5)), ow[4 * i], ow[4 * i + 1], ow[4 * i + 2], ow[4 * i + 3]);
    __syncwarp();
    __nv_bfloat16* const op = at(out, ((qb * 128 + cw * 16 + (lane >> 3)) * DM + hs * 64 + (lane & 7) * 8) * 2);
#pragma unroll
    for (int i = 0; i < 4; i++) {
      uint4 v;
      const int row = cw * 16 + i * 4 + (lane >> 3);
      lds128(cx.sb + SM_XO + row * 128 + (((lane ^ row) & 7) << 4), v.x, v.y, v.z, v.w);
      asm volatile("st.global.v4.b32 [%0], {%1, %2, %3, %4};" ::"l"(op + i * 4 * DM),
                   "r"(v.x), "r"(v.y), "r"(v.z), "r"(v.w) : "memory");
    }
    prof(wg, 22);
    TS(87)
    TS_DUMP()
  }
}

struct KvMaps { CUtensorMap m[4]; };
__global__ void __cluster_dims__(2, 1, 1) __launch_bounds__(THREADS, 1)
fused_kernel(const __nv_bfloat16* __restrict__ x, const __nv_bfloat16* __restrict__ w_r, const __nv_bfloat16* __restrict__ kc,
             const __nv_bfloat16* __restrict__ vc, __nv_bfloat16* __restrict__ out, Scratch* scratch,
             const __grid_constant__ CUtensorMap tmX, const __grid_constant__ CUtensorMap tmWq,
             const __grid_constant__ KvMaps tmKV, const __grid_constant__ CUtensorMap tmWo,
             const __grid_constant__ CUtensorMap tmG, const __grid_constant__ CUtensorMap tmU,
             const __grid_constant__ CUtensorMap tmD, const __grid_constant__ CUtensorMap tmX16,
             const __grid_constant__ CUtensorMap tmWq96, const __grid_constant__ CUtensorMap tmX64) {
  extern __shared__ __align__(1024) uint8_t smem_raw[];
  prof(0, 23, 511);
  if (X_PFX && threadIdx.x == 192) { prefetch_tmap(&tmX); prefetch_tmap(&tmWq); }
  Ctx cx;
  cx.sb = smem_u32(smem_raw);
  cx.sp = smem_raw;
  cx.g = scratch;
  cx.rank = blockIdx.x & 1;
  const int warp = __shfl_sync(0xffffffffu, threadIdx.x >> 5, 0);
  const int cluster = blockIdx.x >> 1;
  const bool is_ffn = blockIdx.x >= N_ATT_CTA;
  const int c7 = ((cluster - 36) * 37) >> 8;
  const int hs = cluster < 4 ? 4 + cluster : cluster < 36 ? (cluster - 4) >> 3 : 4 + c7;
  const int qb = (cluster < 4 ? 0 : cluster < 36 ? (cluster - 4) & 7 : cluster - (is_ffn ? 36 : 35) - 7 * c7) * 2 + cx.rank;

  auto load_x = [&](int w, int i0, int i1) {
#pragma unroll
    for (int i = i0; i < i1; i++) {
      mbar_expect_tx(cx.sb + SM_XFULL + 32 * w + 8 * i, 24576);
      tma3d(cx.sb + SM_X + (3 * w + i) * 24576, &tmX, qb * 128 + w * 64, i * 3, cx.sb + SM_XFULL + 32 * w + 8 * i);
    }
  };
  if (warp < 4) {
    asm volatile("setmaxnreg.dec.sync.aligned.u32 24;");
    if (elect_one()) {
      if (warp == 0) TSP(64)
      if (warp < 2) {
#pragma unroll
        for (int i = 0; i < 4; i++) mbar_init(cx.sb + SM_FULL + 32 * warp + 8 * i, 1 + 3 * warp);
        mbar_init(cx.sb + SM_BAR_XG + 8 * warp, 1);
        mbar_init(cx.sb + SM_BAR_Q + 8 * warp, 1);
        if (warp) mbar_init(cx.sb + SM_BAR_MISC, 1);
      } else if (is_ffn) {
#pragma unroll
        for (int i = 0; i < 8; i++) mbar_init(cx.sb + (warp == 2 ? SM_FFULL : SM_FEMPTY) + 8 * i, 1);
      }
      asm volatile("fence.mbarrier_init.release.cluster;" ::: "memory");
    }
    __syncwarp();
    cluster_arrive();
    if (warp == 0) TSP(70)
    cluster_wait();
    if (warp == 0) TSP(71)
    prof(0, 24, 511);
    if (warp == 0) {
      if (is_ffn) ffn_producer(cx, qb, &tmWq, &tmG, &tmU, &tmD);
      else attn_producer(cx, qb, hs, tmKV.m, &tmWq, &tmWq96, &tmWo);
      prof(0, 25, 511);
    } else {
      sq_publish(cx, qb, hs, warp - 1, read_lane());
      if (warp == 3) sq_collect(cx, qb, read_lane());
      if (!is_ffn) {
        attn_gate(cx, qb, hs, warp - 1, threadIdx.x - 32, x);
        if (warp == 1) TSP(65)
        asm volatile("fence.proxy.async.global;" ::: "memory");
        if (warp == 1) attn_helper(cx, qb, hs, fresh_lane(), &tmX16);
        else bar_arrive(BAR_OA, 352);
        attn_finish8(cx, qb, hs, warp - 1, fresh_lane(), out);
      } else if (warp < 3) {
        ffn_publish(cx, qb, warp - 1, fresh_lane(), &tmX64);
      }
    }
    __syncwarp();
    cluster_arrive();
    cluster_wait();
  } else {
    if (warp == 4 && elect_one()) {
#pragma unroll
      for (int i = 0; i < 3; i++) mbar_init(cx.sb + SM_XFULL + 8 * i, 1);
      TSP(66)
      load_x(0, 0, 3);
#pragma unroll
      for (int i = 4; i < 7; i++) mbar_init(cx.sb + SM_XFULL + 8 * i, 1);
      asm volatile("fence.mbarrier_init.release.cluster;" ::: "memory");
    }
    if (warp == 5 && elect_one()) {
      mbar_init(cx.sb + SM_BAR_W, 1);
      asm volatile("fence.mbarrier_init.release.cluster;" ::: "memory");
      *(uint4*)(cx.sp + SM_ONES) = make_uint4(0x3F803F80u, 0x3F803F80u, 0x3F803F80u, 0x3F803F80u);
      mbar_expect_tx(cx.sb + SM_BAR_W, DM * 2);
      bulk_load(cx.sb + SM_WR, w_r, DM * 2, cx.sb + SM_BAR_W);
    }
    __syncwarp();
    cluster_arrive();
    if (warp == 4 && elect_one()) {
      load_x(1, 0, X_ORD);
      TSP(67)
    }
    __syncwarp();
    asm volatile("setmaxnreg.inc.sync.aligned.u32 240;");
    const int cw = warp - 4, wg = cw >> 2;
    cluster_wait();
    if (warp == 8 && elect_one()) {
      const uint64_t pol = policy_evict_first();
#pragma unroll
      for (int i = 0; i < 4; i++) {
        if (!(i & 1)) mbar_expect_tx(cx.sb + SM_FULL + 4 * i, 32768);
        tma2d_mc(cx.sb + SM_RING + (i >> 1) * STAGE + cx.rank * 16384 + (i & 1) * 8192, &tmWq,
                 is_ffn ? (cx.rank * 4 + 3) * DH + 64 : hs * 512 + cx.rank * 64, i * 64, cx.sb + SM_FULL + 8 * (i >> 1), pol);
        if (i == 1) load_x(1, X_ORD, 3);
      }
      TSP(72)
    }
    __syncwarp();
    attn_consumer(cx, is_ffn, qb, hs, wg, cw, read_lane(), x, kc, vc, out);
  }
}

typedef CUresult (*EncodeFn)(CUtensorMap*, CUtensorMapDataType, cuuint32_t, void*, const cuuint64_t*, const cuuint64_t*,
                             const cuuint32_t*, const cuuint32_t*, CUtensorMapInterleave, CUtensorMapSwizzle,
                             CUtensorMapL2promotion, CUtensorMapFloatOOBfill);

void encode(EncodeFn fn, CUtensorMap* m, const void* p, int rank, const cuuint64_t* dims, const cuuint64_t* strides,
            const cuuint32_t* box) {
  const cuuint32_t es[5] = {1, 1, 1, 1, 1};
  fn(m, CU_TENSOR_MAP_DATA_TYPE_BFLOAT16, rank, const_cast<void*>(p), dims, strides, box, es, CU_TENSOR_MAP_INTERLEAVE_NONE,
     CU_TENSOR_MAP_SWIZZLE_128B, CU_TENSOR_MAP_L2_PROMOTION_L2_128B, CU_TENSOR_MAP_FLOAT_OOB_FILL_NONE);
}
void encode2d(EncodeFn fn, CUtensorMap* m, const void* p, uint64_t rows, uint64_t cols, uint32_t box_rows) {
  const cuuint64_t dims[2] = {cols, rows}, strides[1] = {cols * 2};
  const cuuint32_t box[2] = {64, box_rows};
  encode(fn, m, p, 2, dims, strides, box);
}

}

extern "C" void kernel_launch(void* const* d_in, const int* in_sizes, int n_in, void* d_out, int out_size) {
  (void)in_sizes; (void)n_in; (void)out_size;
  void* fnp = nullptr;
  cudaDriverEntryPointQueryResult qr;
  cudaGetDriverEntryPoint("cuTensorMapEncodeTiled", &fnp, cudaEnableDefault, &qr);
  EncodeFn fn = (EncodeFn)fnp;
  CUtensorMap tmWq, tmWo, tmG, tmU, tmD, tmX, tmX16, tmWq96, tmX64;
  encode2d(fn, &tmX64, d_in[0], SEQ, DM, 64);
  encode2d(fn, &tmWq96, d_in[3], DM, 4096, 96);
  encode2d(fn, &tmX16, d_in[0], SEQ, DM, 16);
  KvMaps tmKV;
  for (int i = 0; i < 4; i++) encode2d(fn, &tmKV.m[i], d_in[1 + (i & 1)], 16 * SEQ, DH, i < 2 ? 112 : 96);
  encode2d(fn, &tmWq, d_in[3], DM, 4096, 64);
  {
    const cuuint64_t dims[3] = {64, SEQ, 9}, strides[2] = {DM * 2, 128};
    const cuuint32_t box[3] = {64, 64, 3};
    encode(fn, &tmX, d_in[0], 3, dims, strides, box);
  }
  encode2d(fn, &tmWo, d_in[4], 4096, DM, 128);
  encode2d(fn, &tmG, d_in[7], DM, FF, 192);
  encode2d(fn, &tmU, d_in[8], DM, FF, 192);
  encode2d(fn, &tmD, d_in[9], FF, DM, 192);
  cudaFuncSetAttribute(fused_kernel, cudaFuncAttributeMaxDynamicSharedMemorySize, SM_TOTAL);
  void* scratch = nullptr;
  cudaGetSymbolAddress(&scratch, g_scratch);
  fused_kernel<<<N_CTA, THREADS, SM_TOTAL>>>((const __nv_bfloat16*)d_in[0], (const __nv_bfloat16*)d_in[6], (const __nv_bfloat16*)d_in[1],
                                            (const __nv_bfloat16*)d_in[2], (__nv_bfloat16*)d_out, (Scratch*)scratch, tmX, tmWq, tmKV,
                                            tmWo, tmG, tmU, tmD, tmX16, tmWq96, tmX64);
}
```

```cpp
#include <cuda_runtime.h>
#include <cuda_bf16.h>
#include <cuda.h>
#include <stdint.h>

#define X_PFW 1
#define X_SPLIT 38
#define X_SPLITA 36
#define X_SPLITS 32
#define X_SPLITSA 30
#define X_PA 8
#define X_PG 4
#define X_E0 10
#define X_F2 12
#define X_Q1 8
#define X_LN 0
#define X_WAKE 31
#define X_F1 4
#define X_BF2 1
#define X_SQI 4
#define X_SQS 300
#define X_ORD 3
#define X_QP 2
#define X_QC 2
#define X_NS 4
namespace {

constexpr int SEQ = 2048, DM = 576, DH = 128, FF = 4608, TOPC = 8;
constexpr int N_ATT_CTA = 128, N_CTA = 132;
constexpr int THREADS = 384;

constexpr uint32_t SM_RING = 0;
constexpr uint32_t STAGE = 32768;
constexpr uint32_t SM_SLOT = 131072;
constexpr uint32_t FSTAGE = 24576;
constexpr uint32_t SM_XSEL = 196608;
constexpr uint32_t SM_H = 205824;
constexpr uint32_t SM_MISC = 229376;
constexpr uint32_t SM_FULL = SM_MISC, SM_EMPTY = SM_MISC + 32, SM_FFULL = SM_MISC + 64, SM_BAR_MISC = SM_MISC + 128,
                   SM_COLD = SM_MISC + 136, SM_TAG = SM_MISC + 144, SM_BAR_W = SM_MISC + 152, SM_ONES = SM_MISC + 160,
                   SM_BAR_Q = SM_MISC + 176, SM_XFULL = SM_MISC + 192, SM_BAR_XG = SM_MISC + 304, SM_BAR_SQ = SM_MISC + 312,
                   SM_STATS = SM_MISC + 320, SM_FEMPTY = SM_MISC + 1344, SM_RAW = SM_FEMPTY, SM_WR = SM_MISC + 1408, SM_TOPK = SM_WR;
constexpr uint32_t SM_TOTAL = SM_MISC + 2560;
constexpr uint32_t SM_X = SM_MISC - 147456;

constexpr int BAR_GATE = 6, BAR_HELPER = 7, BAR_OA = 8, BAR_XREL = 13, BAR_QS = 9, BAR_QF = 11;
constexpr int NST_Q = 18, NST_KV = 76, NST_O = 18;
constexpr float SM_SCALE_LOG2 = 0.08838834764831845f * 1.4426950408889634f;

struct Scratch {
  uint4 part[16 * 64 * 2 * 4 * 128];
  uint4 gate[N_ATT_CTA * 1152];
  uint4 q[16 * 8 * 2 * 512];
  uint2 sq[SEQ];
  uint4 stats[SEQ];
  float ypart[4 * TOPC * DM];
  int2 sel[16];
  unsigned launch[160];
  unsigned pad0, ycnt, pad[30];
  unsigned qflag[128];
};
__device__ __align__(1024) Scratch g_scratch;

__device__ __forceinline__ void prof(int, int, int = 0) {}

#define TS(id) {}
#define TS_DUMP() {}
#define TSH(k) {}
#define TS4(k) {}
#define TSP(k) {}
#define TS1(id) TS(id)
#define TS2(k) {}
#define TS3(k) {}

__device__ __forceinline__ uint32_t smem_u32(const void* p) { return (uint32_t)__cvta_generic_to_shared(p); }
__device__ __forceinline__ void mbar_init(uint32_t bar, uint32_t cnt) {
  asm volatile("mbarrier.init.shared::cta.b64 [%0], %1;" ::"r"(bar), "r"(cnt) : "memory");
}
__device__ __forceinline__ void mbar_expect_tx(uint32_t bar, uint32_t bytes) {
  asm volatile("mbarrier.arrive.expect_tx.shared::cta.b64 _, [%0], %1;" ::"r"(bar), "r"(bytes) : "memory");
}
__device__ __forceinline__ void mbar_arrive(uint32_t bar) {
  asm volatile("mbarrier.arrive.shared::cta.b64 _, [%0];" ::"r"(bar) : "memory");
}
__device__ __forceinline__ void mbar_arrive_cluster(uint32_t bar_cluster_addr, bool pred) {
  asm volatile("{\n.reg .pred p;\nsetp.ne.u32 p, %1, 0;\n@p mbarrier.arrive.shared::cluster.b64 _, [%0];\n}"
               ::"r"(bar_cluster_addr), "r"((uint32_t)pred) : "memory");
}
template <int ID>
__device__ __forceinline__ void mbar_arrive_cluster_now(uint32_t bar_cluster_addr, bool pred) {
  asm volatile("{\n.reg .pred p, q;\nsetp.ne.u32 p, %1, 0;\nsetp.eq.u32 q, %2, %3;\n"
               "ARR_LOOP:\n@p mbarrier.arrive.shared::cluster.b64 _, [%0];\n@q bra.uni ARR_LOOP;\n}"
               ::"r"(bar_cluster_addr), "r"((uint32_t)pred), "r"(blockIdx.y), "n"(ID) : "memory");
}
__device__ __forceinline__ void block_fence(int id) {
  asm volatile("{\n.reg .pred q;\nsetp.eq.u32 q, %0, %1;\nBF_LOOP:\n@q st.volatile.shared.u32 [%0], %0;\n@q bra.uni BF_LOOP;\n}"
               ::"r"(blockIdx.y), "r"(id) : "memory");
}
__device__ __forceinline__ void mbar_wait(uint32_t bar, uint32_t parity) {
  asm volatile("{\n.reg .pred p, q;\n.reg .u32 n;\nmov.u32 n, 0;\n"
               "WAIT_LOOP:\nmbarrier.try_wait.parity.shared::cta.b64 p, [%0], %1;\n"
               "add.u32 n, n, 1;\nsetp.lt.u32 q, n, 4194304;\nand.pred q, q, !p;\n@q bra WAIT_LOOP;\n}"
               ::"r"(bar), "r"(parity) : "memory");
}
__device__ __forceinline__ uint32_t mapa(uint32_t addr, uint32_t rank) {
  uint32_t r;
  asm volatile("mapa.shared::cluster.u32 %0, %1, %2;" : "=r"(r) : "r"(addr), "r"(rank));
  return r;
}
__device__ __forceinline__ void cluster_arrive() { asm volatile("barrier.cluster.arrive.relaxed.aligned;" ::: "memory"); }
__device__ __forceinline__ bool elect_one() {
  uint32_t p;
  asm volatile("{\n.reg .pred p;\nelect.sync _|p, 0xffffffff;\nselp.u32 %0, 1, 0, p;\n}" : "=r"(p));
  return p;
}
__device__ __forceinline__ int read_lane() { return threadIdx.x & 31; }
__device__ __forceinline__ int fresh_lane() {
  int l;
  asm volatile("mov.u32 %0, %%laneid;" : "=r"(l));
  return l;
}
template <class T> __device__ __forceinline__ T* at(T* p, uint32_t bytes) {
  asm("" : "+r"(bytes));
  return (T*)((const char*)p + bytes);
}
__device__ __forceinline__ void cluster_wait() { asm volatile("barrier.cluster.wait.acquire.aligned;" ::: "memory"); }
__device__ __forceinline__ void bar_sync(int id, int n) { asm volatile("barrier.cta.sync %0, %1;" ::"r"(id), "r"(n) : "memory"); }
__device__ __forceinline__ void bar_arrive(int id, int n) { asm volatile("barrier.cta.arrive %0, %1;" ::"r"(id), "r"(n) : "memory"); }

__device__ __forceinline__ uint64_t policy_evict_first() {
  uint64_t p;
  asm("createpolicy.fractional.L2::evict_first.b64 %0, 1.0;" : "=l"(p));
  return p;
}
__device__ __forceinline__ void tma2d_mc(uint32_t dst, const CUtensorMap* tm, int c0, int c1, uint32_t bar, uint64_t pol) {
  asm volatile("cp.async.bulk.tensor.2d.shared::cluster.global.mbarrier::complete_tx::bytes.multicast::cluster.L2::cache_hint"
               " [%0], [%1, {%2, %3}], [%4], %5, %6;"
               ::"r"(dst), "l"(tm), "r"(c0), "r"(c1), "r"(bar), "h"((uint16_t)3), "l"(pol) : "memory");
}
__device__ __forceinline__ void tma3d(uint32_t dst, const CUtensorMap* tm, int c1, int c2, uint32_t bar) {
  asm volatile("cp.async.bulk.tensor.3d.shared::cluster.global.mbarrier::complete_tx::bytes [%0], [%1, {%2, %3, %4}], [%5];"
               ::"r"(dst), "l"(tm), "r"(0), "r"(c1), "r"(c2), "r"(bar) : "memory");
}
__device__ __forceinline__ void tma2d(uint32_t dst, const CUtensorMap* tm, int c0, int c1, uint32_t bar) {
  asm volatile("cp.async.bulk.tensor.2d.shared::cluster.global.mbarrier::complete_tx::bytes [%0], [%1, {%2, %3}], [%4];"
               ::"r"(dst), "l"(tm), "r"(c0), "r"(c1), "r"(bar) : "memory");
}
__device__ __forceinline__ void tma2d_stream(uint32_t dst, const CUtensorMap* tm, int c0, int c1, uint32_t bar) {
  asm volatile("{\n.reg .b64 pol;\ncreatepolicy.fractional.L2::evict_first.b64 pol, 1.0;\n"
               "cp.async.bulk.tensor.2d.shared::cluster.global.mbarrier::complete_tx::bytes.L2::cache_hint [%0], [%1, {%2, %3}], [%4], pol;\n}"
               ::"r"(dst), "l"(tm), "r"(c0), "r"(c1), "r"(bar) : "memory");
}
__device__ __forceinline__ void bulk_load(uint32_t dst, const void* src, uint32_t bytes, uint32_t bar) {
  asm volatile("cp.async.bulk.shared::cluster.global.mbarrier::complete_tx::bytes [%0], [%1], %2, [%3];"
               ::"r"(dst), "l"(src), "r"(bytes), "r"(bar) : "memory");
}
__device__ __forceinline__ void tma2d_prefetch(const CUtensorMap* tm, int c0, int c1) {
  asm volatile("cp.async.bulk.prefetch.tensor.2d.L2.global [%0, {%1, %2}];" ::"l"(tm), "r"(c0), "r"(c1) : "memory");
}

__device__ __forceinline__ void wg_fence() { asm volatile("wgmma.fence.sync.aligned;" ::: "memory"); }
__device__ __forceinline__ void wg_commit() { asm volatile("wgmma.commit_group.sync.aligned;" ::: "memory"); }
template <int N> __device__ __forceinline__ void wg_wait() { asm volatile("wgmma.wait_group.sync.aligned %0;" ::"n"(N) : "memory"); }

__device__ __forceinline__ uint64_t mkdesc(uint32_t addr, uint32_t lbo_bytes) {
  return (uint64_t)(((addr & 0x3FFFF) >> 4) | ((lbo_bytes >> 4) << 16)) | ((uint64_t)0x40000040u << 32);
}
__device__ __forceinline__ uint64_t mkdesc_q(uint32_t addr) {
  return (uint64_t)(((addr & 0x3FFFF) >> 4) | (64u << 16)) | ((uint64_t)8 << 32);
}
template <int N> __device__ __forceinline__ void pin(float (&a)[N]) {
#pragma unroll
  for (int i = 0; i < N; i++) asm volatile("" : "+f"(a[i])::"memory");
}
template <int N> __device__ __forceinline__ void kill(float (&a)[N]) {
#pragma unroll
  for (int i = 0; i < N; i++) asm volatile("" : "=f"(a[i]));
}
template <int N> __device__ __forceinline__ void pin(uint32_t (&a)[N]) {
#pragma unroll
  for (int i = 0; i < N; i++) asm volatile("" : "+r"(a[i])::"memory");
}

#define F8(d, o) "+f"(d[o]), "+f"(d[o + 1]), "+f"(d[o + 2]), "+f"(d[o + 3]), "+f"(d[o + 4]), "+f"(d[o + 5]), "+f"(d[o + 6]), "+f"(d[o + 7])
#define R32A "%0, %1, %2, %3, %4, %5, %6, %7, %8, %9, %10, %11, %12, %13, %14, %15, %16, %17, %18, %19, %20, %21, %22, %23, %24, %25, %26, %27, %28, %29, %30, %31"
#define R32B "%32, %33, %34, %35, %36, %37, %38, %39, %40, %41, %42, %43, %44, %45, %46, %47, %48, %49, %50, %51, %52, %53, %54, %55, %56, %57, %58, %59, %60, %61, %62, %63"

#define O8(d, o) "=f"(d[o]), "=f"(d[o + 1]), "=f"(d[o + 2]), "=f"(d[o + 3]), "=f"(d[o + 4]), "=f"(d[o + 5]), "=f"(d[o + 6]), "=f"(d[o + 7])

__device__ __forceinline__ void mma_n128t(float (&d)[64], uint32_t a0, uint32_t a1, uint32_t a2, uint32_t a3, uint64_t db, bool acc) {
  if (acc)
    asm volatile("wgmma.mma_async.sync.aligned.m64n128k16.f32.bf16.bf16 {" R32A ", " R32B "}, {%64, %65, %66, %67}, %68, 1, 1, 1, 1;\n"
                 : F8(d, 0), F8(d, 8), F8(d, 16), F8(d, 24), F8(d, 32), F8(d, 40), F8(d, 48), F8(d, 56)
                 : "r"(a0), "r"(a1), "r"(a2), "r"(a3), "l"(db));
  else
    asm volatile("wgmma.mma_async.sync.aligned.m64n128k16.f32.bf16.bf16 {" R32A ", " R32B "}, {%64, %65, %66, %67}, %68, 0, 1, 1, 1;\n"
                 : O8(d, 0), O8(d, 8), O8(d, 16), O8(d, 24), O8(d, 32), O8(d, 40), O8(d, 48), O8(d, 56)
                 : "r"(a0), "r"(a1), "r"(a2), "r"(a3), "l"(db));
}
#define PV1(a0, a1, a2, a3, ob, acc) "add.s64 b, %92, " #ob ";\n" \
  "wgmma.mma_async.sync.aligned.m64n128k16.f32.bf16.bf16 {" R32A ", " R32B "}, {%" #a0 ", %" #a1 ", %" #a2 ", %" #a3 "}, b, " #acc ", 1, 1, 1;\n"
#define PV6 "wgmma.fence.sync.aligned;\n" PV1(64, 65, 66, 67, 0, p) PV1(68, 69, 70, 71, 128, 1) PV1(72, 73, 74, 75, 256, 1) \
  PV1(76, 77, 78, 79, 384, 1) PV1(80, 81, 82, 83, 512, 1) PV1(84, 85, 86, 87, 640, 1)
#define U4(a, o) "r"(a[o]), "r"(a[o + 1]), "r"(a[o + 2]), "r"(a[o + 3])
__device__ __forceinline__ void mma_pv(float (&d)[64], const uint32_t (&a)[28], uint64_t dv, bool acc, bool big) {
  asm volatile("{\n.reg .pred p, q;\n.reg .b64 b;\nsetp.ne.b32 p, %93, 0;\nsetp.eq.b32 q, %94, 0;\n@q bra.uni PV_SMALL;\n"
               PV6 PV1(88, 89, 90, 91, 768, 1) "wgmma.commit_group.sync.aligned;\nbra.uni PV_DONE;\n"
               "PV_SMALL:\n" PV6 "wgmma.commit_group.sync.aligned;\nPV_DONE:\n}\n"
               : F8(d, 0), F8(d, 8), F8(d, 16), F8(d, 24), F8(d, 32), F8(d, 40), F8(d, 48), F8(d, 56)
               : U4(a, 0), U4(a, 4), U4(a, 8), U4(a, 12), U4(a, 16), U4(a, 20), U4(a, 24), "l"(dv), "r"((int)acc), "r"((int)big) : "memory");
}
#define R48 R32A ", %32, %33, %34, %35, %36, %37, %38, %39, %40, %41, %42, %43, %44, %45, %46, %47"
#define R56 R48 ", %48, %49, %50, %51, %52, %53, %54, %55"
#define QK1(N, R, A, B, oa, ob, acc) "add.s64 a, " A ", " #oa ";\nadd.s64 b, " B ", " #ob ";\n" \
  "wgmma.mma_async.sync.aligned.m64n" #N "k16.f32.bf16.bf16 {" R "}, a, b, " #acc ", 1, 1, 0, 0;\n"
#define QK8(N, R, A, B) "{\n.reg .b64 a, b;\nwgmma.fence.sync.aligned;\n" QK1(N, R, A, B, 0, 0, 0) QK1(N, R, A, B, 128, 2, 1) \
  QK1(N, R, A, B, 256, 4, 1) QK1(N, R, A, B, 384, 6, 1) QK1(N, R, A, B, 512, 1024, 1) QK1(N, R, A, B, 640, 1026, 1) \
  QK1(N, R, A, B, 768, 1028, 1) QK1(N, R, A, B, 896, 1030, 1) "wgmma.commit_group.sync.aligned;\n}\n"
__device__ __forceinline__ void mma_qk(float (&d)[56], uint64_t dq, uint64_t dk) {
  asm volatile(QK8(112, R56, "%56", "%57")
               : O8(d, 0), O8(d, 8), O8(d, 16), O8(d, 24), O8(d, 32), O8(d, 40), O8(d, 48) : "l"(dq), "l"(dk) : "memory");
}
__device__ __forceinline__ void mma_qk(float (&d)[48], uint64_t dq, uint64_t dk) {
  asm volatile(QK8(96, R48, "%48", "%49")
               : O8(d, 0), O8(d, 8), O8(d, 16), O8(d, 24), O8(d, 32), O8(d, 40) : "l"(dq), "l"(dk) : "memory");
}
__device__ __forceinline__ void mma_n64t(float (&d)[32], uint32_t a0, uint32_t a1, uint32_t a2, uint32_t a3, uint64_t db, bool acc) {
  if (acc)
    asm volatile("wgmma.mma_async.sync.aligned.m64n64k16.f32.bf16.bf16 {" R32A "}, {%32, %33, %34, %35}, %36, 1, 1, 1, 1;\n"
                 : F8(d, 0), F8(d, 8), F8(d, 16), F8(d, 24) : "r"(a0), "r"(a1), "r"(a2), "r"(a3), "l"(db));
  else
    asm volatile("wgmma.mma_async.sync.aligned.m64n64k16.f32.bf16.bf16 {" R32A "}, {%32, %33, %34, %35}, %36, 0, 1, 1, 1;\n"
                 : O8(d, 0), O8(d, 8), O8(d, 16), O8(d, 24) : "r"(a0), "r"(a1), "r"(a2), "r"(a3), "l"(db));
}
__device__ __forceinline__ void mma_n64t_dyn(float (&d)[32], uint32_t a0, uint32_t a1, uint32_t a2, uint32_t a3, uint64_t db, int acc) {
  asm volatile("{\n.reg .pred p;\nsetp.ne.b32 p, %37, 0;\n"
               "wgmma.mma_async.sync.aligned.m64n64k16.f32.bf16.bf16 {" R32A "}, {%32, %33, %34, %35}, %36, p, 1, 1, 1;\n}\n"
               : F8(d, 0), F8(d, 8), F8(d, 16), F8(d, 24) : "r"(a0), "r"(a1), "r"(a2), "r"(a3), "l"(db), "r"(acc));
}
__device__ __forceinline__ void mma_n8(float (&d)[4], uint64_t da, uint64_t db, int acc) {
  asm volatile("{\n.reg .pred p;\nsetp.ne.b32 p, %6, 0;\n"
               "wgmma.mma_async.sync.aligned.m64n8k16.f32.bf16.bf16 {%0, %1, %2, %3}, %4, %5, p, 1, 1, 1, 0;\n}\n"
               : "+f"(d[0]), "+f"(d[1]), "+f"(d[2]), "+f"(d[3])
               : "l"(da), "l"(db), "r"(acc));
}
__device__ __forceinline__ void hmma_k16(float (&d)[4], uint32_t a0, uint32_t a1, uint32_t a2, uint32_t a3, uint32_t b0, uint32_t b1) {
  asm volatile("mma.sync.aligned.m16n8k16.row.col.f32.bf16.bf16.f32 {%0, %1, %2, %3}, {%4, %5, %6, %7}, {%8, %9}, {%0, %1, %2, %3};"
               : "+f"(d[0]), "+f"(d[1]), "+f"(d[2]), "+f"(d[3]) : "r"(a0), "r"(a1), "r"(a2), "r"(a3), "r"(b0), "r"(b1));
}

__device__ __forceinline__ uint32_t pack2(float lo, float hi) {
  uint32_t r;
  asm("cvt.rn.bf16x2.f32 %0, %1, %2;" : "=r"(r) : "f"(hi), "f"(lo));
  return r;
}
__device__ __forceinline__ float bf_lo(uint32_t w) { return __uint_as_float(w << 16); }
__device__ __forceinline__ float bf_hi(uint32_t w) { return __uint_as_float(w & 0xFFFF0000u); }
__device__ __forceinline__ float bfr(float x) { return __bfloat162float(__float2bfloat16_rn(x)); }
__device__ __forceinline__ uint32_t sub2(uint32_t a, uint32_t b) {
  uint32_t r;
  asm("sub.rn.bf16x2 %0, %1, %2;" : "=r"(r) : "r"(a), "r"(b));
  return r;
}
__device__ __forceinline__ uint32_t add2(uint32_t a, uint32_t b) {
  uint32_t r;
  asm("add.rn.bf16x2 %0, %1, %2;" : "=r"(r) : "r"(a), "r"(b));
  return r;
}
__device__ __forceinline__ uint32_t fma2(uint32_t a, uint32_t b, uint32_t c) {
  uint32_t r;
  asm("fma.rn.bf16x2 %0, %1, %2, %3;" : "=r"(r) : "r"(a), "r"(b), "r"(c));
  return r;
}
__device__ __forceinline__ float ex2(float x) {
  float r;
  asm("ex2.approx.ftz.f32 %0, %1;" : "=f"(r) : "f"(x));
  return r;
}
__device__ __forceinline__ float rcp(float x) {
  float r;
  asm("rcp.approx.ftz.f32 %0, %1;" : "=f"(r) : "f"(x));
  return r;
}
__device__ __forceinline__ float silu_f(float t) { return t * rcp(1.0f + ex2(-1.4426950408889634f * t)); }
__device__ __forceinline__ void lds128(uint32_t a, uint32_t& x, uint32_t& y, uint32_t& z, uint32_t& w) {
  asm volatile("ld.shared.v4.u32 {%0, %1, %2, %3}, [%4];" : "=r"(x), "=r"(y), "=r"(z), "=r"(w) : "r"(a) : "memory");
}
__device__ __forceinline__ void ldsm4(uint32_t a, uint32_t& x, uint32_t& y, uint32_t& z, uint32_t& w) {
  asm volatile("ldmatrix.sync.aligned.m8n8.x4.shared.b16 {%0, %1, %2, %3}, [%4];" : "=r"(x), "=r"(y), "=r"(z), "=r"(w) : "r"(a) : "memory");
}
constexpr uint32_t TAG = 0x10000;
__device__ __forceinline__ void st_gran(uint4* p, uint32_t x, uint32_t y, uint32_t z, uint32_t w) {
  asm volatile("st.relaxed.gpu.global.v4.b32 [%0], {%1, %2, %3, %4};" ::"l"(p), "r"(x), "r"(y), "r"(z), "r"(w) : "memory");
}
__device__ __forceinline__ void ld_gran(const uint4* p, uint32_t& x, uint32_t& y, uint32_t& z, uint32_t& w) {
  asm volatile("ld.relaxed.gpu.global.v4.b32 {%0, %1, %2, %3}, [%4];" : "=r"(x), "=r"(y), "=r"(z), "=r"(w) : "l"(p) : "memory");
}
__device__ __forceinline__ void stsm4(uint32_t a, uint32_t x, uint32_t y, uint32_t z, uint32_t w) {
  asm volatile("stmatrix.sync.aligned.m8n8.x4.shared.b16 [%0], {%1, %2, %3, %4};" ::"r"(a), "r"(x), "r"(y), "r"(z), "r"(w) : "memory");
}
__device__ __forceinline__ void cp16(uint32_t dst, const void* src) {
  asm volatile("cp.async.cg.shared.global [%0], [%1], 16;" ::"r"(dst), "l"(src) : "memory");
}
__device__ __forceinline__ void cp_wait_all() { asm volatile("cp.async.wait_all;" ::: "memory"); }
__device__ __forceinline__ void add_granules(float (&red)[32], const uint32_t (&g)[16]) {
#pragma unroll
  for (int i = 0; i < 16; i++) { red[2 * i] += bf_lo(g[i]); red[2 * i + 1] += bf_hi((i & 3) ? g[i] : g[i] & ~TAG); }
}
__device__ __forceinline__ bool granules_ok(const uint32_t (&g)[16], uint32_t tag) {
  uint32_t a, b;
  asm("lop3.b32 %0, %1, %2, %3, 0x7E;" : "=r"(a) : "r"(g[0]), "r"(g[4]), "r"(tag));
  asm("lop3.b32 %0, %1, %2, %3, 0x7E;" : "=r"(b) : "r"(g[8]), "r"(g[12]), "r"(tag));
  return __all_sync(0xffffffffu, ((a | b) & TAG) == 0);
}
__device__ __forceinline__ unsigned ld_acquire(const unsigned* p) {
  unsigned v;
  asm volatile("ld.acquire.gpu.global.u32 %0, [%1];" : "=r"(v) : "l"(p) : "memory");
  return v;
}
__device__ __forceinline__ unsigned atom_add_acq_rel(unsigned* p) {
  unsigned v;
  asm volatile("atom.acq_rel.gpu.global.add.u32 %0, [%1], 1;" : "=r"(v) : "l"(p) : "memory");
  return v;
}

template <int K0, int K1>
__device__ __forceinline__ void ln_fetch(uint32_t (&xa)[144], uint32_t boxes, uint32_t lo) {
#pragma unroll
  for (int k = K0; k < K1; k++) ldsm4(boxes + (k >> 2) * 8192 + (lo ^ ((k & 3) << 5)), xa[4 * k], xa[4 * k + 1], xa[4 * k + 2], xa[4 * k + 3]);
}
__device__ __forceinline__ void ln_fetch_b(uint32_t (&b)[24], uint32_t& wb, uint32_t ws) {
#pragma unroll
  for (int j = 0; j < 6; j++, wb += ws) ldsm4(wb, b[4 * j], b[4 * j + 1], b[4 * j + 2], b[4 * j + 3]);
}
template <int K0, int K1>
__device__ __forceinline__ void ln_sums(const uint32_t (&xa)[144], float (&sm)[X_NS][4], const uint32_t (&b)[24]) {
#pragma unroll
  for (int k = K0; k < K1; k++)
    hmma_k16(sm[k % X_NS], xa[4 * k], xa[4 * k + 1], xa[4 * k + 2], xa[4 * k + 3], b[2 * (k % 12)], b[2 * (k % 12) + 1]);
}
__device__ __forceinline__ void ln_row(float sum, float sq, float& mean_b, float& rstd) {
  const float mean = sum * (1.0f / DM);
  const uint32_t mv = pack2(mean, fmaxf(sq * (1.0f / DM) - mean * mean, 0.0f));
  mean_b = bf_lo(mv);
  float sd;
  asm("sqrt.approx.f32 %0, %1;" : "=f"(sd) : "f"(bf_lo(pack2(bf_hi(mv) + 1e-5f, 0.f))));
  rstd = rcp(bf_lo(pack2(sd, 0.f)));
}

template <bool ROUTED>
__device__ __forceinline__ uint32_t gate2(uint32_t xc, float rstd, float2 upd = make_float2(0.f, 0.f)) {
  uint32_t t = pack2(bf_lo(xc) * rstd, bf_hi(xc) * rstd);
  if (ROUTED) t = pack2(bf_lo(t) + upd.x, bf_hi(t) + upd.y);
  return pack2(silu_f(bf_lo(t)), silu_f(bf_hi(t)));
}

template <int V> struct IC { static constexpr int value = V; };

struct Ctx {
  uint32_t sb;
  uint8_t* sp;
  uint32_t rank;
  Scratch* g;
};

__device__ __forceinline__ bool acquire(const Ctx& cx, uint32_t r, uint32_t n, uint32_t bytes) {
  mbar_wait(cx.sb + SM_EMPTY + 8 * r, (n ^ (r >> 1) ^ 1) & 1);
  __syncwarp();
  const bool e = elect_one();
  if (e) mbar_expect_tx(cx.sb + SM_FULL + 8 * r, bytes);
  return e;
}
__device__ __forceinline__ void load_wq(const Ctx& cx, const CUtensorMap* tmWq, int st, int i, int n0, uint64_t pol) {
  const uint32_t r = st & 3, dst = cx.sb + SM_RING + r * STAGE + cx.rank * 16384, bar = cx.sb + SM_FULL + 8 * r;
  const int k0 = i < 3 ? 128 * i : 128 * i - 64;
  if (acquire(cx, r, st >> 2, i == 2 ? 16384 : 32768)) {
    tma2d_mc(dst, tmWq, n0, k0, bar, pol);
    if (i != 2) tma2d_mc(dst + 8192, tmWq, n0, k0 + 64, bar, pol);
  }
}
__device__ __forceinline__ void attn_producer(const Ctx& cx, int qb, int hs, const CUtensorMap* tmKV, const CUtensorMap* tmWq,
                                              const CUtensorMap* tmWq96, const CUtensorMap* tmWo) {
  const uint32_t full = cx.sb + SM_FULL, ring = cx.sb + SM_RING + cx.rank * 16384;
  const uint64_t last_use = policy_evict_first();
  int st = 0;
#pragma unroll 1
  for (int p = 0; p < 4; p++) {
#pragma unroll 1
    for (int i = 0; i < (p == 2 ? 3 : 5); i++, st++) {
      if (p == 2) {
        if (acquire(cx, st & 3, st >> 2, 24576))
          tma2d_mc(cx.sb + SM_RING + (st & 3) * STAGE + cx.rank * 12288, tmWq96, (hs * 4 + 3) * DH, 192 * i + 96 * cx.rank, full + 8 * (st & 3), last_use);
      } else {
        if (st > 1) load_wq(cx, tmWq, st, i, (hs * 4 + (p ^ (p >> 1))) * DH + cx.rank * 64, last_use);
      }
      if (st == 1 || st == 2) TSP(72 + st)
      if (st == X_PFW) {
#pragma unroll 1
        for (int b = qb < 8; b < 5 - (qb >> 3); b++)
          if (elect_one()) tma2d_prefetch(tmWq, hs * 512 + (b < 4 ? (b ^ (b >> 1)) * DH + (qb & 1) * 64 : qb * 64), b < 4 ? (qb >> 1) * 64 : 512);
      }
      if (st == 8 && qb < 8 && elect_one()) tma2d_prefetch(tmKV + ((qb >> 1) & 1), cx.rank * 64, hs * 2 * SEQ + (qb >> 2) * 96);
    }
  }
  uint32_t r = 2, n = 4;
  int row = hs * 2 * SEQ, rows = 96;
  const CUtensorMap* tm = tmKV + 2;
#pragma unroll 1
  for (int u = 0; u < NST_KV; u++) {
    if (acquire(cx, r, n, rows * 256)) {
      tma2d_mc(ring + r * STAGE, tm, cx.rank * 64, row, full + 8 * r, last_use);
      if (((u ^ (qb >> 1)) & 7) == 0 && u < NST_KV - 4) tma2d_prefetch(tmKV + (u & 1), cx.rank * 64, row + 208);
      if ((unsigned)(u - 32) < 36 && (u & 15) == qb) tma2d_prefetch(tmWo, ((u - 32) >> 2) * 64, hs * 512 + (u & 3) * 128);
    }
    if (++r == 4) { r = 1; n++; }
    if (u & 1) row += rows;
    const bool big = (unsigned)(u - 9) < 56;
    rows = big ? 112 : 96;
    tm = tmKV + (~u & 1) + (big ? 0 : 2);
  }
#pragma unroll 1
  for (int u = 0; u < NST_O; u++) {
    const int s = u >> 1;
    const int blk = s == 0 ? 8 : ((hs + s) & 7);
    r = (0x87 >> (2 * (u & 3))) & 3;
    if (acquire(cx, r, (u >> 2) ^ ~u, 32768))
      tma2d_mc(ring + r * STAGE, tmWo, blk * 64, hs * 512 + ((u & 1) + cx.rank * 2) * 128, full + 8 * r, last_use);
  }
}

__device__ __forceinline__ void sq_publish(const Ctx& cx, int qb, int hs, int j, int lane) {
  if (j == 2 && lane == 0) {
    const unsigned e = cx.g->launch[hs * 16 + qb]++;
    *(uint2*)(cx.sp + SM_TAG) = make_uint2((~e & 1) * TAG, e);
  }
  const int row = (hs & 3) * 16 + (lane >> 1);
  uint32_t a = cx.sb + SM_X + (hs >> 2) * 73728 + j * 8192 + row * 128 + (((lane & 1) ^ (row & 7)) << 4);
  float s0 = 0.f, s1 = 0.f;
#pragma unroll 1
  for (int b = 0; b < 6; b++) {
    if (b == (hs < 4 ? 4 : 0)) {
      const int n = 224 + (__float_as_uint(s1) & blockIdx.y);
      if (j == 1) {
        bar_sync(BAR_XREL, n);
        if (lane < 4) asm volatile("mbarrier.arrive.shared::cluster.b64 _, [%0], 2;" ::"r"(mapa(cx.sb + SM_EMPTY + 16 + 8 * (lane >> 1), lane & 1)) : "memory");
      } else {
        bar_arrive(BAR_XREL, n);
      }
      __syncwarp();
      if (hs == 8) return;
    }
    if (!(b & 1)) mbar_wait(cx.sb + SM_XFULL + 32 * (hs >> 2) + 4 * b, 0);
    uint32_t v[8];
    lds128(a, v[0], v[1], v[2], v[3]);
    lds128(a ^ 32, v[4], v[5], v[6], v[7]);
    a = (a ^ 64) + (b & 1) * 24576;
#pragma unroll
    for (int i = 0; i < 8; i++) { s0 = fmaf(bf_lo(v[i]), bf_lo(v[i]), s0); s1 = fmaf(bf_hi(v[i]), bf_hi(v[i]), s1); }
  }
  s0 += s1;
  s0 += __shfl_xor_sync(0xffffffffu, s0, 1);
  float* part = (float*)(cx.sp + SM_STATS) + (lane >> 1) * 2;
  if (j < 2) {
    part[32 * j] = s0;
    bar_arrive(BAR_HELPER, 96);
  } else {
    bar_sync(BAR_HELPER, 96);
    TSP(68)
    if (!(lane & 1))
      asm volatile("st.relaxed.gpu.global.v2.b32 [%0], {%1, %2};" ::"l"(cx.g->sq + qb * 128 + hs * 16 + (lane >> 1)),
                   "r"(__float_as_uint((part[0] + part[32]) + s0)), "r"(*(const uint32_t*)(cx.sp + SM_TAG + 4) + 1) : "memory");
  }
}
__device__ __forceinline__ void sq_collect(const Ctx& cx, int qb, int lane) {
  const uint32_t e1 = *(const uint32_t*)(cx.sp + SM_TAG + 4) + 1;
#pragma unroll 1
  for (int n = 0; n < (1 << 16); n++) {
    __nanosleep(X_SQS);
    uint32_t bad = 0;
#pragma unroll
    for (int i = 0; i < 2; i++) {
      uint32_t a, t0, b, t1;
      ld_gran((const uint4*)at(cx.g->sq, qb * 1024 + lane * 16) + i * 32, a, t0, b, t1);
      *(uint32_t*)(cx.sp + SM_STATS + (i * 32 + lane) * 16 + 4) = a;
      *(uint32_t*)(cx.sp + SM_STATS + (i * 32 + lane) * 16 + 12) = b;
      bad |= (t0 ^ e1) | (t1 ^ e1);
    }
    if (__all_sync(0xffffffffu, bad == 0)) break;
  }
  __syncwarp();
  if (lane == 0) mbar_arrive(cx.sb + SM_BAR_SQ);
  TSP(69)
}
__device__ __forceinline__ void attn_gate(const Ctx& cx, int qb, int hs, int j, int t, const __nv_bfloat16* x) {
  const uint4* xp = (const uint4*)(x + qb * 128 * DM) + (t >> 3) * 72 + hs * 8 + (t & 7);
  uint4 nx = *xp;
  float wsum = 0.f;
  if (j == 0) {
    mbar_wait(cx.sb + SM_BAR_W, 0);
#pragma unroll 3
    for (int i = 0; i < 9; i++) {
      const uint32_t w = *(const uint32_t*)(cx.sp + SM_WR + i * 128 + t * 4);
      wsum += bf_lo(w) + bf_hi(w);
    }
#pragma unroll
    for (int i = 1; i < 32; i *= 2) wsum += __shfl_xor_sync(0xffffffffu, wsum, i);
  }
  bar_sync(BAR_GATE, 352);
  if (t < 16) {
    const float2 st = *(const float2*)(cx.sp + SM_STATS + 8 * (hs * 16 + t));
    const int row = qb * 128 + hs * 16 + t;
    const uint32_t b = pack2(0.f, fmaf(-st.x, wsum, *(const float*)(cx.sp + SM_RAW + 4 * t)) * st.y);
    st_gran(at(cx.g->stats, row * 16), __float_as_uint(st.x), __float_as_uint(st.y), (b ^ ((int)b < 0 ? 0xFFFF0000u : 0x80000000u)) | (0xFFFF - row),
            *(const uint32_t*)(cx.sp + SM_TAG + 4) + 1);
  }
  __syncwarp();
  uint32_t sa = cx.sb + SM_STATS + (t & ~7);
  uint4* gp = cx.g->gate + blockIdx.x * 1152 + (t ^ ((t >> 3) & 7));
  const int cross = t < 64 ? 10 : 9;
#pragma unroll 1
  for (int i = 0; i < 12; i++) {
    float2 st;
    asm volatile("ld.shared.v2.f32 {%0, %1}, [%2];" : "=f"(st.x), "=f"(st.y) : "r"(sa));
    const uint32_t mm = pack2(st.x, st.x);
    const uint4 v = make_uint4(sub2(nx.x, mm), sub2(nx.y, mm), sub2(nx.z, mm), sub2(nx.w, mm));
    xp += 12 * 72;
    sa += 96;
    if (i == cross) { xp += (hs * 16 - 128) * 72 + 64 - hs * 8; sa += (hs * 16 - 128) * 8; }
    if (i < 11) nx = *xp;
    *gp = make_uint4(gate2<false>(v.x, st.y), gate2<false>(v.y, st.y), gate2<false>(v.z, st.y), gate2<false>(v.w, st.y));
    gp = (uint4*)((size_t)(gp + 96) ^ 64);
  }
}

constexpr uint32_t SM_XO = SM_SLOT, SM_GO = SM_SLOT + STAGE, SM_P8 = SM_SLOT + 2 * STAGE;
__device__ __forceinline__ void attn_helper(const Ctx& cx, int qb, int hs, int lane, const CUtensorMap* tmX16) {
  const unsigned e = *(const uint32_t*)(cx.sp + SM_TAG + 4);
  bar_sync(BAR_HELPER, 64);
  bool todo = lane < 2;
#pragma unroll 1
  for (int n = 0; __any_sync(0xffffffffu, todo); n++) {
    if (todo && (ld_acquire(at(cx.g->qflag, ((qb * 4 + (hs >> 1)) * 2 + lane) * 4)) == e + 1 || n == (1 << 16))) {
      asm volatile("fence.proxy.async.global;" ::: "memory");
      mbar_expect_tx(cx.sb + SM_BAR_Q + 8 * lane, 8192);
      bulk_load(cx.sb + SM_SLOT + 2 * STAGE + lane * 16384 + 8192, at(cx.g->q, ((qb * 8 + hs) * 2 + lane) * 8192), 8192, cx.sb + SM_BAR_Q + 8 * lane);
      todo = false;
    }
  }
  const uint32_t tag = (~e & 1) * TAG;
  const uint4* src = cx.g->part + (size_t)((qb * 64 + 56) * 2 + (hs >> 2)) * 4 * 128 + (hs & 3) * 32 + lane;
  const uint32_t stg = cx.sb + SM_P8 + lane * 16;
  bar_sync(BAR_OA, 352);
  asm volatile("fence.proxy.async.global;" ::: "memory");
  if (lane == 0) {
    mbar_expect_tx(cx.sb + SM_BAR_MISC, 2 * 18432);
    bulk_load(cx.sb + SM_GO, cx.g->gate + blockIdx.x * 1152, 18432, cx.sb + SM_BAR_MISC);
#pragma unroll 1
    for (int i = 0; i < 9; i++)
      tma2d(cx.sb + SM_XO + i * 2048, tmX16, i < 8 ? hs * 64 : 512, qb * 128 + (i < 8 ? i : hs) * 16, cx.sb + SM_BAR_MISC);
  }
#pragma unroll 1
  for (int n = 0; n < (1 << 16); n++) {
    __nanosleep(n ? 500 : 2000);
    uint32_t a, b, d, t;
    ld_gran(src - lane + (lane & 7) * (2 * 4 * 128) + 3 * 128 + 31, a, b, d, t);
    if (__all_sync(0xffffffffu, (a & TAG) == tag)) break;
  }
  TSH(46)
#pragma unroll 1
  for (int n = 0; n < (1 << 16); n++) {
#pragma unroll 1
    for (int i = 0; i < 8; i++) {
#pragma unroll
      for (int g = 0; g < 4; g++) cp16(stg + (i * 4 + g) * 512, src + i * (2 * 4 * 128) + g * 128);
    }
    cp_wait_all();
    uint32_t bad = 0;
#pragma unroll 4
    for (int i = 0; i < 32; i++) bad |= *(const volatile uint32_t*)(cx.sp + SM_P8 + lane * 16 + i * 512) ^ tag;
    if (__all_sync(0xffffffffu, (bad & TAG) == 0)) break;
  }
  TSH(47)
#pragma unroll 1
  for (int n = 0; n < (1 << 16) && ld_acquire(&cx.g->ycnt) != 4 * (e + 1); n++) __nanosleep(200);
  const int2 sel = __ldcg(at(cx.g->sel, (lane & 7) * 8));
  const int lr = sel.x - qb * 128;
  uint32_t m = __ballot_sync(0xffffffffu, lane < 16 && ((lane & 8) ? (lr >> 4) == hs : (lr >> 7) == 0));
  mbar_wait(cx.sb + SM_BAR_MISC, 0);
#pragma unroll 1
  for (; m; m &= m - 1) {
    const int i = __ffs(m) - 1, row = __shfl_sync(0xffffffffu, lr, i);
    const float rs = __int_as_float(__shfl_sync(0xffffffffu, sel.y, i));
    const float* p = cx.g->ypart + (i & 7) * DM + (i < 8 ? hs * 64 : 512) + 2 * lane;
    const float2 a = __ldcg((const float2*)p), b = __ldcg((const float2*)(p + TOPC * DM)), c = __ldcg((const float2*)(p + 2 * TOPC * DM)),
                 d = __ldcg((const float2*)(p + 3 * TOPC * DM));
    const uint32_t y = pack2((a.x + b.x) + (c.x + d.x), (a.y + b.y) + (c.y + d.y));
    const uint32_t u = pack2(bf_lo(y) * rs, bf_hi(y) * rs);
    const float2 st = *(const float2*)(cx.sp + SM_STATS + 8 * row);
    const int o = (i < 8 ? row : 128 + (row & 15)) * 128 + ((lane * 4) ^ ((row & 7) << 4));
    *(uint32_t*)(cx.sp + SM_GO + o) = gate2<true>(sub2(*(const uint32_t*)(cx.sp + SM_XO + o), pack2(st.x, st.x)), st.y, make_float2(bf_lo(u), bf_hi(u)));
  }
  __syncwarp();
  if (lane == 0) mbar_arrive(cx.sb + SM_BAR_XG);
  TSH(48)
}
__device__ __forceinline__ void attn_finish8(const Ctx& cx, int qb, int hs, int hw, int lane, __nv_bfloat16* out) {
  bar_sync(BAR_GATE, 96);
#pragma unroll 1
  for (int g = hw; g < 4; g += 3) {
    float acc[8] = {0.f, 0.f, 0.f, 0.f, 0.f, 0.f, 0.f, 0.f};
#pragma unroll 2
    for (int sidx = 0; sidx < 8; sidx++) {
      uint32_t a, b, d, t;
      lds128(cx.sb + SM_P8 + lane * 16 + (sidx * 4 + g) * 512, a, b, d, t);
      acc[0] += bf_lo(a); acc[1] += bf_hi(a & ~TAG); acc[2] += bf_lo(b); acc[3] += bf_hi(b);
      acc[4] += bf_lo(d); acc[5] += bf_hi(d); acc[6] += bf_lo(t); acc[7] += bf_hi(t);
    }
#pragma unroll
    for (int j = 0; j < 4; j++) {
      const int o = (128 + (lane >> 2) + (j & 1) * 8) * 128 + (((2 * g + (j >> 1)) ^ (lane >> 2)) << 4) + (lane & 3) * 4;
      uint32_t* xp = (uint32_t*)(cx.sp + SM_XO + o);
      *xp = fma2(pack2(acc[2 * j], acc[2 * j + 1]), *(const uint32_t*)(cx.sp + SM_GO + o), *xp);
    }
  }
  bar_sync(BAR_GATE, 96);
#pragma unroll 1
  for (int ch = threadIdx.x - 32; ch < 128; ch += 96)
    *(uint4*)at(out, ((qb * 128 + hs * 16 + (ch >> 3)) * DM + 512 + (ch & 7) * 8) * 2) =
        *(const uint4*)(cx.sp + SM_XO + 16384 + (ch ^ ((ch >> 3) & 7)) * 16);
}

__device__ __forceinline__ void ffn_producer(const Ctx& cx, int f, const CUtensorMap* tmWq, const CUtensorMap* tmG,
                                             const CUtensorMap* tmU, const CUtensorMap* tmD) {
  uint64_t keep;
  asm("createpolicy.fractional.L2::evict_normal.b64 %0, 1.0;" : "=l"(keep));
  int st = 0;
#pragma unroll 1
  for (int p = 0; p < 16; p++) {
#pragma unroll 1
    for (int i = 0; i < 5; i++, st++) if (st > 1) load_wq(cx, tmWq, st, i, ((2 * (p & 3) + cx.rank) * 4 + 3) * DH + 64, keep);
  }
  const uint32_t full = cx.sb + SM_FFULL, empty = cx.sb + SM_FEMPTY;
  int pair = 0, u = 0;
#pragma unroll 1
  for (st = 0; st < 14 * 12; st++) {
    const uint32_t sl = st & 7;
    const int unit = pair * 2 + (u & 1), k = u >> 1, k3 = k >= 3 ? k - 3 : k;
    if (unit < 27) {
      mbar_wait(empty + 8 * sl, (st >> 3) & 1);
      __syncwarp();
      if (elect_one()) {
        mbar_expect_tx(full + 8 * sl, FSTAGE);
        if (pair < 9) tma2d_stream(cx.sb + sl * FSTAGE, k < 3 ? tmG : tmU, f * 1152 + unit * 64, k3 * 192, full + 8 * sl);
        else tma2d_stream(cx.sb + sl * FSTAGE, tmD, (unit - 18) * 64, f * 1152 + k * 192, full + 8 * sl);
      }
    }
    if (++u == 12) { u = 0; pair++; }
  }
}
__device__ __forceinline__ void load_x1(uint32_t dst, const CUtensorMap* tmX64, int row, int box, int n, uint32_t bar) {
  mbar_expect_tx(bar, n * 8192);
#pragma unroll 1
  for (int i = 0; i < n; i++) tma2d(dst + i * 8192, tmX64, (box + i) * 64, row, bar);
}
__device__ __forceinline__ void ffn_publish(const Ctx& cx, int f, int w, int lane, const CUtensorMap* tmX64) {
  const uint32_t xs = cx.sb + SM_SLOT + w * 49152, xf = cx.sb + SM_XFULL + w * 32;
#pragma unroll 1
  for (int n = 0; n < 16; n++) {
    const int p = n & 3, row = (f + (n & 12) + 4) * 128 + w * 64;
    if (n < 12 && p == 3) {
      bar_sync(BAR_QS + w, 160);
      if (lane == 0) load_x1(xs, tmX64, row, 4, 4, xf + 8);
      __syncwarp();
    }
    bar_sync(BAR_QS + w, 160);
    const uint32_t e1 = *(const uint32_t*)(cx.sp + SM_TAG + 4) + 1;
    if (lane == 0) {
#pragma unroll
      for (int i = 0; i < 2; i++)
        asm volatile("cp.async.bulk.global.shared::cta.bulk_group [%0], [%1], 8192;"
                     ::"l"(cx.g->q + (((f + (n & 12)) * 8 + 2 * p + i) * 2 + w) * 512), "r"(xs + 32768 + i * 8192) : "memory");
      asm volatile("cp.async.bulk.commit_group;" ::: "memory");
      asm volatile("cp.async.bulk.wait_group.read 0;" ::: "memory");
      if (n < 12 && (p == 0 || p == 3)) load_x1(xs + (p ? 32768 : 0), tmX64, row, p ? 8 : 0, p ? 1 : 4, xf + (p ? 16 : 0));
      asm volatile("cp.async.bulk.wait_group 0;\nfence.proxy.async.global;" ::: "memory");
      asm volatile("st.release.gpu.global.u32 [%0], %1;" ::"l"(&cx.g->qflag[((f + (n & 12)) * 4 + p) * 2 + w]), "r"(e1) : "memory");
    }
    __syncwarp();
    if (n < 12 && p == 1) {
#pragma unroll 1
      for (int i = 0, k = 0; i < 64 && k < (1 << 16); k++) {
        uint32_t m, r, z, t;
        ld_gran(cx.g->stats + row + i + lane, m, r, z, t);
        *(uint2*)(cx.sp + SM_STATS + 8 * (w * 64 + i + lane)) = make_uint2(m, r);
        if (__all_sync(0xffffffffu, t == e1)) i += 32;
      }
    }
    bar_arrive(BAR_QF + w, 160);
  }
}

__device__ __forceinline__ void ffn_consumer(const Ctx& cx, int f, int wg, int cw, int lane, const __nv_bfloat16* x) {
  const int r = lane >> 2, c = lane & 3, tid = cw * 32 + lane;
  const uint32_t full = cx.sb + SM_FFULL, empty = cx.sb + SM_FEMPTY;
  const bool signaller = (tid & 127) == 0;
  prof(wg, 8);
  const unsigned e = *(const uint32_t*)(cx.sp + SM_TAG + 4);
  uint32_t key[8];
#pragma unroll 1
  for (int n = 0; n < (1 << 16); n++) {
    uint32_t bad = 0;
#pragma unroll
    for (int i = 0; i < 8; i++) {
      uint32_t t;
      asm volatile("ld.relaxed.gpu.global.v2.b32 {%0, %1}, [%2];" : "=r"(key[i]), "=r"(t) : "l"(&cx.g->stats[i * 256 + tid].z) : "memory");
      bad |= t ^ (e + 1);
    }
    if (__all_sync(0xffffffffu, bad == 0)) break;
  }
  bar_sync(BAR_QF + wg, 160);
  bar_sync(3, 256);
  if (tid < 8) mbar_arrive(empty + 8 * tid);
  prof(wg, 9);
  int mysel = 0;
#pragma unroll 1
  for (int k = 0; k < TOPC; k++) {
    uint32_t m = key[0];
#pragma unroll
    for (int i = 1; i < 8; i++) m = max(m, key[i]);
    m = __reduce_max_sync(0xffffffffu, m);
    uint32_t* tk = (uint32_t*)(cx.sp + SM_TOPK) + (k & 1) * 8;
    if (lane == 0) tk[cw] = m;
    bar_sync(3, 256);
    m = __reduce_max_sync(0xffffffffu, tk[lane & 7]);
#pragma unroll
    for (int i = 0; i < 8; i++) if (key[i] == m) key[i] = 0;
    if (k == cw) mysel = 0xFFFF - (int)(m & 0xFFFF);
  }
  {
    const float4 st = __ldcg((const float4*)&cx.g->stats[mysel]);
    const uint32_t mm = pack2(st.x, st.x);
#pragma unroll 3
    for (int i = 0; i < 9; i++) {
      const uint32_t t = sub2(*(const uint32_t*)(x + (size_t)mysel * DM + i * 64 + 2 * lane), mm);
      *(uint32_t*)(cx.sp + SM_XSEL + i * 1024 + cw * 128 + (((lane >> 2) ^ cw) << 4) + (lane & 3) * 4) =
          pack2(bf_lo(t) * st.y, bf_hi(t) * st.y);
    }
    const uint32_t k = __float_as_uint(st.z);
    const float score = bf_hi(k ^ ((int)k < 0 ? 0x80000000u : 0xFFFF0000u));
    if (lane == 0 && f == 0) cx.g->sel[cw] = make_int2(mysel, __float_as_int(bfr(rcp(1.0f + ex2(-1.4426950408889634f * score)))));
  }
  asm volatile("fence.proxy.async.shared::cta;" ::: "memory");
  bar_sync(3, 256);
  prof(wg, 10);
  auto run = [&](float (&acc)[4], int st, int n, uint32_t b) {
#pragma unroll 1
    for (int u = 0; u < n; u++, st += 2, b += 3072) {
      const uint32_t sl = st & 7;
      mbar_wait(full + 8 * sl, (st >> 3) & 1);
      wg_fence();
      const uint64_t da = mkdesc(cx.sb + sl * FSTAGE, 16), db = mkdesc(b, 16);
#pragma unroll
      for (int k = 0; k < 12; k++) mma_n8(acc, da + k * 128, db + (k >> 2) * 64 + (k & 3) * 2, u > 0 || k > 0);
      wg_commit();
      wg_wait<0>();
      if (signaller) mbar_arrive(empty + 8 * sl);
    }
    pin(acc);
  };
#pragma unroll 1
  for (int unit = wg; unit < 27; unit += 2) {
    if (unit >> 1 == 9) {
      asm volatile("fence.proxy.async.shared::cta;" ::: "memory");
      bar_sync(3, 256);
      prof(wg, 11);
    }
    const bool gu = unit < 18;
    float a0[4], a1[4];
#pragma unroll 1
    for (int m = 0; m < (gu ? 2 : 1); m++) {
      run(a1, (unit >> 1) * 12 + m * 6 + wg, gu ? 3 : 6, cx.sb + (gu ? SM_XSEL : SM_H));
      if (m == 0) { a0[0] = a1[0]; a0[1] = a1[1]; a0[2] = a1[2]; a0[3] = a1[3]; }
    }
    float u0 = a1[0], u1 = a1[1];
#pragma unroll 1
    for (int i = 0; i < 2; i++) {
      const int fl = (cw & 3) * 16 + r + i * 8;
      if (gu) {
        const uint32_t g = pack2(a0[0], a0[1]);
        const uint32_t h = fma2(pack2(silu_f(bf_lo(g)), silu_f(bf_hi(g))), pack2(u0, u1), 0x80008000u);
        uint8_t* hp = cx.sp + SM_H + unit * 1024 + c * 256 + (fl & 7) * 2;
        *(uint16_t*)(hp + (((fl >> 3) ^ (2 * c)) << 4)) = (uint16_t)h;
        *(uint16_t*)(hp + 128 + (((fl >> 3) ^ (2 * c + 1)) << 4)) = (uint16_t)(h >> 16);
      } else {
        float* yp = cx.g->ypart + (f * TOPC + 2 * c) * DM + (unit - 18) * 64 + fl;
        yp[0] = u0;
        yp[DM] = u1;
      }
      a0[0] = a0[2]; a0[1] = a0[3]; u0 = a1[2]; u1 = a1[3];
    }
  }
  prof(wg, 12);
  bar_sync(3, 256);
  if (tid == 0) atom_add_acq_rel(&cx.g->ycnt);
  prof(wg, 13);
}

constexpr float SUM_HI = 1.8446744e19f, SUM_LO = 9.0949470e-13f;

template <int LO, int HI, int N>
__device__ __forceinline__ void softmax_exp(float (&s)[N]) {
#pragma unroll
  for (int i = LO; i < HI; i++) s[i] = ex2(s[i]);
}
__device__ __forceinline__ void sum_tree(const uint32_t (&pf)[28], bool big, uint32_t& h0, uint32_t& h1) {
  uint32_t t0 = add2(add2(pf[16], pf[18]), add2(pf[20], pf[22])), t1 = add2(add2(pf[17], pf[19]), add2(pf[21], pf[23]));
  if (big) { t0 = add2(t0, add2(pf[24], pf[26])); t1 = add2(t1, add2(pf[25], pf[27])); }
  h0 = add2(add2(add2(add2(pf[0], pf[2]), add2(pf[4], pf[6])), add2(add2(pf[8], pf[10]), add2(pf[12], pf[14]))), t0);
  h1 = add2(add2(add2(add2(pf[1], pf[3]), add2(pf[5], pf[7])), add2(add2(pf[9], pf[11]), add2(pf[13], pf[15]))), t1);
}
__device__ __forceinline__ void exact_attention(float (&o)[16], float& l0, float& l1, const uint32_t (&q)[32], const __nv_bfloat16* kp,
                                                const __nv_bfloat16* vp) {
  float m0 = -3.0e38f, m1 = -3.0e38f;
  l0 = l1 = 0.f;
#pragma unroll
  for (int i = 0; i < 16; i++) o[i] = 0.f;
#pragma unroll 1
  for (int key = 0; key < SEQ; key += 8, kp += 8 * DH, vp += 8 * DH) {
    float d[4] = {0.f, 0.f, 0.f, 0.f};
#pragma unroll
    for (int k = 0; k < 8; k++)
      hmma_k16(d, q[4 * k], q[4 * k + 1], q[4 * k + 2], q[4 * k + 3], *(const uint32_t*)(kp + k * 16), *(const uint32_t*)(kp + k * 16 + 8));
    float x0 = fmaxf(d[0], d[1]), x1 = fmaxf(d[2], d[3]);
    x0 = fmaxf(x0, __shfl_xor_sync(0xffffffffu, x0, 1));
    x1 = fmaxf(x1, __shfl_xor_sync(0xffffffffu, x1, 1));
    x0 = fmaxf(fmaxf(x0, __shfl_xor_sync(0xffffffffu, x0, 2)), m0);
    x1 = fmaxf(fmaxf(x1, __shfl_xor_sync(0xffffffffu, x1, 2)), m1);
    const float sc0 = ex2(m0 - x0), sc1 = ex2(m1 - x1);
    m0 = x0; m1 = x1;
    const uint32_t p0 = pack2(ex2(d[0] - m0), ex2(d[1] - m0)), p1 = pack2(ex2(d[2] - m1), ex2(d[3] - m1));
    l0 = fmaf(l0, sc0, bf_lo(p0) + bf_hi(p0));
    l1 = fmaf(l1, sc1, bf_lo(p1) + bf_hi(p1));
#pragma unroll
    for (int nb = 0; nb < 4; nb++) {
      uint32_t b;
      asm("movmatrix.sync.aligned.m8n8.trans.b16 %0, %1;" : "=r"(b) : "r"(*(const uint32_t*)(vp + nb * 8)));
      o[4 * nb] *= sc0; o[4 * nb + 1] *= sc0; o[4 * nb + 2] *= sc1; o[4 * nb + 3] *= sc1;
      asm volatile("mma.sync.aligned.m16n8k8.row.col.f32.bf16.bf16.f32 {%0, %1, %2, %3}, {%4, %5}, {%6}, {%0, %1, %2, %3};"
                   : "+f"(o[4 * nb]), "+f"(o[4 * nb + 1]), "+f"(o[4 * nb + 2]), "+f"(o[4 * nb + 3]) : "r"(p0), "r"(p1), "r"(b));
    }
  }
}
__device__ __forceinline__ bool inv_sums(float l0, float l1, float& i0, float& i1) {
  l0 += __shfl_xor_sync(0xffffffffu, l0, 1); l1 += __shfl_xor_sync(0xffffffffu, l1, 1);
  l0 += __shfl_xor_sync(0xffffffffu, l0, 2); l1 += __shfl_xor_sync(0xffffffffu, l1, 2);
  i0 = rcp(l0);
  i1 = rcp(l1);
  return !(l0 + l1 <= SUM_HI) | (fminf(l0, l1) < SUM_LO);
}
template <int LO, int HI, int N>
__device__ __forceinline__ void park(uint32_t a, const float (&o)[N], float i0, float i1, bool on = true) {
#pragma unroll
  for (int i = LO; i < HI; i++)
    asm volatile("{\n.reg .pred p;\nsetp.ne.u32 p, %5, 0;\n@p stmatrix.sync.aligned.m8n8.x4.shared.b16 [%0], {%1, %2, %3, %4};\n}"
                 ::"r"(a + i * 2048), "r"(pack2(o[8 * i] * i0, o[8 * i + 1] * i0)), "r"(pack2(o[8 * i + 2] * i1, o[8 * i + 3] * i1)),
                 "r"(pack2(o[8 * i + 4] * i0, o[8 * i + 5] * i0)), "r"(pack2(o[8 * i + 6] * i1, o[8 * i + 7] * i1)), "r"((uint32_t)on) : "memory");
}

template <int I, int HI, int G, int N>
__device__ __forceinline__ void park_paced(uint32_t a, const float (&o)[N], float i0, float i1, int id) {
  if constexpr (I < HI) {
    park<I, I + G>(a, o, i0, i1);
    if (I + G < HI) block_fence(id + I);
    park_paced<I + G, HI, G>(a, o, i0, i1, id);
  }
}
template <int I, int NP, int E0, int N, int NS>
__device__ __forceinline__ void exp_park(float (&s)[NS], uint32_t a, const float (&o)[64], float i0, float i1, bool on, int id) {
  if constexpr (I < NP) {
    constexpr int E1 = E0 + (N - E0) * X_PG / (NP - I);
    softmax_exp<E0, E1>(s);
    park<I, I + X_PG>(a, o, i0, i1, on);
    if (I + X_PG < NP) {
#pragma unroll
      for (int i = E0; i < E1; i++) asm volatile("" : "+f"(s[i])::"memory");
      block_fence(id + I);
    }
    exp_park<I + X_PG, NP, E1, N>(s, a, o, i0, i1, on, id);
  }
}

__device__ __forceinline__ void attn_consumer(const Ctx& cx, bool hlp, int qb, int hs, int wg, int cw, int lane, const __nv_bfloat16* x,
                                              const __nv_bfloat16* kc, const __nv_bfloat16* vc, __nv_bfloat16* out) {
  const uint32_t full = cx.sb + SM_FULL;
  const uint32_t ring = cx.sb + SM_RING;
  const uint32_t qwg = ring + wg * 16384;
  auto qlane = [&](int l) { return qwg + (cw & 3) * 256 + (l >> 4) * 1024 + (l & 15) * 16; };
  const bool signaller = lane == 0 && (cw & 3) < 2;
  const int my_turn = 1 + wg, other_turn = 2 - wg;
  const uint32_t empty_c = mapa(cx.sb + SM_EMPTY, cw & 1);

  float oA[64], oB[64], i0, i1;
  uint32_t xl[32];
  {
    const int r = lane >> 2, c = lane & 3;
    const int lr0 = cw * 16 + r;
    uint32_t xa[144];
    uint32_t mm0, mm1;
    float rstd0, rstd1, sq0 = 0.f, sq1 = 0.f;
    const uint32_t xf = cx.sb + SM_XFULL + wg * 32, xs = cx.sb + SM_SLOT + wg * 49152;
    auto lo_of = [&](int l) { return ((cw & 3) * 16 + (l & 15)) * 128 + (((l >> 4) ^ (l & 7)) << 4); };
    prof(wg, 0);
    {
      const uint32_t lo = lo_of(lane);
      const uint32_t xb = cx.sb + SM_X + wg * 73728;
      float sm[X_NS][4] = {};
      const uint32_t ws = (lane & 7) == 1 ? 64 : 0;
      uint32_t wb = cx.sb + (ws ? SM_WR + (lane >> 3) * 16 : SM_ONES);
      uint32_t b0[24], b1[24], b2[24];
      mbar_wait(cx.sb + SM_BAR_W, 0);
      TS4(1)
      if (X_LN == 0) {
        ln_fetch_b(b0, wb, ws);
        ln_fetch_b(b1, wb, ws);
        ln_fetch_b(b2, wb, ws);
      }
      mbar_wait(xf, 0);
      TS4(2)
      ln_fetch<0, 12>(xa, xb, lo);
      if (X_LN == 1) {
        ln_fetch_b(b0, wb, ws);
        ln_fetch_b(b1, wb, ws);
        ln_fetch_b(b2, wb, ws);
      }
      ln_sums<0, 12>(xa, sm, b0);
      mbar_wait(xf + 8, 0);
      TS4(3)
      ln_fetch<12, 24>(xa, xb, lo);
      if (wg == 0) {
        bar_arrive(BAR_XREL + (xa[95] & blockIdx.y), 224);
      }
      ln_sums<12, 24>(xa, sm, b1);

      mbar_wait(xf + 16, 0);
      TS4(4)
      prof(wg, 1);
      ln_fetch<24, 36>(xa, xb, lo);
      ln_sums<24, 36>(xa, sm, b2);
#pragma unroll
      for (int i = 0; i < 4; i++) sm[0][i] = X_NS == 2 ? sm[0][i] + sm[1][i] : X_NS == 3 ? sm[0][i] + sm[1][i] + sm[2][i] : (sm[0][i] + sm[1][i]) + (sm[2][i] + sm[X_NS - 1][i]);
      if (cw == hs && c == 0) {
        *(float*)(cx.sp + SM_RAW + 4 * r) = sm[0][1];
        *(float*)(cx.sp + SM_RAW + 4 * r + 32) = sm[0][3];
      }
      rstd0 = sm[0][0];
      rstd1 = sm[0][2];
      mm0 = pack2(rstd0 * (1.0f / DM), rstd0 * (1.0f / DM));
      mm1 = pack2(rstd1 * (1.0f / DM), rstd1 * (1.0f / DM));
    }
#pragma unroll
    for (int i = 0; i < 16; i++) { xa[2 * i] = sub2(xa[2 * i], mm0); xa[2 * i + 1] = sub2(xa[2 * i + 1], mm1); }
    pin(xa);
    prof(wg, 2);
    TS4(5)

    float (&acc)[64] = oB;
    int st0 = 0;
#pragma unroll 1
    for (int n = 0; n < 16; n++) {
      const int p = n & 3, rb = n >> 2;
      const bool last = p == 3 && !hlp;
#pragma unroll
      for (int i = 0; i < 5; i++) {
        if (i == 4 && last) {
          wg_wait<1>();
          mbar_arrive_cluster(empty_c + 8 * 3, signaller && wg);
          wg_wait<0>();
          pin(acc);
          prof(wg, 6);
#pragma unroll
          for (int j = 0; j < 32; j++) xl[j] = xa[112 + j];
          i0 = rstd0;
          i1 = rstd1;
          goto attention;
        }
        const int st = st0 + i;
        const uint32_t sl = st & 3, slp = (st - 1) & 3;
        if (!wg) mbar_wait(full + 8 * sl, (st >> 2) & 1);
        TS4(8 + 2 * (p * 5 + i))
        const bool join = wg && last;
        if ((i || st0 + wg) && i != (wg ? 4 : 1) && !(join && i == 3)) bar_sync(my_turn, 256);
        wg_fence();
        const uint64_t db = mkdesc(ring + sl * STAGE, 16384);
        const int kb0 = i < 3 ? 8 * i : 8 * i - 4;
#pragma unroll
        for (int k = 0; k < (i == 2 ? 4 : 8); k++) {
          const int kb = kb0 + k;
          mma_n128t(acc, xa[4 * kb], xa[4 * kb + 1], xa[4 * kb + 2], xa[4 * kb + 3], db + k * 128, kb > 0);
        }
        wg_commit();
        TS4(9 + 2 * (p * 5 + i))
        if (wg ? (i == 4 ? st0 < 75 : (i < 2 || i == (join ? 3 : 2))) : i) bar_arrive(other_turn, 256);
        if (p == 0 && i < 4) {
          if (i == 1 && rb) {
            mbar_wait(xf + 8, rb & 1);
            ln_fetch<16, 32>(xa, xs - 32768, lo_of(fresh_lane()));
          }
          if (i == 2 && rb) {
            mbar_wait(xf + 16, rb & 1);
            ln_fetch<32, 36>(xa, xs - 32768, lo_of(fresh_lane()));
          }
#pragma unroll
          for (int j = 0; j < 72; j++)
            if (j >= 2 * (i < 2 ? 8 * i + 8 : 8 * i + 4) && j < 2 * (i == 0 ? 16 : 8 * i + 12)) {
              xa[2 * j] = sub2(xa[2 * j], mm0);
              xa[2 * j + 1] = sub2(xa[2 * j + 1], mm1);
            }
          pin(xa);
        }
        if (i == X_SQI && n == 0) {
          mbar_wait(cx.sb + SM_BAR_SQ, 0);
          float2* sp = (float2*)(cx.sp + SM_STATS) + lr0;
          float mean0, mean1;
          ln_row(rstd0, sp[0].y, mean0, rstd0);
          ln_row(rstd1, sp[8].y, mean1, rstd1);
          __syncwarp();
          if (c == 0) {
            sp[0] = make_float2(mean0, rstd0);
            sp[8] = make_float2(mean1, rstd1);
          }
          *((uint32_t*)(cx.sp + SM_COLD) + wg) = 0;
          if (!hlp) bar_arrive(BAR_GATE, 352);
          rstd0 *= SM_SCALE_LOG2;
          rstd1 *= SM_SCALE_LOG2;
        }
        if (i == 3 && hlp && p == 3 && rb < 3) bar_arrive(BAR_QS + wg + (xa[63] & blockIdx.y), 160);
        if (i == 4 && p == 3 && rb < 3) {
          const float2* sp = (const float2*)(cx.sp + SM_STATS) + cw * 16 + (fresh_lane() >> 2);
          mm0 = pack2(sp[0].x, sp[0].x);
          mm1 = pack2(sp[8].x, sp[8].x);
          sq0 = sp[0].y * SM_SCALE_LOG2;
          sq1 = sp[8].y * SM_SCALE_LOG2;
#pragma unroll
          for (int j = 0; j < 16; j++) { xa[2 * j] = sub2(xa[2 * j], mm0); xa[2 * j + 1] = sub2(xa[2 * j + 1], mm1); }
          pin(xa);
        }
        if (i == 0) {
          if (wg) {
            wg_wait<0>();
            mbar_arrive_cluster(empty_c + 8 * sl, signaller);
          }
        } else if (i == 2) {
          if (!join) {
            wg_wait<0>();
            mbar_arrive_cluster(empty_c + 8 * sl, signaller);
          }
          if (hlp && p == 3 && rb < 3) {
            mbar_wait(xf, ~rb & 1);
            ln_fetch<0, 16>(xa, xs, lo_of(fresh_lane()));
            pin(xa);
          }
        } else if (i != 3) {
          wg_wait<1>();
          mbar_arrive_cluster(empty_c + 8 * slp, signaller && (i == 4 || !wg));
          wg_wait<0>();
          mbar_arrive_cluster(empty_c + 8 * sl, signaller);
        }
      }
      pin(acc);
      prof(wg, 3 + p);
      TS4(50 + 2 * p)
      st0 += 5;
      if (hlp && st0 > 5) bar_sync(BAR_QF + wg, 160);
      park_paced<0, 8, X_QP>(qlane(lane) + (hlp ? 5 + wg : 4 + p) * STAGE, acc, rstd0, rstd1, 300);
      if (p || hlp) asm volatile("fence.proxy.async.shared::cta;" ::: "memory");
      if (hlp) bar_arrive(BAR_QS + wg, 160);
      if (p == 3) { rstd0 = sq0; rstd1 = sq1; }
      TS4(51 + 2 * p)
      if (p == 1 && !hlp) {
        float (&ah)[32] = *(float (*)[32])&acc[0];
#pragma unroll
        for (int i = 0; i < 3; i++) {
          const uint32_t sl = (10 + i) & 3;
          if (!wg) mbar_wait(full + 8 * sl, ((10 + i) >> 2) & 1);
          TS4(28 + 2 * i)
          if (i == 0 || i == 2 - wg) bar_sync(my_turn, 256);
          wg_fence();
          const uint64_t db = mkdesc(ring + sl * STAGE, 16);
#pragma unroll
          for (int k = 0; k < 12; k++) {
            const int kb = 12 * i + k;
            if (kb) mma_n64t(ah, xa[4 * kb], xa[4 * kb + 1], xa[4 * kb + 2], xa[4 * kb + 3], db + k * 128, true);
            else mma_n64t_dyn(ah, xa[0], xa[1], xa[2], xa[3], db, blockIdx.y);
          }
          wg_commit();
          TS4(29 + 2 * i)
          if (i == 2 || i != wg) {
            bar_arrive(other_turn, 256);
            if (i) {
              wg_wait<1>();
              mbar_arrive_cluster(empty_c + 8 * ((9 + i) & 3), signaller && i == wg + 1);
            }
            wg_wait<0>();
            mbar_arrive_cluster(empty_c + 8 * sl, signaller);
          }
        }
        pin(ah);
        TS4(54)
        park<0, 4>(qlane(lane) + 6 * STAGE, ah, rstd0, rstd1);
        TS4(55)
        st0 = 13;
        n = 2;
      }
    }
    TS_DUMP()
    ffn_consumer(cx, blockIdx.x & 3, wg, cw, fresh_lane(), x);
    return;
  }

attention:
  uint32_t oa[128];
  float acc[32];
  {
    uint32_t pf[28];
    const uint32_t ql = qlane(fresh_lane());
    float j0, j1;
    uint32_t bad = 0;
    float lA0 = 0.f, lA1 = 0.f, lB0 = 0.f, lB1 = 0.f;
    int t = 0;
    uint32_t ra = 2 * 2048, rb = 2048, rc = 2 * 2048, par = 0;
    const uint64_t dk0 = mkdesc(ring, 16), dv0 = mkdesc(ring, 16384);
    uint64_t dqA = mkdesc_q(qwg + 4 * STAGE), dqB = dqA + 2048;
    auto turn = [&](auto kc_, auto bc_) {
      constexpr int KIND = decltype(kc_)::value, BIG = decltype(bc_)::value;
      constexpr int HB = KIND == 1, ID = 10 * KIND + 30 * BIG, T0 = BIG ? 38 : 0;
      constexpr int NS = BIG ? 56 : 48, SPLIT = BIG ? (HB ? X_SPLIT : X_SPLITA) : (HB ? X_SPLITS : X_SPLITSA);
      float s[NS];
      float (&op)[64] = HB ? oA : oB;
      uint32_t h0 = 0, h1 = 0;
      TS2(0)
      bar_sync(my_turn, 256);
      TS2(1)
      if (KIND) { pin(pf); pin(op); }
      mma_qk(s, HB ? dqB : dqA, dk0 + (HB ? ra : rc));
      TS2(2)
      if (KIND) {
        const bool bigp = HB ? BIG : BIG ? t != 10 : t == 66;
        if (X_BF2) block_fence(ID + 9);
        pin(pf);
        sum_tree(pf, bigp, h0, h1);
        asm volatile("" : "+r"(h0), "+r"(h1)::"memory");
        if (HB) mbar_wait(full + (rb >> 8), par);
        mma_pv(op, pf, dv0 + rb, t != T0 + 2 - HB, bigp);
      } else {
        mbar_wait(full + (rb >> 8), (NST_Q - 1) >> 2 & 1);
#pragma unroll
        for (int k = 0; k < 8; k++) mma_n128t(op, xl[4 * k], xl[4 * k + 1], xl[4 * k + 2], xl[4 * k + 3], dv0 + rb + k * 128, 1);
        wg_commit();
      }
      TS2(3)
      bar_arrive(other_turn, 256);
      (HB ? lA0 : lB0) += bf_lo(h0) + bf_hi(h0);
      (HB ? lA1 : lB1) += bf_lo(h1) + bf_hi(h1);
      wg_wait<1>();
      pin(s);
      TS1(t)
      TS2(4)
      if (KIND == 1) mbar_arrive_cluster_now<ID + 3>(empty_c + (ra >> 8), signaller);
      if (BIG && t == T0 + HB) {
        const uint32_t a = ql + (4 + HB) * STAGE;
        const bool ok = !__any_sync(0xffffffffu, inv_sums(HB ? lB0 : lA0, HB ? lB1 : lA1, i0, i1));
        bad = (HB ? bad : 0) | (ok ? 0 : 1 << HB);
        (HB ? lB0 : lA0) = 0.f;
        (HB ? lB1 : lA1) = 0.f;
        softmax_exp<0, X_E0>(s);
#pragma unroll
        for (int i = 0; i < X_E0; i++) asm volatile("" : "+f"(s[i])::"memory");
        block_fence(ID + 7);
        exp_park<0, X_PA, X_E0, SPLIT>(s, a, HB ? oB : oA, i0, i1, ok, 200 + ID);
        if (!HB) dqB += 2048;
        prof(wg, 8 + HB);
      } else {
        if (HB && !BIG) bad = (bad & 3) | (inv_sums(lA0, lA1, i0, i1) ? 4 : 0);
        softmax_exp<0, SPLIT>(s);
      }
      pin(s);
      if (!BIG) block_fence(ID + 4);
      TS2(5)
      wg_wait<0>();
      TS2(6)
      pin(op);
      if (KIND) pin(pf); else pin(xl);
      if (HB) {
        par ^= rc == 2048;
        if (BIG && t == 37) dqA -= 4 * 2048;
        if (BIG && t == X_WAKE && cw == 0) bar_arrive(BAR_HELPER, 64);
      } else {
        mbar_arrive_cluster_now<ID + 5>(empty_c + (rb >> 8), signaller);
        if (KIND) {
          par ^= ra == 2048;
          const uint32_t x = ra;
          ra = rc; rc = rb; rb = x;
        }
      }
      softmax_exp<SPLIT, NS>(s);
#pragma unroll
      for (int i = 0; i < NS / 2; i++) pf[i] = pack2(s[2 * i], s[2 * i + 1]);
      pin(pf);
      if (KIND == 0) {
        block_fence(ID + 6);
        park_paced<0, X_Q1, X_QC>(ql, oB, i0, i1, 310);
        j0 = i0; j1 = i1;
        prof(wg, 7);
      }
      if (X_Q1 < 8 && HB && !BIG && t == 1) park_paced<X_Q1, 8, X_QC>(ql, oB, j0, j1, 320);
      if (BIG && !HB && t == T0) mbar_wait(cx.sb + SM_BAR_Q + 8 * wg, 0);
      if (HB) mbar_wait(full + (rc >> 8), par);
      t++;
    };
#pragma unroll
    for (int i = 24; i < 28; i++) asm volatile("" : "=r"(pf[i]));
    mbar_wait(full + 8 * 2, 0);
    turn(IC<0>(), IC<0>());
    rb = 3 * 2048; rc = 2048;
    kill(oA);
    const bool never = blockIdx.y == 1;
#pragma unroll 1
    while (true) {
      turn(IC<1>(), IC<0>());
      if (t == 76) break;
      if (t == 10) {
        asm volatile("fence.proxy.async.shared::cta;" ::: "memory");
#pragma unroll 1
        do {
#pragma unroll 1
          do turn(IC<2>(), IC<1>()); while (never);
          turn(IC<1>(), IC<1>());
        } while (t != 66);
      }
#pragma unroll 1
      do turn(IC<2>(), IC<0>()); while (never);
    }
    auto scale = [&](auto lo, auto hi) {
#pragma unroll
      for (int i = decltype(lo)::value; i < decltype(hi)::value; i++) {
        oa[32 + 2 * i] = pack2(oA[4 * i] * i0, oA[4 * i + 1] * i0);
        oa[32 + 2 * i + 1] = pack2(oA[4 * i + 2] * i1, oA[4 * i + 3] * i1);
        asm volatile("" : "+r"(oa[32 + 2 * i]), "+r"(oa[32 + 2 * i + 1])::"memory");
      }
    };
    TS3(1)
    volatile uint32_t* const cold = (volatile uint32_t*)(cx.sp + SM_COLD) + wg;
    if (bad) *cold = 1;
#pragma unroll
    for (int i = 0; i < 8; i++) ldsm4(ql + 4 * STAGE + i * 2048, oa[4 * i], oa[4 * i + 1], oa[4 * i + 2], oa[4 * i + 3]);
    {
      uint32_t h0, h1;
      sum_tree(pf, false, h0, h1);
      lB0 += bf_lo(h0) + bf_hi(h0);
      lB1 += bf_lo(h1) + bf_hi(h1);
      asm volatile("" : "+f"(lB0), "+f"(lB1)::"memory");
    }
    scale(IC<0>(), IC<X_F1>());
    block_fence(93);
    TS3(2)
    bar_sync(my_turn, 256);
    TS3(3)
    pin(pf); pin(oB);
    mma_pv(oB, pf, dv0 + 2 * 2048, true, false);
    block_fence(91);
    TS3(4)
    const uint32_t held = *cold;
    if (inv_sums(lB0, lB1, lB0, lB1)) bad |= 8;
    const uint64_t db = mkdesc(ring + 3 * STAGE, 16);
    scale(IC<X_F1>(), IC<X_F2>());
    mbar_arrive_cluster_now<94>(empty_c, signaller && !held);
#pragma unroll
    for (int i = 0; i < 32; i++) asm volatile("" : "+r"(oa[i])::"memory");
    wg_fence();
#pragma unroll
    for (int k = 0; k < 8; k++) mma_n64t(acc, oa[4 * k], oa[4 * k + 1], oa[4 * k + 2], oa[4 * k + 3], db + k * 128, k > 0);
    if (X_F2 < 16) {
      wg_commit();
      block_fence(95);
      scale(IC<X_F2>(), IC<16>());
      TS3(5)
      wg_fence();
    }
#pragma unroll
    for (int k = 8; k < 16; k++) mma_n64t(acc, oa[4 * k], oa[4 * k + 1], oa[4 * k + 2], oa[4 * k + 3], db + k * 128, 1);
    wg_commit();
    bar_arrive(other_turn, 256);
    if (bad) *cold = 1;
    bar_sync(4 + wg, 128);
    const uint32_t is_cold = *cold;
    wg_wait<(X_F2 < 16 ? 2 : 1)>();
    pin(oB); pin(pf);
    TS(76)
    TS3(6)
    mbar_arrive_cluster_now<97>(empty_c + 8 * 2, signaller);
#pragma unroll
    for (int i = 16; i < 24; i++) ldsm4(ql + 5 * STAGE + (i & 7) * 2048, oa[4 * i], oa[4 * i + 1], oa[4 * i + 2], oa[4 * i + 3]);
#pragma unroll
    for (int i = 0; i < 16; i++) {
      oa[96 + 2 * i] = pack2(oB[4 * i] * lB0, oB[4 * i + 1] * lB0);
      oa[96 + 2 * i + 1] = pack2(oB[4 * i + 2] * lB1, oB[4 * i + 3] * lB1);
    }
    TS3(7)
    if (!wg) mbar_wait(full + 8 * 1, 0);
    TS3(8)
    wg_wait<0>();
    pin(acc); pin(oa);
    if (__any_sync(0xffffffffu, is_cold)) {
      bad = __reduce_or_sync(0xffffffffu, bad);
      if (!(bad & 8)) {
#pragma unroll
        for (int i = 24; i < 32; i++) stsm4(ql + 6 * STAGE + (i & 7) * 2048, oa[4 * i], oa[4 * i + 1], oa[4 * i + 2], oa[4 * i + 3]);
      }
#pragma unroll 1
      for (int h = 0; h < 4; h++) {
        if (bad >> h & 1) {
          const uint32_t a = ql + ((0x6054 >> (4 * h)) & 7) * STAGE;
          const int l = fresh_lane(), o = (hs * 2 + (h >> 1)) * SEQ * DH + (l >> 2) * DH + (l & 3) * 2;
          uint32_t q[32];
#pragma unroll
          for (int i = 0; i < 8; i++) ldsm4(a + i * 2048, q[4 * i], q[4 * i + 1], q[4 * i + 2], q[4 * i + 3]);
#pragma unroll 1
          for (int i = 0; i < 4; i++) {
            float ox[16], l0, l1;
            exact_attention(ox, l0, l1, q, kc + o, vc + o + i * 32);
            inv_sums(l0, l1, l0, l1);
            park<0, 2>(a + i * 4096, ox, l0, l1);
          }
        }
      }
      __syncwarp();
#pragma unroll
      for (int i = 0; i < 32; i++)
        if ((i >> 3) != 1 || (bad & 4))
          ldsm4(ql + ((0x6504 >> (4 * (i >> 3))) & 7) * STAGE + (i & 7) * 2048, oa[4 * i], oa[4 * i + 1], oa[4 * i + 2], oa[4 * i + 3]);
      pin(oa);
      asm volatile("fence.proxy.async.shared::cta;" ::: "memory");
      bar_sync(4 + wg, 128);
      mbar_arrive_cluster(empty_c, signaller && held);
      wg_fence();
#pragma unroll
      for (int k = 0; k < 16; k++) mma_n64t(acc, oa[4 * k], oa[4 * k + 1], oa[4 * k + 2], oa[4 * k + 3], db + k * 128, k > 0);
      wg_commit();
      wg_wait<0>();
      pin(acc);
    }
    mbar_arrive_cluster(empty_c + 8 * 3, signaller);
  }

  prof(wg, 10);
  TS3(9)
  {
    lane = fresh_lane();
    const int tw = (cw & 3) * 32 + lane;
    float red[32];
    kill(red);
    const uint32_t tag = *(const uint32_t*)(cx.sp + SM_TAG);
    uint4* const xch = at(cx.g->part, ((qb * 64 * 2 + wg) * 4 * 128 + tw) * 16);
    int nrx = 1;
    auto region = [](int s, int h) { return h ? 1 + (s & 1) : (s & 1) ? 0 : 3; };
    auto half_step = [&](int s, auto hc, bool arrive) {
      constexpr int h = decltype(hc)::value;
      const uint64_t db = mkdesc(ring + region(s, h) * STAGE, 16);
      bar_sync(my_turn, 256);
      pin(oa);
      wg_fence();
#pragma unroll
      for (int k = 0; k < 16; k++) {
        const int kb = h * 16 + k;
        mma_n64t(acc, oa[4 * kb], oa[4 * kb + 1], oa[4 * kb + 2], oa[4 * kb + 3], db + k * 128, kb > 0);
      }
      wg_commit();
      if (arrive) bar_arrive(other_turn, 256);
    };
    auto await = [&](int s, int h) { mbar_wait(full + 8 * region(s, h), ((s >> 1) ^ h ^ 1) & 1); };
    auto fetch = [&](uint32_t (&g)[16], int n) {
      const uint4* p = at(xch, (hs * 7 + n - 1) * 16384);
#pragma unroll
      for (int i = 0; i < 4; i++) ld_gran(p + i * 128, g[4 * i], g[4 * i + 1], g[4 * i + 2], g[4 * i + 3]);
    };
    uint32_t g[16];
    bool pend = false;
#pragma unroll 1
    for (int s = 0;; s++) {
      half_step(s, IC<1>(), s + wg < 9);
      if (s == 8) break;
      TS3(s < 3 ? 16 + 8 * s : 75)
      if (s == 0) {
        bar_arrive(BAR_OA, 352);
#pragma unroll
        for (int i = 0; i < 32; i++) red[i] = 0.f;
      }
      await(s + 1, 0);
      TS3(s < 3 ? 17 + 8 * s : 75)
      wg_wait<0>();
      TS3(s < 3 ? 18 + 8 * s : 75)
      mbar_arrive_cluster(empty_c + 8 * region(s, 1), signaller && s < 7);
      pin(acc);
      TS(77 + s)
      prof(wg, 12 + s);
      uint4* p = at(xch, (s == 0 ? 56 + hs : ((hs + s) & 7) * 7 + s - 1) * 16384);
#pragma unroll
      for (int i = 0; i < 4; i++)
        st_gran(p + i * 128, (pack2(acc[8 * i], acc[8 * i + 1]) & ~TAG) | tag, pack2(acc[8 * i + 2], acc[8 * i + 3]),
                pack2(acc[8 * i + 4], acc[8 * i + 5]), pack2(acc[8 * i + 6], acc[8 * i + 7]));
      TS3(s < 3 ? 19 + 8 * s : 75)
      half_step(s + 1, IC<0>(), true);
      TS3(s < 3 ? 20 + 8 * s : 75)
      if (pend && granules_ok(g, tag)) { add_granules(red, g); nrx++; }
      pend = nrx < s;
      if (pend) fetch(g, nrx);
      await(s + 1, 1);
      TS3(s < 3 ? 21 + 8 * s : 75)
      wg_wait<0>();
      TS3(s < 3 ? 22 + 8 * s : 75)
      mbar_arrive_cluster(empty_c + 8 * region(s + 1, 0), signaller && s < 6);
    }
    uint32_t xv[16], gt[16], g2[16];
    TS3(42)
    const bool ok = granules_ok(g, tag);
    TS3(43)
    nrx += ok;
    fetch(g2, nrx);
    mbar_wait(cx.sb + SM_BAR_XG, 0);
    const uint32_t frag = (cw * 16 + (lane & 15)) * 128 + (((lane >> 4) ^ (lane & 7)) << 4);
#pragma unroll
    for (int i = 0; i < 4; i++) {
      ldsm4(cx.sb + SM_XO + (frag ^ (i << 5)), xv[4 * i], xv[4 * i + 1], xv[4 * i + 2], xv[4 * i + 3]);
      ldsm4(cx.sb + SM_GO + (frag ^ (i << 5)), gt[4 * i], gt[4 * i + 1], gt[4 * i + 2], gt[4 * i + 3]);
    }
    if (ok) add_granules(red, g);
    TS3(44)
    wg_wait<0>();
    pin(acc);
    TS(85)
#pragma unroll
    for (int i = 0; i < 32; i++) red[i] += acc[i];
    pin(red);
#pragma unroll 1
    for (int spins = 0; spins < (1 << 16); spins++) {
      if (granules_ok(g2, tag)) {
        add_granules(red, g2);
        if (++nrx == 8) break;
      }
      fetch(g2, nrx);
    }
    uint32_t ow[16];
#pragma unroll
    for (int i = 0; i < 16; i++) ow[i] = pack2(red[2 * i], red[2 * i + 1]);
    prof(wg, 20);
    TS(86)
#pragma unroll
    for (int i = 0; i < 16; i++) ow[i] = fma2(ow[i], gt[i], xv[i]);
#pragma unroll
    for (int i = 0; i < 4; i++) stsm4(cx.sb + SM_XO + (frag ^ (i << 5)), ow[4 * i], ow[4 * i + 1], ow[4 * i + 2], ow[4 * i + 3]);
    __syncwarp();
    __nv_bfloat16* const op = at(out, ((qb * 128 + cw * 16 + (lane >> 3)) * DM + hs * 64 + (lane & 7) * 8) * 2);
#pragma unroll
    for (int i = 0; i < 4; i++) {
      uint4 v;
      const int row = cw * 16 + i * 4 + (lane >> 3);
      lds128(cx.sb + SM_XO + row * 128 + (((lane ^ row) & 7) << 4), v.x, v.y, v.z, v.w);
      asm volatile("st.global.v4.b32 [%0], {%1, %2, %3, %4};" ::"l"(op + i * 4 * DM),
                   "r"(v.x), "r"(v.y), "r"(v.z), "r"(v.w) : "memory");
    }
    prof(wg, 22);
    TS(87)
    TS_DUMP()
  }
}

struct KvMaps { CUtensorMap m[4]; };
__global__ void __cluster_dims__(2, 1, 1) __launch_bounds__(THREADS, 1)
fused_kernel(const __nv_bfloat16* __restrict__ x, const __nv_bfloat16* __restrict__ w_r, const __nv_bfloat16* __restrict__ kc,
             const __nv_bfloat16* __restrict__ vc, __nv_bfloat16* __restrict__ out, Scratch* scratch,
             const __grid_constant__ CUtensorMap tmX, const __grid_constant__ CUtensorMap tmWq,
             const __grid_constant__ KvMaps tmKV, const __grid_constant__ CUtensorMap tmWo,
             const __grid_constant__ CUtensorMap tmG, const __grid_constant__ CUtensorMap tmU,
             const __grid_constant__ CUtensorMap tmD, const __grid_constant__ CUtensorMap tmX16,
             const __grid_constant__ CUtensorMap tmWq96, const __grid_constant__ CUtensorMap tmX64) {
  extern __shared__ __align__(1024) uint8_t smem_raw[];
  prof(0, 23, 511);
  Ctx cx;
  cx.sb = smem_u32(smem_raw);
  cx.sp = smem_raw;
  cx.g = scratch;
  cx.rank = blockIdx.x & 1;
  const int warp = __shfl_sync(0xffffffffu, threadIdx.x >> 5, 0);
  const int cluster = blockIdx.x >> 1;
  const bool is_ffn = blockIdx.x >= N_ATT_CTA;
  const int c7 = ((cluster - 36) * 37) >> 8;
  const int hs = cluster < 4 ? 4 + cluster : cluster < 36 ? (cluster - 4) >> 3 : 4 + c7;
  const int qb = (cluster < 4 ? 0 : cluster < 36 ? (cluster - 4) & 7 : cluster - (is_ffn ? 36 : 35) - 7 * c7) * 2 + cx.rank;

  auto load_x = [&](int w, int i0, int i1) {
#pragma unroll
    for (int i = i0; i < i1; i++) {
      mbar_expect_tx(cx.sb + SM_XFULL + 32 * w + 8 * i, 24576);
      tma3d(cx.sb + SM_X + (3 * w + i) * 24576, &tmX, qb * 128 + w * 64, i * 3, cx.sb + SM_XFULL + 32 * w + 8 * i);
    }
  };
  if (warp < 4) {
    asm volatile("setmaxnreg.dec.sync.aligned.u32 24;");
    if (elect_one()) {
      if (warp == 0) TSP(64)
      if (warp < 2) {
#pragma unroll
        for (int i = 0; i < 4; i++) mbar_init(cx.sb + SM_FULL + 32 * warp + 8 * i, 1 + 3 * warp);
        mbar_init(cx.sb + SM_BAR_XG + 8 * warp, 1);
        mbar_init(cx.sb + SM_BAR_Q + 8 * warp, 1);
        if (warp) mbar_init(cx.sb + SM_BAR_MISC, 1);
      } else if (is_ffn) {
#pragma unroll
        for (int i = 0; i < 8; i++) mbar_init(cx.sb + (warp == 2 ? SM_FFULL : SM_FEMPTY) + 8 * i, 1);
      }
      asm volatile("fence.mbarrier_init.release.cluster;" ::: "memory");
    }
    __syncwarp();
    cluster_arrive();
    if (warp == 0) TSP(70)
    cluster_wait();
    if (warp == 0) TSP(71)
    prof(0, 24, 511);
    if (warp == 0) {
      if (is_ffn) ffn_producer(cx, qb, &tmWq, &tmG, &tmU, &tmD);
      else attn_producer(cx, qb, hs, tmKV.m, &tmWq, &tmWq96, &tmWo);
      prof(0, 25, 511);
    } else {
      sq_publish(cx, qb, hs, warp - 1, read_lane());
      if (warp == 3) sq_collect(cx, qb, read_lane());
      if (!is_ffn) {
        attn_gate(cx, qb, hs, warp - 1, threadIdx.x - 32, x);
        if (warp == 1) TSP(65)
        asm volatile("fence.proxy.async.global;" ::: "memory");
        if (warp == 1) attn_helper(cx, qb, hs, fresh_lane(), &tmX16);
        else bar_arrive(BAR_OA, 352);
        attn_finish8(cx, qb, hs, warp - 1, fresh_lane(), out);
      } else if (warp < 3) {
        ffn_publish(cx, qb, warp - 1, fresh_lane(), &tmX64);
      }
    }
    __syncwarp();
    cluster_arrive();
    cluster_wait();
  } else {
    if (warp == 4 && elect_one()) {
#pragma unroll
      for (int i = 0; i < 3; i++) mbar_init(cx.sb + SM_XFULL + 8 * i, 1);
      TSP(66)
      load_x(0, 0, 3);
#pragma unroll
      for (int i = 4; i < 7; i++) mbar_init(cx.sb + SM_XFULL + 8 * i, 1);
      asm volatile("fence.mbarrier_init.release.cluster;" ::: "memory");
    }
    if (warp == 5 && elect_one()) {
      mbar_init(cx.sb + SM_BAR_W, 1);
      asm volatile("fence.mbarrier_init.release.cluster;" ::: "memory");
      *(uint4*)(cx.sp + SM_ONES) = make_uint4(0x3F803F80u, 0x3F803F80u, 0x3F803F80u, 0x3F803F80u);
      mbar_expect_tx(cx.sb + SM_BAR_W, DM * 2);
      bulk_load(cx.sb + SM_WR, w_r, DM * 2, cx.sb + SM_BAR_W);
    }
    __syncwarp();
    cluster_arrive();
    if (warp == 4 && elect_one()) {
      load_x(1, 0, X_ORD);
      TSP(67)
    }
    __syncwarp();
    asm volatile("setmaxnreg.inc.sync.aligned.u32 240;");
    const int cw = warp - 4, wg = cw >> 2;
    cluster_wait();
    if (warp == 8 && elect_one()) {
      const uint64_t pol = policy_evict_first();
#pragma unroll
      for (int i = 0; i < 4; i++) {
        if (!(i & 1)) mbar_expect_tx(cx.sb + SM_FULL + 4 * i, 32768);
        tma2d_mc(cx.sb + SM_RING + (i >> 1) * STAGE + cx.rank * 16384 + (i & 1) * 8192, &tmWq,
                 is_ffn ? (cx.rank * 4 + 3) * DH + 64 : hs * 512 + cx.rank * 64, i * 64, cx.sb + SM_FULL + 8 * (i >> 1), pol);
        if (i == 1) load_x(1, X_ORD, 3);
      }
      TSP(72)
    }
    __syncwarp();
    attn_consumer(cx, is_ffn, qb, hs, wg, cw, read_lane(), x, kc, vc, out);
  }
}

typedef CUresult (*EncodeFn)(CUtensorMap*, CUtensorMapDataType, cuuint32_t, void*, const cuuint64_t*, const cuuint64_t*,
                             const cuuint32_t*, const cuuint32_t*, CUtensorMapInterleave, CUtensorMapSwizzle,
                             CUtensorMapL2promotion, CUtensorMapFloatOOBfill);

void encode(EncodeFn fn, CUtensorMap* m, const void* p, int rank, const cuuint64_t* dims, const cuuint64_t* strides,
            const cuuint32_t* box) {
  const cuuint32_t es[5] = {1, 1, 1, 1, 1};
  fn(m, CU_TENSOR_MAP_DATA_TYPE_BFLOAT16, rank, const_cast<void*>(p), dims, strides, box, es, CU_TENSOR_MAP_INTERLEAVE_NONE,
     CU_TENSOR_MAP_SWIZZLE_128B, CU_TENSOR_MAP_L2_PROMOTION_L2_128B, CU_TENSOR_MAP_FLOAT_OOB_FILL_NONE);
}
void encode2d(EncodeFn fn, CUtensorMap* m, const void* p, uint64_t rows, uint64_t cols, uint32_t box_rows) {
  const cuuint64_t dims[2] = {cols, rows}, strides[1] = {cols * 2};
  const cuuint32_t box[2] = {64, box_rows};
  encode(fn, m, p, 2, dims, strides, box);
}

}

extern "C" void kernel_launch(void* const* d_in, const int* in_sizes, int n_in, void* d_out, int out_size) {
  (void)in_sizes; (void)n_in; (void)out_size;
  void* fnp = nullptr;
  cudaDriverEntryPointQueryResult qr;
  cudaGetDriverEntryPoint("cuTensorMapEncodeTiled", &fnp, cudaEnableDefault, &qr);
  EncodeFn fn = (EncodeFn)fnp;
  CUtensorMap tmWq, tmWo, tmG, tmU, tmD, tmX, tmX16, tmWq96, tmX64;
  encode2d(fn, &tmX64, d_in[0], SEQ, DM, 64);
  encode2d(fn, &tmWq96, d_in[3], DM, 4096, 96);
  encode2d(fn, &tmX16, d_in[0], SEQ, DM, 16);
  KvMaps tmKV;
  for (int i = 0; i < 4; i++) encode2d(fn, &tmKV.m[i], d_in[1 + (i & 1)], 16 * SEQ, DH, i < 2 ? 112 : 96);
  encode2d(fn, &tmWq, d_in[3], DM, 4096, 64);
  {
    const cuuint64_t dims[3] = {64, SEQ, 9}, strides[2] = {DM * 2, 128};
    const cuuint32_t box[3] = {64, 64, 3};
    encode(fn, &tmX, d_in[0], 3, dims, strides, box);
  }
  encode2d(fn, &tmWo, d_in[4], 4096, DM, 128);
  encode2d(fn, &tmG, d_in[7], DM, FF, 192);
  encode2d(fn, &tmU, d_in[8], DM, FF, 192);
  encode2d(fn, &tmD, d_in[9], FF, DM, 192);
  cudaFuncSetAttribute(fused_kernel, cudaFuncAttributeMaxDynamicSharedMemorySize, SM_TOTAL);
  void* scratch = nullptr;
  cudaGetSymbolAddress(&scratch, g_scratch);
  fused_kernel<<<N_CTA, THREADS, SM_TOTAL>>>((const __nv_bfloat16*)d_in[0], (const __nv_bfloat16*)d_in[6], (const __nv_bfloat16*)d_in[1],
                                            (const __nv_bfloat16*)d_in[2], (__nv_bfloat16*)d_out, (Scratch*)scratch, tmX, tmWq, tmKV,
                                            tmWo, tmG, tmU, tmD, tmX16, tmWq96, tmX64);
}
```

```cpp
#include <cuda_runtime.h>
#include <cuda_bf16.h>
#include <cuda.h>
#include <stdint.h>

#define X_PFW 1
#define X_SPLIT 38
#define X_SPLITA 36
#define X_SPLITS 32
#define X_SPLITSA 30
#define X_PA 8
#define X_PG 4
#define X_E0 10
#define X_F2 12
#define X_Q1 6
#define X_LN 0
#define X_WAKE 31
#define X_F1 4
#define X_BF2 1
#define X_SQI 4
#define X_SQS 300
#define X_ORD 3
#define X_QP 2
#define X_QC 2
#define X_NS 4
namespace {

constexpr int SEQ = 2048, DM = 576, DH = 128, FF = 4608, TOPC = 8;
constexpr int N_ATT_CTA = 128, N_CTA = 132;
constexpr int THREADS = 384;

constexpr uint32_t SM_RING = 0;
constexpr uint32_t STAGE = 32768;
constexpr uint32_t SM_SLOT = 131072;
constexpr uint32_t FSTAGE = 24576;
constexpr uint32_t SM_XSEL = 196608;
constexpr uint32_t SM_H = 205824;
constexpr uint32_t SM_MISC = 229376;
constexpr uint32_t SM_FULL = SM_MISC, SM_EMPTY = SM_MISC + 32, SM_FFULL = SM_MISC + 64, SM_BAR_MISC = SM_MISC + 128,
                   SM_COLD = SM_MISC + 136, SM_TAG = SM_MISC + 144, SM_BAR_W = SM_MISC + 152, SM_ONES = SM_MISC + 160,
                   SM_BAR_Q = SM_MISC + 176, SM_XFULL = SM_MISC + 192, SM_BAR_XG = SM_MISC + 304, SM_BAR_SQ = SM_MISC + 312,
                   SM_STATS = SM_MISC + 320, SM_FEMPTY = SM_MISC + 1344, SM_RAW = SM_FEMPTY, SM_WR = SM_MISC + 1408, SM_TOPK = SM_WR;
constexpr uint32_t SM_TOTAL = SM_MISC + 2560;
constexpr uint32_t SM_X = SM_MISC - 147456;

constexpr int BAR_GATE = 6, BAR_HELPER = 7, BAR_OA = 8, BAR_XREL = 13, BAR_QS = 9, BAR_QF = 11;
constexpr int NST_Q = 18, NST_KV = 76, NST_O = 18;
constexpr float SM_SCALE_LOG2 = 0.08838834764831845f * 1.4426950408889634f;

struct Scratch {
  uint4 part[16 * 64 * 2 * 4 * 128];
  uint4 gate[N_ATT_CTA * 1152];
  uint4 q[16 * 8 * 2 * 512];
  uint2 sq[SEQ];
  uint4 stats[SEQ];
  float ypart[4 * TOPC * DM];
  int2 sel[16];
  unsigned launch[160];
  unsigned pad0, ycnt, pad[30];
  unsigned qflag[128];
};
__device__ __align__(1024) Scratch g_scratch;

__device__ __forceinline__ void prof(int, int, int = 0) {}

#define TS(id) {}
#define TS_DUMP() {}
#define TSH(k) {}
#define TS4(k) {}
#define TSP(k) {}
#define TS1(id) TS(id)
#define TS2(k) {}
#define TS3(k) {}

__device__ __forceinline__ uint32_t smem_u32(const void* p) { return (uint32_t)__cvta_generic_to_shared(p); }
__device__ __forceinline__ void mbar_init(uint32_t bar, uint32_t cnt) {
  asm volatile("mbarrier.init.shared::cta.b64 [%0], %1;" ::"r"(bar), "r"(cnt) : "memory");
}
__device__ __forceinline__ void mbar_expect_tx(uint32_t bar, uint32_t bytes) {
  asm volatile("mbarrier.arrive.expect_tx.shared::cta.b64 _, [%0], %1;" ::"r"(bar), "r"(bytes) : "memory");
}
__device__ __forceinline__ void mbar_arrive(uint32_t bar) {
  asm volatile("mbarrier.arrive.shared::cta.b64 _, [%0];" ::"r"(bar) : "memory");
}
__device__ __forceinline__ void mbar_arrive_cluster(uint32_t bar_cluster_addr, bool pred) {
  asm volatile("{\n.reg .pred p;\nsetp.ne.u32 p, %1, 0;\n@p mbarrier.arrive.shared::cluster.b64 _, [%0];\n}"
               ::"r"(bar_cluster_addr), "r"((uint32_t)pred) : "memory");
}
template <int ID>
__device__ __forceinline__ void mbar_arrive_cluster_now(uint32_t bar_cluster_addr, bool pred) {
  asm volatile("{\n.reg .pred p, q;\nsetp.ne.u32 p, %1, 0;\nsetp.eq.u32 q, %2, %3;\n"
               "ARR_LOOP:\n@p mbarrier.arrive.shared::cluster.b64 _, [%0];\n@q bra.uni ARR_LOOP;\n}"
               ::"r"(bar_cluster_addr), "r"((uint32_t)pred), "r"(blockIdx.y), "n"(ID) : "memory");
}
__device__ __forceinline__ void block_fence(int id) {
  asm volatile("{\n.reg .pred q;\nsetp.eq.u32 q, %0, %1;\nBF_LOOP:\n@q st.volatile.shared.u32 [%0], %0;\n@q bra.uni BF_LOOP;\n}"
               ::"r"(blockIdx.y), "r"(id) : "memory");
}
__device__ __forceinline__ void mbar_wait(uint32_t bar, uint32_t parity) {
  asm volatile("{\n.reg .pred p, q;\n.reg .u32 n;\nmov.u32 n, 0;\n"
               "WAIT_LOOP:\nmbarrier.try_wait.parity.shared::cta.b64 p, [%0], %1;\n"
               "add.u32 n, n, 1;\nsetp.lt.u32 q, n, 4194304;\nand.pred q, q, !p;\n@q bra WAIT_LOOP;\n}"
               ::"r"(bar), "r"(parity) : "memory");
}
__device__ __forceinline__ uint32_t mapa(uint32_t addr, uint32_t rank) {
  uint32_t r;
  asm volatile("mapa.shared::cluster.u32 %0, %1, %2;" : "=r"(r) : "r"(addr), "r"(rank));
  return r;
}
__device__ __forceinline__ void cluster_arrive() { asm volatile("barrier.cluster.arrive.relaxed.aligned;" ::: "memory"); }
__device__ __forceinline__ bool elect_one() {
  uint32_t p;
  asm volatile("{\n.reg .pred p;\nelect.sync _|p, 0xffffffff;\nselp.u32 %0, 1, 0, p;\n}" : "=r"(p));
  return p;
}
__device__ __forceinline__ int read_lane() { return threadIdx.x & 31; }
__device__ __forceinline__ int fresh_lane() {
  int l;
  asm volatile("mov.u32 %0, %%laneid;" : "=r"(l));
  return l;
}
template <class T> __device__ __forceinline__ T* at(T* p, uint32_t bytes) {
  asm("" : "+r"(bytes));
  return (T*)((const char*)p + bytes);
}
__device__ __forceinline__ void cluster_wait() { asm volatile("barrier.cluster.wait.acquire.aligned;" ::: "memory"); }
__device__ __forceinline__ void bar_sync(int id, int n) { asm volatile("barrier.cta.sync %0, %1;" ::"r"(id), "r"(n) : "memory"); }
__device__ __forceinline__ void bar_arrive(int id, int n) { asm volatile("barrier.cta.arrive %0, %1;" ::"r"(id), "r"(n) : "memory"); }

__device__ __forceinline__ uint64_t policy_evict_first() {
  uint64_t p;
  asm("createpolicy.fractional.L2::evict_first.b64 %0, 1.0;" : "=l"(p));
  return p;
}
__device__ __forceinline__ void tma2d_mc(uint32_t dst, const CUtensorMap* tm, int c0, int c1, uint32_t bar, uint64_t pol) {
  asm volatile("cp.async.bulk.tensor.2d.shared::cluster.global.mbarrier::complete_tx::bytes.multicast::cluster.L2::cache_hint"
               " [%0], [%1, {%2, %3}], [%4], %5, %6;"
               ::"r"(dst), "l"(tm), "r"(c0), "r"(c1), "r"(bar), "h"((uint16_t)3), "l"(pol) : "memory");
}
__device__ __forceinline__ void tma3d(uint32_t dst, const CUtensorMap* tm, int c1, int c2, uint32_t bar) {
  asm volatile("cp.async.bulk.tensor.3d.shared::cluster.global.mbarrier::complete_tx::bytes [%0], [%1, {%2, %3, %4}], [%5];"
               ::"r"(dst), "l"(tm), "r"(0), "r"(c1), "r"(c2), "r"(bar) : "memory");
}
__device__ __forceinline__ void tma2d(uint32_t dst, const CUtensorMap* tm, int c0, int c1, uint32_t bar) {
  asm volatile("cp.async.bulk.tensor.2d.shared::cluster.global.mbarrier::complete_tx::bytes [%0], [%1, {%2, %3}], [%4];"
               ::"r"(dst), "l"(tm), "r"(c0), "r"(c1), "r"(bar) : "memory");
}
__device__ __forceinline__ void tma2d_stream(uint32_t dst, const CUtensorMap* tm, int c0, int c1, uint32_t bar) {
  asm volatile("{\n.reg .b64 pol;\ncreatepolicy.fractional.L2::evict_first.b64 pol, 1.0;\n"
               "cp.async.bulk.tensor.2d.shared::cluster.global.mbarrier::complete_tx::bytes.L2::cache_hint [%0], [%1, {%2, %3}], [%4], pol;\n}"
               ::"r"(dst), "l"(tm), "r"(c0), "r"(c1), "r"(bar) : "memory");
}
__device__ __forceinline__ void bulk_load(uint32_t dst, const void* src, uint32_t bytes, uint32_t bar) {
  asm volatile("cp.async.bulk.shared::cluster.global.mbarrier::complete_tx::bytes [%0], [%1], %2, [%3];"
               ::"r"(dst), "l"(src), "r"(bytes), "r"(bar) : "memory");
}
__device__ __forceinline__ void tma2d_prefetch(const CUtensorMap* tm, int c0, int c1) {
  asm volatile("cp.async.bulk.prefetch.tensor.2d.L2.global [%0, {%1, %2}];" ::"l"(tm), "r"(c0), "r"(c1) : "memory");
}

__device__ __forceinline__ void wg_fence() { asm volatile("wgmma.fence.sync.aligned;" ::: "memory"); }
__device__ __forceinline__ void wg_commit() { asm volatile("wgmma.commit_group.sync.aligned;" ::: "memory"); }
template <int N> __device__ __forceinline__ void wg_wait() { asm volatile("wgmma.wait_group.sync.aligned %0;" ::"n"(N) : "memory"); }

__device__ __forceinline__ uint64_t mkdesc(uint32_t addr, uint32_t lbo_bytes) {
  return (uint64_t)(((addr & 0x3FFFF) >> 4) | ((lbo_bytes >> 4) << 16)) | ((uint64_t)0x40000040u << 32);
}
__device__ __forceinline__ uint64_t mkdesc_q(uint32_t addr) {
  return (uint64_t)(((addr & 0x3FFFF) >> 4) | (64u << 16)) | ((uint64_t)8 << 32);
}
template <int N> __device__ __forceinline__ void pin(float (&a)[N]) {
#pragma unroll
  for (int i = 0; i < N; i++) asm volatile("" : "+f"(a[i])::"memory");
}
template <int N> __device__ __forceinline__ void kill(float (&a)[N]) {
#pragma unroll
  for (int i = 0; i < N; i++) asm volatile("" : "=f"(a[i]));
}
template <int N> __device__ __forceinline__ void pin(uint32_t (&a)[N]) {
#pragma unroll
  for (int i = 0; i < N; i++) asm volatile("" : "+r"(a[i])::"memory");
}

#define F8(d, o) "+f"(d[o]), "+f"(d[o + 1]), "+f"(d[o + 2]), "+f"(d[o + 3]), "+f"(d[o + 4]), "+f"(d[o + 5]), "+f"(d[o + 6]), "+f"(d[o + 7])
#define R32A "%0, %1, %2, %3, %4, %5, %6, %7, %8, %9, %10, %11, %12, %13, %14, %15, %16, %17, %18, %19, %20, %21, %22, %23, %24, %25, %26, %27, %28, %29, %30, %31"
#define R32B "%32, %33, %34, %35, %36, %37, %38, %39, %40, %41, %42, %43, %44, %45, %46, %47, %48, %49, %50, %51, %52, %53, %54, %55, %56, %57, %58, %59, %60, %61, %62, %63"

#define O8(d, o) "=f"(d[o]), "=f"(d[o + 1]), "=f"(d[o + 2]), "=f"(d[o + 3]), "=f"(d[o + 4]), "=f"(d[o + 5]), "=f"(d[o + 6]), "=f"(d[o + 7])

__device__ __forceinline__ void mma_n128t(float (&d)[64], uint32_t a0, uint32_t a1, uint32_t a2, uint32_t a3, uint64_t db, bool acc) {
  if (acc)
    asm volatile("wgmma.mma_async.sync.aligned.m64n128k16.f32.bf16.bf16 {" R32A ", " R32B "}, {%64, %65, %66, %67}, %68, 1, 1, 1, 1;\n"
                 : F8(d, 0), F8(d, 8), F8(d, 16), F8(d, 24), F8(d, 32), F8(d, 40), F8(d, 48), F8(d, 56)
                 : "r"(a0), "r"(a1), "r"(a2), "r"(a3), "l"(db));
  else
    asm volatile("wgmma.mma_async.sync.aligned.m64n128k16.f32.bf16.bf16 {" R32A ", " R32B "}, {%64, %65, %66, %67}, %68, 0, 1, 1, 1;\n"
                 : O8(d, 0), O8(d, 8), O8(d, 16), O8(d, 24), O8(d, 32), O8(d, 40), O8(d, 48), O8(d, 56)
                 : "r"(a0), "r"(a1), "r"(a2), "r"(a3), "l"(db));
}
#define PV1(a0, a1, a2, a3, ob, acc) "add.s64 b, %92, " #ob ";\n" \
  "wgmma.mma_async.sync.aligned.m64n128k16.f32.bf16.bf16 {" R32A ", " R32B "}, {%" #a0 ", %" #a1 ", %" #a2 ", %" #a3 "}, b, " #acc ", 1, 1, 1;\n"
#define PV6 "wgmma.fence.sync.aligned;\n" PV1(64, 65, 66, 67, 0, p) PV1(68, 69, 70, 71, 128, 1) PV1(72, 73, 74, 75, 256, 1) \
  PV1(76, 77, 78, 79, 384, 1) PV1(80, 81, 82, 83, 512, 1) PV1(84, 85, 86, 87, 640, 1)
#define U4(a, o) "r"(a[o]), "r"(a[o + 1]), "r"(a[o + 2]), "r"(a[o + 3])
__device__ __forceinline__ void mma_pv(float (&d)[64], const uint32_t (&a)[28], uint64_t dv, bool acc, bool big) {
  asm volatile("{\n.reg .pred p, q;\n.reg .b64 b;\nsetp.ne.b32 p, %93, 0;\nsetp.eq.b32 q, %94, 0;\n@q bra.uni PV_SMALL;\n"
               PV6 PV1(88, 89, 90, 91, 768, 1) "wgmma.commit_group.sync.aligned;\nbra.uni PV_DONE;\n"
               "PV_SMALL:\n" PV6 "wgmma.commit_group.sync.aligned;\nPV_DONE:\n}\n"
               : F8(d, 0), F8(d, 8), F8(d, 16), F8(d, 24), F8(d, 32), F8(d, 40), F8(d, 48), F8(d, 56)
               : U4(a, 0), U4(a, 4), U4(a, 8), U4(a, 12), U4(a, 16), U4(a, 20), U4(a, 24), "l"(dv), "r"((int)acc), "r"((int)big) : "memory");
}
#define R48 R32A ", %32, %33, %34, %35, %36, %37, %38, %39, %40, %41, %42, %43, %44, %45, %46, %47"
#define R56 R48 ", %48, %49, %50, %51, %52, %53, %54, %55"
#define QK1(N, R, A, B, oa, ob, acc) "add.s64 a, " A ", " #oa ";\nadd.s64 b, " B ", " #ob ";\n" \
  "wgmma.mma_async.sync.aligned.m64n" #N "k16.f32.bf16.bf16 {" R "}, a, b, " #acc ", 1, 1, 0, 0;\n"
#define QK8(N, R, A, B) "{\n.reg .b64 a, b;\nwgmma.fence.sync.aligned;\n" QK1(N, R, A, B, 0, 0, 0) QK1(N, R, A, B, 128, 2, 1) \
  QK1(N, R, A, B, 256, 4, 1) QK1(N, R, A, B, 384, 6, 1) QK1(N, R, A, B, 512, 1024, 1) QK1(N, R, A, B, 640, 1026, 1) \
  QK1(N, R, A, B, 768, 1028, 1) QK1(N, R, A, B, 896, 1030, 1) "wgmma.commit_group.sync.aligned;\n}\n"
__device__ __forceinline__ void mma_qk(float (&d)[56], uint64_t dq, uint64_t dk) {
  asm volatile(QK8(112, R56, "%56", "%57")
               : O8(d, 0), O8(d, 8), O8(d, 16), O8(d, 24), O8(d, 32), O8(d, 40), O8(d, 48) : "l"(dq), "l"(dk) : "memory");
}
__device__ __forceinline__ void mma_qk(float (&d)[48], uint64_t dq, uint64_t dk) {
  asm volatile(QK8(96, R48, "%48", "%49")
               : O8(d, 0), O8(d, 8), O8(d, 16), O8(d, 24), O8(d, 32), O8(d, 40) : "l"(dq), "l"(dk) : "memory");
}
__device__ __forceinline__ void mma_n64t(float (&d)[32], uint32_t a0, uint32_t a1, uint32_t a2, uint32_t a3, uint64_t db, bool acc) {
  if (acc)
    asm volatile("wgmma.mma_async.sync.aligned.m64n64k16.f32.bf16.bf16 {" R32A "}, {%32, %33, %34, %35}, %36, 1, 1, 1, 1;\n"
                 : F8(d, 0), F8(d, 8), F8(d, 16), F8(d, 24) : "r"(a0), "r"(a1), "r"(a2), "r"(a3), "l"(db));
  else
    asm volatile("wgmma.mma_async.sync.aligned.m64n64k16.f32.bf16.bf16 {" R32A "}, {%32, %33, %34, %35}, %36, 0, 1, 1, 1;\n"
                 : O8(d, 0), O8(d, 8), O8(d, 16), O8(d, 24) : "r"(a0), "r"(a1), "r"(a2), "r"(a3), "l"(db));
}
__device__ __forceinline__ void mma_n64t_dyn(float (&d)[32], uint32_t a0, uint32_t a1, uint32_t a2, uint32_t a3, uint64_t db, int acc) {
  asm volatile("{\n.reg .pred p;\nsetp.ne.b32 p, %37, 0;\n"
               "wgmma.mma_async.sync.aligned.m64n64k16.f32.bf16.bf16 {" R32A "}, {%32, %33, %34, %35}, %36, p, 1, 1, 1;\n}\n"
               : F8(d, 0), F8(d, 8), F8(d, 16), F8(d, 24) : "r"(a0), "r"(a1), "r"(a2), "r"(a3), "l"(db), "r"(acc));
}
__device__ __forceinline__ void mma_n8(float (&d)[4], uint64_t da, uint64_t db, int acc) {
  asm volatile("{\n.reg .pred p;\nsetp.ne.b32 p, %6, 0;\n"
               "wgmma.mma_async.sync.aligned.m64n8k16.f32.bf16.bf16 {%0, %1, %2, %3}, %4, %5, p, 1, 1, 1, 0;\n}\n"
               : "+f"(d[0]), "+f"(d[1]), "+f"(d[2]), "+f"(d[3])
               : "l"(da), "l"(db), "r"(acc));
}
__device__ __forceinline__ void hmma_k16(float (&d)[4], uint32_t a0, uint32_t a1, uint32_t a2, uint32_t a3, uint32_t b0, uint32_t b1) {
  asm volatile("mma.sync.aligned.m16n8k16.row.col.f32.bf16.bf16.f32 {%0, %1, %2, %3}, {%4, %5, %6, %7}, {%8, %9}, {%0, %1, %2, %3};"
               : "+f"(d[0]), "+f"(d[1]), "+f"(d[2]), "+f"(d[3]) : "r"(a0), "r"(a1), "r"(a2), "r"(a3), "r"(b0), "r"(b1));
}

__device__ __forceinline__ uint32_t pack2(float lo, float hi) {
  uint32_t r;
  asm("cvt.rn.bf16x2.f32 %0, %1, %2;" : "=r"(r) : "f"(hi), "f"(lo));
  return r;
}
__device__ __forceinline__ float bf_lo(uint32_t w) { return __uint_as_float(w << 16); }
__device__ __forceinline__ float bf_hi(uint32_t w) { return __uint_as_float(w & 0xFFFF0000u); }
__device__ __forceinline__ float bfr(float x) { return __bfloat162float(__float2bfloat16_rn(x)); }
__device__ __forceinline__ uint32_t sub2(uint32_t a, uint32_t b) {
  uint32_t r;
  asm("sub.rn.bf16x2 %0, %1, %2;" : "=r"(r) : "r"(a), "r"(b));
  return r;
}
__device__ __forceinline__ uint32_t add2(uint32_t a, uint32_t b) {
  uint32_t r;
  asm("add.rn.bf16x2 %0, %1, %2;" : "=r"(r) : "r"(a), "r"(b));
  return r;
}
__device__ __forceinline__ uint32_t fma2(uint32_t a, uint32_t b, uint32_t c) {
  uint32_t r;
  asm("fma.rn.bf16x2 %0, %1, %2, %3;" : "=r"(r) : "r"(a), "r"(b), "r"(c));
  return r;
}
__device__ __forceinline__ float ex2(float x) {
  float r;
  asm("ex2.approx.ftz.f32 %0, %1;" : "=f"(r) : "f"(x));
  return r;
}
__device__ __forceinline__ float rcp(float x) {
  float r;
  asm("rcp.approx.ftz.f32 %0, %1;" : "=f"(r) : "f"(x));
  return r;
}
__device__ __forceinline__ float silu_f(float t) { return t * rcp(1.0f + ex2(-1.4426950408889634f * t)); }
__device__ __forceinline__ void lds128(uint32_t a, uint32_t& x, uint32_t& y, uint32_t& z, uint32_t& w) {
  asm volatile("ld.shared.v4.u32 {%0, %1, %2, %3}, [%4];" : "=r"(x), "=r"(y), "=r"(z), "=r"(w) : "r"(a) : "memory");
}
__device__ __forceinline__ void ldsm4(uint32_t a, uint32_t& x, uint32_t& y, uint32_t& z, uint32_t& w) {
  asm volatile("ldmatrix.sync.aligned.m8n8.x4.shared.b16 {%0, %1, %2, %3}, [%4];" : "=r"(x), "=r"(y), "=r"(z), "=r"(w) : "r"(a) : "memory");
}
constexpr uint32_t TAG = 0x10000;
__device__ __forceinline__ void st_gran(uint4* p, uint32_t x, uint32_t y, uint32_t z, uint32_t w) {
  asm volatile("st.relaxed.gpu.global.v4.b32 [%0], {%1, %2, %3, %4};" ::"l"(p), "r"(x), "r"(y), "r"(z), "r"(w) : "memory");
}
__device__ __forceinline__ void ld_gran(const uint4* p, uint32_t& x, uint32_t& y, uint32_t& z, uint32_t& w) {
  asm volatile("ld.relaxed.gpu.global.v4.b32 {%0, %1, %2, %3}, [%4];" : "=r"(x), "=r"(y), "=r"(z), "=r"(w) : "l"(p) : "memory");
}
__device__ __forceinline__ void stsm4(uint32_t a, uint32_t x, uint32_t y, uint32_t z, uint32_t w) {
  asm volatile("stmatrix.sync.aligned.m8n8.x4.shared.b16 [%0], {%1, %2, %3, %4};" ::"r"(a), "r"(x), "r"(y), "r"(z), "r"(w) : "memory");
}
__device__ __forceinline__ void cp16(uint32_t dst, const void* src) {
  asm volatile("cp.async.cg.shared.global [%0], [%1], 16;" ::"r"(dst), "l"(src) : "memory");
}
__device__ __forceinline__ void cp_wait_all() { asm volatile("cp.async.wait_all;" ::: "memory"); }
__device__ __forceinline__ void add_granules(float (&red)[32], const uint32_t (&g)[16]) {
#pragma unroll
  for (int i = 0; i < 16; i++) { red[2 * i] += bf_lo(g[i]); red[2 * i + 1] += bf_hi((i & 3) ? g[i] : g[i] & ~TAG); }
}
__device__ __forceinline__ bool granules_ok(const uint32_t (&g)[16], uint32_t tag) {
  uint32_t a, b;
  asm("lop3.b32 %0, %1, %2, %3, 0x7E;" : "=r"(a) : "r"(g[0]), "r"(g[4]), "r"(tag));
  asm("lop3.b32 %0, %1, %2, %3, 0x7E;" : "=r"(b) : "r"(g[8]), "r"(g[12]), "r"(tag));
  return __all_sync(0xffffffffu, ((a | b) & TAG) == 0);
}
__device__ __forceinline__ unsigned ld_acquire(const unsigned* p) {
  unsigned v;
  asm volatile("ld.acquire.gpu.global.u32 %0, [%1];" : "=r"(v) : "l"(p) : "memory");
  return v;
}
__device__ __forceinline__ unsigned atom_add_acq_rel(unsigned* p) {
  unsigned v;
  asm volatile("atom.acq_rel.gpu.global.add.u32 %0, [%1], 1;" : "=r"(v) : "l"(p) : "memory");
  return v;
}

template <int K0, int K1>
__device__ __forceinline__ void ln_fetch(uint32_t (&xa)[144], uint32_t boxes, uint32_t lo) {
#pragma unroll
  for (int k = K0; k < K1; k++) ldsm4(boxes + (k >> 2) * 8192 + (lo ^ ((k & 3) << 5)), xa[4 * k], xa[4 * k + 1], xa[4 * k + 2], xa[4 * k + 3]);
}
__device__ __forceinline__ void ln_fetch_b(uint32_t (&b)[24], uint32_t& wb, uint32_t ws) {
#pragma unroll
  for (int j = 0; j < 6; j++, wb += ws) ldsm4(wb, b[4 * j], b[4 * j + 1], b[4 * j + 2], b[4 * j + 3]);
}
template <int K0, int K1>
__device__ __forceinline__ void ln_sums(const uint32_t (&xa)[144], float (&sm)[X_NS][4], const uint32_t (&b)[24]) {
#pragma unroll
  for (int k = K0; k < K1; k++)
    hmma_k16(sm[k % X_NS], xa[4 * k], xa[4 * k + 1], xa[4 * k + 2], xa[4 * k + 3], b[2 * (k % 12)], b[2 * (k % 12) + 1]);
}
__device__ __forceinline__ void ln_row(float sum, float sq, float& mean_b, float& rstd) {
  const float mean = sum * (1.0f / DM);
  const uint32_t mv = pack2(mean, fmaxf(sq * (1.0f / DM) - mean * mean, 0.0f));
  mean_b = bf_lo(mv);
  float sd;
  asm("sqrt.approx.f32 %0, %1;" : "=f"(sd) : "f"(bf_lo(pack2(bf_hi(mv) + 1e-5f, 0.f))));
  rstd = rcp(bf_lo(pack2(sd, 0.f)));
}

template <bool ROUTED>
__device__ __forceinline__ uint32_t gate2(uint32_t xc, float rstd, float2 upd = make_float2(0.f, 0.f)) {
  uint32_t t = pack2(bf_lo(xc) * rstd, bf_hi(xc) * rstd);
  if (ROUTED) t = pack2(bf_lo(t) + upd.x, bf_hi(t) + upd.y);
  return pack2(silu_f(bf_lo(t)), silu_f(bf_hi(t)));
}

template <int V> struct IC { static constexpr int value = V; };

struct Ctx {
  uint32_t sb;
  uint8_t* sp;
  uint32_t rank;
  Scratch* g;
};

__device__ __forceinline__ bool acquire(const Ctx& cx, uint32_t r, uint32_t n, uint32_t bytes) {
  mbar_wait(cx.sb + SM_EMPTY + 8 * r, (n ^ (r >> 1) ^ 1) & 1);
  __syncwarp();
  const bool e = elect_one();
  if (e) mbar_expect_tx(cx.sb + SM_FULL + 8 * r, bytes);
  return e;
}
__device__ __forceinline__ void load_wq(const Ctx& cx, const CUtensorMap* tmWq, int st, int i, int n0, uint64_t pol) {
  const uint32_t r = st & 3, dst = cx.sb + SM_RING + r * STAGE + cx.rank * 16384, bar = cx.sb + SM_FULL + 8 * r;
  const int k0 = i < 3 ? 128 * i : 128 * i - 64;
  if (acquire(cx, r, st >> 2, i == 2 ? 16384 : 32768)) {
    tma2d_mc(dst, tmWq, n0, k0, bar, pol);
    if (i != 2) tma2d_mc(dst + 8192, tmWq, n0, k0 + 64, bar, pol);
  }
}
__device__ __forceinline__ void attn_producer(const Ctx& cx, int qb, int hs, const CUtensorMap* tmKV, const CUtensorMap* tmWq,
                                              const CUtensorMap* tmWq96, const CUtensorMap* tmWo) {
  const uint32_t full = cx.sb + SM_FULL, ring = cx.sb + SM_RING + cx.rank * 16384;
  const uint64_t last_use = policy_evict_first();
  int st = 0;
#pragma unroll 1
  for (int p = 0; p < 4; p++) {
#pragma unroll 1
    for (int i = 0; i < (p == 2 ? 3 : 5); i++, st++) {
      if (p == 2) {
        if (acquire(cx, st & 3, st >> 2, 24576))
          tma2d_mc(cx.sb + SM_RING + (st & 3) * STAGE + cx.rank * 12288, tmWq96, (hs * 4 + 3) * DH, 192 * i + 96 * cx.rank, full + 8 * (st & 3), last_use);
      } else {
        if (st > 1) load_wq(cx, tmWq, st, i, (hs * 4 + (p ^ (p >> 1))) * DH + cx.rank * 64, last_use);
      }
      if (st == 1 || st == 2) TSP(72 + st)
      if (st == X_PFW) {
#pragma unroll 1
        for (int b = qb < 8; b < 5 - (qb >> 3); b++)
          if (elect_one()) tma2d_prefetch(tmWq, hs * 512 + (b < 4 ? (b ^ (b >> 1)) * DH + (qb & 1) * 64 : qb * 64), b < 4 ? (qb >> 1) * 64 : 512);
      }
      if (st == 8 && qb < 8 && elect_one()) tma2d_prefetch(tmKV + ((qb >> 1) & 1), cx.rank * 64, hs * 2 * SEQ + (qb >> 2) * 96);
    }
  }
  uint32_t r = 2, n = 4;
  int row = hs * 2 * SEQ, rows = 96;
  const CUtensorMap* tm = tmKV + 2;
#pragma unroll 1
  for (int u = 0; u < NST_KV; u++) {
    if (acquire(cx, r, n, rows * 256)) {
      tma2d_mc(ring + r * STAGE, tm, cx.rank * 64, row, full + 8 * r, last_use);
      if (((u ^ (qb >> 1)) & 7) == 0 && u < NST_KV - 4) tma2d_prefetch(tmKV + (u & 1), cx.rank * 64, row + 208);
      if ((unsigned)(u - 32) < 36 && (u & 15) == qb) tma2d_prefetch(tmWo, ((u - 32) >> 2) * 64, hs * 512 + (u & 3) * 128);
    }
    if (++r == 4) { r = 1; n++; }
    if (u & 1) row += rows;
    const bool big = (unsigned)(u - 9) < 56;
    rows = big ? 112 : 96;
    tm = tmKV + (~u & 1) + (big ? 0 : 2);
  }
#pragma unroll 1
  for (int u = 0; u < NST_O; u++) {
    const int s = u >> 1;
    const int blk = s == 0 ? 8 : ((hs + s) & 7);
    r = (0x87 >> (2 * (u & 3))) & 3;
    if (acquire(cx, r, (u >> 2) ^ ~u, 32768))
      tma2d_mc(ring + r * STAGE, tmWo, blk * 64, hs * 512 + ((u & 1) + cx.rank * 2) * 128, full + 8 * r, last_use);
  }
}

__device__ __forceinline__ void sq_publish(const Ctx& cx, int qb, int hs, int j, int lane) {
  if (j == 2 && lane == 0) {
    const unsigned e = cx.g->launch[hs * 16 + qb]++;
    *(uint2*)(cx.sp + SM_TAG) = make_uint2((~e & 1) * TAG, e);
  }
  const int row = (hs & 3) * 16 + (lane >> 1);
  uint32_t a = cx.sb + SM_X + (hs >> 2) * 73728 + j * 8192 + row * 128 + (((lane & 1) ^ (row & 7)) << 4);
  float s0 = 0.f, s1 = 0.f;
#pragma unroll 1
  for (int b = 0; b < 6; b++) {
    if (b == (hs < 4 ? 4 : 0)) {
      const int n = 224 + (__float_as_uint(s1) & blockIdx.y);
      if (j == 1) {
        bar_sync(BAR_XREL, n);
        if (lane < 4) asm volatile("mbarrier.arrive.shared::cluster.b64 _, [%0], 2;" ::"r"(mapa(cx.sb + SM_EMPTY + 16 + 8 * (lane >> 1), lane & 1)) : "memory");
      } else {
        bar_arrive(BAR_XREL, n);
      }
      __syncwarp();
      if (hs == 8) return;
    }
    if (!(b & 1)) mbar_wait(cx.sb + SM_XFULL + 32 * (hs >> 2) + 4 * b, 0);
    uint32_t v[8];
    lds128(a, v[0], v[1], v[2], v[3]);
    lds128(a ^ 32, v[4], v[5], v[6], v[7]);
    a = (a ^ 64) + (b & 1) * 24576;
#pragma unroll
    for (int i = 0; i < 8; i++) { s0 = fmaf(bf_lo(v[i]), bf_lo(v[i]), s0); s1 = fmaf(bf_hi(v[i]), bf_hi(v[i]), s1); }
  }
  s0 += s1;
  s0 += __shfl_xor_sync(0xffffffffu, s0, 1);
  float* part = (float*)(cx.sp + SM_STATS) + (lane >> 1) * 2;
  if (j < 2) {
    part[32 * j] = s0;
    bar_arrive(BAR_HELPER, 96);
  } else {
    bar_sync(BAR_HELPER, 96);
    TSP(68)
    if (!(lane & 1))
      asm volatile("st.relaxed.gpu.global.v2.b32 [%0], {%1, %2};" ::"l"(cx.g->sq + qb * 128 + hs * 16 + (lane >> 1)),
                   "r"(__float_as_uint((part[0] + part[32]) + s0)), "r"(*(const uint32_t*)(cx.sp + SM_TAG + 4) + 1) : "memory");
  }
}
__device__ __forceinline__ void sq_collect(const Ctx& cx, int qb, int lane) {
  const uint32_t e1 = *(const uint32_t*)(cx.sp + SM_TAG + 4) + 1;
#pragma unroll 1
  for (int n = 0; n < (1 << 16); n++) {
    __nanosleep(X_SQS);
    uint32_t bad = 0;
#pragma unroll
    for (int i = 0; i < 2; i++) {
      uint32_t a, t0, b, t1;
      ld_gran((const uint4*)at(cx.g->sq, qb * 1024 + lane * 16) + i * 32, a, t0, b, t1);
      *(uint32_t*)(cx.sp + SM_STATS + (i * 32 + lane) * 16 + 4) = a;
      *(uint32_t*)(cx.sp + SM_STATS + (i * 32 + lane) * 16 + 12) = b;
      bad |= (t0 ^ e1) | (t1 ^ e1);
    }
    if (__all_sync(0xffffffffu, bad == 0)) break;
  }
  __syncwarp();
  if (lane == 0) mbar_arrive(cx.sb + SM_BAR_SQ);
  TSP(69)
}
__device__ __forceinline__ void attn_gate(const Ctx& cx, int qb, int hs, int j, int t, const __nv_bfloat16* x) {
  const uint4* xp = (const uint4*)(x + qb * 128 * DM) + (t >> 3) * 72 + hs * 8 + (t & 7);
  uint4 nx = *xp;
  float wsum = 0.f;
  if (j == 0) {
    mbar_wait(cx.sb + SM_BAR_W, 0);
#pragma unroll 3
    for (int i = 0; i < 9; i++) {
      const uint32_t w = *(const uint32_t*)(cx.sp + SM_WR + i * 128 + t * 4);
      wsum += bf_lo(w) + bf_hi(w);
    }
#pragma unroll
    for (int i = 1; i < 32; i *= 2) wsum += __shfl_xor_sync(0xffffffffu, wsum, i);
  }
  bar_sync(BAR_GATE, 352);
  if (t < 16) {
    const float2 st = *(const float2*)(cx.sp + SM_STATS + 8 * (hs * 16 + t));
    const int row = qb * 128 + hs * 16 + t;
    const uint32_t b = pack2(0.f, fmaf(-st.x, wsum, *(const float*)(cx.sp + SM_RAW + 4 * t)) * st.y);
    st_gran(at(cx.g->stats, row * 16), __float_as_uint(st.x), __float_as_uint(st.y), (b ^ ((int)b < 0 ? 0xFFFF0000u : 0x80000000u)) | (0xFFFF - row),
            *(const uint32_t*)(cx.sp + SM_TAG + 4) + 1);
  }
  __syncwarp();
  uint32_t sa = cx.sb + SM_STATS + (t & ~7);
  uint4* gp = cx.g->gate + blockIdx.x * 1152 + (t ^ ((t >> 3) & 7));
  const int cross = t < 64 ? 10 : 9;
#pragma unroll 1
  for (int i = 0; i < 12; i++) {
    float2 st;
    asm volatile("ld.shared.v2.f32 {%0, %1}, [%2];" : "=f"(st.x), "=f"(st.y) : "r"(sa));
    const uint32_t mm = pack2(st.x, st.x);
    const uint4 v = make_uint4(sub2(nx.x, mm), sub2(nx.y, mm), sub2(nx.z, mm), sub2(nx.w, mm));
    xp += 12 * 72;
    sa += 96;
    if (i == cross) { xp += (hs * 16 - 128) * 72 + 64 - hs * 8; sa += (hs * 16 - 128) * 8; }
    if (i < 11) nx = *xp;
    *gp = make_uint4(gate2<false>(v.x, st.y), gate2<false>(v.y, st.y), gate2<false>(v.z, st.y), gate2<false>(v.w, st.y));
    gp = (uint4*)((size_t)(gp + 96) ^ 64);
  }
}

constexpr uint32_t SM_XO = SM_SLOT, SM_GO = SM_SLOT + STAGE, SM_P8 = SM_SLOT + 2 * STAGE;
__device__ __forceinline__ void attn_helper(const Ctx& cx, int qb, int hs, int lane, const CUtensorMap* tmX16) {
  const unsigned e = *(const uint32_t*)(cx.sp + SM_TAG + 4);
  bar_sync(BAR_HELPER, 64);
  bool todo = lane < 2;
#pragma unroll 1
  for (int n = 0; __any_sync(0xffffffffu, todo); n++) {
    if (todo && (ld_acquire(at(cx.g->qflag, ((qb * 4 + (hs >> 1)) * 2 + lane) * 4)) == e + 1 || n == (1 << 16))) {
      asm volatile("fence.proxy.async.global;" ::: "memory");
      mbar_expect_tx(cx.sb + SM_BAR_Q + 8 * lane, 8192);
      bulk_load(cx.sb + SM_SLOT + 2 * STAGE + lane * 16384 + 8192, at(cx.g->q, ((qb * 8 + hs) * 2 + lane) * 8192), 8192, cx.sb + SM_BAR_Q + 8 * lane);
      todo = false;
    }
  }
  const uint32_t tag = (~e & 1) * TAG;
  const uint4* src = cx.g->part + (size_t)((qb * 64 + 56) * 2 + (hs >> 2)) * 4 * 128 + (hs & 3) * 32 + lane;
  const uint32_t stg = cx.sb + SM_P8 + lane * 16;
  bar_sync(BAR_OA, 352);
  asm volatile("fence.proxy.async.global;" ::: "memory");
  if (lane == 0) {
    mbar_expect_tx(cx.sb + SM_BAR_MISC, 2 * 18432);
    bulk_load(cx.sb + SM_GO, cx.g->gate + blockIdx.x * 1152, 18432, cx.sb + SM_BAR_MISC);
#pragma unroll 1
    for (int i = 0; i < 9; i++)
      tma2d(cx.sb + SM_XO + i * 2048, tmX16, i < 8 ? hs * 64 : 512, qb * 128 + (i < 8 ? i : hs) * 16, cx.sb + SM_BAR_MISC);
  }
#pragma unroll 1
  for (int n = 0; n < (1 << 16); n++) {
    __nanosleep(n ? 500 : 2000);
    uint32_t a, b, d, t;
    ld_gran(src - lane + (lane & 7) * (2 * 4 * 128) + 3 * 128 + 31, a, b, d, t);
    if (__all_sync(0xffffffffu, (a & TAG) == tag)) break;
  }
  TSH(46)
#pragma unroll 1
  for (int n = 0; n < (1 << 16); n++) {
#pragma unroll 1
    for (int i = 0; i < 8; i++) {
#pragma unroll
      for (int g = 0; g < 4; g++) cp16(stg + (i * 4 + g) * 512, src + i * (2 * 4 * 128) + g * 128);
    }
    cp_wait_all();
    uint32_t bad = 0;
#pragma unroll 4
    for (int i = 0; i < 32; i++) bad |= *(const volatile uint32_t*)(cx.sp + SM_P8 + lane * 16 + i * 512) ^ tag;
    if (__all_sync(0xffffffffu, (bad & TAG) == 0)) break;
  }
  TSH(47)
#pragma unroll 1
  for (int n = 0; n < (1 << 16) && ld_acquire(&cx.g->ycnt) != 4 * (e + 1); n++) __nanosleep(200);
  const int2 sel = __ldcg(at(cx.g->sel, (lane & 7) * 8));
  const int lr = sel.x - qb * 128;
  uint32_t m = __ballot_sync(0xffffffffu, lane < 16 && ((lane & 8) ? (lr >> 4) == hs : (lr >> 7) == 0));
  mbar_wait(cx.sb + SM_BAR_MISC, 0);
#pragma unroll 1
  for (; m; m &= m - 1) {
    const int i = __ffs(m) - 1, row = __shfl_sync(0xffffffffu, lr, i);
    const float rs = __int_as_float(__shfl_sync(0xffffffffu, sel.y, i));
    const float* p = cx.g->ypart + (i & 7) * DM + (i < 8 ? hs * 64 : 512) + 2 * lane;
    const float2 a = __ldcg((const float2*)p), b = __ldcg((const float2*)(p + TOPC * DM)), c = __ldcg((const float2*)(p + 2 * TOPC * DM)),
                 d = __ldcg((const float2*)(p + 3 * TOPC * DM));
    const uint32_t y = pack2((a.x + b.x) + (c.x + d.x), (a.y + b.y) + (c.y + d.y));
    const uint32_t u = pack2(bf_lo(y) * rs, bf_hi(y) * rs);
    const float2 st = *(const float2*)(cx.sp + SM_STATS + 8 * row);
    const int o = (i < 8 ? row : 128 + (row & 15)) * 128 + ((lane * 4) ^ ((row & 7) << 4));
    *(uint32_t*)(cx.sp + SM_GO + o) = gate2<true>(sub2(*(const uint32_t*)(cx.sp + SM_XO + o), pack2(st.x, st.x)), st.y, make_float2(bf_lo(u), bf_hi(u)));
  }
  __syncwarp();
  if (lane == 0) mbar_arrive(cx.sb + SM_BAR_XG);
  TSH(48)
}
__device__ __forceinline__ void attn_finish8(const Ctx& cx, int qb, int hs, int hw, int lane, __nv_bfloat16* out) {
  bar_sync(BAR_GATE, 96);
#pragma unroll 1
  for (int g = hw; g < 4; g += 3) {
    float acc[8] = {0.f, 0.f, 0.f, 0.f, 0.f, 0.f, 0.f, 0.f};
#pragma unroll 2
    for (int sidx = 0; sidx < 8; sidx++) {
      uint32_t a, b, d, t;
      lds128(cx.sb + SM_P8 + lane * 16 + (sidx * 4 + g) * 512, a, b, d, t);
      acc[0] += bf_lo(a); acc[1] += bf_hi(a & ~TAG); acc[2] += bf_lo(b); acc[3] += bf_hi(b);
      acc[4] += bf_lo(d); acc[5] += bf_hi(d); acc[6] += bf_lo(t); acc[7] += bf_hi(t);
    }
#pragma unroll
    for (int j = 0; j < 4; j++) {
      const int o = (128 + (lane >> 2) + (j & 1) * 8) * 128 + (((2 * g + (j >> 1)) ^ (lane >> 2)) << 4) + (lane & 3) * 4;
      uint32_t* xp = (uint32_t*)(cx.sp + SM_XO + o);
      *xp = fma2(pack2(acc[2 * j], acc[2 * j + 1]), *(const uint32_t*)(cx.sp + SM_GO + o), *xp);
    }
  }
  bar_sync(BAR_GATE, 96);
#pragma unroll 1
  for (int ch = threadIdx.x - 32; ch < 128; ch += 96)
    *(uint4*)at(out, ((qb * 128 + hs * 16 + (ch >> 3)) * DM + 512 + (ch & 7) * 8) * 2) =
        *(const uint4*)(cx.sp + SM_XO + 16384 + (ch ^ ((ch >> 3) & 7)) * 16);
}

__device__ __forceinline__ void ffn_producer(const Ctx& cx, int f, const CUtensorMap* tmWq, const CUtensorMap* tmG,
                                             const CUtensorMap* tmU, const CUtensorMap* tmD) {
  uint64_t keep;
  asm("createpolicy.fractional.L2::evict_normal.b64 %0, 1.0;" : "=l"(keep));
  int st = 0;
#pragma unroll 1
  for (int p = 0; p < 16; p++) {
#pragma unroll 1
    for (int i = 0; i < 5; i++, st++) if (st > 1) load_wq(cx, tmWq, st, i, ((2 * (p & 3) + cx.rank) * 4 + 3) * DH + 64, keep);
  }
  const uint32_t full = cx.sb + SM_FFULL, empty = cx.sb + SM_FEMPTY;
  int pair = 0, u = 0;
#pragma unroll 1
  for (st = 0; st < 14 * 12; st++) {
    const uint32_t sl = st & 7;
    const int unit = pair * 2 + (u & 1), k = u >> 1, k3 = k >= 3 ? k - 3 : k;
    if (unit < 27) {
      mbar_wait(empty + 8 * sl, (st >> 3) & 1);
      __syncwarp();
      if (elect_one()) {
        mbar_expect_tx(full + 8 * sl, FSTAGE);
        if (pair < 9) tma2d_stream(cx.sb + sl * FSTAGE, k < 3 ? tmG : tmU, f * 1152 + unit * 64, k3 * 192, full + 8 * sl);
        else tma2d_stream(cx.sb + sl * FSTAGE, tmD, (unit - 18) * 64, f * 1152 + k * 192, full + 8 * sl);
      }
    }
    if (++u == 12) { u = 0; pair++; }
  }
}
__device__ __forceinline__ void load_x1(uint32_t dst, const CUtensorMap* tmX64, int row, int box, int n, uint32_t bar) {
  mbar_expect_tx(bar, n * 8192);
#pragma unroll 1
  for (int i = 0; i < n; i++) tma2d(dst + i * 8192, tmX64, (box + i) * 64, row, bar);
}
__device__ __forceinline__ void ffn_publish(const Ctx& cx, int f, int w, int lane, const CUtensorMap* tmX64) {
  const uint32_t xs = cx.sb + SM_SLOT + w * 49152, xf = cx.sb + SM_XFULL + w * 32;
#pragma unroll 1
  for (int n = 0; n < 16; n++) {
    const int p = n & 3, row = (f + (n & 12) + 4) * 128 + w * 64;
    if (n < 12 && p == 3) {
      bar_sync(BAR_QS + w, 160);
      if (lane == 0) load_x1(xs, tmX64, row, 4, 4, xf + 8);
      __syncwarp();
    }
    bar_sync(BAR_QS + w, 160);
    const uint32_t e1 = *(const uint32_t*)(cx.sp + SM_TAG + 4) + 1;
    if (lane == 0) {
#pragma unroll
      for (int i = 0; i < 2; i++)
        asm volatile("cp.async.bulk.global.shared::cta.bulk_group [%0], [%1], 8192;"
                     ::"l"(cx.g->q + (((f + (n & 12)) * 8 + 2 * p + i) * 2 + w) * 512), "r"(xs + 32768 + i * 8192) : "memory");
      asm volatile("cp.async.bulk.commit_group;" ::: "memory");
      asm volatile("cp.async.bulk.wait_group.read 0;" ::: "memory");
      if (n < 12 && (p == 0 || p == 3)) load_x1(xs + (p ? 32768 : 0), tmX64, row, p ? 8 : 0, p ? 1 : 4, xf + (p ? 16 : 0));
      asm volatile("cp.async.bulk.wait_group 0;\nfence.proxy.async.global;" ::: "memory");
      asm volatile("st.release.gpu.global.u32 [%0], %1;" ::"l"(&cx.g->qflag[((f + (n & 12)) * 4 + p) * 2 + w]), "r"(e1) : "memory");
    }
    __syncwarp();
    if (n < 12 && p == 1) {
#pragma unroll 1
      for (int i = 0, k = 0; i < 64 && k < (1 << 16); k++) {
        uint32_t m, r, z, t;
        ld_gran(cx.g->stats + row + i + lane, m, r, z, t);
        *(uint2*)(cx.sp + SM_STATS + 8 * (w * 64 + i + lane)) = make_uint2(m, r);
        if (__all_sync(0xffffffffu, t == e1)) i += 32;
      }
    }
    bar_arrive(BAR_QF + w, 160);
  }
}

__device__ __forceinline__ void ffn_consumer(const Ctx& cx, int f, int wg, int cw, int lane, const __nv_bfloat16* x) {
  const int r = lane >> 2, c = lane & 3, tid = cw * 32 + lane;
  const uint32_t full = cx.sb + SM_FFULL, empty = cx.sb + SM_FEMPTY;
  const bool signaller = (tid & 127) == 0;
  prof(wg, 8);
  const unsigned e = *(const uint32_t*)(cx.sp + SM_TAG + 4);
  uint32_t key[8];
#pragma unroll 1
  for (int n = 0; n < (1 << 16); n++) {
    uint32_t bad = 0;
#pragma unroll
    for (int i = 0; i < 8; i++) {
      uint32_t t;
      asm volatile("ld.relaxed.gpu.global.v2.b32 {%0, %1}, [%2];" : "=r"(key[i]), "=r"(t) : "l"(&cx.g->stats[i * 256 + tid].z) : "memory");
      bad |= t ^ (e + 1);
    }
    if (__all_sync(0xffffffffu, bad == 0)) break;
  }
  bar_sync(BAR_QF + wg, 160);
  bar_sync(3, 256);
  if (tid < 8) mbar_arrive(empty + 8 * tid);
  prof(wg, 9);
  int mysel = 0;
#pragma unroll 1
  for (int k = 0; k < TOPC; k++) {
    uint32_t m = key[0];
#pragma unroll
    for (int i = 1; i < 8; i++) m = max(m, key[i]);
    m = __reduce_max_sync(0xffffffffu, m);
    uint32_t* tk = (uint32_t*)(cx.sp + SM_TOPK) + (k & 1) * 8;
    if (lane == 0) tk[cw] = m;
    bar_sync(3, 256);
    m = __reduce_max_sync(0xffffffffu, tk[lane & 7]);
#pragma unroll
    for (int i = 0; i < 8; i++) if (key[i] == m) key[i] = 0;
    if (k == cw) mysel = 0xFFFF - (int)(m & 0xFFFF);
  }
  {
    const float4 st = __ldcg((const float4*)&cx.g->stats[mysel]);
    const uint32_t mm = pack2(st.x, st.x);
#pragma unroll 3
    for (int i = 0; i < 9; i++) {
      const uint32_t t = sub2(*(const uint32_t*)(x + (size_t)mysel * DM + i * 64 + 2 * lane), mm);
      *(uint32_t*)(cx.sp + SM_XSEL + i * 1024 + cw * 128 + (((lane >> 2) ^ cw) << 4) + (lane & 3) * 4) =
          pack2(bf_lo(t) * st.y, bf_hi(t) * st.y);
    }
    const uint32_t k = __float_as_uint(st.z);
    const float score = bf_hi(k ^ ((int)k < 0 ? 0x80000000u : 0xFFFF0000u));
    if (lane == 0 && f == 0) cx.g->sel[cw] = make_int2(mysel, __float_as_int(bfr(rcp(1.0f + ex2(-1.4426950408889634f * score)))));
  }
  asm volatile("fence.proxy.async.shared::cta;" ::: "memory");
  bar_sync(3, 256);
  prof(wg, 10);
  auto run = [&](float (&acc)[4], int st, int n, uint32_t b) {
#pragma unroll 1
    for (int u = 0; u < n; u++, st += 2, b += 3072) {
      const uint32_t sl = st & 7;
      mbar_wait(full + 8 * sl, (st >> 3) & 1);
      wg_fence();
      const uint64_t da = mkdesc(cx.sb + sl * FSTAGE, 16), db = mkdesc(b, 16);
#pragma unroll
      for (int k = 0; k < 12; k++) mma_n8(acc, da + k * 128, db + (k >> 2) * 64 + (k & 3) * 2, u > 0 || k > 0);
      wg_commit();
      wg_wait<0>();
      if (signaller) mbar_arrive(empty + 8 * sl);
    }
    pin(acc);
  };
#pragma unroll 1
  for (int unit = wg; unit < 27; unit += 2) {
    if (unit >> 1 == 9) {
      asm volatile("fence.proxy.async.shared::cta;" ::: "memory");
      bar_sync(3, 256);
      prof(wg, 11);
    }
    const bool gu = unit < 18;
    float a0[4], a1[4];
#pragma unroll 1
    for (int m = 0; m < (gu ? 2 : 1); m++) {
      run(a1, (unit >> 1) * 12 + m * 6 + wg, gu ? 3 : 6, cx.sb + (gu ? SM_XSEL : SM_H));
      if (m == 0) { a0[0] = a1[0]; a0[1] = a1[1]; a0[2] = a1[2]; a0[3] = a1[3]; }
    }
    float u0 = a1[0], u1 = a1[1];
#pragma unroll 1
    for (int i = 0; i < 2; i++) {
      const int fl = (cw & 3) * 16 + r + i * 8;
      if (gu) {
        const uint32_t g = pack2(a0[0], a0[1]);
        const uint32_t h = fma2(pack2(silu_f(bf_lo(g)), silu_f(bf_hi(g))), pack2(u0, u1), 0x80008000u);
        uint8_t* hp = cx.sp + SM_H + unit * 1024 + c * 256 + (fl & 7) * 2;
        *(uint16_t*)(hp + (((fl >> 3) ^ (2 * c)) << 4)) = (uint16_t)h;
        *(uint16_t*)(hp + 128 + (((fl >> 3) ^ (2 * c + 1)) << 4)) = (uint16_t)(h >> 16);
      } else {
        float* yp = cx.g->ypart + (f * TOPC + 2 * c) * DM + (unit - 18) * 64 + fl;
        yp[0] = u0;
        yp[DM] = u1;
      }
      a0[0] = a0[2]; a0[1] = a0[3]; u0 = a1[2]; u1 = a1[3];
    }
  }
  prof(wg, 12);
  bar_sync(3, 256);
  if (tid == 0) atom_add_acq_rel(&cx.g->ycnt);
  prof(wg, 13);
}

constexpr float SUM_HI = 1.8446744e19f, SUM_LO = 9.0949470e-13f;

template <int LO, int HI, int N>
__device__ __forceinline__ void softmax_exp(float (&s)[N]) {
#pragma unroll
  for (int i = LO; i < HI; i++) s[i] = ex2(s[i]);
}
__device__ __forceinline__ void sum_tree(const uint32_t (&pf)[28], bool big, uint32_t& h0, uint32_t& h1) {
  uint32_t t0 = add2(add2(pf[16], pf[18]), add2(pf[20], pf[22])), t1 = add2(add2(pf[17], pf[19]), add2(pf[21], pf[23]));
  if (big) { t0 = add2(t0, add2(pf[24], pf[26])); t1 = add2(t1, add2(pf[25], pf[27])); }
  h0 = add2(add2(add2(add2(pf[0], pf[2]), add2(pf[4], pf[6])), add2(add2(pf[8], pf[10]), add2(pf[12], pf[14]))), t0);
  h1 = add2(add2(add2(add2(pf[1], pf[3]), add2(pf[5], pf[7])), add2(add2(pf[9], pf[11]), add2(pf[13], pf[15]))), t1);
}
__device__ __forceinline__ void exact_attention(float (&o)[16], float& l0, float& l1, const uint32_t (&q)[32], const __nv_bfloat16* kp,
                                                const __nv_bfloat16* vp) {
  float m0 = -3.0e38f, m1 = -3.0e38f;
  l0 = l1 = 0.f;
#pragma unroll
  for (int i = 0; i < 16; i++) o[i] = 0.f;
#pragma unroll 1
  for (int key = 0; key < SEQ; key += 8, kp += 8 * DH, vp += 8 * DH) {
    float d[4] = {0.f, 0.f, 0.f, 0.f};
#pragma unroll
    for (int k = 0; k < 8; k++)
      hmma_k16(d, q[4 * k], q[4 * k + 1], q[4 * k + 2], q[4 * k + 3], *(const uint32_t*)(kp + k * 16), *(const uint32_t*)(kp + k * 16 + 8));
    float x0 = fmaxf(d[0], d[1]), x1 = fmaxf(d[2], d[3]);
    x0 = fmaxf(x0, __shfl_xor_sync(0xffffffffu, x0, 1));
    x1 = fmaxf(x1, __shfl_xor_sync(0xffffffffu, x1, 1));
    x0 = fmaxf(fmaxf(x0, __shfl_xor_sync(0xffffffffu, x0, 2)), m0);
    x1 = fmaxf(fmaxf(x1, __shfl_xor_sync(0xffffffffu, x1, 2)), m1);
    const float sc0 = ex2(m0 - x0), sc1 = ex2(m1 - x1);
    m0 = x0; m1 = x1;
    const uint32_t p0 = pack2(ex2(d[0] - m0), ex2(d[1] - m0)), p1 = pack2(ex2(d[2] - m1), ex2(d[3] - m1));
    l0 = fmaf(l0, sc0, bf_lo(p0) + bf_hi(p0));
    l1 = fmaf(l1, sc1, bf_lo(p1) + bf_hi(p1));
#pragma unroll
    for (int nb = 0; nb < 4; nb++) {
      uint32_t b;
      asm("movmatrix.sync.aligned.m8n8.trans.b16 %0, %1;" : "=r"(b) : "r"(*(const uint32_t*)(vp + nb * 8)));
      o[4 * nb] *= sc0; o[4 * nb + 1] *= sc0; o[4 * nb + 2] *= sc1; o[4 * nb + 3] *= sc1;
      asm volatile("mma.sync.aligned.m16n8k8.row.col.f32.bf16.bf16.f32 {%0, %1, %2, %3}, {%4, %5}, {%6}, {%0, %1, %2, %3};"
                   : "+f"(o[4 * nb]), "+f"(o[4 * nb + 1]), "+f"(o[4 * nb + 2]), "+f"(o[4 * nb + 3]) : "r"(p0), "r"(p1), "r"(b));
    }
  }
}
__device__ __forceinline__ bool inv_sums(float l0, float l1, float& i0, float& i1) {
  l0 += __shfl_xor_sync(0xffffffffu, l0, 1); l1 += __shfl_xor_sync(0xffffffffu, l1, 1);
  l0 += __shfl_xor_sync(0xffffffffu, l0, 2); l1 += __shfl_xor_sync(0xffffffffu, l1, 2);
  i0 = rcp(l0);
  i1 = rcp(l1);
  return !(l0 + l1 <= SUM_HI) | (fminf(l0, l1) < SUM_LO);
}
template <int LO, int HI, int N>
__device__ __forceinline__ void park(uint32_t a, const float (&o)[N], float i0, float i1, bool on = true) {
#pragma unroll
  for (int i = LO; i < HI; i++)
    asm volatile("{\n.reg .pred p;\nsetp.ne.u32 p, %5, 0;\n@p stmatrix.sync.aligned.m8n8.x4.shared.b16 [%0], {%1, %2, %3, %4};\n}"
                 ::"r"(a + i * 2048), "r"(pack2(o[8 * i] * i0, o[8 * i + 1] * i0)), "r"(pack2(o[8 * i + 2] * i1, o[8 * i + 3] * i1)),
                 "r"(pack2(o[8 * i + 4] * i0, o[8 * i + 5] * i0)), "r"(pack2(o[8 * i + 6] * i1, o[8 * i + 7] * i1)), "r"((uint32_t)on) : "memory");
}

template <int I, int HI, int G, int N>
__device__ __forceinline__ void park_paced(uint32_t a, const float (&o)[N], float i0, float i1, int id) {
  if constexpr (I < HI) {
    park<I, I + G>(a, o, i0, i1);
    if (I + G < HI) block_fence(id + I);
    park_paced<I + G, HI, G>(a, o, i0, i1, id);
  }
}
template <int I, int NP, int E0, int N, int NS>
__device__ __forceinline__ void exp_park(float (&s)[NS], uint32_t a, const float (&o)[64], float i0, float i1, bool on, int id) {
  if constexpr (I < NP) {
    constexpr int E1 = E0 + (N - E0) * X_PG / (NP - I);
    softmax_exp<E0, E1>(s);
    park<I, I + X_PG>(a, o, i0, i1, on);
    if (I + X_PG < NP) {
#pragma unroll
      for (int i = E0; i < E1; i++) asm volatile("" : "+f"(s[i])::"memory");
      block_fence(id + I);
    }
    exp_park<I + X_PG, NP, E1, N>(s, a, o, i0, i1, on, id);
  }
}

__device__ __forceinline__ void attn_consumer(const Ctx& cx, bool hlp, int qb, int hs, int wg, int cw, int lane, const __nv_bfloat16* x,
                                              const __nv_bfloat16* kc, const __nv_bfloat16* vc, __nv_bfloat16* out) {
  const uint32_t full = cx.sb + SM_FULL;
  const uint32_t ring = cx.sb + SM_RING;
  const uint32_t qwg = ring + wg * 16384;
  auto qlane = [&](int l) { return qwg + (cw & 3) * 256 + (l >> 4) * 1024 + (l & 15) * 16; };
  const bool signaller = lane == 0 && (cw & 3) < 2;
  const int my_turn = 1 + wg, other_turn = 2 - wg;
  const uint32_t empty_c = mapa(cx.sb + SM_EMPTY, cw & 1);

  float oA[64], oB[64], i0, i1;
  uint32_t xl[32];
  {
    const int r = lane >> 2, c = lane & 3;
    const int lr0 = cw * 16 + r;
    uint32_t xa[144];
    uint32_t mm0, mm1;
    float rstd0, rstd1, sq0 = 0.f, sq1 = 0.f;
    const uint32_t xf = cx.sb + SM_XFULL + wg * 32, xs = cx.sb + SM_SLOT + wg * 49152;
    auto lo_of = [&](int l) { return ((cw & 3) * 16 + (l & 15)) * 128 + (((l >> 4) ^ (l & 7)) << 4); };
    prof(wg, 0);
    {
      const uint32_t lo = lo_of(lane);
      const uint32_t xb = cx.sb + SM_X + wg * 73728;
      float sm[X_NS][4] = {};
      const uint32_t ws = (lane & 7) == 1 ? 64 : 0;
      uint32_t wb = cx.sb + (ws ? SM_WR + (lane >> 3) * 16 : SM_ONES);
      uint32_t b0[24], b1[24], b2[24];
      mbar_wait(cx.sb + SM_BAR_W, 0);
      TS4(1)
      if (X_LN == 0) {
        ln_fetch_b(b0, wb, ws);
        ln_fetch_b(b1, wb, ws);
        ln_fetch_b(b2, wb, ws);
      }
      mbar_wait(xf, 0);
      TS4(2)
      ln_fetch<0, 12>(xa, xb, lo);
      if (X_LN == 1) {
        ln_fetch_b(b0, wb, ws);
        ln_fetch_b(b1, wb, ws);
        ln_fetch_b(b2, wb, ws);
      }
      ln_sums<0, 12>(xa, sm, b0);
      mbar_wait(xf + 8, 0);
      TS4(3)
      ln_fetch<12, 24>(xa, xb, lo);
      if (wg == 0) {
        bar_arrive(BAR_XREL + (xa[95] & blockIdx.y), 224);
      }
      ln_sums<12, 24>(xa, sm, b1);

      mbar_wait(xf + 16, 0);
      TS4(4)
      prof(wg, 1);
      ln_fetch<24, 36>(xa, xb, lo);
      ln_sums<24, 36>(xa, sm, b2);
#pragma unroll
      for (int i = 0; i < 4; i++) sm[0][i] = X_NS == 2 ? sm[0][i] + sm[1][i] : X_NS == 3 ? sm[0][i] + sm[1][i] + sm[2][i] : (sm[0][i] + sm[1][i]) + (sm[2][i] + sm[X_NS - 1][i]);
      if (cw == hs && c == 0) {
        *(float*)(cx.sp + SM_RAW + 4 * r) = sm[0][1];
        *(float*)(cx.sp + SM_RAW + 4 * r + 32) = sm[0][3];
      }
      rstd0 = sm[0][0];
      rstd1 = sm[0][2];
      mm0 = pack2(rstd0 * (1.0f / DM), rstd0 * (1.0f / DM));
      mm1 = pack2(rstd1 * (1.0f / DM), rstd1 * (1.0f / DM));
    }
#pragma unroll
    for (int i = 0; i < 16; i++) { xa[2 * i] = sub2(xa[2 * i], mm0); xa[2 * i + 1] = sub2(xa[2 * i + 1], mm1); }
    pin(xa);
    prof(wg, 2);
    TS4(5)

    float (&acc)[64] = oB;
    int st0 = 0;
#pragma unroll 1
    for (int n = 0; n < 16; n++) {
      const int p = n & 3, rb = n >> 2;
      const bool last = p == 3 && !hlp;
#pragma unroll
      for (int i = 0; i < 5; i++) {
        if (i == 4 && last) {
          wg_wait<1>();
          mbar_arrive_cluster(empty_c + 8 * 3, signaller && wg);
          wg_wait<0>();
          pin(acc);
          prof(wg, 6);
#pragma unroll
          for (int j = 0; j < 32; j++) xl[j] = xa[112 + j];
          i0 = rstd0;
          i1 = rstd1;
          goto attention;
        }
        const int st = st0 + i;
        const uint32_t sl = st & 3, slp = (st - 1) & 3;
        if (!wg) mbar_wait(full + 8 * sl, (st >> 2) & 1);
        TS4(8 + 2 * (p * 5 + i))
        const bool join = wg && last;
        if ((i || st0 + wg) && i != (wg ? 4 : 1) && !(join && i == 3)) bar_sync(my_turn, 256);
        wg_fence();
        const uint64_t db = mkdesc(ring + sl * STAGE, 16384);
        const int kb0 = i < 3 ? 8 * i : 8 * i - 4;
#pragma unroll
        for (int k = 0; k < (i == 2 ? 4 : 8); k++) {
          const int kb = kb0 + k;
          mma_n128t(acc, xa[4 * kb], xa[4 * kb + 1], xa[4 * kb + 2], xa[4 * kb + 3], db + k * 128, kb > 0);
        }
        wg_commit();
        TS4(9 + 2 * (p * 5 + i))
        if (wg ? (i == 4 ? st0 < 75 : (i < 2 || i == (join ? 3 : 2))) : i) bar_arrive(other_turn, 256);
        if (p == 0 && i < 4) {
          if (i == 1 && rb) {
            mbar_wait(xf + 8, rb & 1);
            ln_fetch<16, 32>(xa, xs - 32768, lo_of(fresh_lane()));
          }
          if (i == 2 && rb) {
            mbar_wait(xf + 16, rb & 1);
            ln_fetch<32, 36>(xa, xs - 32768, lo_of(fresh_lane()));
          }
#pragma unroll
          for (int j = 0; j < 72; j++)
            if (j >= 2 * (i < 2 ? 8 * i + 8 : 8 * i + 4) && j < 2 * (i == 0 ? 16 : 8 * i + 12)) {
              xa[2 * j] = sub2(xa[2 * j], mm0);
              xa[2 * j + 1] = sub2(xa[2 * j + 1], mm1);
            }
          pin(xa);
        }
        if (i == X_SQI && n == 0) {
          mbar_wait(cx.sb + SM_BAR_SQ, 0);
          float2* sp = (float2*)(cx.sp + SM_STATS) + lr0;
          float mean0, mean1;
          ln_row(rstd0, sp[0].y, mean0, rstd0);
          ln_row(rstd1, sp[8].y, mean1, rstd1);
          __syncwarp();
          if (c == 0) {
            sp[0] = make_float2(mean0, rstd0);
            sp[8] = make_float2(mean1, rstd1);
          }
          *((uint32_t*)(cx.sp + SM_COLD) + wg) = 0;
          if (!hlp) bar_arrive(BAR_GATE, 352);
          rstd0 *= SM_SCALE_LOG2;
          rstd1 *= SM_SCALE_LOG2;
        }
        if (i == 3 && hlp && p == 3 && rb < 3) bar_arrive(BAR_QS + wg + (xa[63] & blockIdx.y), 160);
        if (i == 4 && p == 3 && rb < 3) {
          const float2* sp = (const float2*)(cx.sp + SM_STATS) + cw * 16 + (fresh_lane() >> 2);
          mm0 = pack2(sp[0].x, sp[0].x);
          mm1 = pack2(sp[8].x, sp[8].x);
          sq0 = sp[0].y * SM_SCALE_LOG2;
          sq1 = sp[8].y * SM_SCALE_LOG2;
#pragma unroll
          for (int j = 0; j < 16; j++) { xa[2 * j] = sub2(xa[2 * j], mm0); xa[2 * j + 1] = sub2(xa[2 * j + 1], mm1); }
          pin(xa);
        }
        if (i == 0) {
          if (wg) {
            wg_wait<0>();
            mbar_arrive_cluster(empty_c + 8 * sl, signaller);
          }
        } else if (i == 2) {
          if (!join) {
            wg_wait<0>();
            mbar_arrive_cluster(empty_c + 8 * sl, signaller);
          }
          if (hlp && p == 3 && rb < 3) {
            mbar_wait(xf, ~rb & 1);
            ln_fetch<0, 16>(xa, xs, lo_of(fresh_lane()));
            pin(xa);
          }
        } else if (i != 3) {
          wg_wait<1>();
          mbar_arrive_cluster(empty_c + 8 * slp, signaller && (i == 4 || !wg));
          wg_wait<0>();
          mbar_arrive_cluster(empty_c + 8 * sl, signaller);
        }
      }
      pin(acc);
      prof(wg, 3 + p);
      TS4(50 + 2 * p)
      st0 += 5;
      if (hlp && st0 > 5) bar_sync(BAR_QF + wg, 160);
      park_paced<0, 8, X_QP>(qlane(lane) + (hlp ? 5 + wg : 4 + p) * STAGE, acc, rstd0, rstd1, 300);
      if (p || hlp) asm volatile("fence.proxy.async.shared::cta;" ::: "memory");
      if (hlp) bar_arrive(BAR_QS + wg, 160);
      if (p == 3) { rstd0 = sq0; rstd1 = sq1; }
      TS4(51 + 2 * p)
      if (p == 1 && !hlp) {
        float (&ah)[32] = *(float (*)[32])&acc[0];
#pragma unroll
        for (int i = 0; i < 3; i++) {
          const uint32_t sl = (10 + i) & 3;
          if (!wg) mbar_wait(full + 8 * sl, ((10 + i) >> 2) & 1);
          TS4(28 + 2 * i)
          if (i == 0 || i == 2 - wg) bar_sync(my_turn, 256);
          wg_fence();
          const uint64_t db = mkdesc(ring + sl * STAGE, 16);
#pragma unroll
          for (int k = 0; k < 12; k++) {
            const int kb = 12 * i + k;
            if (kb) mma_n64t(ah, xa[4 * kb], xa[4 * kb + 1], xa[4 * kb + 2], xa[4 * kb + 3], db + k * 128, true);
            else mma_n64t_dyn(ah, xa[0], xa[1], xa[2], xa[3], db, blockIdx.y);
          }
          wg_commit();
          TS4(29 + 2 * i)
          if (i == 2 || i != wg) {
            bar_arrive(other_turn, 256);
            if (i) {
              wg_wait<1>();
              mbar_arrive_cluster(empty_c + 8 * ((9 + i) & 3), signaller && i == wg + 1);
            }
            wg_wait<0>();
            mbar_arrive_cluster(empty_c + 8 * sl, signaller);
          }
        }
        pin(ah);
        TS4(54)
        park<0, 4>(qlane(lane) + 6 * STAGE, ah, rstd0, rstd1);
        TS4(55)
        st0 = 13;
        n = 2;
      }
    }
    TS_DUMP()
    ffn_consumer(cx, blockIdx.x & 3, wg, cw, fresh_lane(), x);
    return;
  }

attention:
  uint32_t oa[128];
  float acc[32];
  {
    uint32_t pf[28];
    const uint32_t ql = qlane(fresh_lane());
    uint32_t bad = 0;
    float lA0 = 0.f, lA1 = 0.f, lB0 = 0.f, lB1 = 0.f;
    int t = 0;
    uint32_t ra = 2 * 2048, rb = 2048, rc = 2 * 2048, par = 0;
    const uint64_t dk0 = mkdesc(ring, 16), dv0 = mkdesc(ring, 16384);
    uint64_t dqA = mkdesc_q(qwg + 4 * STAGE), dqB = dqA + 2048;
    auto turn = [&](auto kc_, auto bc_) {
      constexpr int KIND = decltype(kc_)::value, BIG = decltype(bc_)::value;
      constexpr int HB = KIND == 1, ID = 10 * KIND + 30 * BIG, T0 = BIG ? 38 : 0;
      constexpr int NS = BIG ? 56 : 48, SPLIT = BIG ? (HB ? X_SPLIT : X_SPLITA) : (HB ? X_SPLITS : X_SPLITSA);
      float s[NS];
      float (&op)[64] = HB ? oA : oB;
      uint32_t h0 = 0, h1 = 0;
      TS2(0)
      bar_sync(my_turn, 256);
      TS2(1)
      if (KIND) { pin(pf); pin(op); }
      mma_qk(s, HB ? dqB : dqA, dk0 + (HB ? ra : rc));
      TS2(2)
      if (KIND) {
        const bool bigp = HB ? BIG : BIG ? t != 10 : t == 66;
        if (X_BF2) block_fence(ID + 9);
        pin(pf);
        sum_tree(pf, bigp, h0, h1);
        asm volatile("" : "+r"(h0), "+r"(h1)::"memory");
        if (HB) mbar_wait(full + (rb >> 8), par);
        mma_pv(op, pf, dv0 + rb, t != T0 + 2 - HB, bigp);
      } else {
        mbar_wait(full + (rb >> 8), (NST_Q - 1) >> 2 & 1);
#pragma unroll
        for (int k = 0; k < 8; k++) mma_n128t(op, xl[4 * k], xl[4 * k + 1], xl[4 * k + 2], xl[4 * k + 3], dv0 + rb + k * 128, 1);
        wg_commit();
      }
      TS2(3)
      bar_arrive(other_turn, 256);
      (HB ? lA0 : lB0) += bf_lo(h0) + bf_hi(h0);
      (HB ? lA1 : lB1) += bf_lo(h1) + bf_hi(h1);
      wg_wait<1>();
      pin(s);
      TS1(t)
      TS2(4)
      if (KIND == 1) mbar_arrive_cluster_now<ID + 3>(empty_c + (ra >> 8), signaller);
      if (BIG && t == T0 + HB) {
        const uint32_t a = ql + (4 + HB) * STAGE;
        const bool ok = !__any_sync(0xffffffffu, inv_sums(HB ? lB0 : lA0, HB ? lB1 : lA1, i0, i1));
        if (!ok) bad |= 1 << HB;
        (HB ? lB0 : lA0) = 0.f;
        (HB ? lB1 : lA1) = 0.f;
        softmax_exp<0, X_E0>(s);
#pragma unroll
        for (int i = 0; i < X_E0; i++) asm volatile("" : "+f"(s[i])::"memory");
        block_fence(ID + 7);
        exp_park<0, X_PA, X_E0, SPLIT>(s, a, HB ? oB : oA, i0, i1, ok, 200 + ID);
        if (!HB) dqB += 2048;
        prof(wg, 8 + HB);
      } else {
        softmax_exp<0, SPLIT>(s);
      }
      pin(s);
      if (!BIG) block_fence(ID + 4);
      TS2(5)
      wg_wait<0>();
      TS2(6)
      pin(op);
      if (KIND) pin(pf); else pin(xl);
      if (HB) {
        par ^= rc == 2048;
        if (BIG && t == 37) dqA -= 4 * 2048;
        if (BIG && t == X_WAKE && cw == 0) bar_arrive(BAR_HELPER, 64);
      } else {
        mbar_arrive_cluster_now<ID + 5>(empty_c + (rb >> 8), signaller);
        if (KIND) {
          par ^= ra == 2048;
          const uint32_t x = ra;
          ra = rc; rc = rb; rb = x;
        }
      }
      softmax_exp<SPLIT, NS>(s);
#pragma unroll
      for (int i = 0; i < NS / 2; i++) pf[i] = pack2(s[2 * i], s[2 * i + 1]);
      pin(pf);
      if (KIND == 0) {
        block_fence(ID + 6);
        park_paced<0, X_Q1, X_QC>(ql, oB, i0, i1, 310);

        prof(wg, 7);
      }
      if (X_Q1 < 8 && HB && !BIG && t == 1) park_paced<X_Q1, 8, X_QC>(ql, oB, i0, i1, 320);
      if (BIG && t == T0 + HB) {
        if (X_PA < 8) park<X_PA, 8>(ql + (4 + HB) * STAGE, HB ? oB : oA, i0, i1, !(bad >> HB));
        if (!HB) mbar_wait(cx.sb + SM_BAR_Q + 8 * wg, 0);
      }
      if (HB) mbar_wait(full + (rc >> 8), par);
      t++;
    };
#pragma unroll
    for (int i = 24; i < 28; i++) asm volatile("" : "=r"(pf[i]));
    mbar_wait(full + 8 * 2, 0);
    turn(IC<0>(), IC<0>());
    rb = 3 * 2048; rc = 2048;
    kill(oA);
    const bool never = blockIdx.y == 1;
#pragma unroll 1
    while (true) {
      turn(IC<1>(), IC<0>());
      if (t == 76) break;
      if (t == 10) {
        asm volatile("fence.proxy.async.shared::cta;" ::: "memory");
#pragma unroll 1
        do {
#pragma unroll 1
          do turn(IC<2>(), IC<1>()); while (never);
          turn(IC<1>(), IC<1>());
        } while (t != 66);
      }
#pragma unroll 1
      do turn(IC<2>(), IC<0>()); while (never);
    }
    auto scale = [&](auto lo, auto hi) {
#pragma unroll
      for (int i = decltype(lo)::value; i < decltype(hi)::value; i++) {
        oa[32 + 2 * i] = pack2(oA[4 * i] * i0, oA[4 * i + 1] * i0);
        oa[32 + 2 * i + 1] = pack2(oA[4 * i + 2] * i1, oA[4 * i + 3] * i1);
        asm volatile("" : "+r"(oa[32 + 2 * i]), "+r"(oa[32 + 2 * i + 1])::"memory");
      }
    };
    TS3(1)
    volatile uint32_t* const cold = (volatile uint32_t*)(cx.sp + SM_COLD) + wg;
    if (inv_sums(lA0, lA1, i0, i1)) bad |= 4;
#pragma unroll
    for (int i = 0; i < 8; i++) ldsm4(ql + 4 * STAGE + i * 2048, oa[4 * i], oa[4 * i + 1], oa[4 * i + 2], oa[4 * i + 3]);
    {
      uint32_t h0, h1;
      sum_tree(pf, false, h0, h1);
      lB0 += bf_lo(h0) + bf_hi(h0);
      lB1 += bf_lo(h1) + bf_hi(h1);
      asm volatile("" : "+f"(lB0), "+f"(lB1)::"memory");
    }
    scale(IC<0>(), IC<X_F1>());
    if (bad) *cold = 1;
    block_fence(93);
    TS3(2)
    bar_sync(my_turn, 256);
    TS3(3)
    pin(pf); pin(oB);
    mma_pv(oB, pf, dv0 + 2 * 2048, true, false);
    block_fence(91);
    TS3(4)
    const uint32_t held = *cold;
    if (inv_sums(lB0, lB1, lB0, lB1)) bad |= 8;
    const uint64_t db = mkdesc(ring + 3 * STAGE, 16);
    scale(IC<X_F1>(), IC<X_F2>());
    mbar_arrive_cluster_now<94>(empty_c, signaller && !held);
#pragma unroll
    for (int i = 0; i < 32; i++) asm volatile("" : "+r"(oa[i])::"memory");
    wg_fence();
#pragma unroll
    for (int k = 0; k < 8; k++) mma_n64t(acc, oa[4 * k], oa[4 * k + 1], oa[4 * k + 2], oa[4 * k + 3], db + k * 128, k > 0);
    if (X_F2 < 16) {
      wg_commit();
      block_fence(95);
      scale(IC<X_F2>(), IC<16>());
      TS3(5)
      wg_fence();
    }
#pragma unroll
    for (int k = 8; k < 16; k++) mma_n64t(acc, oa[4 * k], oa[4 * k + 1], oa[4 * k + 2], oa[4 * k + 3], db + k * 128, 1);
    wg_commit();
    bar_arrive(other_turn, 256);
    if (bad) *cold = 1;
    bar_sync(4 + wg, 128);
    const uint32_t is_cold = *cold;
    wg_wait<(X_F2 < 16 ? 2 : 1)>();
    pin(oB); pin(pf);
    TS(76)
    TS3(6)
    mbar_arrive_cluster_now<97>(empty_c + 8 * 2, signaller);
#pragma unroll
    for (int i = 16; i < 24; i++) ldsm4(ql + 5 * STAGE + (i & 7) * 2048, oa[4 * i], oa[4 * i + 1], oa[4 * i + 2], oa[4 * i + 3]);
#pragma unroll
    for (int i = 0; i < 16; i++) {
      oa[96 + 2 * i] = pack2(oB[4 * i] * lB0, oB[4 * i + 1] * lB0);
      oa[96 + 2 * i + 1] = pack2(oB[4 * i + 2] * lB1, oB[4 * i + 3] * lB1);
    }
    TS3(7)
    if (!wg) mbar_wait(full + 8 * 1, 0);
    TS3(8)
    wg_wait<0>();
    pin(acc); pin(oa);
    if (__any_sync(0xffffffffu, is_cold)) {
      bad = __reduce_or_sync(0xffffffffu, bad);
      if (!(bad & 8)) {
#pragma unroll
        for (int i = 24; i < 32; i++) stsm4(ql + 6 * STAGE + (i & 7) * 2048, oa[4 * i], oa[4 * i + 1], oa[4 * i + 2], oa[4 * i + 3]);
      }
#pragma unroll 1
      for (int h = 0; h < 4; h++) {
        if (bad >> h & 1) {
          const uint32_t a = ql + ((0x6054 >> (4 * h)) & 7) * STAGE;
          const int l = fresh_lane(), o = (hs * 2 + (h >> 1)) * SEQ * DH + (l >> 2) * DH + (l & 3) * 2;
          uint32_t q[32];
#pragma unroll
          for (int i = 0; i < 8; i++) ldsm4(a + i * 2048, q[4 * i], q[4 * i + 1], q[4 * i + 2], q[4 * i + 3]);
#pragma unroll 1
          for (int i = 0; i < 4; i++) {
            float ox[16], l0, l1;
            exact_attention(ox, l0, l1, q, kc + o, vc + o + i * 32);
            inv_sums(l0, l1, l0, l1);
            park<0, 2>(a + i * 4096, ox, l0, l1);
          }
        }
      }
      __syncwarp();
#pragma unroll
      for (int i = 0; i < 32; i++)
        if ((i >> 3) != 1 || (bad & 4))
          ldsm4(ql + ((0x6504 >> (4 * (i >> 3))) & 7) * STAGE + (i & 7) * 2048, oa[4 * i], oa[4 * i + 1], oa[4 * i + 2], oa[4 * i + 3]);
      pin(oa);
      asm volatile("fence.proxy.async.shared::cta;" ::: "memory");
      bar_sync(4 + wg, 128);
      mbar_arrive_cluster(empty_c, signaller && held);
      wg_fence();
#pragma unroll
      for (int k = 0; k < 16; k++) mma_n64t(acc, oa[4 * k], oa[4 * k + 1], oa[4 * k + 2], oa[4 * k + 3], db + k * 128, k > 0);
      wg_commit();
      wg_wait<0>();
      pin(acc);
    }
    mbar_arrive_cluster(empty_c + 8 * 3, signaller);
  }

  prof(wg, 10);
  TS3(9)
  {
    lane = fresh_lane();
    const int tw = (cw & 3) * 32 + lane;
    float red[32];
    kill(red);
    const uint32_t tag = *(const uint32_t*)(cx.sp + SM_TAG);
    uint4* const xch = at(cx.g->part, ((qb * 64 * 2 + wg) * 4 * 128 + tw) * 16);
    int nrx = 1;
    auto region = [](int s, int h) { return h ? 1 + (s & 1) : (s & 1) ? 0 : 3; };
    auto half_step = [&](int s, auto hc, bool arrive) {
      constexpr int h = decltype(hc)::value;
      const uint64_t db = mkdesc(ring + region(s, h) * STAGE, 16);
      bar_sync(my_turn, 256);
      pin(oa);
      wg_fence();
#pragma unroll
      for (int k = 0; k < 16; k++) {
        const int kb = h * 16 + k;
        mma_n64t(acc, oa[4 * kb], oa[4 * kb + 1], oa[4 * kb + 2], oa[4 * kb + 3], db + k * 128, kb > 0);
      }
      wg_commit();
      if (arrive) bar_arrive(other_turn, 256);
    };
    auto await = [&](int s, int h) { mbar_wait(full + 8 * region(s, h), ((s >> 1) ^ h ^ 1) & 1); };
    auto fetch = [&](uint32_t (&g)[16], int n) {
      const uint4* p = at(xch, (hs * 7 + n - 1) * 16384);
#pragma unroll
      for (int i = 0; i < 4; i++) ld_gran(p + i * 128, g[4 * i], g[4 * i + 1], g[4 * i + 2], g[4 * i + 3]);
    };
    uint32_t g[16];
    bool pend = false;
#pragma unroll 1
    for (int s = 0;; s++) {
      half_step(s, IC<1>(), s + wg < 9);
      if (s == 8) break;
      TS3(s < 3 ? 16 + 8 * s : 75)
      if (s == 0) {
        bar_arrive(BAR_OA, 352);
#pragma unroll
        for (int i = 0; i < 32; i++) red[i] = 0.f;
      }
      await(s + 1, 0);
      TS3(s < 3 ? 17 + 8 * s : 75)
      wg_wait<0>();
      TS3(s < 3 ? 18 + 8 * s : 75)
      mbar_arrive_cluster(empty_c + 8 * region(s, 1), signaller && s < 7);
      pin(acc);
      TS(77 + s)
      prof(wg, 12 + s);
      uint4* p = at(xch, (s == 0 ? 56 + hs : ((hs + s) & 7) * 7 + s - 1) * 16384);
#pragma unroll
      for (int i = 0; i < 4; i++)
        st_gran(p + i * 128, (pack2(acc[8 * i], acc[8 * i + 1]) & ~TAG) | tag, pack2(acc[8 * i + 2], acc[8 * i + 3]),
                pack2(acc[8 * i + 4], acc[8 * i + 5]), pack2(acc[8 * i + 6], acc[8 * i + 7]));
      TS3(s < 3 ? 19 + 8 * s : 75)
      half_step(s + 1, IC<0>(), true);
      TS3(s < 3 ? 20 + 8 * s : 75)
      if (pend && granules_ok(g, tag)) { add_granules(red, g); nrx++; }
      pend = nrx < s;
      if (pend) fetch(g, nrx);
      await(s + 1, 1);
      TS3(s < 3 ? 21 + 8 * s : 75)
      wg_wait<0>();
      TS3(s < 3 ? 22 + 8 * s : 75)
      mbar_arrive_cluster(empty_c + 8 * region(s + 1, 0), signaller && s < 6);
    }
    uint32_t xv[16], gt[16], g2[16];
    TS3(42)
    const bool ok = granules_ok(g, tag);
    TS3(43)
    nrx += ok;
    fetch(g2, nrx);
    mbar_wait(cx.sb + SM_BAR_XG, 0);
    const uint32_t frag = (cw * 16 + (lane & 15)) * 128 + (((lane >> 4) ^ (lane & 7)) << 4);
#pragma unroll
    for (int i = 0; i < 4; i++) {
      ldsm4(cx.sb + SM_XO + (frag ^ (i << 5)), xv[4 * i], xv[4 * i + 1], xv[4 * i + 2], xv[4 * i + 3]);
      ldsm4(cx.sb + SM_GO + (frag ^ (i << 5)), gt[4 * i], gt[4 * i + 1], gt[4 * i + 2], gt[4 * i + 3]);
    }
    if (ok) add_granules(red, g);
    TS3(44)
    wg_wait<0>();
    pin(acc);
    TS(85)
#pragma unroll
    for (int i = 0; i < 32; i++) red[i] += acc[i];
    pin(red);
#pragma unroll 1
    for (int spins = 0; spins < (1 << 16); spins++) {
      if (granules_ok(g2, tag)) {
        add_granules(red, g2);
        if (++nrx == 8) break;
      }
      fetch(g2, nrx);
    }
    uint32_t ow[16];
#pragma unroll
    for (int i = 0; i < 16; i++) ow[i] = pack2(red[2 * i], red[2 * i + 1]);
    prof(wg, 20);
    TS(86)
#pragma unroll
    for (int i = 0; i < 16; i++) ow[i] = fma2(ow[i], gt[i], xv[i]);
#pragma unroll
    for (int i = 0; i < 4; i++) stsm4(cx.sb + SM_XO + (frag ^ (i << 5)), ow[4 * i], ow[4 * i + 1], ow[4 * i + 2], ow[4 * i + 3]);
    __syncwarp();
    __nv_bfloat16* const op = at(out, ((qb * 128 + cw * 16 + (lane >> 3)) * DM + hs * 64 + (lane & 7) * 8) * 2);
#pragma unroll
    for (int i = 0; i < 4; i++) {
      uint4 v;
      const int row = cw * 16 + i * 4 + (lane >> 3);
      lds128(cx.sb + SM_XO + row * 128 + (((lane ^ row) & 7) << 4), v.x, v.y, v.z, v.w);
      asm volatile("st.global.v4.b32 [%0], {%1, %2, %3, %4};" ::"l"(op + i * 4 * DM),
                   "r"(v.x), "r"(v.y), "r"(v.z), "r"(v.w) : "memory");
    }
    prof(wg, 22);
    TS(87)
    TS_DUMP()
  }
}

struct KvMaps { CUtensorMap m[4]; };
__global__ void __cluster_dims__(2, 1, 1) __launch_bounds__(THREADS, 1)
fused_kernel(const __nv_bfloat16* __restrict__ x, const __nv_bfloat16* __restrict__ w_r, const __nv_bfloat16* __restrict__ kc,
             const __nv_bfloat16* __restrict__ vc, __nv_bfloat16* __restrict__ out, Scratch* scratch,
             const __grid_constant__ CUtensorMap tmX, const __grid_constant__ CUtensorMap tmWq,
             const __grid_constant__ KvMaps tmKV, const __grid_constant__ CUtensorMap tmWo,
             const __grid_constant__ CUtensorMap tmG, const __grid_constant__ CUtensorMap tmU,
             const __grid_constant__ CUtensorMap tmD, const __grid_constant__ CUtensorMap tmX16,
             const __grid_constant__ CUtensorMap tmWq96, const __grid_constant__ CUtensorMap tmX64) {
  extern __shared__ __align__(1024) uint8_t smem_raw[];
  prof(0, 23, 511);
  Ctx cx;
  cx.sb = smem_u32(smem_raw);
  cx.sp = smem_raw;
  cx.g = scratch;
  cx.rank = blockIdx.x & 1;
  const int warp = __shfl_sync(0xffffffffu, threadIdx.x >> 5, 0);
  const int cluster = blockIdx.x >> 1;
  const bool is_ffn = blockIdx.x >= N_ATT_CTA;
  const int c7 = ((cluster - 36) * 37) >> 8;
  const int hs = cluster < 4 ? 4 + cluster : cluster < 36 ? (cluster - 4) >> 3 : 4 + c7;
  const int qb = (cluster < 4 ? 0 : cluster < 36 ? (cluster - 4) & 7 : cluster - (is_ffn ? 36 : 35) - 7 * c7) * 2 + cx.rank;

  auto load_x = [&](int w, int i0, int i1) {
#pragma unroll
    for (int i = i0; i < i1; i++) {
      mbar_expect_tx(cx.sb + SM_XFULL + 32 * w + 8 * i, 24576);
      tma3d(cx.sb + SM_X + (3 * w + i) * 24576, &tmX, qb * 128 + w * 64, i * 3, cx.sb + SM_XFULL + 32 * w + 8 * i);
    }
  };
  if (warp < 4) {
    asm volatile("setmaxnreg.dec.sync.aligned.u32 24;");
    if (elect_one()) {
      if (warp == 0) TSP(64)
      if (warp < 2) {
#pragma unroll
        for (int i = 0; i < 4; i++) mbar_init(cx.sb + SM_FULL + 32 * warp + 8 * i, 1 + 3 * warp);
        mbar_init(cx.sb + SM_BAR_XG + 8 * warp, 1);
        mbar_init(cx.sb + SM_BAR_Q + 8 * warp, 1);
        if (warp) mbar_init(cx.sb + SM_BAR_MISC, 1);
      } else if (is_ffn) {
#pragma unroll
        for (int i = 0; i < 8; i++) mbar_init(cx.sb + (warp == 2 ? SM_FFULL : SM_FEMPTY) + 8 * i, 1);
      }
      asm volatile("fence.mbarrier_init.release.cluster;" ::: "memory");
    }
    __syncwarp();
    cluster_arrive();
    if (warp == 0) TSP(70)
    cluster_wait();
    if (warp == 0) TSP(71)
    prof(0, 24, 511);
    if (warp == 0) {
      if (is_ffn) ffn_producer(cx, qb, &tmWq, &tmG, &tmU, &tmD);
      else attn_producer(cx, qb, hs, tmKV.m, &tmWq, &tmWq96, &tmWo);
      prof(0, 25, 511);
    } else {
      sq_publish(cx, qb, hs, warp - 1, read_lane());
      if (warp == 3) sq_collect(cx, qb, read_lane());
      if (!is_ffn) {
        attn_gate(cx, qb, hs, warp - 1, threadIdx.x - 32, x);
        if (warp == 1) TSP(65)
        asm volatile("fence.proxy.async.global;" ::: "memory");
        if (warp == 1) attn_helper(cx, qb, hs, fresh_lane(), &tmX16);
        else bar_arrive(BAR_OA, 352);
        attn_finish8(cx, qb, hs, warp - 1, fresh_lane(), out);
      } else if (warp < 3) {
        ffn_publish(cx, qb, warp - 1, fresh_lane(), &tmX64);
      }
    }
    __syncwarp();
    cluster_arrive();
    cluster_wait();
  } else {
    if (warp == 4 && elect_one()) {
#pragma unroll
      for (int i = 0; i < 3; i++) mbar_init(cx.sb + SM_XFULL + 8 * i, 1);
      TSP(66)
      load_x(0, 0, 3);
#pragma unroll
      for (int i = 4; i < 7; i++) mbar_init(cx.sb + SM_XFULL + 8 * i, 1);
      asm volatile("fence.mbarrier_init.release.cluster;" ::: "memory");
    }
    if (warp == 5 && elect_one()) {
      mbar_init(cx.sb + SM_BAR_W, 1);
      asm volatile("fence.mbarrier_init.release.cluster;" ::: "memory");
      *(uint4*)(cx.sp + SM_ONES) = make_uint4(0x3F803F80u, 0x3F803F80u, 0x3F803F80u, 0x3F803F80u);
      mbar_expect_tx(cx.sb + SM_BAR_W, DM * 2);
      bulk_load(cx.sb + SM_WR, w_r, DM * 2, cx.sb + SM_BAR_W);
    }
    __syncwarp();
    cluster_arrive();
    if (warp == 4 && elect_one()) {
      load_x(1, 0, X_ORD);
      TSP(67)
    }
    __syncwarp();
    asm volatile("setmaxnreg.inc.sync.aligned.u32 240;");
    const int cw = warp - 4, wg = cw >> 2;
    cluster_wait();
    if (warp == 8 && elect_one()) {
      const uint64_t pol = policy_evict_first();
#pragma unroll
      for (int i = 0; i < 4; i++) {
        if (!(i & 1)) mbar_expect_tx(cx.sb + SM_FULL + 4 * i, 32768);
        tma2d_mc(cx.sb + SM_RING + (i >> 1) * STAGE + cx.rank * 16384 + (i & 1) * 8192, &tmWq,
                 is_ffn ? (cx.rank * 4 + 3) * DH + 64 : hs * 512 + cx.rank * 64, i * 64, cx.sb + SM_FULL + 8 * (i >> 1), pol);
        if (i == 1) load_x(1, X_ORD, 3);
      }
      TSP(72)
    }
    __syncwarp();
    attn_consumer(cx, is_ffn, qb, hs, wg, cw, read_lane(), x, kc, vc, out);
  }
}

typedef CUresult (*EncodeFn)(CUtensorMap*, CUtensorMapDataType, cuuint32_t, void*, const cuuint64_t*, const cuuint64_t*,
                             const cuuint32_t*, const cuuint32_t*, CUtensorMapInterleave, CUtensorMapSwizzle,
                             CUtensorMapL2promotion, CUtensorMapFloatOOBfill);

void encode(EncodeFn fn, CUtensorMap* m, const void* p, int rank, const cuuint64_t* dims, const cuuint64_t* strides,
            const cuuint32_t* box) {
  const cuuint32_t es[5] = {1, 1, 1, 1, 1};
  fn(m, CU_TENSOR_MAP_DATA_TYPE_BFLOAT16, rank, const_cast<void*>(p), dims, strides, box, es, CU_TENSOR_MAP_INTERLEAVE_NONE,
     CU_TENSOR_MAP_SWIZZLE_128B, CU_TENSOR_MAP_L2_PROMOTION_L2_128B, CU_TENSOR_MAP_FLOAT_OOB_FILL_NONE);
}
void encode2d(EncodeFn fn, CUtensorMap* m, const void* p, uint64_t rows, uint64_t cols, uint32_t box_rows) {
  const cuuint64_t dims[2] = {cols, rows}, strides[1] = {cols * 2};
  const cuuint32_t box[2] = {64, box_rows};
  encode(fn, m, p, 2, dims, strides, box);
}

}

extern "C" void kernel_launch(void* const* d_in, const int* in_sizes, int n_in, void* d_out, int out_size) {
  (void)in_sizes; (void)n_in; (void)out_size;
  void* fnp = nullptr;
  cudaDriverEntryPointQueryResult qr;
  cudaGetDriverEntryPoint("cuTensorMapEncodeTiled", &fnp, cudaEnableDefault, &qr);
  EncodeFn fn = (EncodeFn)fnp;
  CUtensorMap tmWq, tmWo, tmG, tmU, tmD, tmX, tmX16, tmWq96, tmX64;
  encode2d(fn, &tmX64, d_in[0], SEQ, DM, 64);
  encode2d(fn, &tmWq96, d_in[3], DM, 4096, 96);
  encode2d(fn, &tmX16, d_in[0], SEQ, DM, 16);
  KvMaps tmKV;
  for (int i = 0; i < 4; i++) encode2d(fn, &tmKV.m[i], d_in[1 + (i & 1)], 16 * SEQ, DH, i < 2 ? 112 : 96);
  encode2d(fn, &tmWq, d_in[3], DM, 4096, 64);
  {
    const cuuint64_t dims[3] = {64, SEQ, 9}, strides[2] = {DM * 2, 128};
    const cuuint32_t box[3] = {64, 64, 3};
    encode(fn, &tmX, d_in[0], 3, dims, strides, box);
  }
  encode2d(fn, &tmWo, d_in[4], 4096, DM, 128);
  encode2d(fn, &tmG, d_in[7], DM, FF, 192);
  encode2d(fn, &tmU, d_in[8], DM, FF, 192);
  encode2d(fn, &tmD, d_in[9], FF, DM, 192);
  cudaFuncSetAttribute(fused_kernel, cudaFuncAttributeMaxDynamicSharedMemorySize, SM_TOTAL);
  void* scratch = nullptr;
  cudaGetSymbolAddress(&scratch, g_scratch);
  fused_kernel<<<N_CTA, THREADS, SM_TOTAL>>>((const __nv_bfloat16*)d_in[0], (const __nv_bfloat16*)d_in[6], (const __nv_bfloat16*)d_in[1],
                                            (const __nv_bfloat16*)d_in[2], (__nv_bfloat16*)d_out, (Scratch*)scratch, tmX, tmWq, tmKV,
                                            tmWo, tmG, tmU, tmD, tmX16, tmWq96, tmX64);
}
```

```cpp
#include <cuda_runtime.h>
#include <cuda_bf16.h>
#include <cuda.h>
#include <stdint.h>

#define X_PFW 1
#define X_SPLIT 38
#define X_SPLITA 36
#define X_SPLITS 32
#define X_SPLITSA 30
#define X_PA 8
#define X_PG 4
#define X_E0 10
#define X_F2 12
#define X_Q1 6
#define X_WAKE 31
#define X_F1 4
#define X_BF2 1
#define X_SQI 4
#define X_SQS 300
#define X_ORD 3
#define X_QP 2
#define X_QC 2
#define X_NS 4
namespace {

constexpr int SEQ = 2048, DM = 576, DH = 128, FF = 4608, TOPC = 8;
constexpr int N_ATT_CTA = 128, N_CTA = 132;
constexpr int THREADS = 384;

constexpr uint32_t SM_RING = 0;
constexpr uint32_t STAGE = 32768;
constexpr uint32_t SM_SLOT = 131072;
constexpr uint32_t FSTAGE = 24576;
constexpr uint32_t SM_XSEL = 196608;
constexpr uint32_t SM_H = 205824;
constexpr uint32_t SM_MISC = 229376;
constexpr uint32_t SM_FULL = SM_MISC, SM_EMPTY = SM_MISC + 32, SM_FFULL = SM_MISC + 64, SM_BAR_MISC = SM_MISC + 128,
                   SM_COLD = SM_MISC + 136, SM_TAG = SM_MISC + 144, SM_BAR_W = SM_MISC + 152, SM_ONES = SM_MISC + 160,
                   SM_BAR_Q = SM_MISC + 176, SM_XFULL = SM_MISC + 192, SM_BAR_XG = SM_MISC + 304, SM_BAR_SQ = SM_MISC + 312,
                   SM_STATS = SM_MISC + 320, SM_FEMPTY = SM_MISC + 1344, SM_RAW = SM_FEMPTY, SM_WR = SM_MISC + 1408, SM_TOPK = SM_WR;
constexpr uint32_t SM_TOTAL = SM_MISC + 2560;
constexpr uint32_t SM_X = SM_MISC - 147456;

constexpr int BAR_GATE = 6, BAR_HELPER = 7, BAR_OA = 8, BAR_XREL = 13, BAR_QS = 9, BAR_QF = 11;
constexpr int NST_Q = 18, NST_KV = 76, NST_O = 18;
constexpr float SM_SCALE_LOG2 = 0.08838834764831845f * 1.4426950408889634f;

struct Scratch {
  uint4 part[16 * 64 * 2 * 4 * 128];
  uint4 gate[N_ATT_CTA * 1152];
  uint4 q[16 * 8 * 2 * 512];
  uint2 sq[SEQ];
  uint4 stats[SEQ];
  float ypart[4 * TOPC * DM];
  int2 sel[16];
  unsigned launch[160];
  unsigned pad0, ycnt, pad[30];
  unsigned qflag[128];
};
__device__ __align__(1024) Scratch g_scratch;

__device__ __forceinline__ void prof(int, int, int = 0) {}

#define TS(id) {}
#define TS_DUMP() {}
#define TSH(k) {}
#define TS4(k) {}
#define TSP(k) {}
#define TS1(id) TS(id)
#define TS2(k) {}
#define TS3(k) {}

__device__ __forceinline__ uint32_t smem_u32(const void* p) { return (uint32_t)__cvta_generic_to_shared(p); }
__device__ __forceinline__ void mbar_init(uint32_t bar, uint32_t cnt) {
  asm volatile("mbarrier.init.shared::cta.b64 [%0], %1;" ::"r"(bar), "r"(cnt) : "memory");
}
__device__ __forceinline__ void mbar_expect_tx(uint32_t bar, uint32_t bytes) {
  asm volatile("mbarrier.arrive.expect_tx.shared::cta.b64 _, [%0], %1;" ::"r"(bar), "r"(bytes) : "memory");
}
__device__ __forceinline__ void mbar_arrive(uint32_t bar) {
  asm volatile("mbarrier.arrive.shared::cta.b64 _, [%0];" ::"r"(bar) : "memory");
}
__device__ __forceinline__ void mbar_arrive_cluster(uint32_t bar_cluster_addr, bool pred) {
  asm volatile("{\n.reg .pred p;\nsetp.ne.u32 p, %1, 0;\n@p mbarrier.arrive.shared::cluster.b64 _, [%0];\n}"
               ::"r"(bar_cluster_addr), "r"((uint32_t)pred) : "memory");
}
template <int ID>
__device__ __forceinline__ void mbar_arrive_cluster_now(uint32_t bar_cluster_addr, bool pred) {
  asm volatile("{\n.reg .pred p, q;\nsetp.ne.u32 p, %1, 0;\nsetp.eq.u32 q, %2, %3;\n"
               "ARR_LOOP:\n@p mbarrier.arrive.shared::cluster.b64 _, [%0];\n@q bra.uni ARR_LOOP;\n}"
               ::"r"(bar_cluster_addr), "r"((uint32_t)pred), "r"(blockIdx.y), "n"(ID) : "memory");
}
__device__ __forceinline__ void block_fence(int id) {
  asm volatile("{\n.reg .pred q;\nsetp.eq.u32 q, %0, %1;\nBF_LOOP:\n@q st.volatile.shared.u32 [%0], %0;\n@q bra.uni BF_LOOP;\n}"
               ::"r"(blockIdx.y), "r"(id) : "memory");
}
__device__ __forceinline__ void mbar_wait(uint32_t bar, uint32_t parity) {
  asm volatile("{\n.reg .pred p, q;\n.reg .u32 n;\nmov.u32 n, 0;\n"
               "WAIT_LOOP:\nmbarrier.try_wait.parity.shared::cta.b64 p, [%0], %1;\n"
               "add.u32 n, n, 1;\nsetp.lt.u32 q, n, 4194304;\nand.pred q, q, !p;\n@q bra WAIT_LOOP;\n}"
               ::"r"(bar), "r"(parity) : "memory");
}
__device__ __forceinline__ uint32_t mapa(uint32_t addr, uint32_t rank) {
  uint32_t r;
  asm volatile("mapa.shared::cluster.u32 %0, %1, %2;" : "=r"(r) : "r"(addr), "r"(rank));
  return r;
}
__device__ __forceinline__ void cluster_arrive() { asm volatile("barrier.cluster.arrive.relaxed.aligned;" ::: "memory"); }
__device__ __forceinline__ bool elect_one() {
  uint32_t p;
  asm volatile("{\n.reg .pred p;\nelect.sync _|p, 0xffffffff;\nselp.u32 %0, 1, 0, p;\n}" : "=r"(p));
  return p;
}
__device__ __forceinline__ int read_lane() { return threadIdx.x & 31; }
__device__ __forceinline__ int fresh_lane() {
  int l;
  asm volatile("mov.u32 %0, %%laneid;" : "=r"(l));
  return l;
}
template <class T> __device__ __forceinline__ T* at(T* p, uint32_t bytes) {
  asm("" : "+r"(bytes));
  return (T*)((const char*)p + bytes);
}
__device__ __forceinline__ void cluster_wait() { asm volatile("barrier.cluster.wait.acquire.aligned;" ::: "memory"); }
__device__ __forceinline__ void bar_sync(int id, int n) { asm volatile("barrier.cta.sync %0, %1;" ::"r"(id), "r"(n) : "memory"); }
__device__ __forceinline__ void bar_arrive(int id, int n) { asm volatile("barrier.cta.arrive %0, %1;" ::"r"(id), "r"(n) : "memory"); }

__device__ __forceinline__ uint64_t policy_evict_first() {
  uint64_t p;
  asm("createpolicy.fractional.L2::evict_first.b64 %0, 1.0;" : "=l"(p));
  return p;
}
__device__ __forceinline__ void tma2d_mc(uint32_t dst, const CUtensorMap* tm, int c0, int c1, uint32_t bar, uint64_t pol) {
  asm volatile("cp.async.bulk.tensor.2d.shared::cluster.global.mbarrier::complete_tx::bytes.multicast::cluster.L2::cache_hint"
               " [%0], [%1, {%2, %3}], [%4], %5, %6;"
               ::"r"(dst), "l"(tm), "r"(c0), "r"(c1), "r"(bar), "h"((uint16_t)3), "l"(pol) : "memory");
}
__device__ __forceinline__ void tma3d(uint32_t dst, const CUtensorMap* tm, int c1, int c2, uint32_t bar) {
  asm volatile("cp.async.bulk.tensor.3d.shared::cluster.global.mbarrier::complete_tx::bytes [%0], [%1, {%2, %3, %4}], [%5];"
               ::"r"(dst), "l"(tm), "r"(0), "r"(c1), "r"(c2), "r"(bar) : "memory");
}
__device__ __forceinline__ void tma2d(uint32_t dst, const CUtensorMap* tm, int c0, int c1, uint32_t bar) {
  asm volatile("cp.async.bulk.tensor.2d.shared::cluster.global.mbarrier::complete_tx::bytes [%0], [%1, {%2, %3}], [%4];"
               ::"r"(dst), "l"(tm), "r"(c0), "r"(c1), "r"(bar) : "memory");
}
__device__ __forceinline__ void tma2d_stream(uint32_t dst, const CUtensorMap* tm, int c0, int c1, uint32_t bar) {
  asm volatile("{\n.reg .b64 pol;\ncreatepolicy.fractional.L2::evict_first.b64 pol, 1.0;\n"
               "cp.async.bulk.tensor.2d.shared::cluster.global.mbarrier::complete_tx::bytes.L2::cache_hint [%0], [%1, {%2, %3}], [%4], pol;\n}"
               ::"r"(dst), "l"(tm), "r"(c0), "r"(c1), "r"(bar) : "memory");
}
__device__ __forceinline__ void bulk_load(uint32_t dst, const void* src, uint32_t bytes, uint32_t bar) {
  asm volatile("cp.async.bulk.shared::cluster.global.mbarrier::complete_tx::bytes [%0], [%1], %2, [%3];"
               ::"r"(dst), "l"(src), "r"(bytes), "r"(bar) : "memory");
}
__device__ __forceinline__ void tma2d_prefetch(const CUtensorMap* tm, int c0, int c1) {
  asm volatile("cp.async.bulk.prefetch.tensor.2d.L2.global [%0, {%1, %2}];" ::"l"(tm), "r"(c0), "r"(c1) : "memory");
}

__device__ __forceinline__ void wg_fence() { asm volatile("wgmma.fence.sync.aligned;" ::: "memory"); }
__device__ __forceinline__ void wg_commit() { asm volatile("wgmma.commit_group.sync.aligned;" ::: "memory"); }
template <int N> __device__ __forceinline__ void wg_wait() { asm volatile("wgmma.wait_group.sync.aligned %0;" ::"n"(N) : "memory"); }

__device__ __forceinline__ uint64_t mkdesc(uint32_t addr, uint32_t lbo_bytes) {
  return (uint64_t)(((addr & 0x3FFFF) >> 4) | ((lbo_bytes >> 4) << 16)) | ((uint64_t)0x40000040u << 32);
}
__device__ __forceinline__ uint64_t mkdesc_q(uint32_t addr) {
  return (uint64_t)(((addr & 0x3FFFF) >> 4) | (64u << 16)) | ((uint64_t)8 << 32);
}
template <int N> __device__ __forceinline__ void pin(float (&a)[N]) {
#pragma unroll
  for (int i = 0; i < N; i++) asm volatile("" : "+f"(a[i])::"memory");
}
template <int N> __device__ __forceinline__ void kill(float (&a)[N]) {
#pragma unroll
  for (int i = 0; i < N; i++) asm volatile("" : "=f"(a[i]));
}
template <int N> __device__ __forceinline__ void pin(uint32_t (&a)[N]) {
#pragma unroll
  for (int i = 0; i < N; i++) asm volatile("" : "+r"(a[i])::"memory");
}

#define F8(d, o) "+f"(d[o]), "+f"(d[o + 1]), "+f"(d[o + 2]), "+f"(d[o + 3]), "+f"(d[o + 4]), "+f"(d[o + 5]), "+f"(d[o + 6]), "+f"(d[o + 7])
#define R32A "%0, %1, %2, %3, %4, %5, %6, %7, %8, %9, %10, %11, %12, %13, %14, %15, %16, %17, %18, %19, %20, %21, %22, %23, %24, %25, %26, %27, %28, %29, %30, %31"
#define R32B "%32, %33, %34, %35, %36, %37, %38, %39, %40, %41, %42, %43, %44, %45, %46, %47, %48, %49, %50, %51, %52, %53, %54, %55, %56, %57, %58, %59, %60, %61, %62, %63"

#define O8(d, o) "=f"(d[o]), "=f"(d[o + 1]), "=f"(d[o + 2]), "=f"(d[o + 3]), "=f"(d[o + 4]), "=f"(d[o + 5]), "=f"(d[o + 6]), "=f"(d[o + 7])

__device__ __forceinline__ void mma_n128t(float (&d)[64], uint32_t a0, uint32_t a1, uint32_t a2, uint32_t a3, uint64_t db, bool acc) {
  if (acc)
    asm volatile("wgmma.mma_async.sync.aligned.m64n128k16.f32.bf16.bf16 {" R32A ", " R32B "}, {%64, %65, %66, %67}, %68, 1, 1, 1, 1;\n"
                 : F8(d, 0), F8(d, 8), F8(d, 16), F8(d, 24), F8(d, 32), F8(d, 40), F8(d, 48), F8(d, 56)
                 : "r"(a0), "r"(a1), "r"(a2), "r"(a3), "l"(db));
  else
    asm volatile("wgmma.mma_async.sync.aligned.m64n128k16.f32.bf16.bf16 {" R32A ", " R32B "}, {%64, %65, %66, %67}, %68, 0, 1, 1, 1;\n"
                 : O8(d, 0), O8(d, 8), O8(d, 16), O8(d, 24), O8(d, 32), O8(d, 40), O8(d, 48), O8(d, 56)
                 : "r"(a0), "r"(a1), "r"(a2), "r"(a3), "l"(db));
}
#define PV1(a0, a1, a2, a3, ob, acc) "add.s64 b, %92, " #ob ";\n" \
  "wgmma.mma_async.sync.aligned.m64n128k16.f32.bf16.bf16 {" R32A ", " R32B "}, {%" #a0 ", %" #a1 ", %" #a2 ", %" #a3 "}, b, " #acc ", 1, 1, 1;\n"
#define PV6 "wgmma.fence.sync.aligned;\n" PV1(64, 65, 66, 67, 0, p) PV1(68, 69, 70, 71, 128, 1) PV1(72, 73, 74, 75, 256, 1) \
  PV1(76, 77, 78, 79, 384, 1) PV1(80, 81, 82, 83, 512, 1) PV1(84, 85, 86, 87, 640, 1)
#define U4(a, o) "r"(a[o]), "r"(a[o + 1]), "r"(a[o + 2]), "r"(a[o + 3])
__device__ __forceinline__ void mma_pv(float (&d)[64], const uint32_t (&a)[28], uint64_t dv, bool acc, bool big) {
  asm volatile("{\n.reg .pred p, q;\n.reg .b64 b;\nsetp.ne.b32 p, %93, 0;\nsetp.eq.b32 q, %94, 0;\n@q bra.uni PV_SMALL;\n"
               PV6 PV1(88, 89, 90, 91, 768, 1) "wgmma.commit_group.sync.aligned;\nbra.uni PV_DONE;\n"
               "PV_SMALL:\n" PV6 "wgmma.commit_group.sync.aligned;\nPV_DONE:\n}\n"
               : F8(d, 0), F8(d, 8), F8(d, 16), F8(d, 24), F8(d, 32), F8(d, 40), F8(d, 48), F8(d, 56)
               : U4(a, 0), U4(a, 4), U4(a, 8), U4(a, 12), U4(a, 16), U4(a, 20), U4(a, 24), "l"(dv), "r"((int)acc), "r"((int)big) : "memory");
}
#define R48 R32A ", %32, %33, %34, %35, %36, %37, %38, %39, %40, %41, %42, %43, %44, %45, %46, %47"
#define R56 R48 ", %48, %49, %50, %51, %52, %53, %54, %55"
#define QK1(N, R, A, B, oa, ob, acc) "add.s64 a, " A ", " #oa ";\nadd.s64 b, " B ", " #ob ";\n" \
  "wgmma.mma_async.sync.aligned.m64n" #N "k16.f32.bf16.bf16 {" R "}, a, b, " #acc ", 1, 1, 0, 0;\n"
#define QK8(N, R, A, B) "{\n.reg .b64 a, b;\nwgmma.fence.sync.aligned;\n" QK1(N, R, A, B, 0, 0, 0) QK1(N, R, A, B, 128, 2, 1) \
  QK1(N, R, A, B, 256, 4, 1) QK1(N, R, A, B, 384, 6, 1) QK1(N, R, A, B, 512, 1024, 1) QK1(N, R, A, B, 640, 1026, 1) \
  QK1(N, R, A, B, 768, 1028, 1) QK1(N, R, A, B, 896, 1030, 1) "wgmma.commit_group.sync.aligned;\n}\n"
__device__ __forceinline__ void mma_qk(float (&d)[56], uint64_t dq, uint64_t dk) {
  asm volatile(QK8(112, R56, "%56", "%57")
               : O8(d, 0), O8(d, 8), O8(d, 16), O8(d, 24), O8(d, 32), O8(d, 40), O8(d, 48) : "l"(dq), "l"(dk) : "memory");
}
__device__ __forceinline__ void mma_qk(float (&d)[48], uint64_t dq, uint64_t dk) {
  asm volatile(QK8(96, R48, "%48", "%49")
               : O8(d, 0), O8(d, 8), O8(d, 16), O8(d, 24), O8(d, 32), O8(d, 40) : "l"(dq), "l"(dk) : "memory");
}
__device__ __forceinline__ void mma_n64t(float (&d)[32], uint32_t a0, uint32_t a1, uint32_t a2, uint32_t a3, uint64_t db, bool acc) {
  if (acc)
    asm volatile("wgmma.mma_async.sync.aligned.m64n64k16.f32.bf16.bf16 {" R32A "}, {%32, %33, %34, %35}, %36, 1, 1, 1, 1;\n"
                 : F8(d, 0), F8(d, 8), F8(d, 16), F8(d, 24) : "r"(a0), "r"(a1), "r"(a2), "r"(a3), "l"(db));
  else
    asm volatile("wgmma.mma_async.sync.aligned.m64n64k16.f32.bf16.bf16 {" R32A "}, {%32, %33, %34, %35}, %36, 0, 1, 1, 1;\n"
                 : O8(d, 0), O8(d, 8), O8(d, 16), O8(d, 24) : "r"(a0), "r"(a1), "r"(a2), "r"(a3), "l"(db));
}
__device__ __forceinline__ void mma_n64t_dyn(float (&d)[32], uint32_t a0, uint32_t a1, uint32_t a2, uint32_t a3, uint64_t db, int acc) {
  asm volatile("{\n.reg .pred p;\nsetp.ne.b32 p, %37, 0;\n"
               "wgmma.mma_async.sync.aligned.m64n64k16.f32.bf16.bf16 {" R32A "}, {%32, %33, %34, %35}, %36, p, 1, 1, 1;\n}\n"
               : F8(d, 0), F8(d, 8), F8(d, 16), F8(d, 24) : "r"(a0), "r"(a1), "r"(a2), "r"(a3), "l"(db), "r"(acc));
}
__device__ __forceinline__ void mma_n8(float (&d)[4], uint64_t da, uint64_t db, int acc) {
  asm volatile("{\n.reg .pred p;\nsetp.ne.b32 p, %6, 0;\n"
               "wgmma.mma_async.sync.aligned.m64n8k16.f32.bf16.bf16 {%0, %1, %2, %3}, %4, %5, p, 1, 1, 1, 0;\n}\n"
               : "+f"(d[0]), "+f"(d[1]), "+f"(d[2]), "+f"(d[3])
               : "l"(da), "l"(db), "r"(acc));
}
__device__ __forceinline__ void hmma_k16(float (&d)[4], uint32_t a0, uint32_t a1, uint32_t a2, uint32_t a3, uint32_t b0, uint32_t b1) {
  asm volatile("mma.sync.aligned.m16n8k16.row.col.f32.bf16.bf16.f32 {%0, %1, %2, %3}, {%4, %5, %6, %7}, {%8, %9}, {%0, %1, %2, %3};"
               : "+f"(d[0]), "+f"(d[1]), "+f"(d[2]), "+f"(d[3]) : "r"(a0), "r"(a1), "r"(a2), "r"(a3), "r"(b0), "r"(b1));
}

__device__ __forceinline__ uint32_t pack2(float lo, float hi) {
  uint32_t r;
  asm("cvt.rn.bf16x2.f32 %0, %1, %2;" : "=r"(r) : "f"(hi), "f"(lo));
  return r;
}
__device__ __forceinline__ float bf_lo(uint32_t w) { return __uint_as_float(w << 16); }
__device__ __forceinline__ float bf_hi(uint32_t w) { return __uint_as_float(w & 0xFFFF0000u); }
__device__ __forceinline__ float bfr(float x) { return __bfloat162float(__float2bfloat16_rn(x)); }
__device__ __forceinline__ uint32_t sub2(uint32_t a, uint32_t b) {
  uint32_t r;
  asm("sub.rn.bf16x2 %0, %1, %2;" : "=r"(r) : "r"(a), "r"(b));
  return r;
}
__device__ __forceinline__ uint32_t add2(uint32_t a, uint32_t b) {
  uint32_t r;
  asm("add.rn.bf16x2 %0, %1, %2;" : "=r"(r) : "r"(a), "r"(b));
  return r;
}
__device__ __forceinline__ uint32_t fma2(uint32_t a, uint32_t b, uint32_t c) {
  uint32_t r;
  asm("fma.rn.bf16x2 %0, %1, %2, %3;" : "=r"(r) : "r"(a), "r"(b), "r"(c));
  return r;
}
__device__ __forceinline__ float ex2(float x) {
  float r;
  asm("ex2.approx.ftz.f32 %0, %1;" : "=f"(r) : "f"(x));
  return r;
}
__device__ __forceinline__ float rcp(float x) {
  float r;
  asm("rcp.approx.ftz.f32 %0, %1;" : "=f"(r) : "f"(x));
  return r;
}
__device__ __forceinline__ float silu_f(float t) { return t * rcp(1.0f + ex2(-1.4426950408889634f * t)); }
__device__ __forceinline__ void lds128(uint32_t a, uint32_t& x, uint32_t& y, uint32_t& z, uint32_t& w) {
  asm volatile("ld.shared.v4.u32 {%0, %1, %2, %3}, [%4];" : "=r"(x), "=r"(y), "=r"(z), "=r"(w) : "r"(a) : "memory");
}
__device__ __forceinline__ void ldsm4(uint32_t a, uint32_t& x, uint32_t& y, uint32_t& z, uint32_t& w) {
  asm volatile("ldmatrix.sync.aligned.m8n8.x4.shared.b16 {%0, %1, %2, %3}, [%4];" : "=r"(x), "=r"(y), "=r"(z), "=r"(w) : "r"(a) : "memory");
}
constexpr uint32_t TAG = 0x10000;
__device__ __forceinline__ void st_gran(uint4* p, uint32_t x, uint32_t y, uint32_t z, uint32_t w) {
  asm volatile("st.relaxed.gpu.global.v4.b32 [%0], {%1, %2, %3, %4};" ::"l"(p), "r"(x), "r"(y), "r"(z), "r"(w) : "memory");
}
__device__ __forceinline__ void ld_gran(const uint4* p, uint32_t& x, uint32_t& y, uint32_t& z, uint32_t& w) {
  asm volatile("ld.relaxed.gpu.global.v4.b32 {%0, %1, %2, %3}, [%4];" : "=r"(x), "=r"(y), "=r"(z), "=r"(w) : "l"(p) : "memory");
}
__device__ __forceinline__ void stsm4(uint32_t a, uint32_t x, uint32_t y, uint32_t z, uint32_t w) {
  asm volatile("stmatrix.sync.aligned.m8n8.x4.shared.b16 [%0], {%1, %2, %3, %4};" ::"r"(a), "r"(x), "r"(y), "r"(z), "r"(w) : "memory");
}
__device__ __forceinline__ void cp16(uint32_t dst, const void* src) {
  asm volatile("cp.async.cg.shared.global [%0], [%1], 16;" ::"r"(dst), "l"(src) : "memory");
}
__device__ __forceinline__ void cp_wait_all() { asm volatile("cp.async.wait_all;" ::: "memory"); }
__device__ __forceinline__ void add_granules(float (&red)[32], const uint32_t (&g)[16]) {
#pragma unroll
  for (int i = 0; i < 16; i++) { red[2 * i] += bf_lo(g[i]); red[2 * i + 1] += bf_hi((i & 3) ? g[i] : g[i] & ~TAG); }
}
__device__ __forceinline__ bool granules_ok(const uint32_t (&g)[16], uint32_t tag) {
  uint32_t a, b;
  asm("lop3.b32 %0, %1, %2, %3, 0x7E;" : "=r"(a) : "r"(g[0]), "r"(g[4]), "r"(tag));
  asm("lop3.b32 %0, %1, %2, %3, 0x7E;" : "=r"(b) : "r"(g[8]), "r"(g[12]), "r"(tag));
  return __all_sync(0xffffffffu, ((a | b) & TAG) == 0);
}
__device__ __forceinline__ unsigned ld_acquire(const unsigned* p) {
  unsigned v;
  asm volatile("ld.acquire.gpu.global.u32 %0, [%1];" : "=r"(v) : "l"(p) : "memory");
  return v;
}
__device__ __forceinline__ unsigned atom_add_acq_rel(unsigned* p) {
  unsigned v;
  asm volatile("atom.acq_rel.gpu.global.add.u32 %0, [%1], 1;" : "=r"(v) : "l"(p) : "memory");
  return v;
}

template <int K0, int K1>
__device__ __forceinline__ void ln_fetch(uint32_t (&xa)[144], uint32_t boxes, uint32_t lo) {
#pragma unroll
  for (int k = K0; k < K1; k++) ldsm4(boxes + (k >> 2) * 8192 + (lo ^ ((k & 3) << 5)), xa[4 * k], xa[4 * k + 1], xa[4 * k + 2], xa[4 * k + 3]);
}
__device__ __forceinline__ void ln_fetch_b(uint32_t (&b)[24], uint32_t& wb, uint32_t ws) {
#pragma unroll
  for (int j = 0; j < 6; j++, wb += ws) ldsm4(wb, b[4 * j], b[4 * j + 1], b[4 * j + 2], b[4 * j + 3]);
}
template <int K0, int K1>
__device__ __forceinline__ void ln_sums(const uint32_t (&xa)[144], float (&sm)[X_NS][4], const uint32_t (&b)[24]) {
#pragma unroll
  for (int k = K0; k < K1; k++)
    hmma_k16(sm[k % X_NS], xa[4 * k], xa[4 * k + 1], xa[4 * k + 2], xa[4 * k + 3], b[2 * (k % 12)], b[2 * (k % 12) + 1]);
}
template <int K0, int K1>
__device__ __forceinline__ uint32_t after_fetch(const uint32_t (&xa)[144]) {
  uint32_t d = blockIdx.y;
#pragma unroll
  for (int k = K0; k < K1; k++) d &= xa[4 * k];
  return d;
}
__device__ __forceinline__ void ln_row(float sum, float sq, float& mean_b, float& rstd) {
  const float mean = sum * (1.0f / DM);
  const uint32_t mv = pack2(mean, fmaxf(sq * (1.0f / DM) - mean * mean, 0.0f));
  mean_b = bf_lo(mv);
  float sd;
  asm("sqrt.approx.f32 %0, %1;" : "=f"(sd) : "f"(bf_lo(pack2(bf_hi(mv) + 1e-5f, 0.f))));
  rstd = rcp(bf_lo(pack2(sd, 0.f)));
}

template <bool ROUTED>
__device__ __forceinline__ uint32_t gate2(uint32_t xc, float rstd, float2 upd = make_float2(0.f, 0.f)) {
  uint32_t t = pack2(bf_lo(xc) * rstd, bf_hi(xc) * rstd);
  if (ROUTED) t = pack2(bf_lo(t) + upd.x, bf_hi(t) + upd.y);
  return pack2(silu_f(bf_lo(t)), silu_f(bf_hi(t)));
}

template <int V> struct IC { static constexpr int value = V; };

struct Ctx {
  uint32_t sb;
  uint8_t* sp;
  uint32_t rank;
  Scratch* g;
};

__device__ __forceinline__ bool acquire(const Ctx& cx, uint32_t r, uint32_t n, uint32_t bytes) {
  mbar_wait(cx.sb + SM_EMPTY + 8 * r, (n ^ (r >> 1) ^ 1) & 1);
  __syncwarp();
  const bool e = elect_one();
  if (e) mbar_expect_tx(cx.sb + SM_FULL + 8 * r, bytes);
  return e;
}
__device__ __forceinline__ void load_wq(const Ctx& cx, const CUtensorMap* tmWq, int st, int i, int n0, uint64_t pol) {
  const uint32_t r = st & 3, dst = cx.sb + SM_RING + r * STAGE + cx.rank * 16384, bar = cx.sb + SM_FULL + 8 * r;
  const int k0 = i < 3 ? 128 * i : 128 * i - 64;
  if (acquire(cx, r, st >> 2, i == 2 ? 16384 : 32768)) {
    tma2d_mc(dst, tmWq, n0, k0, bar, pol);
    if (i != 2) tma2d_mc(dst + 8192, tmWq, n0, k0 + 64, bar, pol);
  }
}
__device__ __forceinline__ void attn_producer(const Ctx& cx, int qb, int hs, const CUtensorMap* tmKV, const CUtensorMap* tmWq,
                                              const CUtensorMap* tmWq96, const CUtensorMap* tmWo) {
  const uint32_t full = cx.sb + SM_FULL, ring = cx.sb + SM_RING + cx.rank * 16384;
  const uint64_t last_use = policy_evict_first();
  int st = 0;
#pragma unroll 1
  for (int p = 0; p < 4; p++) {
#pragma unroll 1
    for (int i = 0; i < (p == 2 ? 3 : 5); i++, st++) {
      if (p == 2) {
        if (acquire(cx, st & 3, st >> 2, 24576))
          tma2d_mc(cx.sb + SM_RING + (st & 3) * STAGE + cx.rank * 12288, tmWq96, (hs * 4 + 3) * DH, 192 * i + 96 * cx.rank, full + 8 * (st & 3), last_use);
      } else {
        if (st > 1) load_wq(cx, tmWq, st, i, (hs * 4 + (p ^ (p >> 1))) * DH + cx.rank * 64, last_use);
      }
      if (st == 1 || st == 2) TSP(72 + st)
      if (st == X_PFW) {
#pragma unroll 1
        for (int b = qb < 8; b < 5 - (qb >> 3); b++)
          if (elect_one()) tma2d_prefetch(tmWq, hs * 512 + (b < 4 ? (b ^ (b >> 1)) * DH + (qb & 1) * 64 : qb * 64), b < 4 ? (qb >> 1) * 64 : 512);
      }
      if (st == 8 && qb < 8 && elect_one()) tma2d_prefetch(tmKV + ((qb >> 1) & 1), cx.rank * 64, hs * 2 * SEQ + (qb >> 2) * 96);
    }
  }
  uint32_t r = 2, n = 4;
  int row = hs * 2 * SEQ, rows = 96;
  const CUtensorMap* tm = tmKV + 2;
#pragma unroll 1
  for (int u = 0; u < NST_KV; u++) {
    if (acquire(cx, r, n, rows * 256)) {
      tma2d_mc(ring + r * STAGE, tm, cx.rank * 64, row, full + 8 * r, last_use);
      if (((u ^ (qb >> 1)) & 7) == 0 && u < NST_KV - 4) tma2d_prefetch(tmKV + (u & 1), cx.rank * 64, row + 208);
      if ((unsigned)(u - 32) < 36 && (u & 15) == qb) tma2d_prefetch(tmWo, ((u - 32) >> 2) * 64, hs * 512 + (u & 3) * 128);
    }
    if (++r == 4) { r = 1; n++; }
    if (u & 1) row += rows;
    const bool big = (unsigned)(u - 9) < 56;
    rows = big ? 112 : 96;
    tm = tmKV + (~u & 1) + (big ? 0 : 2);
  }
#pragma unroll 1
  for (int u = 0; u < NST_O; u++) {
    const int s = u >> 1;
    const int blk = s == 0 ? 8 : ((hs + s) & 7);
    r = (0x87 >> (2 * (u & 3))) & 3;
    if (acquire(cx, r, (u >> 2) ^ ~u, 32768))
      tma2d_mc(ring + r * STAGE, tmWo, blk * 64, hs * 512 + ((u & 1) + cx.rank * 2) * 128, full + 8 * r, last_use);
  }
}

__device__ __forceinline__ void sq_publish(const Ctx& cx, int qb, int hs, int j, int lane) {
  if (j == 2 && lane == 0) {
    const unsigned e = cx.g->launch[hs * 16 + qb]++;
    *(uint2*)(cx.sp + SM_TAG) = make_uint2((~e & 1) * TAG, e);
  }
  const int row = (hs & 3) * 16 + (lane >> 1);
  uint32_t a = cx.sb + SM_X + (hs >> 2) * 73728 + j * 8192 + row * 128 + (((lane & 1) ^ (row & 7)) << 4);
  float s0 = 0.f, s1 = 0.f;
#pragma unroll 1
  for (int b = 0; b < 6; b++) {
    if (b == (hs < 4 ? 4 : 0)) {
      const int n = 224 + (__float_as_uint(s1) & blockIdx.y);
      if (j == 1) {
        bar_sync(BAR_XREL, n);
        if (lane < 4) asm volatile("mbarrier.arrive.shared::cluster.b64 _, [%0], 2;" ::"r"(mapa(cx.sb + SM_EMPTY + 16 + 8 * (lane >> 1), lane & 1)) : "memory");
      } else {
        bar_arrive(BAR_XREL, n);
      }
      __syncwarp();
      if (hs == 8) return;
    }
    if (!(b & 1)) mbar_wait(cx.sb + SM_XFULL + 32 * (hs >> 2) + 4 * b, 0);
    uint32_t v[8];
    lds128(a, v[0], v[1], v[2], v[3]);
    lds128(a ^ 32, v[4], v[5], v[6], v[7]);
    a = (a ^ 64) + (b & 1) * 24576;
#pragma unroll
    for (int i = 0; i < 8; i++) { s0 = fmaf(bf_lo(v[i]), bf_lo(v[i]), s0); s1 = fmaf(bf_hi(v[i]), bf_hi(v[i]), s1); }
  }
  s0 += s1;
  s0 += __shfl_xor_sync(0xffffffffu, s0, 1);
  float* part = (float*)(cx.sp + SM_STATS) + (lane >> 1) * 2;
  if (j < 2) {
    part[32 * j] = s0;
    bar_arrive(BAR_HELPER, 96);
  } else {
    bar_sync(BAR_HELPER, 96);
    TSP(68)
    if (!(lane & 1))
      asm volatile("st.relaxed.gpu.global.v2.b32 [%0], {%1, %2};" ::"l"(cx.g->sq + qb * 128 + hs * 16 + (lane >> 1)),
                   "r"(__float_as_uint((part[0] + part[32]) + s0)), "r"(*(const uint32_t*)(cx.sp + SM_TAG + 4) + 1) : "memory");
  }
}
__device__ __forceinline__ void sq_collect(const Ctx& cx, int qb, int lane) {
  const uint32_t e1 = *(const uint32_t*)(cx.sp + SM_TAG + 4) + 1;
#pragma unroll 1
  for (int n = 0; n < (1 << 16); n++) {
    __nanosleep(X_SQS);
    uint32_t bad = 0;
#pragma unroll
    for (int i = 0; i < 2; i++) {
      uint32_t a, t0, b, t1;
      ld_gran((const uint4*)at(cx.g->sq, qb * 1024 + lane * 16) + i * 32, a, t0, b, t1);
      *(uint32_t*)(cx.sp + SM_STATS + (i * 32 + lane) * 16 + 4) = a;
      *(uint32_t*)(cx.sp + SM_STATS + (i * 32 + lane) * 16 + 12) = b;
      bad |= (t0 ^ e1) | (t1 ^ e1);
    }
    if (__all_sync(0xffffffffu, bad == 0)) break;
  }
  __syncwarp();
  if (lane == 0) mbar_arrive(cx.sb + SM_BAR_SQ);
  TSP(69)
}
__device__ __forceinline__ void attn_gate(const Ctx& cx, int qb, int hs, int j, int t, const __nv_bfloat16* x) {
  const uint4* xp = (const uint4*)(x + qb * 128 * DM) + (t >> 3) * 72 + hs * 8 + (t & 7);
  uint4 nx = *xp;
  float wsum = 0.f;
  if (j == 0) {
    mbar_wait(cx.sb + SM_BAR_W, 0);
#pragma unroll 3
    for (int i = 0; i < 9; i++) {
      const uint32_t w = *(const uint32_t*)(cx.sp + SM_WR + i * 128 + t * 4);
      wsum += bf_lo(w) + bf_hi(w);
    }
#pragma unroll
    for (int i = 1; i < 32; i *= 2) wsum += __shfl_xor_sync(0xffffffffu, wsum, i);
  }
  bar_sync(BAR_GATE, 352);
  if (t < 16) {
    const float2 st = *(const float2*)(cx.sp + SM_STATS + 8 * (hs * 16 + t));
    const int row = qb * 128 + hs * 16 + t;
    const uint32_t b = pack2(0.f, fmaf(-st.x, wsum, *(const float*)(cx.sp + SM_RAW + 4 * t)) * st.y);
    st_gran(at(cx.g->stats, row * 16), __float_as_uint(st.x), __float_as_uint(st.y), (b ^ ((int)b < 0 ? 0xFFFF0000u : 0x80000000u)) | (0xFFFF - row),
            *(const uint32_t*)(cx.sp + SM_TAG + 4) + 1);
  }
  __syncwarp();
  uint32_t sa = cx.sb + SM_STATS + (t & ~7);
  uint4* gp = cx.g->gate + blockIdx.x * 1152 + (t ^ ((t >> 3) & 7));
  const int cross = t < 64 ? 10 : 9;
#pragma unroll 1
  for (int i = 0; i < 12; i++) {
    float2 st;
    asm volatile("ld.shared.v2.f32 {%0, %1}, [%2];" : "=f"(st.x), "=f"(st.y) : "r"(sa));
    const uint32_t mm = pack2(st.x, st.x);
    const uint4 v = make_uint4(sub2(nx.x, mm), sub2(nx.y, mm), sub2(nx.z, mm), sub2(nx.w, mm));
    xp += 12 * 72;
    sa += 96;
    if (i == cross) { xp += (hs * 16 - 128) * 72 + 64 - hs * 8; sa += (hs * 16 - 128) * 8; }
    if (i < 11) nx = *xp;
    *gp = make_uint4(gate2<false>(v.x, st.y), gate2<false>(v.y, st.y), gate2<false>(v.z, st.y), gate2<false>(v.w, st.y));
    gp = (uint4*)((size_t)(gp + 96) ^ 64);
  }
}

constexpr uint32_t SM_XO = SM_SLOT, SM_GO = SM_SLOT + STAGE, SM_P8 = SM_SLOT + 2 * STAGE;
__device__ __forceinline__ void attn_helper(const Ctx& cx, int qb, int hs, int lane, const CUtensorMap* tmX16) {
  const unsigned e = *(const uint32_t*)(cx.sp + SM_TAG + 4);
  bar_sync(BAR_HELPER, 64);
  bool todo = lane < 2;
#pragma unroll 1
  for (int n = 0; __any_sync(0xffffffffu, todo); n++) {
    if (todo && (ld_acquire(at(cx.g->qflag, ((qb * 4 + (hs >> 1)) * 2 + lane) * 4)) == e + 1 || n == (1 << 16))) {
      asm volatile("fence.proxy.async.global;" ::: "memory");
      mbar_expect_tx(cx.sb + SM_BAR_Q + 8 * lane, 8192);
      bulk_load(cx.sb + SM_SLOT + 2 * STAGE + lane * 16384 + 8192, at(cx.g->q, ((qb * 8 + hs) * 2 + lane) * 8192), 8192, cx.sb + SM_BAR_Q + 8 * lane);
      todo = false;
    }
  }
  const uint32_t tag = (~e & 1) * TAG;
  const uint4* src = cx.g->part + (size_t)((qb * 64 + 56) * 2 + (hs >> 2)) * 4 * 128 + (hs & 3) * 32 + lane;
  const uint32_t stg = cx.sb + SM_P8 + lane * 16;
  bar_sync(BAR_OA, 352);
  asm volatile("fence.proxy.async.global;" ::: "memory");
  if (lane == 0) {
    mbar_expect_tx(cx.sb + SM_BAR_MISC, 2 * 18432);
    bulk_load(cx.sb + SM_GO, cx.g->gate + blockIdx.x * 1152, 18432, cx.sb + SM_BAR_MISC);
#pragma unroll 1
    for (int i = 0; i < 9; i++)
      tma2d(cx.sb + SM_XO + i * 2048, tmX16, i < 8 ? hs * 64 : 512, qb * 128 + (i < 8 ? i : hs) * 16, cx.sb + SM_BAR_MISC);
  }
#pragma unroll 1
  for (int n = 0; n < (1 << 16); n++) {
    __nanosleep(n ? 500 : 2000);
    uint32_t a, b, d, t;
    ld_gran(src - lane + (lane & 7) * (2 * 4 * 128) + 3 * 128 + 31, a, b, d, t);
    if (__all_sync(0xffffffffu, (a & TAG) == tag)) break;
  }
  TSH(46)
#pragma unroll 1
  for (int n = 0; n < (1 << 16); n++) {
#pragma unroll 1
    for (int i = 0; i < 8; i++) {
#pragma unroll
      for (int g = 0; g < 4; g++) cp16(stg + (i * 4 + g) * 512, src + i * (2 * 4 * 128) + g * 128);
    }
    cp_wait_all();
    uint32_t bad = 0;
#pragma unroll 4
    for (int i = 0; i < 32; i++) bad |= *(const volatile uint32_t*)(cx.sp + SM_P8 + lane * 16 + i * 512) ^ tag;
    if (__all_sync(0xffffffffu, (bad & TAG) == 0)) break;
  }
  TSH(47)
#pragma unroll 1
  for (int n = 0; n < (1 << 16) && ld_acquire(&cx.g->ycnt) != 4 * (e + 1); n++) __nanosleep(200);
  const int2 sel = __ldcg(at(cx.g->sel, (lane & 7) * 8));
  const int lr = sel.x - qb * 128;
  uint32_t m = __ballot_sync(0xffffffffu, lane < 16 && ((lane & 8) ? (lr >> 4) == hs : (lr >> 7) == 0));
  mbar_wait(cx.sb + SM_BAR_MISC, 0);
#pragma unroll 1
  for (; m; m &= m - 1) {
    const int i = __ffs(m) - 1, row = __shfl_sync(0xffffffffu, lr, i);
    const float rs = __int_as_float(__shfl_sync(0xffffffffu, sel.y, i));
    const float* p = cx.g->ypart + (i & 7) * DM + (i < 8 ? hs * 64 : 512) + 2 * lane;
    const float2 a = __ldcg((const float2*)p), b = __ldcg((const float2*)(p + TOPC * DM)), c = __ldcg((const float2*)(p + 2 * TOPC * DM)),
                 d = __ldcg((const float2*)(p + 3 * TOPC * DM));
    const uint32_t y = pack2((a.x + b.x) + (c.x + d.x), (a.y + b.y) + (c.y + d.y));
    const uint32_t u = pack2(bf_lo(y) * rs, bf_hi(y) * rs);
    const float2 st = *(const float2*)(cx.sp + SM_STATS + 8 * row);
    const int o = (i < 8 ? row : 128 + (row & 15)) * 128 + ((lane * 4) ^ ((row & 7) << 4));
    *(uint32_t*)(cx.sp + SM_GO + o) = gate2<true>(sub2(*(const uint32_t*)(cx.sp + SM_XO + o), pack2(st.x, st.x)), st.y, make_float2(bf_lo(u), bf_hi(u)));
  }
  __syncwarp();
  if (lane == 0) mbar_arrive(cx.sb + SM_BAR_XG);
  TSH(48)
}
__device__ __forceinline__ void attn_finish8(const Ctx& cx, int qb, int hs, int hw, int lane, __nv_bfloat16* out) {
  bar_sync(BAR_GATE, 96);
#pragma unroll 1
  for (int g = hw; g < 4; g += 3) {
    float acc[8] = {0.f, 0.f, 0.f, 0.f, 0.f, 0.f, 0.f, 0.f};
#pragma unroll 2
    for (int sidx = 0; sidx < 8; sidx++) {
      uint32_t a, b, d, t;
      lds128(cx.sb + SM_P8 + lane * 16 + (sidx * 4 + g) * 512, a, b, d, t);
      acc[0] += bf_lo(a); acc[1] += bf_hi(a & ~TAG); acc[2] += bf_lo(b); acc[3] += bf_hi(b);
      acc[4] += bf_lo(d); acc[5] += bf_hi(d); acc[6] += bf_lo(t); acc[7] += bf_hi(t);
    }
#pragma unroll
    for (int j = 0; j < 4; j++) {
      const int o = (128 + (lane >> 2) + (j & 1) * 8) * 128 + (((2 * g + (j >> 1)) ^ (lane >> 2)) << 4) + (lane & 3) * 4;
      uint32_t* xp = (uint32_t*)(cx.sp + SM_XO + o);
      *xp = fma2(pack2(acc[2 * j], acc[2 * j + 1]), *(const uint32_t*)(cx.sp + SM_GO + o), *xp);
    }
  }
  bar_sync(BAR_GATE, 96);
#pragma unroll 1
  for (int ch = threadIdx.x - 32; ch < 128; ch += 96)
    *(uint4*)at(out, ((qb * 128 + hs * 16 + (ch >> 3)) * DM + 512 + (ch & 7) * 8) * 2) =
        *(const uint4*)(cx.sp + SM_XO + 16384 + (ch ^ ((ch >> 3) & 7)) * 16);
}

__device__ __forceinline__ void ffn_producer(const Ctx& cx, int f, const CUtensorMap* tmWq, const CUtensorMap* tmG,
                                             const CUtensorMap* tmU, const CUtensorMap* tmD) {
  uint64_t keep;
  asm("createpolicy.fractional.L2::evict_normal.b64 %0, 1.0;" : "=l"(keep));
  int st = 0;
#pragma unroll 1
  for (int p = 0; p < 16; p++) {
#pragma unroll 1
    for (int i = 0; i < 5; i++, st++) if (st > 1) load_wq(cx, tmWq, st, i, ((2 * (p & 3) + cx.rank) * 4 + 3) * DH + 64, keep);
  }
  const uint32_t full = cx.sb + SM_FFULL, empty = cx.sb + SM_FEMPTY;
  int pair = 0, u = 0;
#pragma unroll 1
  for (st = 0; st < 14 * 12; st++) {
    const uint32_t sl = st & 7;
    const int unit = pair * 2 + (u & 1), k = u >> 1, k3 = k >= 3 ? k - 3 : k;
    if (unit < 27) {
      mbar_wait(empty + 8 * sl, (st >> 3) & 1);
      __syncwarp();
      if (elect_one()) {
        mbar_expect_tx(full + 8 * sl, FSTAGE);
        if (pair < 9) tma2d_stream(cx.sb + sl * FSTAGE, k < 3 ? tmG : tmU, f * 1152 + unit * 64, k3 * 192, full + 8 * sl);
        else tma2d_stream(cx.sb + sl * FSTAGE, tmD, (unit - 18) * 64, f * 1152 + k * 192, full + 8 * sl);
      }
    }
    if (++u == 12) { u = 0; pair++; }
  }
}
__device__ __forceinline__ void load_x1(uint32_t dst, const CUtensorMap* tmX64, int row, int box, int n, uint32_t bar) {
  mbar_expect_tx(bar, n * 8192);
#pragma unroll 1
  for (int i = 0; i < n; i++) tma2d(dst + i * 8192, tmX64, (box + i) * 64, row, bar);
}
__device__ __forceinline__ void ffn_publish(const Ctx& cx, int f, int w, int lane, const CUtensorMap* tmX64) {
  const uint32_t xs = cx.sb + SM_SLOT + w * 49152, xf = cx.sb + SM_XFULL + w * 32;
#pragma unroll 1
  for (int n = 0; n < 16; n++) {
    const int p = n & 3, row = (f + (n & 12) + 4) * 128 + w * 64;
    if (n < 12 && p == 3) {
      bar_sync(BAR_QS + w, 160);
      if (lane == 0) load_x1(xs, tmX64, row, 4, 4, xf + 8);
      __syncwarp();
    }
    bar_sync(BAR_QS + w, 160);
    const uint32_t e1 = *(const uint32_t*)(cx.sp + SM_TAG + 4) + 1;
    if (lane == 0) {
#pragma unroll
      for (int i = 0; i < 2; i++)
        asm volatile("cp.async.bulk.global.shared::cta.bulk_group [%0], [%1], 8192;"
                     ::"l"(cx.g->q + (((f + (n & 12)) * 8 + 2 * p + i) * 2 + w) * 512), "r"(xs + 32768 + i * 8192) : "memory");
      asm volatile("cp.async.bulk.commit_group;" ::: "memory");
      asm volatile("cp.async.bulk.wait_group.read 0;" ::: "memory");
      if (n < 12 && (p == 0 || p == 3)) load_x1(xs + (p ? 32768 : 0), tmX64, row, p ? 8 : 0, p ? 1 : 4, xf + (p ? 16 : 0));
      asm volatile("cp.async.bulk.wait_group 0;\nfence.proxy.async.global;" ::: "memory");
      asm volatile("st.release.gpu.global.u32 [%0], %1;" ::"l"(&cx.g->qflag[((f + (n & 12)) * 4 + p) * 2 + w]), "r"(e1) : "memory");
    }
    __syncwarp();
    if (n < 12 && p == 1) {
#pragma unroll 1
      for (int i = 0, k = 0; i < 64 && k < (1 << 16); k++) {
        uint32_t m, r, z, t;
        ld_gran(cx.g->stats + row + i + lane, m, r, z, t);
        *(uint2*)(cx.sp + SM_STATS + 8 * (w * 64 + i + lane)) = make_uint2(m, r);
        if (__all_sync(0xffffffffu, t == e1)) i += 32;
      }
    }
    bar_arrive(BAR_QF + w, 160);
  }
}

__device__ __forceinline__ void ffn_consumer(const Ctx& cx, int f, int wg, int cw, int lane, const __nv_bfloat16* x) {
  const int r = lane >> 2, c = lane & 3, tid = cw * 32 + lane;
  const uint32_t full = cx.sb + SM_FFULL, empty = cx.sb + SM_FEMPTY;
  const bool signaller = (tid & 127) == 0;
  prof(wg, 8);
  const unsigned e = *(const uint32_t*)(cx.sp + SM_TAG + 4);
  uint32_t key[8];
#pragma unroll 1
  for (int n = 0; n < (1 << 16); n++) {
    uint32_t bad = 0;
#pragma unroll
    for (int i = 0; i < 8; i++) {
      uint32_t t;
      asm volatile("ld.relaxed.gpu.global.v2.b32 {%0, %1}, [%2];" : "=r"(key[i]), "=r"(t) : "l"(&cx.g->stats[i * 256 + tid].z) : "memory");
      bad |= t ^ (e + 1);
    }
    if (__all_sync(0xffffffffu, bad == 0)) break;
  }
  bar_sync(BAR_QF + wg, 160);
  bar_sync(3, 256);
  if (tid < 8) mbar_arrive(empty + 8 * tid);
  prof(wg, 9);
  int mysel = 0;
#pragma unroll 1
  for (int k = 0; k < TOPC; k++) {
    uint32_t m = key[0];
#pragma unroll
    for (int i = 1; i < 8; i++) m = max(m, key[i]);
    m = __reduce_max_sync(0xffffffffu, m);
    uint32_t* tk = (uint32_t*)(cx.sp + SM_TOPK) + (k & 1) * 8;
    if (lane == 0) tk[cw] = m;
    bar_sync(3, 256);
    m = __reduce_max_sync(0xffffffffu, tk[lane & 7]);
#pragma unroll
    for (int i = 0; i < 8; i++) if (key[i] == m) key[i] = 0;
    if (k == cw) mysel = 0xFFFF - (int)(m & 0xFFFF);
  }
  {
    const float4 st = __ldcg((const float4*)&cx.g->stats[mysel]);
    const uint32_t mm = pack2(st.x, st.x);
#pragma unroll 3
    for (int i = 0; i < 9; i++) {
      const uint32_t t = sub2(*(const uint32_t*)(x + (size_t)mysel * DM + i * 64 + 2 * lane), mm);
      *(uint32_t*)(cx.sp + SM_XSEL + i * 1024 + cw * 128 + (((lane >> 2) ^ cw) << 4) + (lane & 3) * 4) =
          pack2(bf_lo(t) * st.y, bf_hi(t) * st.y);
    }
    const uint32_t k = __float_as_uint(st.z);
    const float score = bf_hi(k ^ ((int)k < 0 ? 0x80000000u : 0xFFFF0000u));
    if (lane == 0 && f == 0) cx.g->sel[cw] = make_int2(mysel, __float_as_int(bfr(rcp(1.0f + ex2(-1.4426950408889634f * score)))));
  }
  asm volatile("fence.proxy.async.shared::cta;" ::: "memory");
  bar_sync(3, 256);
  prof(wg, 10);
  auto run = [&](float (&acc)[4], int st, int n, uint32_t b) {
#pragma unroll 1
    for (int u = 0; u < n; u++, st += 2, b += 3072) {
      const uint32_t sl = st & 7;
      mbar_wait(full + 8 * sl, (st >> 3) & 1);
      wg_fence();
      const uint64_t da = mkdesc(cx.sb + sl * FSTAGE, 16), db = mkdesc(b, 16);
#pragma unroll
      for (int k = 0; k < 12; k++) mma_n8(acc, da + k * 128, db + (k >> 2) * 64 + (k & 3) * 2, u > 0 || k > 0);
      wg_commit();
      wg_wait<0>();
      if (signaller) mbar_arrive(empty + 8 * sl);
    }
    pin(acc);
  };
#pragma unroll 1
  for (int unit = wg; unit < 27; unit += 2) {
    if (unit >> 1 == 9) {
      asm volatile("fence.proxy.async.shared::cta;" ::: "memory");
      bar_sync(3, 256);
      prof(wg, 11);
    }
    const bool gu = unit < 18;
    float a0[4], a1[4];
#pragma unroll 1
    for (int m = 0; m < (gu ? 2 : 1); m++) {
      run(a1, (unit >> 1) * 12 + m * 6 + wg, gu ? 3 : 6, cx.sb + (gu ? SM_XSEL : SM_H));
      if (m == 0) { a0[0] = a1[0]; a0[1] = a1[1]; a0[2] = a1[2]; a0[3] = a1[3]; }
    }
    float u0 = a1[0], u1 = a1[1];
#pragma unroll 1
    for (int i = 0; i < 2; i++) {
      const int fl = (cw & 3) * 16 + r + i * 8;
      if (gu) {
        const uint32_t g = pack2(a0[0], a0[1]);
        const uint32_t h = fma2(pack2(silu_f(bf_lo(g)), silu_f(bf_hi(g))), pack2(u0, u1), 0x80008000u);
        uint8_t* hp = cx.sp + SM_H + unit * 1024 + c * 256 + (fl & 7) * 2;
        *(uint16_t*)(hp + (((fl >> 3) ^ (2 * c)) << 4)) = (uint16_t)h;
        *(uint16_t*)(hp + 128 + (((fl >> 3) ^ (2 * c + 1)) << 4)) = (uint16_t)(h >> 16);
      } else {
        float* yp = cx.g->ypart + (f * TOPC + 2 * c) * DM + (unit - 18) * 64 + fl;
        yp[0] = u0;
        yp[DM] = u1;
      }
      a0[0] = a0[2]; a0[1] = a0[3]; u0 = a1[2]; u1 = a1[3];
    }
  }
  prof(wg, 12);
  bar_sync(3, 256);
  if (tid == 0) atom_add_acq_rel(&cx.g->ycnt);
  prof(wg, 13);
}

constexpr float SUM_HI = 1.8446744e19f, SUM_LO = 9.0949470e-13f;

template <int LO, int HI, int N>
__device__ __forceinline__ void softmax_exp(float (&s)[N]) {
#pragma unroll
  for (int i = LO; i < HI; i++) s[i] = ex2(s[i]);
}
__device__ __forceinline__ void sum_tree(const uint32_t (&pf)[28], bool big, uint32_t& h0, uint32_t& h1) {
  uint32_t t0 = add2(add2(pf[16], pf[18]), add2(pf[20], pf[22])), t1 = add2(add2(pf[17], pf[19]), add2(pf[21], pf[23]));
  if (big) { t0 = add2(t0, add2(pf[24], pf[26])); t1 = add2(t1, add2(pf[25], pf[27])); }
  h0 = add2(add2(add2(add2(pf[0], pf[2]), add2(pf[4], pf[6])), add2(add2(pf[8], pf[10]), add2(pf[12], pf[14]))), t0);
  h1 = add2(add2(add2(add2(pf[1], pf[3]), add2(pf[5], pf[7])), add2(add2(pf[9], pf[11]), add2(pf[13], pf[15]))), t1);
}
__device__ __forceinline__ void exact_attention(float (&o)[16], float& l0, float& l1, const uint32_t (&q)[32], const __nv_bfloat16* kp,
                                                const __nv_bfloat16* vp) {
  float m0 = -3.0e38f, m1 = -3.0e38f;
  l0 = l1 = 0.f;
#pragma unroll
  for (int i = 0; i < 16; i++) o[i] = 0.f;
#pragma unroll 1
  for (int key = 0; key < SEQ; key += 8, kp += 8 * DH, vp += 8 * DH) {
    float d[4] = {0.f, 0.f, 0.f, 0.f};
#pragma unroll
    for (int k = 0; k < 8; k++)
      hmma_k16(d, q[4 * k], q[4 * k + 1], q[4 * k + 2], q[4 * k + 3], *(const uint32_t*)(kp + k * 16), *(const uint32_t*)(kp + k * 16 + 8));
    float x0 = fmaxf(d[0], d[1]), x1 = fmaxf(d[2], d[3]);
    x0 = fmaxf(x0, __shfl_xor_sync(0xffffffffu, x0, 1));
    x1 = fmaxf(x1, __shfl_xor_sync(0xffffffffu, x1, 1));
    x0 = fmaxf(fmaxf(x0, __shfl_xor_sync(0xffffffffu, x0, 2)), m0);
    x1 = fmaxf(fmaxf(x1, __shfl_xor_sync(0xffffffffu, x1, 2)), m1);
    const float sc0 = ex2(m0 - x0), sc1 = ex2(m1 - x1);
    m0 = x0; m1 = x1;
    const uint32_t p0 = pack2(ex2(d[0] - m0), ex2(d[1] - m0)), p1 = pack2(ex2(d[2] - m1), ex2(d[3] - m1));
    l0 = fmaf(l0, sc0, bf_lo(p0) + bf_hi(p0));
    l1 = fmaf(l1, sc1, bf_lo(p1) + bf_hi(p1));
#pragma unroll
    for (int nb = 0; nb < 4; nb++) {
      uint32_t b;
      asm("movmatrix.sync.aligned.m8n8.trans.b16 %0, %1;" : "=r"(b) : "r"(*(const uint32_t*)(vp + nb * 8)));
      o[4 * nb] *= sc0; o[4 * nb + 1] *= sc0; o[4 * nb + 2] *= sc1; o[4 * nb + 3] *= sc1;
      asm volatile("mma.sync.aligned.m16n8k8.row.col.f32.bf16.bf16.f32 {%0, %1, %2, %3}, {%4, %5}, {%6}, {%0, %1, %2, %3};"
                   : "+f"(o[4 * nb]), "+f"(o[4 * nb + 1]), "+f"(o[4 * nb + 2]), "+f"(o[4 * nb + 3]) : "r"(p0), "r"(p1), "r"(b));
    }
  }
}
__device__ __forceinline__ bool inv_sums(float l0, float l1, float& i0, float& i1) {
  l0 += __shfl_xor_sync(0xffffffffu, l0, 1); l1 += __shfl_xor_sync(0xffffffffu, l1, 1);
  l0 += __shfl_xor_sync(0xffffffffu, l0, 2); l1 += __shfl_xor_sync(0xffffffffu, l1, 2);
  i0 = rcp(l0);
  i1 = rcp(l1);
  return !(l0 + l1 <= SUM_HI) | (fminf(l0, l1) < SUM_LO);
}
template <int LO, int HI, int N>
__device__ __forceinline__ void park(uint32_t a, const float (&o)[N], float i0, float i1, bool on = true) {
#pragma unroll
  for (int i = LO; i < HI; i++)
    asm volatile("{\n.reg .pred p;\nsetp.ne.u32 p, %5, 0;\n@p stmatrix.sync.aligned.m8n8.x4.shared.b16 [%0], {%1, %2, %3, %4};\n}"
                 ::"r"(a + i * 2048), "r"(pack2(o[8 * i] * i0, o[8 * i + 1] * i0)), "r"(pack2(o[8 * i + 2] * i1, o[8 * i + 3] * i1)),
                 "r"(pack2(o[8 * i + 4] * i0, o[8 * i + 5] * i0)), "r"(pack2(o[8 * i + 6] * i1, o[8 * i + 7] * i1)), "r"((uint32_t)on) : "memory");
}

template <int I, int HI, int G, int N>
__device__ __forceinline__ void park_paced(uint32_t a, const float (&o)[N], float i0, float i1, int id) {
  if constexpr (I < HI) {
    park<I, I + G>(a, o, i0, i1);
    if (I + G < HI) block_fence(id + I);
    park_paced<I + G, HI, G>(a, o, i0, i1, id);
  }
}
template <int I, int NP, int E0, int N, int NS>
__device__ __forceinline__ void exp_park(float (&s)[NS], uint32_t a, const float (&o)[64], float i0, float i1, bool on, int id) {
  if constexpr (I < NP) {
    constexpr int E1 = E0 + (N - E0) * X_PG / (NP - I);
    softmax_exp<E0, E1>(s);
    park<I, I + X_PG>(a, o, i0, i1, on);
    if (I + X_PG < NP) {
#pragma unroll
      for (int i = E0; i < E1; i++) asm volatile("" : "+f"(s[i])::"memory");
      block_fence(id + I);
    }
    exp_park<I + X_PG, NP, E1, N>(s, a, o, i0, i1, on, id);
  }
}

__device__ __forceinline__ void attn_consumer(const Ctx& cx, bool hlp, int qb, int hs, int wg, int cw, int lane, const __nv_bfloat16* x,
                                              const __nv_bfloat16* kc, const __nv_bfloat16* vc, __nv_bfloat16* out) {
  const uint32_t full = cx.sb + SM_FULL;
  const uint32_t ring = cx.sb + SM_RING;
  const uint32_t qwg = ring + wg * 16384;
  auto qlane = [&](int l) { return qwg + (cw & 3) * 256 + (l >> 4) * 1024 + (l & 15) * 16; };
  const bool signaller = lane == 0 && (cw & 3) < 2;
  const int my_turn = 1 + wg, other_turn = 2 - wg;
  const uint32_t empty_c = mapa(cx.sb + SM_EMPTY, cw & 1);

  float oA[64], oB[64], i0, i1;
  uint32_t xl[32];
  {
    const int r = lane >> 2, c = lane & 3;
    const int lr0 = cw * 16 + r;
    uint32_t xa[144];
    uint32_t mm0, mm1;
    float rstd0, rstd1, sq0 = 0.f, sq1 = 0.f;
    const uint32_t xf = cx.sb + SM_XFULL + wg * 32, xs = cx.sb + SM_SLOT + wg * 49152;
    auto lo_of = [&](int l) { return ((cw & 3) * 16 + (l & 15)) * 128 + (((l >> 4) ^ (l & 7)) << 4); };
    prof(wg, 0);
    {
      const uint32_t lo = lo_of(lane);
      const uint32_t xb = cx.sb + SM_X + wg * 73728;
      float sm[X_NS][4] = {};
      const uint32_t ws = (lane & 7) == 1 ? 64 : 0;
      uint32_t wb = cx.sb + (ws ? SM_WR + (lane >> 3) * 16 : SM_ONES);
      uint32_t b0[24], b1[24], b2[24];
      mbar_wait(cx.sb + SM_BAR_W, 0);
      TS4(1)
      ln_fetch_b(b0, wb, ws);
      ln_fetch_b(b1, wb, ws);
      ln_fetch_b(b2, wb, ws);
      mbar_wait(xf, 0);
      TS4(2)
      ln_fetch<0, 12>(xa, xb, lo);
      mbar_wait(xf + 8, 0);
      TS4(3)
      ln_fetch<12, 24>(xa, xb, lo);
      ln_sums<0, 12>(xa, sm, b0);
      if (wg == 0) bar_arrive(BAR_XREL + after_fetch<12, 24>(xa), 224);
      mbar_wait(xf + 16, 0);
      TS4(4)
      prof(wg, 1);
      ln_fetch<24, 36>(xa, xb, lo);
      ln_sums<12, 24>(xa, sm, b1);
      ln_sums<24, 36>(xa, sm, b2);
#pragma unroll
      for (int i = 0; i < 4; i++) sm[0][i] = X_NS == 2 ? sm[0][i] + sm[1][i] : X_NS == 3 ? sm[0][i] + sm[1][i] + sm[2][i] : (sm[0][i] + sm[1][i]) + (sm[2][i] + sm[X_NS - 1][i]);
      if (cw == hs && c == 0) {
        *(float*)(cx.sp + SM_RAW + 4 * r) = sm[0][1];
        *(float*)(cx.sp + SM_RAW + 4 * r + 32) = sm[0][3];
      }
      rstd0 = sm[0][0];
      rstd1 = sm[0][2];
      mm0 = pack2(rstd0 * (1.0f / DM), rstd0 * (1.0f / DM));
      mm1 = pack2(rstd1 * (1.0f / DM), rstd1 * (1.0f / DM));
    }
#pragma unroll
    for (int i = 0; i < 16; i++) { xa[2 * i] = sub2(xa[2 * i], mm0); xa[2 * i + 1] = sub2(xa[2 * i + 1], mm1); }
    pin(xa);
    prof(wg, 2);
    TS4(5)

    float (&acc)[64] = oB;
    int st0 = 0;
#pragma unroll 1
    for (int n = 0; n < 16; n++) {
      const int p = n & 3, rb = n >> 2;
      const bool last = p == 3 && !hlp;
#pragma unroll
      for (int i = 0; i < 5; i++) {
        if (i == 4 && last) {
          wg_wait<1>();
          mbar_arrive_cluster(empty_c + 8 * 3, signaller && wg);
          wg_wait<0>();
          pin(acc);
          prof(wg, 6);
#pragma unroll
          for (int j = 0; j < 32; j++) xl[j] = xa[112 + j];
          i0 = rstd0;
          i1 = rstd1;
          goto attention;
        }
        const int st = st0 + i;
        const uint32_t sl = st & 3, slp = (st - 1) & 3;
        if (!wg) mbar_wait(full + 8 * sl, (st >> 2) & 1);
        TS4(8 + 2 * (p * 5 + i))
        const bool join = wg && last;
        if ((i || st0 + wg) && i != (wg ? 4 : 1) && !(join && i == 3)) bar_sync(my_turn, 256);
        wg_fence();
        const uint64_t db = mkdesc(ring + sl * STAGE, 16384);
        const int kb0 = i < 3 ? 8 * i : 8 * i - 4;
#pragma unroll
        for (int k = 0; k < (i == 2 ? 4 : 8); k++) {
          const int kb = kb0 + k;
          mma_n128t(acc, xa[4 * kb], xa[4 * kb + 1], xa[4 * kb + 2], xa[4 * kb + 3], db + k * 128, kb > 0);
        }
        wg_commit();
        TS4(9 + 2 * (p * 5 + i))
        if (wg ? (i == 4 ? st0 < 75 : (i < 2 || i == (join ? 3 : 2))) : i) bar_arrive(other_turn, 256);
        if (p == 0 && i < 4) {
          if (i == 1 && rb) {
            mbar_wait(xf + 8, rb & 1);
            ln_fetch<16, 32>(xa, xs - 32768, lo_of(fresh_lane()));
          }
          if (i == 2 && rb) {
            mbar_wait(xf + 16, rb & 1);
            ln_fetch<32, 36>(xa, xs - 32768, lo_of(fresh_lane()));
          }
#pragma unroll
          for (int j = 0; j < 72; j++)
            if (j >= 2 * (i < 2 ? 8 * i + 8 : 8 * i + 4) && j < 2 * (i == 0 ? 16 : 8 * i + 12)) {
              xa[2 * j] = sub2(xa[2 * j], mm0);
              xa[2 * j + 1] = sub2(xa[2 * j + 1], mm1);
            }
          pin(xa);
        }
        if (i == X_SQI && n == 0) {
          mbar_wait(cx.sb + SM_BAR_SQ, 0);
          float2* sp = (float2*)(cx.sp + SM_STATS) + lr0;
          float mean0, mean1;
          ln_row(rstd0, sp[0].y, mean0, rstd0);
          ln_row(rstd1, sp[8].y, mean1, rstd1);
          __syncwarp();
          if (c == 0) {
            sp[0] = make_float2(mean0, rstd0);
            sp[8] = make_float2(mean1, rstd1);
          }
          *((uint32_t*)(cx.sp + SM_COLD) + wg) = 0;
          if (!hlp) bar_arrive(BAR_GATE, 352);
          rstd0 *= SM_SCALE_LOG2;
          rstd1 *= SM_SCALE_LOG2;
        }
        if (i == 3 && hlp && p == 3 && rb < 3) bar_arrive(BAR_QS + wg + after_fetch<0, 16>(xa), 160);
        if (i == 4 && p == 3 && rb < 3) {
          const float2* sp = (const float2*)(cx.sp + SM_STATS) + cw * 16 + (fresh_lane() >> 2);
          mm0 = pack2(sp[0].x, sp[0].x);
          mm1 = pack2(sp[8].x, sp[8].x);
          sq0 = sp[0].y * SM_SCALE_LOG2;
          sq1 = sp[8].y * SM_SCALE_LOG2;
#pragma unroll
          for (int j = 0; j < 16; j++) { xa[2 * j] = sub2(xa[2 * j], mm0); xa[2 * j + 1] = sub2(xa[2 * j + 1], mm1); }
          pin(xa);
        }
        if (i == 0) {
          if (wg) {
            wg_wait<0>();
            mbar_arrive_cluster(empty_c + 8 * sl, signaller);
          }
        } else if (i == 2) {
          if (!join) {
            wg_wait<0>();
            mbar_arrive_cluster(empty_c + 8 * sl, signaller);
          }
          if (hlp && p == 3 && rb < 3) {
            mbar_wait(xf, ~rb & 1);
            ln_fetch<0, 16>(xa, xs, lo_of(fresh_lane()));
            pin(xa);
          }
        } else if (i != 3) {
          wg_wait<1>();
          mbar_arrive_cluster(empty_c + 8 * slp, signaller && (i == 4 || !wg));
          wg_wait<0>();
          mbar_arrive_cluster(empty_c + 8 * sl, signaller);
        }
      }
      pin(acc);
      prof(wg, 3 + p);
      TS4(50 + 2 * p)
      st0 += 5;
      if (hlp && st0 > 5) bar_sync(BAR_QF + wg, 160);
      park_paced<0, 8, X_QP>(qlane(lane) + (hlp ? 5 + wg : 4 + p) * STAGE, acc, rstd0, rstd1, 300);
      if (p || hlp) asm volatile("fence.proxy.async.shared::cta;" ::: "memory");
      if (hlp) bar_arrive(BAR_QS + wg, 160);
      if (p == 3) { rstd0 = sq0; rstd1 = sq1; }
      TS4(51 + 2 * p)
      if (p == 1 && !hlp) {
        float (&ah)[32] = *(float (*)[32])&acc[0];
#pragma unroll
        for (int i = 0; i < 3; i++) {
          const uint32_t sl = (10 + i) & 3;
          if (!wg) mbar_wait(full + 8 * sl, ((10 + i) >> 2) & 1);
          TS4(28 + 2 * i)
          if (i == 0 || i == 2 - wg) bar_sync(my_turn, 256);
          wg_fence();
          const uint64_t db = mkdesc(ring + sl * STAGE, 16);
#pragma unroll
          for (int k = 0; k < 12; k++) {
            const int kb = 12 * i + k;
            if (kb) mma_n64t(ah, xa[4 * kb], xa[4 * kb + 1], xa[4 * kb + 2], xa[4 * kb + 3], db + k * 128, true);
            else mma_n64t_dyn(ah, xa[0], xa[1], xa[2], xa[3], db, blockIdx.y);
          }
          wg_commit();
          TS4(29 + 2 * i)
          if (i == 2 || i != wg) {
            bar_arrive(other_turn, 256);
            if (i) {
              wg_wait<1>();
              mbar_arrive_cluster(empty_c + 8 * ((9 + i) & 3), signaller && i == wg + 1);
            }
            wg_wait<0>();
            mbar_arrive_cluster(empty_c + 8 * sl, signaller);
          }
        }
        pin(ah);
        TS4(54)
        park<0, 4>(qlane(lane) + 6 * STAGE, ah, rstd0, rstd1);
        TS4(55)
        st0 = 13;
        n = 2;
      }
    }
    TS_DUMP()
    ffn_consumer(cx, blockIdx.x & 3, wg, cw, fresh_lane(), x);
    return;
  }

attention:
  uint32_t oa[128];
  float acc[32];
  {
    uint32_t pf[28];
    const uint32_t ql = qlane(fresh_lane());
    uint32_t bad = 0;
    float lA0 = 0.f, lA1 = 0.f, lB0 = 0.f, lB1 = 0.f;
    int t = 0;
    uint32_t ra = 2 * 2048, rb = 2048, rc = 2 * 2048, par = 0;
    const uint64_t dk0 = mkdesc(ring, 16), dv0 = mkdesc(ring, 16384);
    uint64_t dqA = mkdesc_q(qwg + 4 * STAGE), dqB = dqA + 2048;
    auto turn = [&](auto kc_, auto bc_) {
      constexpr int KIND = decltype(kc_)::value, BIG = decltype(bc_)::value;
      constexpr int HB = KIND == 1, ID = 10 * KIND + 30 * BIG, T0 = BIG ? 38 : 0;
      constexpr int NS = BIG ? 56 : 48, SPLIT = BIG ? (HB ? X_SPLIT : X_SPLITA) : (HB ? X_SPLITS : X_SPLITSA);
      float s[NS];
      float (&op)[64] = HB ? oA : oB;
      uint32_t h0 = 0, h1 = 0;
      TS2(0)
      bar_sync(my_turn, 256);
      TS2(1)
      if (KIND) { pin(pf); pin(op); }
      mma_qk(s, HB ? dqB : dqA, dk0 + (HB ? ra : rc));
      TS2(2)
      if (KIND) {
        const bool bigp = HB ? BIG : BIG ? t != 10 : t == 66;
        if (X_BF2) block_fence(ID + 9);
        pin(pf);
        sum_tree(pf, bigp, h0, h1);
        asm volatile("" : "+r"(h0), "+r"(h1)::"memory");
        if (HB) mbar_wait(full + (rb >> 8), par);
        mma_pv(op, pf, dv0 + rb, t != T0 + 2 - HB, bigp);
      } else {
        mbar_wait(full + (rb >> 8), (NST_Q - 1) >> 2 & 1);
#pragma unroll
        for (int k = 0; k < 8; k++) mma_n128t(op, xl[4 * k], xl[4 * k + 1], xl[4 * k + 2], xl[4 * k + 3], dv0 + rb + k * 128, 1);
        wg_commit();
      }
      TS2(3)
      bar_arrive(other_turn, 256);
      (HB ? lA0 : lB0) += bf_lo(h0) + bf_hi(h0);
      (HB ? lA1 : lB1) += bf_lo(h1) + bf_hi(h1);
      wg_wait<1>();
      pin(s);
      TS1(t)
      TS2(4)
      if (KIND == 1) mbar_arrive_cluster_now<ID + 3>(empty_c + (ra >> 8), signaller);
      if (BIG && t == T0 + HB) {
        const uint32_t a = ql + (4 + HB) * STAGE;
        const bool ok = !__any_sync(0xffffffffu, inv_sums(HB ? lB0 : lA0, HB ? lB1 : lA1, i0, i1));
        if (!ok) bad |= 1 << HB;
        (HB ? lB0 : lA0) = 0.f;
        (HB ? lB1 : lA1) = 0.f;
        softmax_exp<0, X_E0>(s);
#pragma unroll
        for (int i = 0; i < X_E0; i++) asm volatile("" : "+f"(s[i])::"memory");
        block_fence(ID + 7);
        exp_park<0, X_PA, X_E0, SPLIT>(s, a, HB ? oB : oA, i0, i1, ok, 200 + ID);
        if (!HB) dqB += 2048;
        prof(wg, 8 + HB);
      } else {
        softmax_exp<0, SPLIT>(s);
      }
      pin(s);
      if (!BIG) block_fence(ID + 4);
      TS2(5)
      wg_wait<0>();
      TS2(6)
      pin(op);
      if (KIND) pin(pf); else pin(xl);
      if (HB) {
        par ^= rc == 2048;
        if (BIG && t == 37) dqA -= 4 * 2048;
        if (BIG && t == X_WAKE && cw == 0) bar_arrive(BAR_HELPER, 64);
      } else {
        mbar_arrive_cluster_now<ID + 5>(empty_c + (rb >> 8), signaller);
        if (KIND) {
          par ^= ra == 2048;
          const uint32_t x = ra;
          ra = rc; rc = rb; rb = x;
        }
      }
      softmax_exp<SPLIT, NS>(s);
#pragma unroll
      for (int i = 0; i < NS / 2; i++) pf[i] = pack2(s[2 * i], s[2 * i + 1]);
      pin(pf);
      if (KIND == 0) {
        block_fence(ID + 6);
        park_paced<0, X_Q1, X_QC>(ql, oB, i0, i1, 310);

        prof(wg, 7);
      }
      if (X_Q1 < 8 && HB && !BIG && t == 1) park_paced<X_Q1, 8, X_QC>(ql, oB, i0, i1, 320);
      if (BIG && t == T0 + HB) {
        if (X_PA < 8) park<X_PA, 8>(ql + (4 + HB) * STAGE, HB ? oB : oA, i0, i1, !(bad >> HB));
        if (!HB) mbar_wait(cx.sb + SM_BAR_Q + 8 * wg, 0);
      }
      if (HB) mbar_wait(full + (rc >> 8), par);
      t++;
    };
#pragma unroll
    for (int i = 24; i < 28; i++) asm volatile("" : "=r"(pf[i]));
    mbar_wait(full + 8 * 2, 0);
    turn(IC<0>(), IC<0>());
    rb = 3 * 2048; rc = 2048;
    kill(oA);
    const bool never = blockIdx.y == 1;
#pragma unroll 1
    while (true) {
      turn(IC<1>(), IC<0>());
      if (t == 76) break;
      if (t == 10) {
        asm volatile("fence.proxy.async.shared::cta;" ::: "memory");
#pragma unroll 1
        do {
#pragma unroll 1
          do turn(IC<2>(), IC<1>()); while (never);
          turn(IC<1>(), IC<1>());
        } while (t != 66);
      }
#pragma unroll 1
      do turn(IC<2>(), IC<0>()); while (never);
    }
    auto scale = [&](auto lo, auto hi) {
#pragma unroll
      for (int i = decltype(lo)::value; i < decltype(hi)::value; i++) {
        oa[32 + 2 * i] = pack2(oA[4 * i] * i0, oA[4 * i + 1] * i0);
        oa[32 + 2 * i + 1] = pack2(oA[4 * i + 2] * i1, oA[4 * i + 3] * i1);
        asm volatile("" : "+r"(oa[32 + 2 * i]), "+r"(oa[32 + 2 * i + 1])::"memory");
      }
    };
    TS3(1)
    volatile uint32_t* const cold = (volatile uint32_t*)(cx.sp + SM_COLD) + wg;
    if (inv_sums(lA0, lA1, i0, i1)) bad |= 4;
#pragma unroll
    for (int i = 0; i < 8; i++) ldsm4(ql + 4 * STAGE + i * 2048, oa[4 * i], oa[4 * i + 1], oa[4 * i + 2], oa[4 * i + 3]);
    {
      uint32_t h0, h1;
      sum_tree(pf, false, h0, h1);
      lB0 += bf_lo(h0) + bf_hi(h0);
      lB1 += bf_lo(h1) + bf_hi(h1);
      asm volatile("" : "+f"(lB0), "+f"(lB1)::"memory");
    }
    scale(IC<0>(), IC<X_F1>());
    if (bad) *cold = 1;
    block_fence(93);
    TS3(2)
    bar_sync(my_turn, 256);
    TS3(3)
    pin(pf); pin(oB);
    mma_pv(oB, pf, dv0 + 2 * 2048, true, false);
    block_fence(91);
    TS3(4)
    const uint32_t held = *cold;
    if (inv_sums(lB0, lB1, lB0, lB1)) bad |= 8;
    const uint64_t db = mkdesc(ring + 3 * STAGE, 16);
    scale(IC<X_F1>(), IC<X_F2>());
    mbar_arrive_cluster_now<94>(empty_c, signaller && !held);
#pragma unroll
    for (int i = 0; i < 32; i++) asm volatile("" : "+r"(oa[i])::"memory");
    wg_fence();
#pragma unroll
    for (int k = 0; k < 8; k++) mma_n64t(acc, oa[4 * k], oa[4 * k + 1], oa[4 * k + 2], oa[4 * k + 3], db + k * 128, k > 0);
    if (X_F2 < 16) {
      wg_commit();
      block_fence(95);
      scale(IC<X_F2>(), IC<16>());
      TS3(5)
      wg_fence();
    }
#pragma unroll
    for (int k = 8; k < 16; k++) mma_n64t(acc, oa[4 * k], oa[4 * k + 1], oa[4 * k + 2], oa[4 * k + 3], db + k * 128, 1);
    wg_commit();
    bar_arrive(other_turn, 256);
    if (bad) *cold = 1;
    bar_sync(4 + wg, 128);
    const uint32_t is_cold = *cold;
    wg_wait<(X_F2 < 16 ? 2 : 1)>();
    pin(oB); pin(pf);
    TS(76)
    TS3(6)
    mbar_arrive_cluster_now<97>(empty_c + 8 * 2, signaller);
#pragma unroll
    for (int i = 16; i < 24; i++) ldsm4(ql + 5 * STAGE + (i & 7) * 2048, oa[4 * i], oa[4 * i + 1], oa[4 * i + 2], oa[4 * i + 3]);
#pragma unroll
    for (int i = 0; i < 16; i++) {
      oa[96 + 2 * i] = pack2(oB[4 * i] * lB0, oB[4 * i + 1] * lB0);
      oa[96 + 2 * i + 1] = pack2(oB[4 * i + 2] * lB1, oB[4 * i + 3] * lB1);
    }
    TS3(7)
    if (!wg) mbar_wait(full + 8 * 1, 0);
    TS3(8)
    wg_wait<0>();
    pin(acc); pin(oa);
    if (__any_sync(0xffffffffu, is_cold)) {
      bad = __reduce_or_sync(0xffffffffu, bad);
      if (!(bad & 8)) {
#pragma unroll
        for (int i = 24; i < 32; i++) stsm4(ql + 6 * STAGE + (i & 7) * 2048, oa[4 * i], oa[4 * i + 1], oa[4 * i + 2], oa[4 * i + 3]);
      }
#pragma unroll 1
      for (int h = 0; h < 4; h++) {
        if (bad >> h & 1) {
          const uint32_t a = ql + ((0x6054 >> (4 * h)) & 7) * STAGE;
          const int l = fresh_lane(), o = (hs * 2 + (h >> 1)) * SEQ * DH + (l >> 2) * DH + (l & 3) * 2;
          uint32_t q[32];
#pragma unroll
          for (int i = 0; i < 8; i++) ldsm4(a + i * 2048, q[4 * i], q[4 * i + 1], q[4 * i + 2], q[4 * i + 3]);
#pragma unroll 1
          for (int i = 0; i < 4; i++) {
            float ox[16], l0, l1;
            exact_attention(ox, l0, l1, q, kc + o, vc + o + i * 32);
            inv_sums(l0, l1, l0, l1);
            park<0, 2>(a + i * 4096, ox, l0, l1);
          }
        }
      }
      __syncwarp();
#pragma unroll
      for (int i = 0; i < 32; i++)
        if ((i >> 3) != 1 || (bad & 4))
          ldsm4(ql + ((0x6504 >> (4 * (i >> 3))) & 7) * STAGE + (i & 7) * 2048, oa[4 * i], oa[4 * i + 1], oa[4 * i + 2], oa[4 * i + 3]);
      pin(oa);
      asm volatile("fence.proxy.async.shared::cta;" ::: "memory");
      bar_sync(4 + wg, 128);
      mbar_arrive_cluster(empty_c, signaller && held);
      wg_fence();
#pragma unroll
      for (int k = 0; k < 16; k++) mma_n64t(acc, oa[4 * k], oa[4 * k + 1], oa[4 * k + 2], oa[4 * k + 3], db + k * 128, k > 0);
      wg_commit();
      wg_wait<0>();
      pin(acc);
    }
    mbar_arrive_cluster(empty_c + 8 * 3, signaller);
  }

  prof(wg, 10);
  TS3(9)
  {
    lane = fresh_lane();
    const int tw = (cw & 3) * 32 + lane;
    float red[32];
    kill(red);
    const uint32_t tag = *(const uint32_t*)(cx.sp + SM_TAG);
    uint4* const xch = at(cx.g->part, ((qb * 64 * 2 + wg) * 4 * 128 + tw) * 16);
    int nrx = 1;
    auto region = [](int s, int h) { return h ? 1 + (s & 1) : (s & 1) ? 0 : 3; };
    auto half_step = [&](int s, auto hc, bool arrive) {
      constexpr int h = decltype(hc)::value;
      const uint64_t db = mkdesc(ring + region(s, h) * STAGE, 16);
      bar_sync(my_turn, 256);
      pin(oa);
      wg_fence();
#pragma unroll
      for (int k = 0; k < 16; k++) {
        const int kb = h * 16 + k;
        mma_n64t(acc, oa[4 * kb], oa[4 * kb + 1], oa[4 * kb + 2], oa[4 * kb + 3], db + k * 128, kb > 0);
      }
      wg_commit();
      if (arrive) bar_arrive(other_turn, 256);
    };
    auto await = [&](int s, int h) { mbar_wait(full + 8 * region(s, h), ((s >> 1) ^ h ^ 1) & 1); };
    auto fetch = [&](uint32_t (&g)[16], int n) {
      const uint4* p = at(xch, (hs * 7 + n - 1) * 16384);
#pragma unroll
      for (int i = 0; i < 4; i++) ld_gran(p + i * 128, g[4 * i], g[4 * i + 1], g[4 * i + 2], g[4 * i + 3]);
    };
    uint32_t g[16];
    bool pend = false;
#pragma unroll 1
    for (int s = 0;; s++) {
      half_step(s, IC<1>(), s + wg < 9);
      if (s == 8) break;
      TS3(s < 3 ? 16 + 8 * s : 75)
      if (s == 0) {
        bar_arrive(BAR_OA, 352);
#pragma unroll
        for (int i = 0; i < 32; i++) red[i] = 0.f;
      }
      await(s + 1, 0);
      TS3(s < 3 ? 17 + 8 * s : 75)
      wg_wait<0>();
      TS3(s < 3 ? 18 + 8 * s : 75)
      mbar_arrive_cluster(empty_c + 8 * region(s, 1), signaller && s < 7);
      pin(acc);
      TS(77 + s)
      prof(wg, 12 + s);
      uint4* p = at(xch, (s == 0 ? 56 + hs : ((hs + s) & 7) * 7 + s - 1) * 16384);
#pragma unroll
      for (int i = 0; i < 4; i++)
        st_gran(p + i * 128, (pack2(acc[8 * i], acc[8 * i + 1]) & ~TAG) | tag, pack2(acc[8 * i + 2], acc[8 * i + 3]),
                pack2(acc[8 * i + 4], acc[8 * i + 5]), pack2(acc[8 * i + 6], acc[8 * i + 7]));
      TS3(s < 3 ? 19 + 8 * s : 75)
      half_step(s + 1, IC<0>(), true);
      TS3(s < 3 ? 20 + 8 * s : 75)
      if (pend && granules_ok(g, tag)) { add_granules(red, g); nrx++; }
      pend = nrx < s;
      if (pend) fetch(g, nrx);
      await(s + 1, 1);
      TS3(s < 3 ? 21 + 8 * s : 75)
      wg_wait<0>();
      TS3(s < 3 ? 22 + 8 * s : 75)
      mbar_arrive_cluster(empty_c + 8 * region(s + 1, 0), signaller && s < 6);
    }
    uint32_t xv[16], gt[16], g2[16];
    TS3(42)
    const bool ok = granules_ok(g, tag);
    TS3(43)
    nrx += ok;
    fetch(g2, nrx);
    mbar_wait(cx.sb + SM_BAR_XG, 0);
    const uint32_t frag = (cw * 16 + (lane & 15)) * 128 + (((lane >> 4) ^ (lane & 7)) << 4);
#pragma unroll
    for (int i = 0; i < 4; i++) {
      ldsm4(cx.sb + SM_XO + (frag ^ (i << 5)), xv[4 * i], xv[4 * i + 1], xv[4 * i + 2], xv[4 * i + 3]);
      ldsm4(cx.sb + SM_GO + (frag ^ (i << 5)), gt[4 * i], gt[4 * i + 1], gt[4 * i + 2], gt[4 * i + 3]);
    }
    if (ok) add_granules(red, g);
    TS3(44)
    wg_wait<0>();
    pin(acc);
    TS(85)
#pragma unroll
    for (int i = 0; i < 32; i++) red[i] += acc[i];
    pin(red);
#pragma unroll 1
    for (int spins = 0; spins < (1 << 16); spins++) {
      if (granules_ok(g2, tag)) {
        add_granules(red, g2);
        if (++nrx == 8) break;
      }
      fetch(g2, nrx);
    }
    uint32_t ow[16];
#pragma unroll
    for (int i = 0; i < 16; i++) ow[i] = pack2(red[2 * i], red[2 * i + 1]);
    prof(wg, 20);
    TS(86)
#pragma unroll
    for (int i = 0; i < 16; i++) ow[i] = fma2(ow[i], gt[i], xv[i]);
#pragma unroll
    for (int i = 0; i < 4; i++) stsm4(cx.sb + SM_XO + (frag ^ (i << 5)), ow[4 * i], ow[4 * i + 1], ow[4 * i + 2], ow[4 * i + 3]);
    __syncwarp();
    __nv_bfloat16* const op = at(out, ((qb * 128 + cw * 16 + (lane >> 3)) * DM + hs * 64 + (lane & 7) * 8) * 2);
#pragma unroll
    for (int i = 0; i < 4; i++) {
      uint4 v;
      const int row = cw * 16 + i * 4 + (lane >> 3);
      lds128(cx.sb + SM_XO + row * 128 + (((lane ^ row) & 7) << 4), v.x, v.y, v.z, v.w);
      asm volatile("st.global.v4.b32 [%0], {%1, %2, %3, %4};" ::"l"(op + i * 4 * DM),
                   "r"(v.x), "r"(v.y), "r"(v.z), "r"(v.w) : "memory");
    }
    prof(wg, 22);
    TS(87)
    TS_DUMP()
  }
}

struct KvMaps { CUtensorMap m[4]; };
__global__ void __cluster_dims__(2, 1, 1) __launch_bounds__(THREADS, 1)
fused_kernel(const __nv_bfloat16* __restrict__ x, const __nv_bfloat16* __restrict__ w_r, const __nv_bfloat16* __restrict__ kc,
             const __nv_bfloat16* __restrict__ vc, __nv_bfloat16* __restrict__ out, Scratch* scratch,
             const __grid_constant__ CUtensorMap tmX, const __grid_constant__ CUtensorMap tmWq,
             const __grid_constant__ KvMaps tmKV, const __grid_constant__ CUtensorMap tmWo,
             const __grid_constant__ CUtensorMap tmG, const __grid_constant__ CUtensorMap tmU,
             const __grid_constant__ CUtensorMap tmD, const __grid_constant__ CUtensorMap tmX16,
             const __grid_constant__ CUtensorMap tmWq96, const __grid_constant__ CUtensorMap tmX64) {
  extern __shared__ __align__(1024) uint8_t smem_raw[];
  prof(0, 23, 511);
  Ctx cx;
  cx.sb = smem_u32(smem_raw);
  cx.sp = smem_raw;
  cx.g = scratch;
  cx.rank = blockIdx.x & 1;
  const int warp = __shfl_sync(0xffffffffu, threadIdx.x >> 5, 0);
  const int cluster = blockIdx.x >> 1;
  const bool is_ffn = blockIdx.x >= N_ATT_CTA;
  const int c7 = ((cluster - 36) * 37) >> 8;
  const int hs = cluster < 4 ? 4 + cluster : cluster < 36 ? (cluster - 4) >> 3 : 4 + c7;
  const int qb = (cluster < 4 ? 0 : cluster < 36 ? (cluster - 4) & 7 : cluster - (is_ffn ? 36 : 35) - 7 * c7) * 2 + cx.rank;

  auto load_x = [&](int w, int i0, int i1) {
#pragma unroll
    for (int i = i0; i < i1; i++) {
      mbar_expect_tx(cx.sb + SM_XFULL + 32 * w + 8 * i, 24576);
      tma3d(cx.sb + SM_X + (3 * w + i) * 24576, &tmX, qb * 128 + w * 64, i * 3, cx.sb + SM_XFULL + 32 * w + 8 * i);
    }
  };
  if (warp < 4) {
    asm volatile("setmaxnreg.dec.sync.aligned.u32 24;");
    if (elect_one()) {
      if (warp == 0) TSP(64)
      if (warp < 2) {
#pragma unroll
        for (int i = 0; i < 4; i++) mbar_init(cx.sb + SM_FULL + 32 * warp + 8 * i, 1 + 3 * warp);
        mbar_init(cx.sb + SM_BAR_XG + 8 * warp, 1);
        mbar_init(cx.sb + SM_BAR_Q + 8 * warp, 1);
        if (warp) mbar_init(cx.sb + SM_BAR_MISC, 1);
      } else if (is_ffn) {
#pragma unroll
        for (int i = 0; i < 8; i++) mbar_init(cx.sb + (warp == 2 ? SM_FFULL : SM_FEMPTY) + 8 * i, 1);
      }
      asm volatile("fence.mbarrier_init.release.cluster;" ::: "memory");
    }
    __syncwarp();
    cluster_arrive();
    if (warp == 0) TSP(70)
    cluster_wait();
    if (warp == 0) TSP(71)
    prof(0, 24, 511);
    if (warp == 0) {
      if (is_ffn) ffn_producer(cx, qb, &tmWq, &tmG, &tmU, &tmD);
      else attn_producer(cx, qb, hs, tmKV.m, &tmWq, &tmWq96, &tmWo);
      prof(0, 25, 511);
    } else {
      sq_publish(cx, qb, hs, warp - 1, read_lane());
      if (warp == 3) sq_collect(cx, qb, read_lane());
      if (!is_ffn) {
        attn_gate(cx, qb, hs, warp - 1, threadIdx.x - 32, x);
        if (warp == 1) TSP(65)
        asm volatile("fence.proxy.async.global;" ::: "memory");
        if (warp == 1) attn_helper(cx, qb, hs, fresh_lane(), &tmX16);
        else bar_arrive(BAR_OA, 352);
        attn_finish8(cx, qb, hs, warp - 1, fresh_lane(), out);
      } else if (warp < 3) {
        ffn_publish(cx, qb, warp - 1, fresh_lane(), &tmX64);
      }
    }
    __syncwarp();
    cluster_arrive();
    cluster_wait();
  } else {
    if (warp == 4 && elect_one()) {
#pragma unroll
      for (int i = 0; i < 3; i++) mbar_init(cx.sb + SM_XFULL + 8 * i, 1);
      TSP(66)
      load_x(0, 0, 3);
#pragma unroll
      for (int i = 4; i < 7; i++) mbar_init(cx.sb + SM_XFULL + 8 * i, 1);
      asm volatile("fence.mbarrier_init.release.cluster;" ::: "memory");
    }
    if (warp == 5 && elect_one()) {
      mbar_init(cx.sb + SM_BAR_W, 1);
      asm volatile("fence.mbarrier_init.release.cluster;" ::: "memory");
      *(uint4*)(cx.sp + SM_ONES) = make_uint4(0x3F803F80u, 0x3F803F80u, 0x3F803F80u, 0x3F803F80u);
      mbar_expect_tx(cx.sb + SM_BAR_W, DM * 2);
      bulk_load(cx.sb + SM_WR, w_r, DM * 2, cx.sb + SM_BAR_W);
    }
    __syncwarp();
    cluster_arrive();
    if (warp == 4 && elect_one()) {
      load_x(1, 0, X_ORD);
      TSP(67)
    }
    __syncwarp();
    asm volatile("setmaxnreg.inc.sync.aligned.u32 240;");
    const int cw = warp - 4, wg = cw >> 2;
    cluster_wait();
    if (warp == 8 && elect_one()) {
      const uint64_t pol = policy_evict_first();
#pragma unroll
      for (int i = 0; i < 4; i++) {
        if (!(i & 1)) mbar_expect_tx(cx.sb + SM_FULL + 4 * i, 32768);
        tma2d_mc(cx.sb + SM_RING + (i >> 1) * STAGE + cx.rank * 16384 + (i & 1) * 8192, &tmWq,
                 is_ffn ? (cx.rank * 4 + 3) * DH + 64 : hs * 512 + cx.rank * 64, i * 64, cx.sb + SM_FULL + 8 * (i >> 1), pol);
        if (i == 1) load_x(1, X_ORD, 3);
      }
      TSP(72)
    }
    __syncwarp();
    attn_consumer(cx, is_ffn, qb, hs, wg, cw, read_lane(), x, kc, vc, out);
  }
}

typedef CUresult (*EncodeFn)(CUtensorMap*, CUtensorMapDataType, cuuint32_t, void*, const cuuint64_t*, const cuuint64_t*,
                             const cuuint32_t*, const cuuint32_t*, CUtensorMapInterleave, CUtensorMapSwizzle,
                             CUtensorMapL2promotion, CUtensorMapFloatOOBfill);

void encode(EncodeFn fn, CUtensorMap* m, const void* p, int rank, const cuuint64_t* dims, const cuuint64_t* strides,
            const cuuint32_t* box) {
  const cuuint32_t es[5] = {1, 1, 1, 1, 1};
  fn(m, CU_TENSOR_MAP_DATA_TYPE_BFLOAT16, rank, const_cast<void*>(p), dims, strides, box, es, CU_TENSOR_MAP_INTERLEAVE_NONE,
     CU_TENSOR_MAP_SWIZZLE_128B, CU_TENSOR_MAP_L2_PROMOTION_L2_128B, CU_TENSOR_MAP_FLOAT_OOB_FILL_NONE);
}
void encode2d(EncodeFn fn, CUtensorMap* m, const void* p, uint64_t rows, uint64_t cols, uint32_t box_rows) {
  const cuuint64_t dims[2] = {cols, rows}, strides[1] = {cols * 2};
  const cuuint32_t box[2] = {64, box_rows};
  encode(fn, m, p, 2, dims, strides, box);
}

}

extern "C" void kernel_launch(void* const* d_in, const int* in_sizes, int n_in, void* d_out, int out_size) {
  (void)in_sizes; (void)n_in; (void)out_size;
  void* fnp = nullptr;
  cudaDriverEntryPointQueryResult qr;
  cudaGetDriverEntryPoint("cuTensorMapEncodeTiled", &fnp, cudaEnableDefault, &qr);
  EncodeFn fn = (EncodeFn)fnp;
  CUtensorMap tmWq, tmWo, tmG, tmU, tmD, tmX, tmX16, tmWq96, tmX64;
  encode2d(fn, &tmX64, d_in[0], SEQ, DM, 64);
  encode2d(fn, &tmWq96, d_in[3], DM, 4096, 96);
  encode2d(fn, &tmX16, d_in[0], SEQ, DM, 16);
  KvMaps tmKV;
  for (int i = 0; i < 4; i++) encode2d(fn, &tmKV.m[i], d_in[1 + (i & 1)], 16 * SEQ, DH, i < 2 ? 112 : 96);
  encode2d(fn, &tmWq, d_in[3], DM, 4096, 64);
  {
    const cuuint64_t dims[3] = {64, SEQ, 9}, strides[2] = {DM * 2, 128};
    const cuuint32_t box[3] = {64, 64, 3};
    encode(fn, &tmX, d_in[0], 3, dims, strides, box);
  }
  encode2d(fn, &tmWo, d_in[4], 4096, DM, 128);
  encode2d(fn, &tmG, d_in[7], DM, FF, 192);
  encode2d(fn, &tmU, d_in[8], DM, FF, 192);
  encode2d(fn, &tmD, d_in[9], FF, DM, 192);
  cudaFuncSetAttribute(fused_kernel, cudaFuncAttributeMaxDynamicSharedMemorySize, SM_TOTAL);
  void* scratch = nullptr;
  cudaGetSymbolAddress(&scratch, g_scratch);
  fused_kernel<<<N_CTA, THREADS, SM_TOTAL>>>((const __nv_bfloat16*)d_in[0], (const __nv_bfloat16*)d_in[6], (const __nv_bfloat16*)d_in[1],
                                            (const __nv_bfloat16*)d_in[2], (__nv_bfloat16*)d_out, (Scratch*)scratch, tmX, tmWq, tmKV,
                                            tmWo, tmG, tmU, tmD, tmX16, tmWq96, tmX64);
}
```

```cpp
#include <cuda_runtime.h>
#include <cuda_bf16.h>
#include <cuda.h>
#include <stdint.h>

namespace {

constexpr int SEQ = 2048, DM = 576, DH = 128, FF = 4608, TOPC = 8;
constexpr int N_ATT_CTA = 128, N_CTA = 132;
constexpr int THREADS = 384;

constexpr uint32_t SM_RING = 0;
constexpr uint32_t STAGE = 32768;
constexpr uint32_t SM_SLOT = 131072;
constexpr uint32_t FSTAGE = 24576;
constexpr uint32_t SM_XSEL = 196608;
constexpr uint32_t SM_H = 205824;
constexpr uint32_t SM_MISC = 229376;
constexpr uint32_t SM_FULL = SM_MISC, SM_EMPTY = SM_MISC + 32, SM_FFULL = SM_MISC + 64, SM_BAR_MISC = SM_MISC + 128,
                   SM_COLD = SM_MISC + 136, SM_TAG = SM_MISC + 144, SM_BAR_W = SM_MISC + 152, SM_ONES = SM_MISC + 160,
                   SM_BAR_Q = SM_MISC + 176, SM_XFULL = SM_MISC + 192, SM_BAR_XG = SM_MISC + 304, SM_BAR_SQ = SM_MISC + 312,
                   SM_STATS = SM_MISC + 320, SM_FEMPTY = SM_MISC + 1344, SM_RAW = SM_FEMPTY, SM_WR = SM_MISC + 1408, SM_TOPK = SM_WR;
constexpr uint32_t SM_TOTAL = SM_MISC + 2560;
constexpr uint32_t SM_X = SM_MISC - 147456;

constexpr int BAR_GATE = 6, BAR_HELPER = 7, BAR_OA = 8, BAR_XREL = 13, BAR_QS = 9, BAR_QF = 11;
constexpr int NST_Q = 18, NST_KV = 76, NST_O = 18;
constexpr float SM_SCALE_LOG2 = 0.08838834764831845f * 1.4426950408889634f;

struct Scratch {
  uint4 part[16 * 64 * 2 * 4 * 128];
  uint4 gate[N_ATT_CTA * 1152];
  uint4 q[16 * 8 * 2 * 512];
  uint2 sq[SEQ];
  uint4 stats[SEQ];
  float ypart[4 * TOPC * DM];
  int2 sel[16];
  unsigned launch[160];
  unsigned pad0, ycnt, pad[30];
  unsigned qflag[128];
};
__device__ __align__(1024) Scratch g_scratch;

__device__ __forceinline__ void prof(int, int, int = 0) {}

#define TS(id) {}
#define TS_DUMP() {}
#define TSH(k) {}
#define TS4(k) {}
#define TSP(k) {}
#define TS1(id) TS(id)
#define TS2(k) {}
#define TS3(k) {}

__device__ __forceinline__ uint32_t smem_u32(const void* p) { return (uint32_t)__cvta_generic_to_shared(p); }
__device__ __forceinline__ void mbar_init(uint32_t bar, uint32_t cnt) {
  asm volatile("mbarrier.init.shared::cta.b64 [%0], %1;" ::"r"(bar), "r"(cnt) : "memory");
}
__device__ __forceinline__ void mbar_expect_tx(uint32_t bar, uint32_t bytes) {
  asm volatile("mbarrier.arrive.expect_tx.shared::cta.b64 _, [%0], %1;" ::"r"(bar), "r"(bytes) : "memory");
}
__device__ __forceinline__ void mbar_arrive(uint32_t bar) {
  asm volatile("mbarrier.arrive.shared::cta.b64 _, [%0];" ::"r"(bar) : "memory");
}
__device__ __forceinline__ void mbar_arrive_cluster(uint32_t bar_cluster_addr, bool pred) {
  asm volatile("{\n.reg .pred p;\nsetp.ne.u32 p, %1, 0;\n@p mbarrier.arrive.shared::cluster.b64 _, [%0];\n}"
               ::"r"(bar_cluster_addr), "r"((uint32_t)pred) : "memory");
}
template <int ID>
__device__ __forceinline__ void mbar_arrive_cluster_now(uint32_t bar_cluster_addr, bool pred) {
  asm volatile("{\n.reg .pred p, q;\nsetp.ne.u32 p, %1, 0;\nsetp.eq.u32 q, %2, %3;\n"
               "ARR_LOOP:\n@p mbarrier.arrive.shared::cluster.b64 _, [%0];\n@q bra.uni ARR_LOOP;\n}"
               ::"r"(bar_cluster_addr), "r"((uint32_t)pred), "r"(blockIdx.y), "n"(ID) : "memory");
}
__device__ __forceinline__ void block_fence(int id) {
  asm volatile("{\n.reg .pred q;\nsetp.eq.u32 q, %0, %1;\nBF_LOOP:\n@q st.volatile.shared.u32 [%0], %0;\n@q bra.uni BF_LOOP;\n}"
               ::"r"(blockIdx.y), "r"(id) : "memory");
}
__device__ __forceinline__ void mbar_wait(uint32_t bar, uint32_t parity) {
  asm volatile("{\n.reg .pred p, q;\n.reg .u32 n;\nmov.u32 n, 0;\n"
               "WAIT_LOOP:\nmbarrier.try_wait.parity.shared::cta.b64 p, [%0], %1;\n"
               "add.u32 n, n, 1;\nsetp.lt.u32 q, n, 4194304;\nand.pred q, q, !p;\n@q bra WAIT_LOOP;\n}"
               ::"r"(bar), "r"(parity) : "memory");
}
__device__ __forceinline__ uint32_t mapa(uint32_t addr, uint32_t rank) {
  uint32_t r;
  asm volatile("mapa.shared::cluster.u32 %0, %1, %2;" : "=r"(r) : "r"(addr), "r"(rank));
  return r;
}
__device__ __forceinline__ void cluster_arrive() { asm volatile("barrier.cluster.arrive.relaxed.aligned;" ::: "memory"); }
__device__ __forceinline__ bool elect_one() {
  uint32_t p;
  asm volatile("{\n.reg .pred p;\nelect.sync _|p, 0xffffffff;\nselp.u32 %0, 1, 0, p;\n}" : "=r"(p));
  return p;
}
__device__ __forceinline__ int read_lane() { return threadIdx.x & 31; }
__device__ __forceinline__ int fresh_lane() {
  int l;
  asm volatile("mov.u32 %0, %%laneid;" : "=r"(l));
  return l;
}
template <class T> __device__ __forceinline__ T* at(T* p, uint32_t bytes) {
  asm("" : "+r"(bytes));
  return (T*)((const char*)p + bytes);
}
__device__ __forceinline__ void cluster_wait() { asm volatile("barrier.cluster.wait.acquire.aligned;" ::: "memory"); }
__device__ __forceinline__ void bar_sync(int id, int n) { asm volatile("barrier.cta.sync %0, %1;" ::"r"(id), "r"(n) : "memory"); }
__device__ __forceinline__ void bar_arrive(int id, int n) { asm volatile("barrier.cta.arrive %0, %1;" ::"r"(id), "r"(n) : "memory"); }

__device__ __forceinline__ uint64_t policy_evict_first() {
  uint64_t p;
  asm("createpolicy.fractional.L2::evict_first.b64 %0, 1.0;" : "=l"(p));
  return p;
}
__device__ __forceinline__ void tma2d_mc(uint32_t dst, const CUtensorMap* tm, int c0, int c1, uint32_t bar, uint64_t pol) {
  asm volatile("cp.async.bulk.tensor.2d.shared::cluster.global.mbarrier::complete_tx::bytes.multicast::cluster.L2::cache_hint"
               " [%0], [%1, {%2, %3}], [%4], %5, %6;"
               ::"r"(dst), "l"(tm), "r"(c0), "r"(c1), "r"(bar), "h"((uint16_t)3), "l"(pol) : "memory");
}
__device__ __forceinline__ void tma3d(uint32_t dst, const CUtensorMap* tm, int c1, int c2, uint32_t bar) {
  asm volatile("cp.async.bulk.tensor.3d.shared::cluster.global.mbarrier::complete_tx::bytes [%0], [%1, {%2, %3, %4}], [%5];"
               ::"r"(dst), "l"(tm), "r"(0), "r"(c1), "r"(c2), "r"(bar) : "memory");
}
__device__ __forceinline__ void tma2d(uint32_t dst, const CUtensorMap* tm, int c0, int c1, uint32_t bar) {
  asm volatile("cp.async.bulk.tensor.2d.shared::cluster.global.mbarrier::complete_tx::bytes [%0], [%1, {%2, %3}], [%4];"
               ::"r"(dst), "l"(tm), "r"(c0), "r"(c1), "r"(bar) : "memory");
}
__device__ __forceinline__ void tma2d_stream(uint32_t dst, const CUtensorMap* tm, int c0, int c1, uint32_t bar) {
  asm volatile("{\n.reg .b64 pol;\ncreatepolicy.fractional.L2::evict_first.b64 pol, 1.0;\n"
               "cp.async.bulk.tensor.2d.shared::cluster.global.mbarrier::complete_tx::bytes.L2::cache_hint [%0], [%1, {%2, %3}], [%4], pol;\n}"
               ::"r"(dst), "l"(tm), "r"(c0), "r"(c1), "r"(bar) : "memory");
}
__device__ __forceinline__ void bulk_load(uint32_t dst, const void* src, uint32_t bytes, uint32_t bar) {
  asm volatile("cp.async.bulk.shared::cluster.global.mbarrier::complete_tx::bytes [%0], [%1], %2, [%3];"
               ::"r"(dst), "l"(src), "r"(bytes), "r"(bar) : "memory");
}
__device__ __forceinline__ void tma2d_prefetch(const CUtensorMap* tm, int c0, int c1) {
  asm volatile("cp.async.bulk.prefetch.tensor.2d.L2.global [%0, {%1, %2}];" ::"l"(tm), "r"(c0), "r"(c1) : "memory");
}

__device__ __forceinline__ void wg_fence() { asm volatile("wgmma.fence.sync.aligned;" ::: "memory"); }
__device__ __forceinline__ void wg_commit() { asm volatile("wgmma.commit_group.sync.aligned;" ::: "memory"); }
template <int N> __device__ __forceinline__ void wg_wait() { asm volatile("wgmma.wait_group.sync.aligned %0;" ::"n"(N) : "memory"); }

__device__ __forceinline__ uint64_t mkdesc(uint32_t addr, uint32_t lbo_bytes) {
  return (uint64_t)(((addr & 0x3FFFF) >> 4) | ((lbo_bytes >> 4) << 16)) | ((uint64_t)0x40000040u << 32);
}
__device__ __forceinline__ uint64_t mkdesc_q(uint32_t addr) {
  return (uint64_t)(((addr & 0x3FFFF) >> 4) | (64u << 16)) | ((uint64_t)8 << 32);
}
template <int N> __device__ __forceinline__ void pin(float (&a)[N]) {
#pragma unroll
  for (int i = 0; i < N; i++) asm volatile("" : "+f"(a[i])::"memory");
}
template <int N> __device__ __forceinline__ void kill(float (&a)[N]) {
#pragma unroll
  for (int i = 0; i < N; i++) asm volatile("" : "=f"(a[i]));
}
template <int N> __device__ __forceinline__ void pin(uint32_t (&a)[N]) {
#pragma unroll
  for (int i = 0; i < N; i++) asm volatile("" : "+r"(a[i])::"memory");
}

#define F8(d, o) "+f"(d[o]), "+f"(d[o + 1]), "+f"(d[o + 2]), "+f"(d[o + 3]), "+f"(d[o + 4]), "+f"(d[o + 5]), "+f"(d[o + 6]), "+f"(d[o + 7])
#define R32A "%0, %1, %2, %3, %4, %5, %6, %7, %8, %9, %10, %11, %12, %13, %14, %15, %16, %17, %18, %19, %20, %21, %22, %23, %24, %25, %26, %27, %28, %29, %30, %31"
#define R32B "%32, %33, %34, %35, %36, %37, %38, %39, %40, %41, %42, %43, %44, %45, %46, %47, %48, %49, %50, %51, %52, %53, %54, %55, %56, %57, %58, %59, %60, %61, %62, %63"

#define O8(d, o) "=f"(d[o]), "=f"(d[o + 1]), "=f"(d[o + 2]), "=f"(d[o + 3]), "=f"(d[o + 4]), "=f"(d[o + 5]), "=f"(d[o + 6]), "=f"(d[o + 7])

__device__ __forceinline__ void mma_n128t(float (&d)[64], uint32_t a0, uint32_t a1, uint32_t a2, uint32_t a3, uint64_t db, bool acc) {
  if (acc)
    asm volatile("wgmma.mma_async.sync.aligned.m64n128k16.f32.bf16.bf16 {" R32A ", " R32B "}, {%64, %65, %66, %67}, %68, 1, 1, 1, 1;\n"
                 : F8(d, 0), F8(d, 8), F8(d, 16), F8(d, 24), F8(d, 32), F8(d, 40), F8(d, 48), F8(d, 56)
                 : "r"(a0), "r"(a1), "r"(a2), "r"(a3), "l"(db));
  else
    asm volatile("wgmma.mma_async.sync.aligned.m64n128k16.f32.bf16.bf16 {" R32A ", " R32B "}, {%64, %65, %66, %67}, %68, 0, 1, 1, 1;\n"
                 : O8(d, 0), O8(d, 8), O8(d, 16), O8(d, 24), O8(d, 32), O8(d, 40), O8(d, 48), O8(d, 56)
                 : "r"(a0), "r"(a1), "r"(a2), "r"(a3), "l"(db));
}
#define PV1(a0, a1, a2, a3, ob, acc) "add.s64 b, %92, " #ob ";\n" \
  "wgmma.mma_async.sync.aligned.m64n128k16.f32.bf16.bf16 {" R32A ", " R32B "}, {%" #a0 ", %" #a1 ", %" #a2 ", %" #a3 "}, b, " #acc ", 1, 1, 1;\n"
#define PV6 "wgmma.fence.sync.aligned;\n" PV1(64, 65, 66, 67, 0, p) PV1(68, 69, 70, 71, 128, 1) PV1(72, 73, 74, 75, 256, 1) \
  PV1(76, 77, 78, 79, 384, 1) PV1(80, 81, 82, 83, 512, 1) PV1(84, 85, 86, 87, 640, 1)
#define U4(a, o) "r"(a[o]), "r"(a[o + 1]), "r"(a[o + 2]), "r"(a[o + 3])
__device__ __forceinline__ void mma_pv(float (&d)[64], const uint32_t (&a)[28], uint64_t dv, bool acc, bool big) {
  asm volatile("{\n.reg .pred p, q;\n.reg .b64 b;\nsetp.ne.b32 p, %93, 0;\nsetp.eq.b32 q, %94, 0;\n@q bra.uni PV_SMALL;\n"
               PV6 PV1(88, 89, 90, 91, 768, 1) "wgmma.commit_group.sync.aligned;\nbra.uni PV_DONE;\n"
               "PV_SMALL:\n" PV6 "wgmma.commit_group.sync.aligned;\nPV_DONE:\n}\n"
               : F8(d, 0), F8(d, 8), F8(d, 16), F8(d, 24), F8(d, 32), F8(d, 40), F8(d, 48), F8(d, 56)
               : U4(a, 0), U4(a, 4), U4(a, 8), U4(a, 12), U4(a, 16), U4(a, 20), U4(a, 24), "l"(dv), "r"((int)acc), "r"((int)big) : "memory");
}
#define R48 R32A ", %32, %33, %34, %35, %36, %37, %38, %39, %40, %41, %42, %43, %44, %45, %46, %47"
#define R56 R48 ", %48, %49, %50, %51, %52, %53, %54, %55"
#define QK1(N, R, A, B, oa, ob, acc) "add.s64 a, " A ", " #oa ";\nadd.s64 b, " B ", " #ob ";\n" \
  "wgmma.mma_async.sync.aligned.m64n" #N "k16.f32.bf16.bf16 {" R "}, a, b, " #acc ", 1, 1, 0, 0;\n"
#define QK8(N, R, A, B) "{\n.reg .b64 a, b;\nwgmma.fence.sync.aligned;\n" QK1(N, R, A, B, 0, 0, 0) QK1(N, R, A, B, 128, 2, 1) \
  QK1(N, R, A, B, 256, 4, 1) QK1(N, R, A, B, 384, 6, 1) QK1(N, R, A, B, 512, 1024, 1) QK1(N, R, A, B, 640, 1026, 1) \
  QK1(N, R, A, B, 768, 1028, 1) QK1(N, R, A, B, 896, 1030, 1) "wgmma.commit_group.sync.aligned;\n}\n"
__device__ __forceinline__ void mma_qk(float (&d)[56], uint64_t dq, uint64_t dk) {
  asm volatile(QK8(112, R56, "%56", "%57")
               : O8(d, 0), O8(d, 8), O8(d, 16), O8(d, 24), O8(d, 32), O8(d, 40), O8(d, 48) : "l"(dq), "l"(dk) : "memory");
}
__device__ __forceinline__ void mma_qk(float (&d)[48], uint64_t dq, uint64_t dk) {
  asm volatile(QK8(96, R48, "%48", "%49")
               : O8(d, 0), O8(d, 8), O8(d, 16), O8(d, 24), O8(d, 32), O8(d, 40) : "l"(dq), "l"(dk) : "memory");
}
__device__ __forceinline__ void mma_n64t(float (&d)[32], uint32_t a0, uint32_t a1, uint32_t a2, uint32_t a3, uint64_t db, bool acc) {
  if (acc)
    asm volatile("wgmma.mma_async.sync.aligned.m64n64k16.f32.bf16.bf16 {" R32A "}, {%32, %33, %34, %35}, %36, 1, 1, 1, 1;\n"
                 : F8(d, 0), F8(d, 8), F8(d, 16), F8(d, 24) : "r"(a0), "r"(a1), "r"(a2), "r"(a3), "l"(db));
  else
    asm volatile("wgmma.mma_async.sync.aligned.m64n64k16.f32.bf16.bf16 {" R32A "}, {%32, %33, %34, %35}, %36, 0, 1, 1, 1;\n"
                 : O8(d, 0), O8(d, 8), O8(d, 16), O8(d, 24) : "r"(a0), "r"(a1), "r"(a2), "r"(a3), "l"(db));
}
__device__ __forceinline__ void mma_n64t_dyn(float (&d)[32], uint32_t a0, uint32_t a1, uint32_t a2, uint32_t a3, uint64_t db, int acc) {
  asm volatile("{\n.reg .pred p;\nsetp.ne.b32 p, %37, 0;\n"
               "wgmma.mma_async.sync.aligned.m64n64k16.f32.bf16.bf16 {" R32A "}, {%32, %33, %34, %35}, %36, p, 1, 1, 1;\n}\n"
               : F8(d, 0), F8(d, 8), F8(d, 16), F8(d, 24) : "r"(a0), "r"(a1), "r"(a2), "r"(a3), "l"(db), "r"(acc));
}
__device__ __forceinline__ void mma_n8(float (&d)[4], uint64_t da, uint64_t db, int acc) {
  asm volatile("{\n.reg .pred p;\nsetp.ne.b32 p, %6, 0;\n"
               "wgmma.mma_async.sync.aligned.m64n8k16.f32.bf16.bf16 {%0, %1, %2, %3}, %4, %5, p, 1, 1, 1, 0;\n}\n"
               : "+f"(d[0]), "+f"(d[1]), "+f"(d[2]), "+f"(d[3])
               : "l"(da), "l"(db), "r"(acc));
}
__device__ __forceinline__ void hmma_k16(float (&d)[4], uint32_t a0, uint32_t a1, uint32_t a2, uint32_t a3, uint32_t b0, uint32_t b1) {
  asm volatile("mma.sync.aligned.m16n8k16.row.col.f32.bf16.bf16.f32 {%0, %1, %2, %3}, {%4, %5, %6, %7}, {%8, %9}, {%0, %1, %2, %3};"
               : "+f"(d[0]), "+f"(d[1]), "+f"(d[2]), "+f"(d[3]) : "r"(a0), "r"(a1), "r"(a2), "r"(a3), "r"(b0), "r"(b1));
}

__device__ __forceinline__ uint32_t pack2(float lo, float hi) {
  uint32_t r;
  asm("cvt.rn.bf16x2.f32 %0, %1, %2;" : "=r"(r) : "f"(hi), "f"(lo));
  return r;
}
__device__ __forceinline__ float bf_lo(uint32_t w) { return __uint_as_float(w << 16); }
__device__ __forceinline__ float bf_hi(uint32_t w) { return __uint_as_float(w & 0xFFFF0000u); }
__device__ __forceinline__ float bfr(float x) { return __bfloat162float(__float2bfloat16_rn(x)); }
__device__ __forceinline__ uint32_t sub2(uint32_t a, uint32_t b) {
  uint32_t r;
  asm("sub.rn.bf16x2 %0, %1, %2;" : "=r"(r) : "r"(a), "r"(b));
  return r;
}
__device__ __forceinline__ uint32_t add2(uint32_t a, uint32_t b) {
  uint32_t r;
  asm("add.rn.bf16x2 %0, %1, %2;" : "=r"(r) : "r"(a), "r"(b));
  return r;
}
__device__ __forceinline__ uint32_t fma2(uint32_t a, uint32_t b, uint32_t c) {
  uint32_t r;
  asm("fma.rn.bf16x2 %0, %1, %2, %3;" : "=r"(r) : "r"(a), "r"(b), "r"(c));
  return r;
}
__device__ __forceinline__ float ex2(float x) {
  float r;
  asm("ex2.approx.ftz.f32 %0, %1;" : "=f"(r) : "f"(x));
  return r;
}
__device__ __forceinline__ float rcp(float x) {
  float r;
  asm("rcp.approx.ftz.f32 %0, %1;" : "=f"(r) : "f"(x));
  return r;
}
__device__ __forceinline__ float silu_f(float t) { return t * rcp(1.0f + ex2(-1.4426950408889634f * t)); }
__device__ __forceinline__ void lds128(uint32_t a, uint32_t& x, uint32_t& y, uint32_t& z, uint32_t& w) {
  asm volatile("ld.shared.v4.u32 {%0, %1, %2, %3}, [%4];" : "=r"(x), "=r"(y), "=r"(z), "=r"(w) : "r"(a) : "memory");
}
__device__ __forceinline__ void ldsm4(uint32_t a, uint32_t& x, uint32_t& y, uint32_t& z, uint32_t& w) {
  asm volatile("ldmatrix.sync.aligned.m8n8.x4.shared.b16 {%0, %1, %2, %3}, [%4];" : "=r"(x), "=r"(y), "=r"(z), "=r"(w) : "r"(a) : "memory");
}
constexpr uint32_t TAG = 0x10000;
__device__ __forceinline__ void st_gran(uint4* p, uint32_t x, uint32_t y, uint32_t z, uint32_t w) {
  asm volatile("st.relaxed.gpu.global.v4.b32 [%0], {%1, %2, %3, %4};" ::"l"(p), "r"(x), "r"(y), "r"(z), "r"(w) : "memory");
}
__device__ __forceinline__ void ld_gran(const uint4* p, uint32_t& x, uint32_t& y, uint32_t& z, uint32_t& w) {
  asm volatile("ld.relaxed.gpu.global.v4.b32 {%0, %1, %2, %3}, [%4];" : "=r"(x), "=r"(y), "=r"(z), "=r"(w) : "l"(p) : "memory");
}
__device__ __forceinline__ void stsm4(uint32_t a, uint32_t x, uint32_t y, uint32_t z, uint32_t w) {
  asm volatile("stmatrix.sync.aligned.m8n8.x4.shared.b16 [%0], {%1, %2, %3, %4};" ::"r"(a), "r"(x), "r"(y), "r"(z), "r"(w) : "memory");
}
__device__ __forceinline__ void cp16(uint32_t dst, const void* src) {
  asm volatile("cp.async.cg.shared.global [%0], [%1], 16;" ::"r"(dst), "l"(src) : "memory");
}
__device__ __forceinline__ void cp_wait_all() { asm volatile("cp.async.wait_all;" ::: "memory"); }
__device__ __forceinline__ void add_granules(float (&red)[32], const uint32_t (&g)[16]) {
#pragma unroll
  for (int i = 0; i < 16; i++) { red[2 * i] += bf_lo(g[i]); red[2 * i + 1] += bf_hi((i & 3) ? g[i] : g[i] & ~TAG); }
}
__device__ __forceinline__ bool granules_ok(const uint32_t (&g)[16], uint32_t tag) {
  uint32_t a, b;
  asm("lop3.b32 %0, %1, %2, %3, 0x7E;" : "=r"(a) : "r"(g[0]), "r"(g[4]), "r"(tag));
  asm("lop3.b32 %0, %1, %2, %3, 0x7E;" : "=r"(b) : "r"(g[8]), "r"(g[12]), "r"(tag));
  return __all_sync(0xffffffffu, ((a | b) & TAG) == 0);
}
__device__ __forceinline__ unsigned ld_acquire(const unsigned* p) {
  unsigned v;
  asm volatile("ld.acquire.gpu.global.u32 %0, [%1];" : "=r"(v) : "l"(p) : "memory");
  return v;
}
__device__ __forceinline__ unsigned atom_add_acq_rel(unsigned* p) {
  unsigned v;
  asm volatile("atom.acq_rel.gpu.global.add.u32 %0, [%1], 1;" : "=r"(v) : "l"(p) : "memory");
  return v;
}

template <int K0, int K1>
__device__ __forceinline__ void ln_fetch(uint32_t (&xa)[144], uint32_t boxes, uint32_t lo) {
#pragma unroll
  for (int k = K0; k < K1; k++) ldsm4(boxes + (k >> 2) * 8192 + (lo ^ ((k & 3) << 5)), xa[4 * k], xa[4 * k + 1], xa[4 * k + 2], xa[4 * k + 3]);
}
__device__ __forceinline__ void ln_fetch_b(uint32_t (&b)[24], uint32_t& wb, uint32_t ws) {
#pragma unroll
  for (int j = 0; j < 6; j++, wb += ws) ldsm4(wb, b[4 * j], b[4 * j + 1], b[4 * j + 2], b[4 * j + 3]);
}
template <int K0, int K1>
__device__ __forceinline__ void ln_sums(const uint32_t (&xa)[144], float (&sm)[4][4], const uint32_t (&b)[24]) {
#pragma unroll
  for (int k = K0; k < K1; k++)
    hmma_k16(sm[k & 3], xa[4 * k], xa[4 * k + 1], xa[4 * k + 2], xa[4 * k + 3], b[2 * (k % 12)], b[2 * (k % 12) + 1]);
}
template <int K0, int K1>
__device__ __forceinline__ uint32_t after_fetch(const uint32_t (&xa)[144]) {
  uint32_t d = blockIdx.y;
#pragma unroll
  for (int k = K0; k < K1; k++) d &= xa[4 * k];
  return d;
}
__device__ __forceinline__ void ln_row(float sum, float sq, float& mean_b, float& rstd) {
  const float mean = sum * (1.0f / DM);
  const uint32_t mv = pack2(mean, fmaxf(sq * (1.0f / DM) - mean * mean, 0.0f));
  mean_b = bf_lo(mv);
  float sd;
  asm("sqrt.approx.f32 %0, %1;" : "=f"(sd) : "f"(bf_lo(pack2(bf_hi(mv) + 1e-5f, 0.f))));
  rstd = rcp(bf_lo(pack2(sd, 0.f)));
}

template <bool ROUTED>
__device__ __forceinline__ uint32_t gate2(uint32_t xc, float rstd, float2 upd = make_float2(0.f, 0.f)) {
  uint32_t t = pack2(bf_lo(xc) * rstd, bf_hi(xc) * rstd);
  if (ROUTED) t = pack2(bf_lo(t) + upd.x, bf_hi(t) + upd.y);
  return pack2(silu_f(bf_lo(t)), silu_f(bf_hi(t)));
}

template <int V> struct IC { static constexpr int value = V; };

struct Ctx {
  uint32_t sb;
  uint8_t* sp;
  uint32_t rank;
  Scratch* g;
};

__device__ __forceinline__ bool acquire(const Ctx& cx, uint32_t r, uint32_t n, uint32_t bytes) {
  mbar_wait(cx.sb + SM_EMPTY + 8 * r, (n ^ (r >> 1) ^ 1) & 1);
  __syncwarp();
  const bool e = elect_one();
  if (e) mbar_expect_tx(cx.sb + SM_FULL + 8 * r, bytes);
  return e;
}
__device__ __forceinline__ void load_wq(const Ctx& cx, const CUtensorMap* tmWq, int st, int i, int n0, uint64_t pol) {
  const uint32_t r = st & 3, dst = cx.sb + SM_RING + r * STAGE + cx.rank * 16384, bar = cx.sb + SM_FULL + 8 * r;
  const int k0 = i < 3 ? 128 * i : 128 * i - 64;
  if (acquire(cx, r, st >> 2, i == 2 ? 16384 : 32768)) {
    tma2d_mc(dst, tmWq, n0, k0, bar, pol);
    if (i != 2) tma2d_mc(dst + 8192, tmWq, n0, k0 + 64, bar, pol);
  }
}
__device__ __forceinline__ void attn_producer(const Ctx& cx, int qb, int hs, const CUtensorMap* tmKV, const CUtensorMap* tmWq,
                                              const CUtensorMap* tmWq96, const CUtensorMap* tmWo) {
  const uint32_t full = cx.sb + SM_FULL, ring = cx.sb + SM_RING + cx.rank * 16384;
  const uint64_t last_use = policy_evict_first();
  int st = 0;
#pragma unroll 1
  for (int p = 0; p < 4; p++) {
#pragma unroll 1
    for (int i = 0; i < (p == 2 ? 3 : 5); i++, st++) {
      if (p == 2) {
        if (acquire(cx, st & 3, st >> 2, 24576))
          tma2d_mc(cx.sb + SM_RING + (st & 3) * STAGE + cx.rank * 12288, tmWq96, (hs * 4 + 3) * DH, 192 * i + 96 * cx.rank, full + 8 * (st & 3), last_use);
      } else {
        if (st > 1) load_wq(cx, tmWq, st, i, (hs * 4 + (p ^ (p >> 1))) * DH + cx.rank * 64, last_use);
      }
      if (st == 1 || st == 2) TSP(72 + st)
      if (st == 1) {
#pragma unroll 1
        for (int b = qb < 8; b < 5 - (qb >> 3); b++)
          if (elect_one()) tma2d_prefetch(tmWq, hs * 512 + (b < 4 ? (b ^ (b >> 1)) * DH + (qb & 1) * 64 : qb * 64), b < 4 ? (qb >> 1) * 64 : 512);
      }
      if (st == 8 && qb < 8 && elect_one()) tma2d_prefetch(tmKV + ((qb >> 1) & 1), cx.rank * 64, hs * 2 * SEQ + (qb >> 2) * 96);
    }
  }
  uint32_t r = 2, n = 4;
  int row = hs * 2 * SEQ, rows = 96;
  const CUtensorMap* tm = tmKV + 2;
#pragma unroll 1
  for (int u = 0; u < NST_KV; u++) {
    if (acquire(cx, r, n, rows * 256)) {
      tma2d_mc(ring + r * STAGE, tm, cx.rank * 64, row, full + 8 * r, last_use);
      if (((u ^ (qb >> 1)) & 7) == 0 && u < NST_KV - 4) tma2d_prefetch(tmKV + (u & 1), cx.rank * 64, row + 208);
      if ((unsigned)(u - 32) < 36 && (u & 15) == qb) tma2d_prefetch(tmWo, ((u - 32) >> 2) * 64, hs * 512 + (u & 3) * 128);
    }
    if (++r == 4) { r = 1; n++; }
    if (u & 1) row += rows;
    const bool big = (unsigned)(u - 9) < 56;
    rows = big ? 112 : 96;
    tm = tmKV + (~u & 1) + (big ? 0 : 2);
  }
#pragma unroll 1
  for (int u = 0; u < NST_O; u++) {
    const int s = u >> 1;
    const int blk = s == 0 ? 8 : ((hs + s) & 7);
    r = (0x87 >> (2 * (u & 3))) & 3;
    if (acquire(cx, r, (u >> 2) ^ ~u, 32768))
      tma2d_mc(ring + r * STAGE, tmWo, blk * 64, hs * 512 + ((u & 1) + cx.rank * 2) * 128, full + 8 * r, last_use);
  }
}

__device__ __forceinline__ void sq_publish(const Ctx& cx, int qb, int hs, int j, int lane) {
  if (j == 2 && lane == 0) {
    const unsigned e = cx.g->launch[hs * 16 + qb]++;
    *(uint2*)(cx.sp + SM_TAG) = make_uint2((~e & 1) * TAG, e);
  }
  const int row = (hs & 3) * 16 + (lane >> 1);
  uint32_t a = cx.sb + SM_X + (hs >> 2) * 73728 + j * 8192 + row * 128 + (((lane & 1) ^ (row & 7)) << 4);
  float s0 = 0.f, s1 = 0.f;
#pragma unroll 1
  for (int b = 0; b < 6; b++) {
    if (b == (hs < 4 ? 4 : 0)) {
      const int n = 224 + (__float_as_uint(s1) & blockIdx.y);
      if (j == 1) {
        bar_sync(BAR_XREL, n);
        if (lane < 4) asm volatile("mbarrier.arrive.shared::cluster.b64 _, [%0], 2;" ::"r"(mapa(cx.sb + SM_EMPTY + 16 + 8 * (lane >> 1), lane & 1)) : "memory");
      } else {
        bar_arrive(BAR_XREL, n);
      }
      __syncwarp();
      if (hs == 8) return;
    }
    if (!(b & 1)) mbar_wait(cx.sb + SM_XFULL + 32 * (hs >> 2) + 4 * b, 0);
    uint32_t v[8];
    lds128(a, v[0], v[1], v[2], v[3]);
    lds128(a ^ 32, v[4], v[5], v[6], v[7]);
    a = (a ^ 64) + (b & 1) * 24576;
#pragma unroll
    for (int i = 0; i < 8; i++) { s0 = fmaf(bf_lo(v[i]), bf_lo(v[i]), s0); s1 = fmaf(bf_hi(v[i]), bf_hi(v[i]), s1); }
  }
  s0 += s1;
  s0 += __shfl_xor_sync(0xffffffffu, s0, 1);
  float* part = (float*)(cx.sp + SM_STATS) + (lane >> 1) * 2;
  if (j < 2) {
    part[32 * j] = s0;
    bar_arrive(BAR_HELPER, 96);
  } else {
    bar_sync(BAR_HELPER, 96);
    TSP(68)
    if (!(lane & 1))
      asm volatile("st.relaxed.gpu.global.v2.b32 [%0], {%1, %2};" ::"l"(cx.g->sq + qb * 128 + hs * 16 + (lane >> 1)),
                   "r"(__float_as_uint((part[0] + part[32]) + s0)), "r"(*(const uint32_t*)(cx.sp + SM_TAG + 4) + 1) : "memory");
  }
}
__device__ __forceinline__ void sq_collect(const Ctx& cx, int qb, int lane) {
  const uint32_t e1 = *(const uint32_t*)(cx.sp + SM_TAG + 4) + 1;
#pragma unroll 1
  for (int n = 0; n < (1 << 16); n++) {
    __nanosleep(300);
    uint32_t bad = 0;
#pragma unroll
    for (int i = 0; i < 2; i++) {
      uint32_t a, t0, b, t1;
      ld_gran((const uint4*)at(cx.g->sq, qb * 1024 + lane * 16) + i * 32, a, t0, b, t1);
      *(uint32_t*)(cx.sp + SM_STATS + (i * 32 + lane) * 16 + 4) = a;
      *(uint32_t*)(cx.sp + SM_STATS + (i * 32 + lane) * 16 + 12) = b;
      bad |= (t0 ^ e1) | (t1 ^ e1);
    }
    if (__all_sync(0xffffffffu, bad == 0)) break;
  }
  __syncwarp();
  if (lane == 0) mbar_arrive(cx.sb + SM_BAR_SQ);
  TSP(69)
}
__device__ __forceinline__ void attn_gate(const Ctx& cx, int qb, int hs, int j, int t, const __nv_bfloat16* x) {
  const uint4* xp = (const uint4*)(x + qb * 128 * DM) + (t >> 3) * 72 + hs * 8 + (t & 7);
  uint4 nx = *xp;
  float wsum = 0.f;
  if (j == 0) {
    mbar_wait(cx.sb + SM_BAR_W, 0);
#pragma unroll 3
    for (int i = 0; i < 9; i++) {
      const uint32_t w = *(const uint32_t*)(cx.sp + SM_WR + i * 128 + t * 4);
      wsum += bf_lo(w) + bf_hi(w);
    }
#pragma unroll
    for (int i = 1; i < 32; i *= 2) wsum += __shfl_xor_sync(0xffffffffu, wsum, i);
  }
  bar_sync(BAR_GATE, 352);
  if (t < 16) {
    const float2 st = *(const float2*)(cx.sp + SM_STATS + 8 * (hs * 16 + t));
    const int row = qb * 128 + hs * 16 + t;
    const uint32_t b = pack2(0.f, fmaf(-st.x, wsum, *(const float*)(cx.sp + SM_RAW + 4 * t)) * st.y);
    st_gran(at(cx.g->stats, row * 16), __float_as_uint(st.x), __float_as_uint(st.y), (b ^ ((int)b < 0 ? 0xFFFF0000u : 0x80000000u)) | (0xFFFF - row),
            *(const uint32_t*)(cx.sp + SM_TAG + 4) + 1);
  }
  __syncwarp();
  uint32_t sa = cx.sb + SM_STATS + (t & ~7);
  uint4* gp = cx.g->gate + blockIdx.x * 1152 + (t ^ ((t >> 3) & 7));
  const int cross = t < 64 ? 10 : 9;
#pragma unroll 1
  for (int i = 0; i < 12; i++) {
    float2 st;
    asm volatile("ld.shared.v2.f32 {%0, %1}, [%2];" : "=f"(st.x), "=f"(st.y) : "r"(sa));
    const uint32_t mm = pack2(st.x, st.x);
    const uint4 v = make_uint4(sub2(nx.x, mm), sub2(nx.y, mm), sub2(nx.z, mm), sub2(nx.w, mm));
    xp += 12 * 72;
    sa += 96;
    if (i == cross) { xp += (hs * 16 - 128) * 72 + 64 - hs * 8; sa += (hs * 16 - 128) * 8; }
    if (i < 11) nx = *xp;
    *gp = make_uint4(gate2<false>(v.x, st.y), gate2<false>(v.y, st.y), gate2<false>(v.z, st.y), gate2<false>(v.w, st.y));
    gp = (uint4*)((size_t)(gp + 96) ^ 64);
  }
}

constexpr uint32_t SM_XO = SM_SLOT, SM_GO = SM_SLOT + STAGE, SM_P8 = SM_SLOT + 2 * STAGE;
__device__ __forceinline__ void attn_helper(const Ctx& cx, int qb, int hs, int lane, const CUtensorMap* tmX16) {
  const unsigned e = *(const uint32_t*)(cx.sp + SM_TAG + 4);
  bar_sync(BAR_HELPER, 64);
  bool todo = lane < 2;
#pragma unroll 1
  for (int n = 0; __any_sync(0xffffffffu, todo); n++) {
    if (todo && (ld_acquire(at(cx.g->qflag, ((qb * 4 + (hs >> 1)) * 2 + lane) * 4)) == e + 1 || n == (1 << 16))) {
      asm volatile("fence.proxy.async.global;" ::: "memory");
      mbar_expect_tx(cx.sb + SM_BAR_Q + 8 * lane, 8192);
      bulk_load(cx.sb + SM_SLOT + 2 * STAGE + lane * 16384 + 8192, at(cx.g->q, ((qb * 8 + hs) * 2 + lane) * 8192), 8192, cx.sb + SM_BAR_Q + 8 * lane);
      todo = false;
    }
  }
  const uint32_t tag = (~e & 1) * TAG;
  const uint4* src = cx.g->part + (size_t)((qb * 64 + 56) * 2 + (hs >> 2)) * 4 * 128 + (hs & 3) * 32 + lane;
  const uint32_t stg = cx.sb + SM_P8 + lane * 16;
  bar_sync(BAR_OA, 352);
  asm volatile("fence.proxy.async.global;" ::: "memory");
  if (lane == 0) {
    mbar_expect_tx(cx.sb + SM_BAR_MISC, 2 * 18432);
    bulk_load(cx.sb + SM_GO, cx.g->gate + blockIdx.x * 1152, 18432, cx.sb + SM_BAR_MISC);
#pragma unroll 1
    for (int i = 0; i < 9; i++)
      tma2d(cx.sb + SM_XO + i * 2048, tmX16, i < 8 ? hs * 64 : 512, qb * 128 + (i < 8 ? i : hs) * 16, cx.sb + SM_BAR_MISC);
  }
#pragma unroll 1
  for (int n = 0; n < (1 << 16); n++) {
    __nanosleep(n ? 500 : 2000);
    uint32_t a, b, d, t;
    ld_gran(src - lane + (lane & 7) * (2 * 4 * 128) + 3 * 128 + 31, a, b, d, t);
    if (__all_sync(0xffffffffu, (a & TAG) == tag)) break;
  }
  TSH(46)
#pragma unroll 1
  for (int n = 0; n < (1 << 16); n++) {
#pragma unroll 1
    for (int i = 0; i < 8; i++) {
#pragma unroll
      for (int g = 0; g < 4; g++) cp16(stg + (i * 4 + g) * 512, src + i * (2 * 4 * 128) + g * 128);
    }
    cp_wait_all();
    uint32_t bad = 0;
#pragma unroll 4
    for (int i = 0; i < 32; i++) bad |= *(const volatile uint32_t*)(cx.sp + SM_P8 + lane * 16 + i * 512) ^ tag;
    if (__all_sync(0xffffffffu, (bad & TAG) == 0)) break;
  }
  TSH(47)
#pragma unroll 1
  for (int n = 0; n < (1 << 16) && ld_acquire(&cx.g->ycnt) != 4 * (e + 1); n++) __nanosleep(200);
  const int2 sel = __ldcg(at(cx.g->sel, (lane & 7) * 8));
  const int lr = sel.x - qb * 128;
  uint32_t m = __ballot_sync(0xffffffffu, lane < 16 && ((lane & 8) ? (lr >> 4) == hs : (lr >> 7) == 0));
  mbar_wait(cx.sb + SM_BAR_MISC, 0);
#pragma unroll 1
  for (; m; m &= m - 1) {
    const int i = __ffs(m) - 1, row = __shfl_sync(0xffffffffu, lr, i);
    const float rs = __int_as_float(__shfl_sync(0xffffffffu, sel.y, i));
    const float* p = cx.g->ypart + (i & 7) * DM + (i < 8 ? hs * 64 : 512) + 2 * lane;
    const float2 a = __ldcg((const float2*)p), b = __ldcg((const float2*)(p + TOPC * DM)), c = __ldcg((const float2*)(p + 2 * TOPC * DM)),
                 d = __ldcg((const float2*)(p + 3 * TOPC * DM));
    const uint32_t y = pack2((a.x + b.x) + (c.x + d.x), (a.y + b.y) + (c.y + d.y));
    const uint32_t u = pack2(bf_lo(y) * rs, bf_hi(y) * rs);
    const float2 st = *(const float2*)(cx.sp + SM_STATS + 8 * row);
    const int o = (i < 8 ? row : 128 + (row & 15)) * 128 + ((lane * 4) ^ ((row & 7) << 4));
    *(uint32_t*)(cx.sp + SM_GO + o) = gate2<true>(sub2(*(const uint32_t*)(cx.sp + SM_XO + o), pack2(st.x, st.x)), st.y, make_float2(bf_lo(u), bf_hi(u)));
  }
  __syncwarp();
  if (lane == 0) mbar_arrive(cx.sb + SM_BAR_XG);
  TSH(48)
}
__device__ __forceinline__ void attn_finish8(const Ctx& cx, int qb, int hs, int hw, int lane, __nv_bfloat16* out) {
  bar_sync(BAR_GATE, 96);
#pragma unroll 1
  for (int g = hw; g < 4; g += 3) {
    float acc[8] = {0.f, 0.f, 0.f, 0.f, 0.f, 0.f, 0.f, 0.f};
#pragma unroll 2
    for (int sidx = 0; sidx < 8; sidx++) {
      uint32_t a, b, d, t;
      lds128(cx.sb + SM_P8 + lane * 16 + (sidx * 4 + g) * 512, a, b, d, t);
      acc[0] += bf_lo(a); acc[1] += bf_hi(a & ~TAG); acc[2] += bf_lo(b); acc[3] += bf_hi(b);
      acc[4] += bf_lo(d); acc[5] += bf_hi(d); acc[6] += bf_lo(t); acc[7] += bf_hi(t);
    }
#pragma unroll
    for (int j = 0; j < 4; j++) {
      const int o = (128 + (lane >> 2) + (j & 1) * 8) * 128 + (((2 * g + (j >> 1)) ^ (lane >> 2)) << 4) + (lane & 3) * 4;
      uint32_t* xp = (uint32_t*)(cx.sp + SM_XO + o);
      *xp = fma2(pack2(acc[2 * j], acc[2 * j + 1]), *(const uint32_t*)(cx.sp + SM_GO + o), *xp);
    }
  }
  bar_sync(BAR_GATE, 96);
#pragma unroll 1
  for (int ch = threadIdx.x - 32; ch < 128; ch += 96)
    *(uint4*)at(out, ((qb * 128 + hs * 16 + (ch >> 3)) * DM + 512 + (ch & 7) * 8) * 2) =
        *(const uint4*)(cx.sp + SM_XO + 16384 + (ch ^ ((ch >> 3) & 7)) * 16);
}

__device__ __forceinline__ void ffn_producer(const Ctx& cx, int f, const CUtensorMap* tmWq, const CUtensorMap* tmG,
                                             const CUtensorMap* tmU, const CUtensorMap* tmD) {
  uint64_t keep;
  asm("createpolicy.fractional.L2::evict_normal.b64 %0, 1.0;" : "=l"(keep));
  int st = 0;
#pragma unroll 1
  for (int p = 0; p < 16; p++) {
#pragma unroll 1
    for (int i = 0; i < 5; i++, st++) if (st > 1) load_wq(cx, tmWq, st, i, ((2 * (p & 3) + cx.rank) * 4 + 3) * DH + 64, keep);
  }
  const uint32_t full = cx.sb + SM_FFULL, empty = cx.sb + SM_FEMPTY;
  int pair = 0, u = 0;
#pragma unroll 1
  for (st = 0; st < 14 * 12; st++) {
    const uint32_t sl = st & 7;
    const int unit = pair * 2 + (u & 1), k = u >> 1, k3 = k >= 3 ? k - 3 : k;
    if (unit < 27) {
      mbar_wait(empty + 8 * sl, (st >> 3) & 1);
      __syncwarp();
      if (elect_one()) {
        mbar_expect_tx(full + 8 * sl, FSTAGE);
        if (pair < 9) tma2d_stream(cx.sb + sl * FSTAGE, k < 3 ? tmG : tmU, f * 1152 + unit * 64, k3 * 192, full + 8 * sl);
        else tma2d_stream(cx.sb + sl * FSTAGE, tmD, (unit - 18) * 64, f * 1152 + k * 192, full + 8 * sl);
      }
    }
    if (++u == 12) { u = 0; pair++; }
  }
}
__device__ __forceinline__ void load_x1(uint32_t dst, const CUtensorMap* tmX64, int row, int box, int n, uint32_t bar) {
  mbar_expect_tx(bar, n * 8192);
#pragma unroll 1
  for (int i = 0; i < n; i++) tma2d(dst + i * 8192, tmX64, (box + i) * 64, row, bar);
}
__device__ __forceinline__ void ffn_publish(const Ctx& cx, int f, int w, int lane, const CUtensorMap* tmX64) {
  const uint32_t xs = cx.sb + SM_SLOT + w * 49152, xf = cx.sb + SM_XFULL + w * 32;
#pragma unroll 1
  for (int n = 0; n < 16; n++) {
    const int p = n & 3, row = (f + (n & 12) + 4) * 128 + w * 64;
    if (n < 12 && p == 3) {
      bar_sync(BAR_QS + w, 160);
      if (lane == 0) load_x1(xs, tmX64, row, 4, 4, xf + 8);
      __syncwarp();
    }
    bar_sync(BAR_QS + w, 160);
    const uint32_t e1 = *(const uint32_t*)(cx.sp + SM_TAG + 4) + 1;
    if (lane == 0) {
#pragma unroll
      for (int i = 0; i < 2; i++)
        asm volatile("cp.async.bulk.global.shared::cta.bulk_group [%0], [%1], 8192;"
                     ::"l"(cx.g->q + (((f + (n & 12)) * 8 + 2 * p + i) * 2 + w) * 512), "r"(xs + 32768 + i * 8192) : "memory");
      asm volatile("cp.async.bulk.commit_group;" ::: "memory");
      asm volatile("cp.async.bulk.wait_group.read 0;" ::: "memory");
      if (n < 12 && (p == 0 || p == 3)) load_x1(xs + (p ? 32768 : 0), tmX64, row, p ? 8 : 0, p ? 1 : 4, xf + (p ? 16 : 0));
      asm volatile("cp.async.bulk.wait_group 0;\nfence.proxy.async.global;" ::: "memory");
      asm volatile("st.release.gpu.global.u32 [%0], %1;" ::"l"(&cx.g->qflag[((f + (n & 12)) * 4 + p) * 2 + w]), "r"(e1) : "memory");
    }
    __syncwarp();
    if (n < 12 && p == 1) {
#pragma unroll 1
      for (int i = 0, k = 0; i < 64 && k < (1 << 16); k++) {
        uint32_t m, r, z, t;
        ld_gran(cx.g->stats + row + i + lane, m, r, z, t);
        *(uint2*)(cx.sp + SM_STATS + 8 * (w * 64 + i + lane)) = make_uint2(m, r);
        if (__all_sync(0xffffffffu, t == e1)) i += 32;
      }
    }
    bar_arrive(BAR_QF + w, 160);
  }
}

__device__ __forceinline__ void ffn_consumer(const Ctx& cx, int f, int wg, int cw, int lane, const __nv_bfloat16* x) {
  const int r = lane >> 2, c = lane & 3, tid = cw * 32 + lane;
  const uint32_t full = cx.sb + SM_FFULL, empty = cx.sb + SM_FEMPTY;
  const bool signaller = (tid & 127) == 0;
  prof(wg, 8);
  const unsigned e = *(const uint32_t*)(cx.sp + SM_TAG + 4);
  uint32_t key[8];
#pragma unroll 1
  for (int n = 0; n < (1 << 16); n++) {
    uint32_t bad = 0;
#pragma unroll
    for (int i = 0; i < 8; i++) {
      uint32_t t;
      asm volatile("ld.relaxed.gpu.global.v2.b32 {%0, %1}, [%2];" : "=r"(key[i]), "=r"(t) : "l"(&cx.g->stats[i * 256 + tid].z) : "memory");
      bad |= t ^ (e + 1);
    }
    if (__all_sync(0xffffffffu, bad == 0)) break;
  }
  bar_sync(BAR_QF + wg, 160);
  bar_sync(3, 256);
  if (tid < 8) mbar_arrive(empty + 8 * tid);
  prof(wg, 9);
  int mysel = 0;
#pragma unroll 1
  for (int k = 0; k < TOPC; k++) {
    uint32_t m = key[0];
#pragma unroll
    for (int i = 1; i < 8; i++) m = max(m, key[i]);
    m = __reduce_max_sync(0xffffffffu, m);
    uint32_t* tk = (uint32_t*)(cx.sp + SM_TOPK) + (k & 1) * 8;
    if (lane == 0) tk[cw] = m;
    bar_sync(3, 256);
    m = __reduce_max_sync(0xffffffffu, tk[lane & 7]);
#pragma unroll
    for (int i = 0; i < 8; i++) if (key[i] == m) key[i] = 0;
    if (k == cw) mysel = 0xFFFF - (int)(m & 0xFFFF);
  }
  {
    const float4 st = __ldcg((const float4*)&cx.g->stats[mysel]);
    const uint32_t mm = pack2(st.x, st.x);
#pragma unroll 3
    for (int i = 0; i < 9; i++) {
      const uint32_t t = sub2(*(const uint32_t*)(x + (size_t)mysel * DM + i * 64 + 2 * lane), mm);
      *(uint32_t*)(cx.sp + SM_XSEL + i * 1024 + cw * 128 + (((lane >> 2) ^ cw) << 4) + (lane & 3) * 4) =
          pack2(bf_lo(t) * st.y, bf_hi(t) * st.y);
    }
    const uint32_t k = __float_as_uint(st.z);
    const float score = bf_hi(k ^ ((int)k < 0 ? 0x80000000u : 0xFFFF0000u));
    if (lane == 0 && f == 0) cx.g->sel[cw] = make_int2(mysel, __float_as_int(bfr(rcp(1.0f + ex2(-1.4426950408889634f * score)))));
  }
  asm volatile("fence.proxy.async.shared::cta;" ::: "memory");
  bar_sync(3, 256);
  prof(wg, 10);
  auto run = [&](float (&acc)[4], int st, int n, uint32_t b) {
#pragma unroll 1
    for (int u = 0; u < n; u++, st += 2, b += 3072) {
      const uint32_t sl = st & 7;
      mbar_wait(full + 8 * sl, (st >> 3) & 1);
      wg_fence();
      const uint64_t da = mkdesc(cx.sb + sl * FSTAGE, 16), db = mkdesc(b, 16);
#pragma unroll
      for (int k = 0; k < 12; k++) mma_n8(acc, da + k * 128, db + (k >> 2) * 64 + (k & 3) * 2, u > 0 || k > 0);
      wg_commit();
      wg_wait<0>();
      if (signaller) mbar_arrive(empty + 8 * sl);
    }
    pin(acc);
  };
#pragma unroll 1
  for (int unit = wg; unit < 27; unit += 2) {
    if (unit >> 1 == 9) {
      asm volatile("fence.proxy.async.shared::cta;" ::: "memory");
      bar_sync(3, 256);
      prof(wg, 11);
    }
    const bool gu = unit < 18;
    float a0[4], a1[4];
#pragma unroll 1
    for (int m = 0; m < (gu ? 2 : 1); m++) {
      run(a1, (unit >> 1) * 12 + m * 6 + wg, gu ? 3 : 6, cx.sb + (gu ? SM_XSEL : SM_H));
      if (m == 0) { a0[0] = a1[0]; a0[1] = a1[1]; a0[2] = a1[2]; a0[3] = a1[3]; }
    }
    float u0 = a1[0], u1 = a1[1];
#pragma unroll 1
    for (int i = 0; i < 2; i++) {
      const int fl = (cw & 3) * 16 + r + i * 8;
      if (gu) {
        const uint32_t g = pack2(a0[0], a0[1]);
        const uint32_t h = fma2(pack2(silu_f(bf_lo(g)), silu_f(bf_hi(g))), pack2(u0, u1), 0x80008000u);
        uint8_t* hp = cx.sp + SM_H + unit * 1024 + c * 256 + (fl & 7) * 2;
        *(uint16_t*)(hp + (((fl >> 3) ^ (2 * c)) << 4)) = (uint16_t)h;
        *(uint16_t*)(hp + 128 + (((fl >> 3) ^ (2 * c + 1)) << 4)) = (uint16_t)(h >> 16);
      } else {
        float* yp = cx.g->ypart + (f * TOPC + 2 * c) * DM + (unit - 18) * 64 + fl;
        yp[0] = u0;
        yp[DM] = u1;
      }
      a0[0] = a0[2]; a0[1] = a0[3]; u0 = a1[2]; u1 = a1[3];
    }
  }
  prof(wg, 12);
  bar_sync(3, 256);
  if (tid == 0) atom_add_acq_rel(&cx.g->ycnt);
  prof(wg, 13);
}

constexpr float SUM_HI = 1.8446744e19f, SUM_LO = 9.0949470e-13f;

template <int LO, int HI, int N>
__device__ __forceinline__ void softmax_exp(float (&s)[N]) {
#pragma unroll
  for (int i = LO; i < HI; i++) s[i] = ex2(s[i]);
}
__device__ __forceinline__ void sum_tree(const uint32_t (&pf)[28], bool big, uint32_t& h0, uint32_t& h1) {
  uint32_t t0 = add2(add2(pf[16], pf[18]), add2(pf[20], pf[22])), t1 = add2(add2(pf[17], pf[19]), add2(pf[21], pf[23]));
  if (big) { t0 = add2(t0, add2(pf[24], pf[26])); t1 = add2(t1, add2(pf[25], pf[27])); }
  h0 = add2(add2(add2(add2(pf[0], pf[2]), add2(pf[4], pf[6])), add2(add2(pf[8], pf[10]), add2(pf[12], pf[14]))), t0);
  h1 = add2(add2(add2(add2(pf[1], pf[3]), add2(pf[5], pf[7])), add2(add2(pf[9], pf[11]), add2(pf[13], pf[15]))), t1);
}
__device__ __forceinline__ void exact_attention(float (&o)[16], float& l0, float& l1, const uint32_t (&q)[32], const __nv_bfloat16* kp,
                                                const __nv_bfloat16* vp) {
  float m0 = -3.0e38f, m1 = -3.0e38f;
  l0 = l1 = 0.f;
#pragma unroll
  for (int i = 0; i < 16; i++) o[i] = 0.f;
#pragma unroll 1
  for (int key = 0; key < SEQ; key += 8, kp += 8 * DH, vp += 8 * DH) {
    float d[4] = {0.f, 0.f, 0.f, 0.f};
#pragma unroll
    for (int k = 0; k < 8; k++)
      hmma_k16(d, q[4 * k], q[4 * k + 1], q[4 * k + 2], q[4 * k + 3], *(const uint32_t*)(kp + k * 16), *(const uint32_t*)(kp + k * 16 + 8));
    float x0 = fmaxf(d[0], d[1]), x1 = fmaxf(d[2], d[3]);
    x0 = fmaxf(x0, __shfl_xor_sync(0xffffffffu, x0, 1));
    x1 = fmaxf(x1, __shfl_xor_sync(0xffffffffu, x1, 1));
    x0 = fmaxf(fmaxf(x0, __shfl_xor_sync(0xffffffffu, x0, 2)), m0);
    x1 = fmaxf(fmaxf(x1, __shfl_xor_sync(0xffffffffu, x1, 2)), m1);
    const float sc0 = ex2(m0 - x0), sc1 = ex2(m1 - x1);
    m0 = x0; m1 = x1;
    const uint32_t p0 = pack2(ex2(d[0] - m0), ex2(d[1] - m0)), p1 = pack2(ex2(d[2] - m1), ex2(d[3] - m1));
    l0 = fmaf(l0, sc0, bf_lo(p0) + bf_hi(p0));
    l1 = fmaf(l1, sc1, bf_lo(p1) + bf_hi(p1));
#pragma unroll
    for (int nb = 0; nb < 4; nb++) {
      uint32_t b;
      asm("movmatrix.sync.aligned.m8n8.trans.b16 %0, %1;" : "=r"(b) : "r"(*(const uint32_t*)(vp + nb * 8)));
      o[4 * nb] *= sc0; o[4 * nb + 1] *= sc0; o[4 * nb + 2] *= sc1; o[4 * nb + 3] *= sc1;
      asm volatile("mma.sync.aligned.m16n8k8.row.col.f32.bf16.bf16.f32 {%0, %1, %2, %3}, {%4, %5}, {%6}, {%0, %1, %2, %3};"
                   : "+f"(o[4 * nb]), "+f"(o[4 * nb + 1]), "+f"(o[4 * nb + 2]), "+f"(o[4 * nb + 3]) : "r"(p0), "r"(p1), "r"(b));
    }
  }
}
__device__ __forceinline__ bool inv_sums(float l0, float l1, float& i0, float& i1) {
  l0 += __shfl_xor_sync(0xffffffffu, l0, 1); l1 += __shfl_xor_sync(0xffffffffu, l1, 1);
  l0 += __shfl_xor_sync(0xffffffffu, l0, 2); l1 += __shfl_xor_sync(0xffffffffu, l1, 2);
  i0 = rcp(l0);
  i1 = rcp(l1);
  return !(l0 + l1 <= SUM_HI) | (fminf(l0, l1) < SUM_LO);
}
template <int LO, int HI, int N>
__device__ __forceinline__ void park(uint32_t a, const float (&o)[N], float i0, float i1, bool on = true) {
#pragma unroll
  for (int i = LO; i < HI; i++)
    asm volatile("{\n.reg .pred p;\nsetp.ne.u32 p, %5, 0;\n@p stmatrix.sync.aligned.m8n8.x4.shared.b16 [%0], {%1, %2, %3, %4};\n}"
                 ::"r"(a + i * 2048), "r"(pack2(o[8 * i] * i0, o[8 * i + 1] * i0)), "r"(pack2(o[8 * i + 2] * i1, o[8 * i + 3] * i1)),
                 "r"(pack2(o[8 * i + 4] * i0, o[8 * i + 5] * i0)), "r"(pack2(o[8 * i + 6] * i1, o[8 * i + 7] * i1)), "r"((uint32_t)on) : "memory");
}

template <int I, int HI>
__device__ __forceinline__ void park_paced(uint32_t a, const float (&o)[64], float i0, float i1, int id) {
  if constexpr (I < HI) {
    park<I, I + 2>(a, o, i0, i1);
    if (I + 2 < HI) block_fence(id + I);
    park_paced<I + 2, HI>(a, o, i0, i1, id);
  }
}

__device__ __forceinline__ void attn_consumer(const Ctx& cx, bool hlp, int qb, int hs, int wg, int cw, int lane, const __nv_bfloat16* x,
                                              const __nv_bfloat16* kc, const __nv_bfloat16* vc, __nv_bfloat16* out) {
  const uint32_t full = cx.sb + SM_FULL;
  const uint32_t ring = cx.sb + SM_RING;
  const uint32_t qwg = ring + wg * 16384;
  auto qlane = [&](int l) { return qwg + (cw & 3) * 256 + (l >> 4) * 1024 + (l & 15) * 16; };
  const bool signaller = lane == 0 && (cw & 3) < 2;
  const int my_turn = 1 + wg, other_turn = 2 - wg;
  const uint32_t empty_c = mapa(cx.sb + SM_EMPTY, cw & 1);

  float oA[64], oB[64], i0, i1;
  uint32_t xl[32];
  {
    const int r = lane >> 2, c = lane & 3;
    const int lr0 = cw * 16 + r;
    uint32_t xa[144];
    uint32_t mm0, mm1;
    float rstd0, rstd1, sq0 = 0.f, sq1 = 0.f;
    const uint32_t xf = cx.sb + SM_XFULL + wg * 32, xs = cx.sb + SM_SLOT + wg * 49152;
    auto lo_of = [&](int l) { return ((cw & 3) * 16 + (l & 15)) * 128 + (((l >> 4) ^ (l & 7)) << 4); };
    prof(wg, 0);
    {
      const uint32_t lo = lo_of(lane);
      const uint32_t xb = cx.sb + SM_X + wg * 73728;
      float sm[4][4] = {};
      const uint32_t ws = (lane & 7) == 1 ? 64 : 0;
      uint32_t wb = cx.sb + (ws ? SM_WR + (lane >> 3) * 16 : SM_ONES);
      uint32_t b0[24], b1[24], b2[24];
      mbar_wait(cx.sb + SM_BAR_W, 0);
      TS4(1)
      ln_fetch_b(b0, wb, ws);
      ln_fetch_b(b1, wb, ws);
      ln_fetch_b(b2, wb, ws);
      mbar_wait(xf, 0);
      TS4(2)
      ln_fetch<0, 12>(xa, xb, lo);
      mbar_wait(xf + 8, 0);
      TS4(3)
      ln_fetch<12, 24>(xa, xb, lo);
      ln_sums<0, 12>(xa, sm, b0);
      if (wg == 0) bar_arrive(BAR_XREL + after_fetch<12, 24>(xa), 224);
      mbar_wait(xf + 16, 0);
      TS4(4)
      prof(wg, 1);
      ln_fetch<24, 36>(xa, xb, lo);
      ln_sums<12, 24>(xa, sm, b1);
      ln_sums<24, 36>(xa, sm, b2);
#pragma unroll
      for (int i = 0; i < 4; i++) sm[0][i] = (sm[0][i] + sm[1][i]) + (sm[2][i] + sm[3][i]);
      if (cw == hs && c == 0) {
        *(float*)(cx.sp + SM_RAW + 4 * r) = sm[0][1];
        *(float*)(cx.sp + SM_RAW + 4 * r + 32) = sm[0][3];
      }
      rstd0 = sm[0][0];
      rstd1 = sm[0][2];
      mm0 = pack2(rstd0 * (1.0f / DM), rstd0 * (1.0f / DM));
      mm1 = pack2(rstd1 * (1.0f / DM), rstd1 * (1.0f / DM));
    }
#pragma unroll
    for (int i = 0; i < 16; i++) { xa[2 * i] = sub2(xa[2 * i], mm0); xa[2 * i + 1] = sub2(xa[2 * i + 1], mm1); }
    pin(xa);
    prof(wg, 2);
    TS4(5)

    float (&acc)[64] = oB;
    int st0 = 0;
#pragma unroll 1
    for (int n = 0; n < 16; n++) {
      const int p = n & 3, rb = n >> 2;
      const bool last = p == 3 && !hlp;
#pragma unroll
      for (int i = 0; i < 5; i++) {
        if (i == 4 && last) {
          wg_wait<1>();
          mbar_arrive_cluster(empty_c + 8 * 3, signaller && wg);
          wg_wait<0>();
          pin(acc);
          prof(wg, 6);
#pragma unroll
          for (int j = 0; j < 32; j++) xl[j] = xa[112 + j];
          i0 = rstd0;
          i1 = rstd1;
          goto attention;
        }
        const int st = st0 + i;
        const uint32_t sl = st & 3, slp = (st - 1) & 3;
        if (!wg) mbar_wait(full + 8 * sl, (st >> 2) & 1);
        TS4(8 + 2 * (p * 5 + i))
        const bool join = wg && last;
        if ((i || st0 + wg) && i != (wg ? 4 : 1) && !(join && i == 3)) bar_sync(my_turn, 256);
        wg_fence();
        const uint64_t db = mkdesc(ring + sl * STAGE, 16384);
        const int kb0 = i < 3 ? 8 * i : 8 * i - 4;
#pragma unroll
        for (int k = 0; k < (i == 2 ? 4 : 8); k++) {
          const int kb = kb0 + k;
          mma_n128t(acc, xa[4 * kb], xa[4 * kb + 1], xa[4 * kb + 2], xa[4 * kb + 3], db + k * 128, kb > 0);
        }
        wg_commit();
        TS4(9 + 2 * (p * 5 + i))
        if (wg ? (i == 4 ? st0 < 75 : (i < 2 || i == (join ? 3 : 2))) : i) bar_arrive(other_turn, 256);
        if (p == 0 && i < 4) {
          if (i == 1 && rb) {
            mbar_wait(xf + 8, rb & 1);
            ln_fetch<16, 32>(xa, xs - 32768, lo_of(fresh_lane()));
          }
          if (i == 2 && rb) {
            mbar_wait(xf + 16, rb & 1);
            ln_fetch<32, 36>(xa, xs - 32768, lo_of(fresh_lane()));
          }
#pragma unroll
          for (int j = 0; j < 72; j++)
            if (j >= 2 * (i < 2 ? 8 * i + 8 : 8 * i + 4) && j < 2 * (i == 0 ? 16 : 8 * i + 12)) {
              xa[2 * j] = sub2(xa[2 * j], mm0);
              xa[2 * j + 1] = sub2(xa[2 * j + 1], mm1);
            }
          pin(xa);
        }
        if (i == 4 && n == 0) {
          mbar_wait(cx.sb + SM_BAR_SQ, 0);
          float2* sp = (float2*)(cx.sp + SM_STATS) + lr0;
          float mean0, mean1;
          ln_row(rstd0, sp[0].y, mean0, rstd0);
          ln_row(rstd1, sp[8].y, mean1, rstd1);
          __syncwarp();
          if (c == 0) {
            sp[0] = make_float2(mean0, rstd0);
            sp[8] = make_float2(mean1, rstd1);
          }
          *((uint32_t*)(cx.sp + SM_COLD) + wg) = 0;
          if (!hlp) bar_arrive(BAR_GATE, 352);
          rstd0 *= SM_SCALE_LOG2;
          rstd1 *= SM_SCALE_LOG2;
        }
        if (i == 3 && hlp && p == 3 && rb < 3) bar_arrive(BAR_QS + wg + after_fetch<0, 16>(xa), 160);
        if (i == 4 && p == 3 && rb < 3) {
          const float2* sp = (const float2*)(cx.sp + SM_STATS) + cw * 16 + (fresh_lane() >> 2);
          mm0 = pack2(sp[0].x, sp[0].x);
          mm1 = pack2(sp[8].x, sp[8].x);
          sq0 = sp[0].y * SM_SCALE_LOG2;
          sq1 = sp[8].y * SM_SCALE_LOG2;
#pragma unroll
          for (int j = 0; j < 16; j++) { xa[2 * j] = sub2(xa[2 * j], mm0); xa[2 * j + 1] = sub2(xa[2 * j + 1], mm1); }
          pin(xa);
        }
        if (i == 0) {
          if (wg) {
            wg_wait<0>();
            mbar_arrive_cluster(empty_c + 8 * sl, signaller);
          }
        } else if (i == 2) {
          if (!join) {
            wg_wait<0>();
            mbar_arrive_cluster(empty_c + 8 * sl, signaller);
          }
          if (hlp && p == 3 && rb < 3) {
            mbar_wait(xf, ~rb & 1);
            ln_fetch<0, 16>(xa, xs, lo_of(fresh_lane()));
            pin(xa);
          }
        } else if (i != 3) {
          wg_wait<1>();
          mbar_arrive_cluster(empty_c + 8 * slp, signaller && (i == 4 || !wg));
          wg_wait<0>();
          mbar_arrive_cluster(empty_c + 8 * sl, signaller);
        }
      }
      pin(acc);
      prof(wg, 3 + p);
      TS4(50 + 2 * p)
      st0 += 5;
      if (hlp && st0 > 5) bar_sync(BAR_QF + wg, 160);
      park_paced<0, 8>(qlane(lane) + (hlp ? 5 + wg : 4 + p) * STAGE, acc, rstd0, rstd1, 300);
      if (p || hlp) asm volatile("fence.proxy.async.shared::cta;" ::: "memory");
      if (hlp) bar_arrive(BAR_QS + wg, 160);
      if (p == 3) { rstd0 = sq0; rstd1 = sq1; }
      TS4(51 + 2 * p)
      if (p == 1 && !hlp) {
        float (&ah)[32] = *(float (*)[32])&acc[0];
#pragma unroll
        for (int i = 0; i < 3; i++) {
          const uint32_t sl = (10 + i) & 3;
          if (!wg) mbar_wait(full + 8 * sl, ((10 + i) >> 2) & 1);
          TS4(28 + 2 * i)
          if (i == 0 || i == 2 - wg) bar_sync(my_turn, 256);
          wg_fence();
          const uint64_t db = mkdesc(ring + sl * STAGE, 16);
#pragma unroll
          for (int k = 0; k < 12; k++) {
            const int kb = 12 * i + k;
            if (kb) mma_n64t(ah, xa[4 * kb], xa[4 * kb + 1], xa[4 * kb + 2], xa[4 * kb + 3], db + k * 128, true);
            else mma_n64t_dyn(ah, xa[0], xa[1], xa[2], xa[3], db, blockIdx.y);
          }
          wg_commit();
          TS4(29 + 2 * i)
          if (i == 2 || i != wg) {
            bar_arrive(other_turn, 256);
            if (i) {
              wg_wait<1>();
              mbar_arrive_cluster(empty_c + 8 * ((9 + i) & 3), signaller && i == wg + 1);
            }
            wg_wait<0>();
            mbar_arrive_cluster(empty_c + 8 * sl, signaller);
          }
        }
        pin(ah);
        TS4(54)
        park<0, 4>(qlane(lane) + 6 * STAGE, ah, rstd0, rstd1);
        TS4(55)
        st0 = 13;
        n = 2;
      }
    }
    TS_DUMP()
    ffn_consumer(cx, blockIdx.x & 3, wg, cw, fresh_lane(), x);
    return;
  }

attention:
  uint32_t oa[128];
  float acc[32];
  {
    uint32_t pf[28];
    const uint32_t ql = qlane(fresh_lane());
    uint32_t bad = 0;
    float lA0 = 0.f, lA1 = 0.f, lB0 = 0.f, lB1 = 0.f;
    int t = 0;
    uint32_t ra = 2 * 2048, rb = 2048, rc = 2 * 2048, par = 0;
    const uint64_t dk0 = mkdesc(ring, 16), dv0 = mkdesc(ring, 16384);
    uint64_t dqA = mkdesc_q(qwg + 4 * STAGE), dqB = dqA + 2048;
    auto turn = [&](auto kc_, auto bc_) {
      constexpr int KIND = decltype(kc_)::value, BIG = decltype(bc_)::value;
      constexpr int HB = KIND == 1, ID = 10 * KIND + 30 * BIG, T0 = BIG ? 38 : 0;
      constexpr int NS = BIG ? 56 : 48, SPLIT = (BIG ? 36 : 30) + 2 * HB;
      float s[NS];
      float (&op)[64] = HB ? oA : oB;
      uint32_t h0 = 0, h1 = 0;
      TS2(0)
      bar_sync(my_turn, 256);
      TS2(1)
      if (KIND) { pin(pf); pin(op); }
      mma_qk(s, HB ? dqB : dqA, dk0 + (HB ? ra : rc));
      TS2(2)
      if (KIND) {
        const bool bigp = HB ? BIG : BIG ? t != 10 : t == 66;
        block_fence(ID + 9);
        pin(pf);
        sum_tree(pf, bigp, h0, h1);
        asm volatile("" : "+r"(h0), "+r"(h1)::"memory");
        if (HB) mbar_wait(full + (rb >> 8), par);
        mma_pv(op, pf, dv0 + rb, t != T0 + 2 - HB, bigp);
      } else {
        mbar_wait(full + (rb >> 8), (NST_Q - 1) >> 2 & 1);
#pragma unroll
        for (int k = 0; k < 8; k++) mma_n128t(op, xl[4 * k], xl[4 * k + 1], xl[4 * k + 2], xl[4 * k + 3], dv0 + rb + k * 128, 1);
        wg_commit();
      }
      TS2(3)
      bar_arrive(other_turn, 256);
      (HB ? lA0 : lB0) += bf_lo(h0) + bf_hi(h0);
      (HB ? lA1 : lB1) += bf_lo(h1) + bf_hi(h1);
      wg_wait<1>();
      pin(s);
      TS1(t)
      TS2(4)
      if (KIND == 1) mbar_arrive_cluster_now<ID + 3>(empty_c + (ra >> 8), signaller);
      if (BIG && t == T0 + HB) {
        const uint32_t a = ql + (4 + HB) * STAGE;
        const bool ok = !__any_sync(0xffffffffu, inv_sums(HB ? lB0 : lA0, HB ? lB1 : lA1, i0, i1));
        if (!ok) bad |= 1 << HB;
        (HB ? lB0 : lA0) = 0.f;
        (HB ? lB1 : lA1) = 0.f;
        constexpr int E0 = 10, E1 = (E0 + SPLIT) / 2;
        softmax_exp<0, E0>(s);
#pragma unroll
        for (int i = 0; i < E0; i++) asm volatile("" : "+f"(s[i])::"memory");
        block_fence(ID + 7);
        softmax_exp<E0, E1>(s);
        park<0, 4>(a, HB ? oB : oA, i0, i1, ok);
#pragma unroll
        for (int i = E0; i < E1; i++) asm volatile("" : "+f"(s[i])::"memory");
        block_fence(200 + ID);
        softmax_exp<E1, SPLIT>(s);
        park<4, 8>(a, HB ? oB : oA, i0, i1, ok);
        if (!HB) dqB += 2048;
        prof(wg, 8 + HB);
      } else {
        softmax_exp<0, SPLIT>(s);
      }
      pin(s);
      if (!BIG) block_fence(ID + 4);
      TS2(5)
      wg_wait<0>();
      TS2(6)
      pin(op);
      if (KIND) pin(pf); else pin(xl);
      if (HB) {
        par ^= rc == 2048;
        if (BIG && t == 37) dqA -= 4 * 2048;
        if (BIG && t == 33 && cw == 0) bar_arrive(BAR_HELPER, 64);
      } else {
        mbar_arrive_cluster_now<ID + 5>(empty_c + (rb >> 8), signaller);
        if (KIND) {
          par ^= ra == 2048;
          const uint32_t x = ra;
          ra = rc; rc = rb; rb = x;
        }
      }
      softmax_exp<SPLIT, NS>(s);
#pragma unroll
      for (int i = 0; i < NS / 2; i++) pf[i] = pack2(s[2 * i], s[2 * i + 1]);
      pin(pf);
      if (KIND == 0) {
        block_fence(ID + 6);
        park_paced<0, 6>(ql, oB, i0, i1, 310);

        prof(wg, 7);
      }
      if (HB && !BIG && t == 1) park<6, 8>(ql, oB, i0, i1);
      if (BIG && !HB && t == T0) mbar_wait(cx.sb + SM_BAR_Q + 8 * wg, 0);
      if (HB) mbar_wait(full + (rc >> 8), par);
      t++;
    };
#pragma unroll
    for (int i = 24; i < 28; i++) asm volatile("" : "=r"(pf[i]));
    mbar_wait(full + 8 * 2, 0);
    turn(IC<0>(), IC<0>());
    rb = 3 * 2048; rc = 2048;
    kill(oA);
    const bool never = blockIdx.y == 1;
#pragma unroll 1
    while (true) {
      turn(IC<1>(), IC<0>());
      if (t == 76) break;
      if (t == 10) {
        asm volatile("fence.proxy.async.shared::cta;" ::: "memory");
#pragma unroll 1
        do {
#pragma unroll 1
          do turn(IC<2>(), IC<1>()); while (never);
          turn(IC<1>(), IC<1>());
        } while (t != 66);
      }
#pragma unroll 1
      do turn(IC<2>(), IC<0>()); while (never);
    }
    auto scale = [&](auto lo, auto hi) {
#pragma unroll
      for (int i = decltype(lo)::value; i < decltype(hi)::value; i++) {
        oa[32 + 2 * i] = pack2(oA[4 * i] * i0, oA[4 * i + 1] * i0);
        oa[32 + 2 * i + 1] = pack2(oA[4 * i + 2] * i1, oA[4 * i + 3] * i1);
        asm volatile("" : "+r"(oa[32 + 2 * i]), "+r"(oa[32 + 2 * i + 1])::"memory");
      }
    };
    TS3(1)
    volatile uint32_t* const cold = (volatile uint32_t*)(cx.sp + SM_COLD) + wg;
    if (inv_sums(lA0, lA1, i0, i1)) bad |= 4;
#pragma unroll
    for (int i = 0; i < 8; i++) ldsm4(ql + 4 * STAGE + i * 2048, oa[4 * i], oa[4 * i + 1], oa[4 * i + 2], oa[4 * i + 3]);
    {
      uint32_t h0, h1;
      sum_tree(pf, false, h0, h1);
      lB0 += bf_lo(h0) + bf_hi(h0);
      lB1 += bf_lo(h1) + bf_hi(h1);
      asm volatile("" : "+f"(lB0), "+f"(lB1)::"memory");
    }
    scale(IC<0>(), IC<4>());
    if (bad) *cold = 1;
    block_fence(93);
    TS3(2)
    bar_sync(my_turn, 256);
    TS3(3)
    pin(pf); pin(oB);
    mma_pv(oB, pf, dv0 + 2 * 2048, true, false);
    block_fence(91);
    TS3(4)
    const uint32_t held = *cold;
    if (inv_sums(lB0, lB1, lB0, lB1)) bad |= 8;
    const uint64_t db = mkdesc(ring + 3 * STAGE, 16);
    scale(IC<4>(), IC<12>());
    mbar_arrive_cluster_now<94>(empty_c, signaller && !held);
#pragma unroll
    for (int i = 0; i < 32; i++) asm volatile("" : "+r"(oa[i])::"memory");
    wg_fence();
#pragma unroll
    for (int k = 0; k < 8; k++) mma_n64t(acc, oa[4 * k], oa[4 * k + 1], oa[4 * k + 2], oa[4 * k + 3], db + k * 128, k > 0);
    wg_commit();
    block_fence(95);
    scale(IC<12>(), IC<16>());
    TS3(5)
    wg_fence();
#pragma unroll
    for (int k = 8; k < 16; k++) mma_n64t(acc, oa[4 * k], oa[4 * k + 1], oa[4 * k + 2], oa[4 * k + 3], db + k * 128, 1);
    wg_commit();
    bar_arrive(other_turn, 256);
    if (bad) *cold = 1;
    bar_sync(4 + wg, 128);
    const uint32_t is_cold = *cold;
    wg_wait<2>();
    pin(oB); pin(pf);
    TS(76)
    TS3(6)
    mbar_arrive_cluster_now<97>(empty_c + 8 * 2, signaller);
#pragma unroll
    for (int i = 16; i < 24; i++) ldsm4(ql + 5 * STAGE + (i & 7) * 2048, oa[4 * i], oa[4 * i + 1], oa[4 * i + 2], oa[4 * i + 3]);
#pragma unroll
    for (int i = 0; i < 16; i++) {
      oa[96 + 2 * i] = pack2(oB[4 * i] * lB0, oB[4 * i + 1] * lB0);
      oa[96 + 2 * i + 1] = pack2(oB[4 * i + 2] * lB1, oB[4 * i + 3] * lB1);
    }
    TS3(7)
    if (!wg) mbar_wait(full + 8 * 1, 0);
    TS3(8)
    wg_wait<0>();
    pin(acc); pin(oa);
    if (__any_sync(0xffffffffu, is_cold)) {
      bad = __reduce_or_sync(0xffffffffu, bad);
      if (!(bad & 8)) {
#pragma unroll
        for (int i = 24; i < 32; i++) stsm4(ql + 6 * STAGE + (i & 7) * 2048, oa[4 * i], oa[4 * i + 1], oa[4 * i + 2], oa[4 * i + 3]);
      }
#pragma unroll 1
      for (int h = 0; h < 4; h++) {
        if (bad >> h & 1) {
          const uint32_t a = ql + ((0x6054 >> (4 * h)) & 7) * STAGE;
          const int l = fresh_lane(), o = (hs * 2 + (h >> 1)) * SEQ * DH + (l >> 2) * DH + (l & 3) * 2;
          uint32_t q[32];
#pragma unroll
          for (int i = 0; i < 8; i++) ldsm4(a + i * 2048, q[4 * i], q[4 * i + 1], q[4 * i + 2], q[4 * i + 3]);
#pragma unroll 1
          for (int i = 0; i < 4; i++) {
            float ox[16], l0, l1;
            exact_attention(ox, l0, l1, q, kc + o, vc + o + i * 32);
            inv_sums(l0, l1, l0, l1);
            park<0, 2>(a + i * 4096, ox, l0, l1);
          }
        }
      }
      __syncwarp();
#pragma unroll
      for (int i = 0; i < 32; i++)
        if ((i >> 3) != 1 || (bad & 4))
          ldsm4(ql + ((0x6504 >> (4 * (i >> 3))) & 7) * STAGE + (i & 7) * 2048, oa[4 * i], oa[4 * i + 1], oa[4 * i + 2], oa[4 * i + 3]);
      pin(oa);
      asm volatile("fence.proxy.async.shared::cta;" ::: "memory");
      bar_sync(4 + wg, 128);
      mbar_arrive_cluster(empty_c, signaller && held);
      wg_fence();
#pragma unroll
      for (int k = 0; k < 16; k++) mma_n64t(acc, oa[4 * k], oa[4 * k + 1], oa[4 * k + 2], oa[4 * k + 3], db + k * 128, k > 0);
      wg_commit();
      wg_wait<0>();
      pin(acc);
    }
    mbar_arrive_cluster(empty_c + 8 * 3, signaller);
  }

  prof(wg, 10);
  TS3(9)
  {
    lane = fresh_lane();
    const int tw = (cw & 3) * 32 + lane;
    float red[32];
    kill(red);
    const uint32_t tag = *(const uint32_t*)(cx.sp + SM_TAG);
    uint4* const xch = at(cx.g->part, ((qb * 64 * 2 + wg) * 4 * 128 + tw) * 16);
    int nrx = 1;
    auto region = [](int s, int h) { return h ? 1 + (s & 1) : (s & 1) ? 0 : 3; };
    auto half_step = [&](int s, auto hc, bool arrive) {
      constexpr int h = decltype(hc)::value;
      const uint64_t db = mkdesc(ring + region(s, h) * STAGE, 16);
      bar_sync(my_turn, 256);
      pin(oa);
      wg_fence();
#pragma unroll
      for (int k = 0; k < 16; k++) {
        const int kb = h * 16 + k;
        mma_n64t(acc, oa[4 * kb], oa[4 * kb + 1], oa[4 * kb + 2], oa[4 * kb + 3], db + k * 128, kb > 0);
      }
      wg_commit();
      if (arrive) bar_arrive(other_turn, 256);
    };
    auto await = [&](int s, int h) { mbar_wait(full + 8 * region(s, h), ((s >> 1) ^ h ^ 1) & 1); };
    auto fetch = [&](uint32_t (&g)[16], int n) {
      const uint4* p = at(xch, (hs * 7 + n - 1) * 16384);
#pragma unroll
      for (int i = 0; i < 4; i++) ld_gran(p + i * 128, g[4 * i], g[4 * i + 1], g[4 * i + 2], g[4 * i + 3]);
    };
    uint32_t g[16];
    bool pend = false;
#pragma unroll 1
    for (int s = 0;; s++) {
      half_step(s, IC<1>(), s + wg < 9);
      if (s == 8) break;
      TS3(s < 3 ? 16 + 8 * s : 75)
      if (s == 0) {
        bar_arrive(BAR_OA, 352);
#pragma unroll
        for (int i = 0; i < 32; i++) red[i] = 0.f;
      }
      await(s + 1, 0);
      TS3(s < 3 ? 17 + 8 * s : 75)
      wg_wait<0>();
      TS3(s < 3 ? 18 + 8 * s : 75)
      mbar_arrive_cluster(empty_c + 8 * region(s, 1), signaller && s < 7);
      pin(acc);
      TS(77 + s)
      prof(wg, 12 + s);
      uint4* p = at(xch, (s == 0 ? 56 + hs : ((hs + s) & 7) * 7 + s - 1) * 16384);
#pragma unroll
      for (int i = 0; i < 4; i++)
        st_gran(p + i * 128, (pack2(acc[8 * i], acc[8 * i + 1]) & ~TAG) | tag, pack2(acc[8 * i + 2], acc[8 * i + 3]),
                pack2(acc[8 * i + 4], acc[8 * i + 5]), pack2(acc[8 * i + 6], acc[8 * i + 7]));
      TS3(s < 3 ? 19 + 8 * s : 75)
      half_step(s + 1, IC<0>(), true);
      TS3(s < 3 ? 20 + 8 * s : 75)
      if (pend && granules_ok(g, tag)) { add_granules(red, g); nrx++; }
      pend = nrx < s;
      if (pend) fetch(g, nrx);
      await(s + 1, 1);
      TS3(s < 3 ? 21 + 8 * s : 75)
      wg_wait<0>();
      TS3(s < 3 ? 22 + 8 * s : 75)
      mbar_arrive_cluster(empty_c + 8 * region(s + 1, 0), signaller && s < 6);
    }
    uint32_t xv[16], gt[16], g2[16];
    TS3(42)
    const bool ok = granules_ok(g, tag);
    TS3(43)
    nrx += ok;
    fetch(g2, nrx);
    mbar_wait(cx.sb + SM_BAR_XG, 0);
    const uint32_t frag = (cw * 16 + (lane & 15)) * 128 + (((lane >> 4) ^ (lane & 7)) << 4);
#pragma unroll
    for (int i = 0; i < 4; i++) {
      ldsm4(cx.sb + SM_XO + (frag ^ (i << 5)), xv[4 * i], xv[4 * i + 1], xv[4 * i + 2], xv[4 * i + 3]);
      ldsm4(cx.sb + SM_GO + (frag ^ (i << 5)), gt[4 * i], gt[4 * i + 1], gt[4 * i + 2], gt[4 * i + 3]);
    }
    if (ok) add_granules(red, g);
    TS3(44)
    wg_wait<0>();
    pin(acc);
    TS(85)
#pragma unroll
    for (int i = 0; i < 32; i++) red[i] += acc[i];
    pin(red);
#pragma unroll 1
    for (int spins = 0; spins < (1 << 16); spins++) {
      if (granules_ok(g2, tag)) {
        add_granules(red, g2);
        if (++nrx == 8) break;
      }
      fetch(g2, nrx);
    }
    uint32_t ow[16];
#pragma unroll
    for (int i = 0; i < 16; i++) ow[i] = pack2(red[2 * i], red[2 * i + 1]);
    prof(wg, 20);
    TS(86)
#pragma unroll
    for (int i = 0; i < 16; i++) ow[i] = fma2(ow[i], gt[i], xv[i]);
#pragma unroll
    for (int i = 0; i < 4; i++) stsm4(cx.sb + SM_XO + (frag ^ (i << 5)), ow[4 * i], ow[4 * i + 1], ow[4 * i + 2], ow[4 * i + 3]);
    __syncwarp();
    __nv_bfloat16* const op = at(out, ((qb * 128 + cw * 16 + (lane >> 3)) * DM + hs * 64 + (lane & 7) * 8) * 2);
#pragma unroll
    for (int i = 0; i < 4; i++) {
      uint4 v;
      const int row = cw * 16 + i * 4 + (lane >> 3);
      lds128(cx.sb + SM_XO + row * 128 + (((lane ^ row) & 7) << 4), v.x, v.y, v.z, v.w);
      asm volatile("st.global.v4.b32 [%0], {%1, %2, %3, %4};" ::"l"(op + i * 4 * DM),
                   "r"(v.x), "r"(v.y), "r"(v.z), "r"(v.w) : "memory");
    }
    prof(wg, 22);
    TS(87)
    TS_DUMP()
  }
}

struct KvMaps { CUtensorMap m[4]; };
__global__ void __cluster_dims__(2, 1, 1) __launch_bounds__(THREADS, 1)
fused_kernel(const __nv_bfloat16* __restrict__ x, const __nv_bfloat16* __restrict__ w_r, const __nv_bfloat16* __restrict__ kc,
             const __nv_bfloat16* __restrict__ vc, __nv_bfloat16* __restrict__ out, Scratch* scratch,
             const __grid_constant__ CUtensorMap tmX, const __grid_constant__ CUtensorMap tmWq,
             const __grid_constant__ KvMaps tmKV, const __grid_constant__ CUtensorMap tmWo,
             const __grid_constant__ CUtensorMap tmG, const __grid_constant__ CUtensorMap tmU,
             const __grid_constant__ CUtensorMap tmD, const __grid_constant__ CUtensorMap tmX16,
             const __grid_constant__ CUtensorMap tmWq96, const __grid_constant__ CUtensorMap tmX64) {
  extern __shared__ __align__(1024) uint8_t smem_raw[];
  prof(0, 23, 511);
  Ctx cx;
  cx.sb = smem_u32(smem_raw);
  cx.sp = smem_raw;
  cx.g = scratch;
  cx.rank = blockIdx.x & 1;
  const int warp = __shfl_sync(0xffffffffu, threadIdx.x >> 5, 0);
  const int cluster = blockIdx.x >> 1;
  const bool is_ffn = blockIdx.x >= N_ATT_CTA;
  const int c7 = ((cluster - 36) * 37) >> 8;
  const int hs = cluster < 4 ? 4 + cluster : cluster < 36 ? (cluster - 4) >> 3 : 4 + c7;
  const int qb = (cluster < 4 ? 0 : cluster < 36 ? (cluster - 4) & 7 : cluster - (is_ffn ? 36 : 35) - 7 * c7) * 2 + cx.rank;

  auto load_x = [&](int w) {
#pragma unroll
    for (int i = 0; i < 3; i++) {
      mbar_expect_tx(cx.sb + SM_XFULL + 32 * w + 8 * i, 24576);
      tma3d(cx.sb + SM_X + (3 * w + i) * 24576, &tmX, qb * 128 + w * 64, i * 3, cx.sb + SM_XFULL + 32 * w + 8 * i);
    }
  };
  if (warp < 4) {
    asm volatile("setmaxnreg.dec.sync.aligned.u32 24;");
    if (elect_one()) {
      if (warp == 0) TSP(64)
      if (warp < 2) {
#pragma unroll
        for (int i = 0; i < 4; i++) mbar_init(cx.sb + SM_FULL + 32 * warp + 8 * i, 1 + 3 * warp);
        mbar_init(cx.sb + SM_BAR_XG + 8 * warp, 1);
        mbar_init(cx.sb + SM_BAR_Q + 8 * warp, 1);
        if (warp) mbar_init(cx.sb + SM_BAR_MISC, 1);
      } else if (is_ffn) {
#pragma unroll
        for (int i = 0; i < 8; i++) mbar_init(cx.sb + (warp == 2 ? SM_FFULL : SM_FEMPTY) + 8 * i, 1);
      }
      asm volatile("fence.mbarrier_init.release.cluster;" ::: "memory");
    }
    __syncwarp();
    cluster_arrive();
    if (warp == 0) TSP(70)
    cluster_wait();
    if (warp == 0) TSP(71)
    prof(0, 24, 511);
    if (warp == 0) {
      if (is_ffn) ffn_producer(cx, qb, &tmWq, &tmG, &tmU, &tmD);
      else attn_producer(cx, qb, hs, tmKV.m, &tmWq, &tmWq96, &tmWo);
      prof(0, 25, 511);
    } else {
      sq_publish(cx, qb, hs, warp - 1, read_lane());
      if (warp == 3) sq_collect(cx, qb, read_lane());
      if (!is_ffn) {
        attn_gate(cx, qb, hs, warp - 1, threadIdx.x - 32, x);
        if (warp == 1) TSP(65)
        asm volatile("fence.proxy.async.global;" ::: "memory");
        if (warp == 1) attn_helper(cx, qb, hs, fresh_lane(), &tmX16);
        else bar_arrive(BAR_OA, 352);
        attn_finish8(cx, qb, hs, warp - 1, fresh_lane(), out);
      } else if (warp < 3) {
        ffn_publish(cx, qb, warp - 1, fresh_lane(), &tmX64);
      }
    }
    __syncwarp();
    cluster_arrive();
    cluster_wait();
  } else {
    if (warp == 4 && elect_one()) {
#pragma unroll
      for (int i = 0; i < 3; i++) mbar_init(cx.sb + SM_XFULL + 8 * i, 1);
      TSP(66)
      load_x(0);
#pragma unroll
      for (int i = 4; i < 7; i++) mbar_init(cx.sb + SM_XFULL + 8 * i, 1);
      asm volatile("fence.mbarrier_init.release.cluster;" ::: "memory");
    }
    if (warp == 5 && elect_one()) {
      mbar_init(cx.sb + SM_BAR_W, 1);
      asm volatile("fence.mbarrier_init.release.cluster;" ::: "memory");
      *(uint4*)(cx.sp + SM_ONES) = make_uint4(0x3F803F80u, 0x3F803F80u, 0x3F803F80u, 0x3F803F80u);
      mbar_expect_tx(cx.sb + SM_BAR_W, DM * 2);
      bulk_load(cx.sb + SM_WR, w_r, DM * 2, cx.sb + SM_BAR_W);
    }
    __syncwarp();
    cluster_arrive();
    if (warp == 4 && elect_one()) {
      load_x(1);
      TSP(67)
    }
    __syncwarp();
    asm volatile("setmaxnreg.inc.sync.aligned.u32 240;");
    const int cw = warp - 4, wg = cw >> 2;
    cluster_wait();
    if (warp == 8 && elect_one()) {
      const uint64_t pol = policy_evict_first();
#pragma unroll
      for (int i = 0; i < 4; i++) {
        if (!(i & 1)) mbar_expect_tx(cx.sb + SM_FULL + 4 * i, 32768);
        tma2d_mc(cx.sb + SM_RING + (i >> 1) * STAGE + cx.rank * 16384 + (i & 1) * 8192, &tmWq,
                 is_ffn ? (cx.rank * 4 + 3) * DH + 64 : hs * 512 + cx.rank * 64, i * 64, cx.sb + SM_FULL + 8 * (i >> 1), pol);
      }
      TSP(72)
    }
    __syncwarp();
    attn_consumer(cx, is_ffn, qb, hs, wg, cw, read_lane(), x, kc, vc, out);
  }
}

typedef CUresult (*EncodeFn)(CUtensorMap*, CUtensorMapDataType, cuuint32_t, void*, const cuuint64_t*, const cuuint64_t*,
                             const cuuint32_t*, const cuuint32_t*, CUtensorMapInterleave, CUtensorMapSwizzle,
                             CUtensorMapL2promotion, CUtensorMapFloatOOBfill);

void encode(EncodeFn fn, CUtensorMap* m, const void* p, int rank, const cuuint64_t* dims, const cuuint64_t* strides,
            const cuuint32_t* box) {
  const cuuint32_t es[5] = {1, 1, 1, 1, 1};
  fn(m, CU_TENSOR_MAP_DATA_TYPE_BFLOAT16, rank, const_cast<void*>(p), dims, strides, box, es, CU_TENSOR_MAP_INTERLEAVE_NONE,
     CU_TENSOR_MAP_SWIZZLE_128B, CU_TENSOR_MAP_L2_PROMOTION_L2_128B, CU_TENSOR_MAP_FLOAT_OOB_FILL_NONE);
}
void encode2d(EncodeFn fn, CUtensorMap* m, const void* p, uint64_t rows, uint64_t cols, uint32_t box_rows) {
  const cuuint64_t dims[2] = {cols, rows}, strides[1] = {cols * 2};
  const cuuint32_t box[2] = {64, box_rows};
  encode(fn, m, p, 2, dims, strides, box);
}

}

extern "C" void kernel_launch(void* const* d_in, const int* in_sizes, int n_in, void* d_out, int out_size) {
  (void)in_sizes; (void)n_in; (void)out_size;
  void* fnp = nullptr;
  cudaDriverEntryPointQueryResult qr;
  cudaGetDriverEntryPoint("cuTensorMapEncodeTiled", &fnp, cudaEnableDefault, &qr);
  EncodeFn fn = (EncodeFn)fnp;
  CUtensorMap tmWq, tmWo, tmG, tmU, tmD, tmX, tmX16, tmWq96, tmX64;
  encode2d(fn, &tmX64, d_in[0], SEQ, DM, 64);
  encode2d(fn, &tmWq96, d_in[3], DM, 4096, 96);
  encode2d(fn, &tmX16, d_in[0], SEQ, DM, 16);
  KvMaps tmKV;
  for (int i = 0; i < 4; i++) encode2d(fn, &tmKV.m[i], d_in[1 + (i & 1)], 16 * SEQ, DH, i < 2 ? 112 : 96);
  encode2d(fn, &tmWq, d_in[3], DM, 4096, 64);
  {
    const cuuint64_t dims[3] = {64, SEQ, 9}, strides[2] = {DM * 2, 128};
    const cuuint32_t box[3] = {64, 64, 3};
    encode(fn, &tmX, d_in[0], 3, dims, strides, box);
  }
  encode2d(fn, &tmWo, d_in[4], 4096, DM, 128);
  encode2d(fn, &tmG, d_in[7], DM, FF, 192);
  encode2d(fn, &tmU, d_in[8], DM, FF, 192);
  encode2d(fn, &tmD, d_in[9], FF, DM, 192);
  cudaFuncSetAttribute(fused_kernel, cudaFuncAttributeMaxDynamicSharedMemorySize, SM_TOTAL);
  void* scratch = nullptr;
  cudaGetSymbolAddress(&scratch, g_scratch);
  fused_kernel<<<N_CTA, THREADS, SM_TOTAL>>>((const __nv_bfloat16*)d_in[0], (const __nv_bfloat16*)d_in[6], (const __nv_bfloat16*)d_in[1],
                                            (const __nv_bfloat16*)d_in[2], (__nv_bfloat16*)d_out, (Scratch*)scratch, tmX, tmWq, tmKV,
                                            tmWo, tmG, tmU, tmD, tmX16, tmWq96, tmX64);
}
```

```cpp
#include <cuda_runtime.h>
#include <cuda_bf16.h>
#include <cuda.h>
#include <stdint.h>

namespace {

constexpr int SEQ = 2048, DM = 576, DH = 128, FF = 4608, TOPC = 8;
constexpr int N_ATT_CTA = 128, N_CTA = 132;
constexpr int THREADS = 384;

constexpr uint32_t SM_RING = 0;
constexpr uint32_t STAGE = 32768;
constexpr uint32_t SM_SLOT = 131072;
constexpr uint32_t FSTAGE = 24576;
constexpr uint32_t SM_XSEL = 196608;
constexpr uint32_t SM_H = 205824;
constexpr uint32_t SM_MISC = 229376;
constexpr uint32_t SM_FULL = SM_MISC, SM_EMPTY = SM_MISC + 32, SM_FFULL = SM_MISC + 64, SM_BAR_MISC = SM_MISC + 128,
                   SM_COLD = SM_MISC + 136, SM_TAG = SM_MISC + 144, SM_BAR_W = SM_MISC + 152, SM_ONES = SM_MISC + 160,
                   SM_BAR_Q = SM_MISC + 176, SM_XFULL = SM_MISC + 192, SM_BAR_XG = SM_MISC + 304, SM_BAR_SQ = SM_MISC + 312,
                   SM_STATS = SM_MISC + 320, SM_FEMPTY = SM_MISC + 1344, SM_RAW = SM_FEMPTY, SM_WR = SM_MISC + 1408, SM_TOPK = SM_WR;
constexpr uint32_t SM_TOTAL = SM_MISC + 2560;
constexpr uint32_t SM_X = SM_MISC - 147456;

constexpr int BAR_GATE = 6, BAR_HELPER = 7, BAR_OA = 8, BAR_XREL = 13, BAR_QS = 9, BAR_QF = 11;
constexpr int NST_Q = 18, NST_KV = 76, NST_O = 18;
constexpr float SM_SCALE_LOG2 = 0.08838834764831845f * 1.4426950408889634f;

struct Scratch {
  uint4 part[16 * 64 * 2 * 4 * 128];
  uint4 gate[N_ATT_CTA * 1152];
  uint4 q[16 * 8 * 2 * 512];
  uint2 sq[SEQ];
  uint4 stats[SEQ];
  float ypart[4 * TOPC * DM];
  int2 sel[16];
  unsigned launch[160];
  unsigned pad0, ycnt, pad[30];
  unsigned qflag[128];
};
__device__ __align__(1024) Scratch g_scratch;

__device__ __forceinline__ void prof(int, int, int = 0) {}

#define TS(id) {}
#define TS_DUMP() {}
#define TSH(k) {}
#define TS4(k) {}
#define TSP(k) {}
#define TS1(id) TS(id)
#define TS2(k) {}
#define TS3(k) {}

__device__ __forceinline__ uint32_t smem_u32(const void* p) { return (uint32_t)__cvta_generic_to_shared(p); }
__device__ __forceinline__ void mbar_init(uint32_t bar, uint32_t cnt) {
  asm volatile("mbarrier.init.shared::cta.b64 [%0], %1;" ::"r"(bar), "r"(cnt) : "memory");
}
__device__ __forceinline__ void mbar_expect_tx(uint32_t bar, uint32_t bytes) {
  asm volatile("mbarrier.arrive.expect_tx.shared::cta.b64 _, [%0], %1;" ::"r"(bar), "r"(bytes) : "memory");
}
__device__ __forceinline__ void mbar_arrive(uint32_t bar) {
  asm volatile("mbarrier.arrive.shared::cta.b64 _, [%0];" ::"r"(bar) : "memory");
}
__device__ __forceinline__ void mbar_arrive_cluster(uint32_t bar_cluster_addr, bool pred) {
  asm volatile("{\n.reg .pred p;\nsetp.ne.u32 p, %1, 0;\n@p mbarrier.arrive.shared::cluster.b64 _, [%0];\n}"
               ::"r"(bar_cluster_addr), "r"((uint32_t)pred) : "memory");
}
template <int ID>
__device__ __forceinline__ void mbar_arrive_cluster_now(uint32_t bar_cluster_addr, bool pred) {
  asm volatile("{\n.reg .pred p, q;\nsetp.ne.u32 p, %1, 0;\nsetp.eq.u32 q, %2, %3;\n"
               "ARR_LOOP:\n@p mbarrier.arrive.shared::cluster.b64 _, [%0];\n@q bra.uni ARR_LOOP;\n}"
               ::"r"(bar_cluster_addr), "r"((uint32_t)pred), "r"(blockIdx.y), "n"(ID) : "memory");
}
__device__ __forceinline__ void block_fence(int id) {
  asm volatile("{\n.reg .pred q;\nsetp.eq.u32 q, %0, %1;\nBF_LOOP:\n@q st.volatile.shared.u32 [%0], %0;\n@q bra.uni BF_LOOP;\n}"
               ::"r"(blockIdx.y), "r"(id) : "memory");
}
__device__ __forceinline__ void mbar_wait(uint32_t bar, uint32_t parity) {
  asm volatile("{\n.reg .pred p, q;\n.reg .u32 n;\nmov.u32 n, 0;\n"
               "WAIT_LOOP:\nmbarrier.try_wait.parity.shared::cta.b64 p, [%0], %1;\n"
               "add.u32 n, n, 1;\nsetp.lt.u32 q, n, 262144;\nand.pred q, q, !p;\n@q bra WAIT_LOOP;\n}"
               ::"r"(bar), "r"(parity) : "memory");
}
__device__ __forceinline__ uint32_t mapa(uint32_t addr, uint32_t rank) {
  uint32_t r;
  asm volatile("mapa.shared::cluster.u32 %0, %1, %2;" : "=r"(r) : "r"(addr), "r"(rank));
  return r;
}
__device__ __forceinline__ void cluster_arrive() { asm volatile("barrier.cluster.arrive.relaxed.aligned;" ::: "memory"); }
__device__ __forceinline__ bool elect_one() {
  uint32_t p;
  asm volatile("{\n.reg .pred p;\nelect.sync _|p, 0xffffffff;\nselp.u32 %0, 1, 0, p;\n}" : "=r"(p));
  return p;
}
__device__ __forceinline__ int read_lane() { return threadIdx.x & 31; }
__device__ __forceinline__ int fresh_lane() {
  int l;
  asm volatile("mov.u32 %0, %%laneid;" : "=r"(l));
  return l;
}
template <class T> __device__ __forceinline__ T* at(T* p, uint32_t bytes) {
  asm("" : "+r"(bytes));
  return (T*)((const char*)p + bytes);
}
__device__ __forceinline__ void cluster_wait() { asm volatile("barrier.cluster.wait.acquire.aligned;" ::: "memory"); }
__device__ __forceinline__ void bar_sync(int id, int n) { asm volatile("barrier.cta.sync %0, %1;" ::"r"(id), "r"(n) : "memory"); }
__device__ __forceinline__ void bar_arrive(int id, int n) { asm volatile("barrier.cta.arrive %0, %1;" ::"r"(id), "r"(n) : "memory"); }

__device__ __forceinline__ uint64_t policy_evict_first() {
  uint64_t p;
  asm("createpolicy.fractional.L2::evict_first.b64 %0, 1.0;" : "=l"(p));
  return p;
}
__device__ __forceinline__ void tma2d_mc(uint32_t dst, const CUtensorMap* tm, int c0, int c1, uint32_t bar, uint64_t pol) {
  asm volatile("cp.async.bulk.tensor.2d.shared::cluster.global.mbarrier::complete_tx::bytes.multicast::cluster.L2::cache_hint"
               " [%0], [%1, {%2, %3}], [%4], %5, %6;"
               ::"r"(dst), "l"(tm), "r"(c0), "r"(c1), "r"(bar), "h"((uint16_t)3), "l"(pol) : "memory");
}
__device__ __forceinline__ void tma3d(uint32_t dst, const CUtensorMap* tm, int c1, int c2, uint32_t bar) {
  asm volatile("cp.async.bulk.tensor.3d.shared::cluster.global.mbarrier::complete_tx::bytes [%0], [%1, {%2, %3, %4}], [%5];"
               ::"r"(dst), "l"(tm), "r"(0), "r"(c1), "r"(c2), "r"(bar) : "memory");
}
__device__ __forceinline__ void tma2d(uint32_t dst, const CUtensorMap* tm, int c0, int c1, uint32_t bar) {
  asm volatile("cp.async.bulk.tensor.2d.shared::cluster.global.mbarrier::complete_tx::bytes [%0], [%1, {%2, %3}], [%4];"
               ::"r"(dst), "l"(tm), "r"(c0), "r"(c1), "r"(bar) : "memory");
}
__device__ __forceinline__ void tma2d_stream(uint32_t dst, const CUtensorMap* tm, int c0, int c1, uint32_t bar) {
  asm volatile("{\n.reg .b64 pol;\ncreatepolicy.fractional.L2::evict_first.b64 pol, 1.0;\n"
               "cp.async.bulk.tensor.2d.shared::cluster.global.mbarrier::complete_tx::bytes.L2::cache_hint [%0], [%1, {%2, %3}], [%4], pol;\n}"
               ::"r"(dst), "l"(tm), "r"(c0), "r"(c1), "r"(bar) : "memory");
}
__device__ __forceinline__ void bulk_load(uint32_t dst, const void* src, uint32_t bytes, uint32_t bar) {
  asm volatile("cp.async.bulk.shared::cluster.global.mbarrier::complete_tx::bytes [%0], [%1], %2, [%3];"
               ::"r"(dst), "l"(src), "r"(bytes), "r"(bar) : "memory");
}
__device__ __forceinline__ void tma2d_prefetch(const CUtensorMap* tm, int c0, int c1) {
  asm volatile("cp.async.bulk.prefetch.tensor.2d.L2.global [%0, {%1, %2}];" ::"l"(tm), "r"(c0), "r"(c1) : "memory");
}

__device__ __forceinline__ void wg_fence() { asm volatile("wgmma.fence.sync.aligned;" ::: "memory"); }
__device__ __forceinline__ void wg_commit() { asm volatile("wgmma.commit_group.sync.aligned;" ::: "memory"); }
template <int N> __device__ __forceinline__ void wg_wait() { asm volatile("wgmma.wait_group.sync.aligned %0;" ::"n"(N) : "memory"); }

__device__ __forceinline__ uint64_t mkdesc(uint32_t addr, uint32_t lbo_bytes) {
  return (uint64_t)(((addr & 0x3FFFF) >> 4) | ((lbo_bytes >> 4) << 16)) | ((uint64_t)0x40000040u << 32);
}
__device__ __forceinline__ uint64_t mkdesc_q(uint32_t addr) {
  return (uint64_t)(((addr & 0x3FFFF) >> 4) | (64u << 16)) | ((uint64_t)8 << 32);
}
template <int N> __device__ __forceinline__ void pin(float (&a)[N]) {
#pragma unroll
  for (int i = 0; i < N; i++) asm volatile("" : "+f"(a[i])::"memory");
}
template <int N> __device__ __forceinline__ void kill(float (&a)[N]) {
#pragma unroll
  for (int i = 0; i < N; i++) asm volatile("" : "=f"(a[i]));
}
template <int N> __device__ __forceinline__ void pin(uint32_t (&a)[N]) {
#pragma unroll
  for (int i = 0; i < N; i++) asm volatile("" : "+r"(a[i])::"memory");
}

#define F8(d, o) "+f"(d[o]), "+f"(d[o + 1]), "+f"(d[o + 2]), "+f"(d[o + 3]), "+f"(d[o + 4]), "+f"(d[o + 5]), "+f"(d[o + 6]), "+f"(d[o + 7])
#define R32A "%0, %1, %2, %3, %4, %5, %6, %7, %8, %9, %10, %11, %12, %13, %14, %15, %16, %17, %18, %19, %20, %21, %22, %23, %24, %25, %26, %27, %28, %29, %30, %31"
#define R32B "%32, %33, %34, %35, %36, %37, %38, %39, %40, %41, %42, %43, %44, %45, %46, %47, %48, %49, %50, %51, %52, %53, %54, %55, %56, %57, %58, %59, %60, %61, %62, %63"

#define O8(d, o) "=f"(d[o]), "=f"(d[o + 1]), "=f"(d[o + 2]), "=f"(d[o + 3]), "=f"(d[o + 4]), "=f"(d[o + 5]), "=f"(d[o + 6]), "=f"(d[o + 7])

__device__ __forceinline__ void mma_n128t(float (&d)[64], uint32_t a0, uint32_t a1, uint32_t a2, uint32_t a3, uint64_t db, bool acc) {
  if (acc)
    asm volatile("wgmma.mma_async.sync.aligned.m64n128k16.f32.bf16.bf16 {" R32A ", " R32B "}, {%64, %65, %66, %67}, %68, 1, 1, 1, 1;\n"
                 : F8(d, 0), F8(d, 8), F8(d, 16), F8(d, 24), F8(d, 32), F8(d, 40), F8(d, 48), F8(d, 56)
                 : "r"(a0), "r"(a1), "r"(a2), "r"(a3), "l"(db));
  else
    asm volatile("wgmma.mma_async.sync.aligned.m64n128k16.f32.bf16.bf16 {" R32A ", " R32B "}, {%64, %65, %66, %67}, %68, 0, 1, 1, 1;\n"
                 : O8(d, 0), O8(d, 8), O8(d, 16), O8(d, 24), O8(d, 32), O8(d, 40), O8(d, 48), O8(d, 56)
                 : "r"(a0), "r"(a1), "r"(a2), "r"(a3), "l"(db));
}
#define PV1(a0, a1, a2, a3, ob, acc) "add.s64 b, %92, " #ob ";\n" \
  "wgmma.mma_async.sync.aligned.m64n128k16.f32.bf16.bf16 {" R32A ", " R32B "}, {%" #a0 ", %" #a1 ", %" #a2 ", %" #a3 "}, b, " #acc ", 1, 1, 1;\n"
#define PV6 "wgmma.fence.sync.aligned;\n" PV1(64, 65, 66, 67, 0, p) PV1(68, 69, 70, 71, 128, 1) PV1(72, 73, 74, 75, 256, 1) \
  PV1(76, 77, 78, 79, 384, 1) PV1(80, 81, 82, 83, 512, 1) PV1(84, 85, 86, 87, 640, 1)
#define U4(a, o) "r"(a[o]), "r"(a[o + 1]), "r"(a[o + 2]), "r"(a[o + 3])
__device__ __forceinline__ void mma_pv(float (&d)[64], const uint32_t (&a)[28], uint64_t dv, bool acc, bool big) {
  asm volatile("{\n.reg .pred p, q;\n.reg .b64 b;\nsetp.ne.b32 p, %93, 0;\nsetp.eq.b32 q, %94, 0;\n@q bra.uni PV_SMALL;\n"
               PV6 PV1(88, 89, 90, 91, 768, 1) "wgmma.commit_group.sync.aligned;\nbra.uni PV_DONE;\n"
               "PV_SMALL:\n" PV6 "wgmma.commit_group.sync.aligned;\nPV_DONE:\n}\n"
               : F8(d, 0), F8(d, 8), F8(d, 16), F8(d, 24), F8(d, 32), F8(d, 40), F8(d, 48), F8(d, 56)
               : U4(a, 0), U4(a, 4), U4(a, 8), U4(a, 12), U4(a, 16), U4(a, 20), U4(a, 24), "l"(dv), "r"((int)acc), "r"((int)big) : "memory");
}
#define R48 R32A ", %32, %33, %34, %35, %36, %37, %38, %39, %40, %41, %42, %43, %44, %45, %46, %47"
#define R56 R48 ", %48, %49, %50, %51, %52, %53, %54, %55"
#define QK1(N, R, A, B, oa, ob, acc) "add.s64 a, " A ", " #oa ";\nadd.s64 b, " B ", " #ob ";\n" \
  "wgmma.mma_async.sync.aligned.m64n" #N "k16.f32.bf16.bf16 {" R "}, a, b, " #acc ", 1, 1, 0, 0;\n"
#define QK8(N, R, A, B) "{\n.reg .b64 a, b;\nwgmma.fence.sync.aligned;\n" QK1(N, R, A, B, 0, 0, 0) QK1(N, R, A, B, 128, 2, 1) \
  QK1(N, R, A, B, 256, 4, 1) QK1(N, R, A, B, 384, 6, 1) QK1(N, R, A, B, 512, 1024, 1) QK1(N, R, A, B, 640, 1026, 1) \
  QK1(N, R, A, B, 768, 1028, 1) QK1(N, R, A, B, 896, 1030, 1) "wgmma.commit_group.sync.aligned;\n}\n"
__device__ __forceinline__ void mma_qk(float (&d)[56], uint64_t dq, uint64_t dk) {
  asm volatile(QK8(112, R56, "%56", "%57")
               : O8(d, 0), O8(d, 8), O8(d, 16), O8(d, 24), O8(d, 32), O8(d, 40), O8(d, 48) : "l"(dq), "l"(dk) : "memory");
}
__device__ __forceinline__ void mma_qk(float (&d)[48], uint64_t dq, uint64_t dk) {
  asm volatile(QK8(96, R48, "%48", "%49")
               : O8(d, 0), O8(d, 8), O8(d, 16), O8(d, 24), O8(d, 32), O8(d, 40) : "l"(dq), "l"(dk) : "memory");
}
__device__ __forceinline__ void mma_n64t(float (&d)[32], uint32_t a0, uint32_t a1, uint32_t a2, uint32_t a3, uint64_t db, bool acc) {
  if (acc)
    asm volatile("wgmma.mma_async.sync.aligned.m64n64k16.f32.bf16.bf16 {" R32A "}, {%32, %33, %34, %35}, %36, 1, 1, 1, 1;\n"
                 : F8(d, 0), F8(d, 8), F8(d, 16), F8(d, 24) : "r"(a0), "r"(a1), "r"(a2), "r"(a3), "l"(db));
  else
    asm volatile("wgmma.mma_async.sync.aligned.m64n64k16.f32.bf16.bf16 {" R32A "}, {%32, %33, %34, %35}, %36, 0, 1, 1, 1;\n"
                 : O8(d, 0), O8(d, 8), O8(d, 16), O8(d, 24) : "r"(a0), "r"(a1), "r"(a2), "r"(a3), "l"(db));
}
__device__ __forceinline__ void mma_n64t_dyn(float (&d)[32], uint32_t a0, uint32_t a1, uint32_t a2, uint32_t a3, uint64_t db, int acc) {
  asm volatile("{\n.reg .pred p;\nsetp.ne.b32 p, %37, 0;\n"
               "wgmma.mma_async.sync.aligned.m64n64k16.f32.bf16.bf16 {" R32A "}, {%32, %33, %34, %35}, %36, p, 1, 1, 1;\n}\n"
               : F8(d, 0), F8(d, 8), F8(d, 16), F8(d, 24) : "r"(a0), "r"(a1), "r"(a2), "r"(a3), "l"(db), "r"(acc));
}
__device__ __forceinline__ void mma_n8(float (&d)[4], uint64_t da, uint64_t db, int acc) {
  asm volatile("{\n.reg .pred p;\nsetp.ne.b32 p, %6, 0;\n"
               "wgmma.mma_async.sync.aligned.m64n8k16.f32.bf16.bf16 {%0, %1, %2, %3}, %4, %5, p, 1, 1, 1, 0;\n}\n"
               : "+f"(d[0]), "+f"(d[1]), "+f"(d[2]), "+f"(d[3])
               : "l"(da), "l"(db), "r"(acc));
}
__device__ __forceinline__ void hmma_k16(float (&d)[4], uint32_t a0, uint32_t a1, uint32_t a2, uint32_t a3, uint32_t b0, uint32_t b1) {
  asm volatile("mma.sync.aligned.m16n8k16.row.col.f32.bf16.bf16.f32 {%0, %1, %2, %3}, {%4, %5, %6, %7}, {%8, %9}, {%0, %1, %2, %3};"
               : "+f"(d[0]), "+f"(d[1]), "+f"(d[2]), "+f"(d[3]) : "r"(a0), "r"(a1), "r"(a2), "r"(a3), "r"(b0), "r"(b1));
}

__device__ __forceinline__ uint32_t pack2(float lo, float hi) {
  uint32_t r;
  asm("cvt.rn.bf16x2.f32 %0, %1, %2;" : "=r"(r) : "f"(hi), "f"(lo));
  return r;
}
__device__ __forceinline__ float bf_lo(uint32_t w) { return __uint_as_float(w << 16); }
__device__ __forceinline__ float bf_hi(uint32_t w) { return __uint_as_float(w & 0xFFFF0000u); }
__device__ __forceinline__ float bfr(float x) { return __bfloat162float(__float2bfloat16_rn(x)); }
__device__ __forceinline__ uint32_t sub2(uint32_t a, uint32_t b) {
  uint32_t r;
  asm("sub.rn.bf16x2 %0, %1, %2;" : "=r"(r) : "r"(a), "r"(b));
  return r;
}
__device__ __forceinline__ uint32_t add2(uint32_t a, uint32_t b) {
  uint32_t r;
  asm("add.rn.bf16x2 %0, %1, %2;" : "=r"(r) : "r"(a), "r"(b));
  return r;
}
__device__ __forceinline__ uint32_t fma2(uint32_t a, uint32_t b, uint32_t c) {
  uint32_t r;
  asm("fma.rn.bf16x2 %0, %1, %2, %3;" : "=r"(r) : "r"(a), "r"(b), "r"(c));
  return r;
}
__device__ __forceinline__ float ex2(float x) {
  float r;
  asm("ex2.approx.ftz.f32 %0, %1;" : "=f"(r) : "f"(x));
  return r;
}
__device__ __forceinline__ float rcp(float x) {
  float r;
  asm("rcp.approx.ftz.f32 %0, %1;" : "=f"(r) : "f"(x));
  return r;
}
__device__ __forceinline__ float silu_f(float t) { return t * rcp(1.0f + ex2(-1.4426950408889634f * t)); }
__device__ __forceinline__ void lds128(uint32_t a, uint32_t& x, uint32_t& y, uint32_t& z, uint32_t& w) {
  asm volatile("ld.shared.v4.u32 {%0, %1, %2, %3}, [%4];" : "=r"(x), "=r"(y), "=r"(z), "=r"(w) : "r"(a) : "memory");
}
__device__ __forceinline__ void ldsm4(uint32_t a, uint32_t& x, uint32_t& y, uint32_t& z, uint32_t& w) {
  asm volatile("ldmatrix.sync.aligned.m8n8.x4.shared.b16 {%0, %1, %2, %3}, [%4];" : "=r"(x), "=r"(y), "=r"(z), "=r"(w) : "r"(a) : "memory");
}
constexpr uint32_t TAG = 0x10000;
__device__ __forceinline__ void st_gran(uint4* p, uint32_t x, uint32_t y, uint32_t z, uint32_t w) {
  asm volatile("st.relaxed.gpu.global.v4.b32 [%0], {%1, %2, %3, %4};" ::"l"(p), "r"(x), "r"(y), "r"(z), "r"(w) : "memory");
}
__device__ __forceinline__ void ld_gran(const uint4* p, uint32_t& x, uint32_t& y, uint32_t& z, uint32_t& w) {
  asm volatile("ld.relaxed.gpu.global.v4.b32 {%0, %1, %2, %3}, [%4];" : "=r"(x), "=r"(y), "=r"(z), "=r"(w) : "l"(p) : "memory");
}
__device__ __forceinline__ void stsm4(uint32_t a, uint32_t x, uint32_t y, uint32_t z, uint32_t w) {
  asm volatile("stmatrix.sync.aligned.m8n8.x4.shared.b16 [%0], {%1, %2, %3, %4};" ::"r"(a), "r"(x), "r"(y), "r"(z), "r"(w) : "memory");
}
__device__ __forceinline__ void cp16(uint32_t dst, const void* src) {
  asm volatile("cp.async.cg.shared.global [%0], [%1], 16;" ::"r"(dst), "l"(src) : "memory");
}
__device__ __forceinline__ void cp_wait_all() { asm volatile("cp.async.wait_all;" ::: "memory"); }
__device__ __forceinline__ void add_granules(float (&red)[32], const uint32_t (&g)[16]) {
#pragma unroll
  for (int i = 0; i < 16; i++) { red[2 * i] += bf_lo(g[i]); red[2 * i + 1] += bf_hi((i & 3) ? g[i] : g[i] & ~TAG); }
}
__device__ __forceinline__ bool granules_ok(const uint32_t (&g)[16], uint32_t tag) {
  uint32_t a, b;
  asm("lop3.b32 %0, %1, %2, %3, 0x7E;" : "=r"(a) : "r"(g[0]), "r"(g[4]), "r"(tag));
  asm("lop3.b32 %0, %1, %2, %3, 0x7E;" : "=r"(b) : "r"(g[8]), "r"(g[12]), "r"(tag));
  return __all_sync(0xffffffffu, ((a | b) & TAG) == 0);
}
__device__ __forceinline__ unsigned ld_acquire(const unsigned* p) {
  unsigned v;
  asm volatile("ld.acquire.gpu.global.u32 %0, [%1];" : "=r"(v) : "l"(p) : "memory");
  return v;
}
__device__ __forceinline__ unsigned atom_add_acq_rel(unsigned* p) {
  unsigned v;
  asm volatile("atom.acq_rel.gpu.global.add.u32 %0, [%1], 1;" : "=r"(v) : "l"(p) : "memory");
  return v;
}

template <int K0, int K1>
__device__ __forceinline__ void ln_fetch(uint32_t (&xa)[144], uint32_t boxes, uint32_t lo) {
#pragma unroll
  for (int k = K0; k < K1; k++) ldsm4(boxes + (k >> 2) * 8192 + (lo ^ ((k & 3) << 5)), xa[4 * k], xa[4 * k + 1], xa[4 * k + 2], xa[4 * k + 3]);
}
__device__ __forceinline__ void ln_fetch_b(uint32_t (&b)[24], uint32_t& wb, uint32_t ws) {
#pragma unroll
  for (int j = 0; j < 6; j++, wb += ws) ldsm4(wb, b[4 * j], b[4 * j + 1], b[4 * j + 2], b[4 * j + 3]);
}
template <int K0, int K1>
__device__ __forceinline__ void ln_sums(const uint32_t (&xa)[144], float (&sm)[4][4], const uint32_t (&b)[24]) {
#pragma unroll
  for (int k = K0; k < K1; k++)
    hmma_k16(sm[k & 3], xa[4 * k], xa[4 * k + 1], xa[4 * k + 2], xa[4 * k + 3], b[2 * (k % 12)], b[2 * (k % 12) + 1]);
}
template <int K0, int K1>
__device__ __forceinline__ uint32_t after_fetch(const uint32_t (&xa)[144]) {
  uint32_t d = blockIdx.y;
#pragma unroll
  for (int k = K0; k < K1; k++) d &= xa[4 * k];
  return d;
}
__device__ __forceinline__ void ln_row(float sum, float sq, float& mean_b, float& rstd) {
  const float mean = sum * (1.0f / DM);
  const uint32_t mv = pack2(mean, fmaxf(sq * (1.0f / DM) - mean * mean, 0.0f));
  mean_b = bf_lo(mv);
  float sd;
  asm("sqrt.approx.f32 %0, %1;" : "=f"(sd) : "f"(bf_lo(pack2(bf_hi(mv) + 1e-5f, 0.f))));
  rstd = rcp(bf_lo(pack2(sd, 0.f)));
}

template <bool ROUTED>
__device__ __forceinline__ uint32_t gate2(uint32_t xc, float rstd, float2 upd = make_float2(0.f, 0.f)) {
  uint32_t t = pack2(bf_lo(xc) * rstd, bf_hi(xc) * rstd);
  if (ROUTED) t = pack2(bf_lo(t) + upd.x, bf_hi(t) + upd.y);
  return pack2(silu_f(bf_lo(t)), silu_f(bf_hi(t)));
}

template <int V> struct IC { static constexpr int value = V; };

struct Ctx {
  uint32_t sb;
  uint8_t* sp;
  uint32_t rank;
  Scratch* g;
};

__device__ __forceinline__ bool acquire(const Ctx& cx, uint32_t r, uint32_t n, uint32_t bytes) {
  mbar_wait(cx.sb + SM_EMPTY + 8 * r, (n ^ (r >> 1) ^ 1) & 1);
  __syncwarp();
  const bool e = elect_one();
  if (e) mbar_expect_tx(cx.sb + SM_FULL + 8 * r, bytes);
  return e;
}
__device__ __forceinline__ void load_wq(const Ctx& cx, const CUtensorMap* tmWq, int st, int i, int n0, uint64_t pol) {
  const uint32_t r = st & 3, dst = cx.sb + SM_RING + r * STAGE + cx.rank * 16384, bar = cx.sb + SM_FULL + 8 * r;
  const int k0 = i < 3 ? 128 * i : 128 * i - 64;
  if (acquire(cx, r, st >> 2, i == 2 ? 16384 : 32768)) {
    tma2d_mc(dst, tmWq, n0, k0, bar, pol);
    if (i != 2) tma2d_mc(dst + 8192, tmWq, n0, k0 + 64, bar, pol);
  }
}
__device__ __forceinline__ void attn_producer(const Ctx& cx, int qb, int hs, const CUtensorMap* tmKV, const CUtensorMap* tmWq,
                                              const CUtensorMap* tmWq96, const CUtensorMap* tmWo) {
  const uint32_t full = cx.sb + SM_FULL, ring = cx.sb + SM_RING + cx.rank * 16384;
  const uint64_t last_use = policy_evict_first();
  int st = 0;
#pragma unroll 1
  for (int p = 0; p < 4; p++) {
#pragma unroll 1
    for (int i = 0; i < (p == 2 ? 3 : 5); i++, st++) {
      if (p == 2) {
        if (acquire(cx, st & 3, st >> 2, 24576))
          tma2d_mc(cx.sb + SM_RING + (st & 3) * STAGE + cx.rank * 12288, tmWq96, (hs * 4 + 3) * DH, 192 * i + 96 * cx.rank, full + 8 * (st & 3), last_use);
      } else {
        if (st > 1) load_wq(cx, tmWq, st, i, (hs * 4 + (p ^ (p >> 1))) * DH + cx.rank * 64, last_use);
      }
      if (st == 1 || st == 2) TSP(72 + st)
      if (st == 1) {
#pragma unroll 1
        for (int b = 0; b < 4; b++) {
          const bool k8 = b == 0 && qb < 8;
          if (elect_one()) tma2d_prefetch(tmWq, hs * 512 + (k8 ? qb * 64 : (b ^ (b >> 1)) * DH + (qb & 1) * 64), k8 ? 512 : (qb >> 1) * 64);
        }
      }
      if (st == 8 && qb < 8 && elect_one()) tma2d_prefetch(tmKV + ((qb >> 1) & 1), cx.rank * 64, hs * 2 * SEQ + (qb >> 2) * 96);
    }
  }
  uint32_t r = 2, n = 4;
  int row = hs * 2 * SEQ, rows = 96;
  const CUtensorMap* tm = tmKV + 2;
#pragma unroll 1
  for (int u = 0; u < NST_KV; u++) {
    if (acquire(cx, r, n, rows * 256)) {
      tma2d_mc(ring + r * STAGE, tm, cx.rank * 64, row, full + 8 * r, last_use);
      if (((u ^ (qb >> 1)) & 7) == 0 && u < NST_KV - 4) tma2d_prefetch(tmKV + (u & 1), cx.rank * 64, row + 208);
      if ((unsigned)(u - 32) < 36 && (u & 15) == qb) tma2d_prefetch(tmWo, ((u - 32) >> 2) * 64, hs * 512 + (u & 3) * 128);
    }
    if (++r == 4) { r = 1; n++; }
    if (u & 1) row += rows;
    const bool big = (unsigned)(u - 9) < 56;
    rows = big ? 112 : 96;
    tm = tmKV + (~u & 1) + (big ? 0 : 2);
  }
#pragma unroll 1
  for (int u = 0; u < NST_O; u++) {
    const int s = u >> 1;
    const int blk = s == 0 ? 8 : ((hs + s) & 7);
    r = (0x87 >> (2 * (u & 3))) & 3;
    if (acquire(cx, r, (u >> 2) ^ ~u, 32768))
      tma2d_mc(ring + r * STAGE, tmWo, blk * 64, hs * 512 + ((u & 1) + cx.rank * 2) * 128, full + 8 * r, last_use);
  }
}

__device__ __forceinline__ void sq_publish(const Ctx& cx, int qb, int hs, int j, int lane) {
  if (j == 2 && lane == 0) {
    const unsigned e = cx.g->launch[hs * 16 + qb]++;
    *(uint2*)(cx.sp + SM_TAG) = make_uint2((~e & 1) * TAG, e);
  }
  const int row = (hs & 3) * 16 + (lane >> 1);
  uint32_t a = cx.sb + SM_X + (hs >> 2) * 73728 + j * 8192 + row * 128 + (((lane & 1) ^ (row & 7)) << 4);
  float s0 = 0.f, s1 = 0.f;
#pragma unroll 1
  for (int b = 0; b < 6; b++) {
    if (b == (hs < 4 ? 4 : 0)) {
      const int n = 224 + (__float_as_uint(s1) & blockIdx.y);
      if (j == 1) {
        bar_sync(BAR_XREL, n);
        if (lane < 4) asm volatile("mbarrier.arrive.shared::cluster.b64 _, [%0], 2;" ::"r"(mapa(cx.sb + SM_EMPTY + 16 + 8 * (lane >> 1), lane & 1)) : "memory");
      } else {
        bar_arrive(BAR_XREL, n);
      }
      __syncwarp();
      if (hs == 8) return;
    }
    if (!(b & 1)) mbar_wait(cx.sb + SM_XFULL + 32 * (hs >> 2) + 4 * b, 0);
    uint32_t v[8];
    lds128(a, v[0], v[1], v[2], v[3]);
    lds128(a ^ 32, v[4], v[5], v[6], v[7]);
    a = (a ^ 64) + (b & 1) * 24576;
#pragma unroll
    for (int i = 0; i < 8; i++) { s0 = fmaf(bf_lo(v[i]), bf_lo(v[i]), s0); s1 = fmaf(bf_hi(v[i]), bf_hi(v[i]), s1); }
  }
  s0 += s1;
  s0 += __shfl_xor_sync(0xffffffffu, s0, 1);
  float* part = (float*)(cx.sp + SM_STATS) + (lane >> 1) * 2;
  if (j < 2) {
    part[32 * j] = s0;
    bar_arrive(BAR_HELPER, 96);
  } else {
    bar_sync(BAR_HELPER, 96);
    TSP(68)
    if (!(lane & 1))
      asm volatile("st.relaxed.gpu.global.v2.b32 [%0], {%1, %2};" ::"l"(cx.g->sq + qb * 128 + hs * 16 + (lane >> 1)),
                   "r"(__float_as_uint((part[0] + part[32]) + s0)), "r"(*(const uint32_t*)(cx.sp + SM_TAG + 4) + 1) : "memory");
  }
}
__device__ __forceinline__ void sq_collect(const Ctx& cx, int qb, int lane) {
  const uint32_t e1 = *(const uint32_t*)(cx.sp + SM_TAG + 4) + 1;
#pragma unroll 1
  for (int n = 0; n < (1 << 16); n++) {
    __nanosleep(300);
    uint32_t bad = 0;
#pragma unroll
    for (int i = 0; i < 2; i++) {
      uint32_t a, t0, b, t1;
      ld_gran((const uint4*)at(cx.g->sq, qb * 1024 + lane * 16) + i * 32, a, t0, b, t1);
      *(uint32_t*)(cx.sp + SM_STATS + (i * 32 + lane) * 16 + 4) = a;
      *(uint32_t*)(cx.sp + SM_STATS + (i * 32 + lane) * 16 + 12) = b;
      bad |= (t0 ^ e1) | (t1 ^ e1);
    }
    if (__all_sync(0xffffffffu, bad == 0)) break;
  }
  __syncwarp();
  if (lane == 0) mbar_arrive(cx.sb + SM_BAR_SQ);
  TSP(69)
}
__device__ __forceinline__ void attn_gate(const Ctx& cx, int qb, int hs, int j, int t, const __nv_bfloat16* x) {
  const uint4* xp = (const uint4*)(x + qb * 128 * DM) + (t >> 3) * 72 + hs * 8 + (t & 7);
  uint4 nx = *xp;
  float wsum = 0.f;
  if (j == 0) {
    mbar_wait(cx.sb + SM_BAR_W, 0);
#pragma unroll 3
    for (int i = 0; i < 9; i++) {
      const uint32_t w = *(const uint32_t*)(cx.sp + SM_WR + i * 128 + t * 4);
      wsum += bf_lo(w) + bf_hi(w);
    }
#pragma unroll
    for (int i = 1; i < 32; i *= 2) wsum += __shfl_xor_sync(0xffffffffu, wsum, i);
  }
  bar_sync(BAR_GATE, 352);
  if (t < 16) {
    const float2 st = *(const float2*)(cx.sp + SM_STATS + 8 * (hs * 16 + t));
    const int row = qb * 128 + hs * 16 + t;
    const uint32_t b = pack2(0.f, fmaf(-st.x, wsum, *(const float*)(cx.sp + SM_RAW + 4 * t)) * st.y);
    st_gran(at(cx.g->stats, row * 16), __float_as_uint(st.x), __float_as_uint(st.y), (b ^ ((int)b < 0 ? 0xFFFF0000u : 0x80000000u)) | (0xFFFF - row),
            *(const uint32_t*)(cx.sp + SM_TAG + 4) + 1);
  }
  __syncwarp();
  uint32_t sa = cx.sb + SM_STATS + (t & ~7);
  uint4* gp = cx.g->gate + blockIdx.x * 1152 + (t ^ ((t >> 3) & 7));
  const int cross = t < 64 ? 10 : 9;
#pragma unroll 1
  for (int i = 0; i < 12; i++) {
    float2 st;
    asm volatile("ld.shared.v2.f32 {%0, %1}, [%2];" : "=f"(st.x), "=f"(st.y) : "r"(sa));
    const uint32_t mm = pack2(st.x, st.x);
    const uint4 v = make_uint4(sub2(nx.x, mm), sub2(nx.y, mm), sub2(nx.z, mm), sub2(nx.w, mm));
    xp += 12 * 72;
    sa += 96;
    if (i == cross) { xp += (hs * 16 - 128) * 72 + 64 - hs * 8; sa += (hs * 16 - 128) * 8; }
    if (i < 11) nx = *xp;
    *gp = make_uint4(gate2<false>(v.x, st.y), gate2<false>(v.y, st.y), gate2<false>(v.z, st.y), gate2<false>(v.w, st.y));
    gp = (uint4*)((size_t)(gp + 96) ^ 64);
  }
}

constexpr uint32_t SM_XO = SM_SLOT, SM_GO = SM_SLOT + STAGE, SM_P8 = SM_SLOT + 2 * STAGE;
__device__ __forceinline__ void attn_helper(const Ctx& cx, int qb, int hs, int lane, const CUtensorMap* tmX16) {
  const unsigned e = *(const uint32_t*)(cx.sp + SM_TAG + 4);
  bar_sync(BAR_HELPER, 64);
  bool todo = lane < 2;
#pragma unroll 1
  for (int n = 0; __any_sync(0xffffffffu, todo); n++) {
    if (todo && (ld_acquire(at(cx.g->qflag, ((qb * 4 + (hs >> 1)) * 2 + lane) * 4)) == e + 1 || n == (1 << 16))) {
      asm volatile("fence.proxy.async.global;" ::: "memory");
      mbar_expect_tx(cx.sb + SM_BAR_Q + 8 * lane, 8192);
      bulk_load(cx.sb + SM_SLOT + 2 * STAGE + lane * 16384 + 8192, at(cx.g->q, ((qb * 8 + hs) * 2 + lane) * 8192), 8192, cx.sb + SM_BAR_Q + 8 * lane);
      todo = false;
    }
  }
  const uint32_t tag = (~e & 1) * TAG;
  const uint4* src = cx.g->part + (size_t)((qb * 64 + 56) * 2 + (hs >> 2)) * 4 * 128 + (hs & 3) * 32 + lane;
  const uint32_t stg = cx.sb + SM_P8 + lane * 16;
  bar_sync(BAR_OA, 352);
  asm volatile("fence.proxy.async.global;" ::: "memory");
  if (lane == 0) {
    mbar_expect_tx(cx.sb + SM_BAR_MISC, 2 * 18432);
    bulk_load(cx.sb + SM_GO, cx.g->gate + blockIdx.x * 1152, 18432, cx.sb + SM_BAR_MISC);
#pragma unroll 1
    for (int i = 0; i < 9; i++)
      tma2d(cx.sb + SM_XO + i * 2048, tmX16, i < 8 ? hs * 64 : 512, qb * 128 + (i < 8 ? i : hs) * 16, cx.sb + SM_BAR_MISC);
  }
#pragma unroll 1
  for (int n = 0; n < (1 << 16); n++) {
    __nanosleep(n ? 500 : 2000);
    uint32_t a, b, d, t;
    ld_gran(src - lane + (lane & 7) * (2 * 4 * 128) + 3 * 128 + 31, a, b, d, t);
    if (__all_sync(0xffffffffu, (a & TAG) == tag)) break;
  }
  TSH(46)
#pragma unroll 1
  for (int n = 0; n < (1 << 16); n++) {
#pragma unroll 1
    for (int i = 0; i < 8; i++) {
#pragma unroll
      for (int g = 0; g < 4; g++) cp16(stg + (i * 4 + g) * 512, src + i * (2 * 4 * 128) + g * 128);
    }
    cp_wait_all();
    uint32_t bad = 0;
#pragma unroll 4
    for (int i = 0; i < 32; i++) bad |= *(const volatile uint32_t*)(cx.sp + SM_P8 + lane * 16 + i * 512) ^ tag;
    if (__all_sync(0xffffffffu, (bad & TAG) == 0)) break;
  }
  TSH(47)
#pragma unroll 1
  for (int n = 0; n < (1 << 16) && ld_acquire(&cx.g->ycnt) != 4 * (e + 1); n++) __nanosleep(200);
  const int2 sel = __ldcg(at(cx.g->sel, (lane & 7) * 8));
  const int lr = sel.x - qb * 128;
  uint32_t m = __ballot_sync(0xffffffffu, lane < 16 && ((lane & 8) ? (lr >> 4) == hs : (lr >> 7) == 0));
  mbar_wait(cx.sb + SM_BAR_MISC, 0);
#pragma unroll 1
  for (; m; m &= m - 1) {
    const int i = __ffs(m) - 1, row = __shfl_sync(0xffffffffu, lr, i);
    const float rs = __int_as_float(__shfl_sync(0xffffffffu, sel.y, i));
    const float* p = cx.g->ypart + (i & 7) * DM + (i < 8 ? hs * 64 : 512) + 2 * lane;
    const float2 a = __ldcg((const float2*)p), b = __ldcg((const float2*)(p + TOPC * DM)), c = __ldcg((const float2*)(p + 2 * TOPC * DM)),
                 d = __ldcg((const float2*)(p + 3 * TOPC * DM));
    const uint32_t y = pack2((a.x + b.x) + (c.x + d.x), (a.y + b.y) + (c.y + d.y));
    const uint32_t u = pack2(bf_lo(y) * rs, bf_hi(y) * rs);
    const float2 st = *(const float2*)(cx.sp + SM_STATS + 8 * row);
    const int o = (i < 8 ? row : 128 + (row & 15)) * 128 + ((lane * 4) ^ ((row & 7) << 4));
    *(uint32_t*)(cx.sp + SM_GO + o) = gate2<true>(sub2(*(const uint32_t*)(cx.sp + SM_XO + o), pack2(st.x, st.x)), st.y, make_float2(bf_lo(u), bf_hi(u)));
  }
  __syncwarp();
  if (lane == 0) mbar_arrive(cx.sb + SM_BAR_XG);
  TSH(48)
}
__device__ __forceinline__ void attn_finish8(const Ctx& cx, int qb, int hs, int hw, int lane, __nv_bfloat16* out) {
  bar_sync(BAR_GATE, 96);
#pragma unroll 1
  for (int g = hw; g < 4; g += 3) {
    float acc[8] = {0.f, 0.f, 0.f, 0.f, 0.f, 0.f, 0.f, 0.f};
#pragma unroll 2
    for (int sidx = 0; sidx < 8; sidx++) {
      uint32_t a, b, d, t;
      lds128(cx.sb + SM_P8 + lane * 16 + (sidx * 4 + g) * 512, a, b, d, t);
      acc[0] += bf_lo(a); acc[1] += bf_hi(a & ~TAG); acc[2] += bf_lo(b); acc[3] += bf_hi(b);
      acc[4] += bf_lo(d); acc[5] += bf_hi(d); acc[6] += bf_lo(t); acc[7] += bf_hi(t);
    }
#pragma unroll
    for (int j = 0; j < 4; j++) {
      const int o = (128 + (lane >> 2) + (j & 1) * 8) * 128 + (((2 * g + (j >> 1)) ^ (lane >> 2)) << 4) + (lane & 3) * 4;
      uint32_t* xp = (uint32_t*)(cx.sp + SM_XO + o);
      *xp = fma2(pack2(acc[2 * j], acc[2 * j + 1]), *(const uint32_t*)(cx.sp + SM_GO + o), *xp);
    }
  }
  bar_sync(BAR_GATE, 96);
#pragma unroll 1
  for (int ch = threadIdx.x - 32; ch < 128; ch += 96)
    *(uint4*)at(out, ((qb * 128 + hs * 16 + (ch >> 3)) * DM + 512 + (ch & 7) * 8) * 2) =
        *(const uint4*)(cx.sp + SM_XO + 16384 + (ch ^ ((ch >> 3) & 7)) * 16);
}

__device__ __forceinline__ void ffn_producer(const Ctx& cx, int f, const CUtensorMap* tmWq, const CUtensorMap* tmG,
                                             const CUtensorMap* tmU, const CUtensorMap* tmD) {
  uint64_t keep;
  asm("createpolicy.fractional.L2::evict_normal.b64 %0, 1.0;" : "=l"(keep));
  int st = 0;
#pragma unroll 1
  for (int p = 0; p < 16; p++) {
#pragma unroll 1
    for (int i = 0; i < 5; i++, st++) if (st > 1) load_wq(cx, tmWq, st, i, ((2 * (p & 3) + cx.rank) * 4 + 3) * DH + 64, keep);
  }
  const uint32_t full = cx.sb + SM_FFULL, empty = cx.sb + SM_FEMPTY;
  int pair = 0, u = 0;
#pragma unroll 1
  for (st = 0; st < 14 * 12; st++) {
    const uint32_t sl = st & 7;
    const int unit = pair * 2 + (u & 1), k = u >> 1, k3 = k >= 3 ? k - 3 : k;
    if (unit < 27) {
      mbar_wait(empty + 8 * sl, (st >> 3) & 1);
      __syncwarp();
      if (elect_one()) {
        mbar_expect_tx(full + 8 * sl, FSTAGE);
        if (pair < 9) tma2d_stream(cx.sb + sl * FSTAGE, k < 3 ? tmG : tmU, f * 1152 + unit * 64, k3 * 192, full + 8 * sl);
        else tma2d_stream(cx.sb + sl * FSTAGE, tmD, (unit - 18) * 64, f * 1152 + k * 192, full + 8 * sl);
      }
    }
    if (++u == 12) { u = 0; pair++; }
  }
}
__device__ __forceinline__ void load_x1(uint32_t dst, const CUtensorMap* tmX64, int row, int box, int n, uint32_t bar) {
  mbar_expect_tx(bar, n * 8192);
#pragma unroll 1
  for (int i = 0; i < n; i++) tma2d(dst + i * 8192, tmX64, (box + i) * 64, row, bar);
}
__device__ __forceinline__ void ffn_publish(const Ctx& cx, int f, int w, int lane, const CUtensorMap* tmX64) {
  const uint32_t xs = cx.sb + SM_SLOT + w * 49152, xf = cx.sb + SM_XFULL + w * 32;
#pragma unroll 1
  for (int n = 0; n < 16; n++) {
    const int p = n & 3, row = (f + (n & 12) + 4) * 128 + w * 64;
    if (n < 12 && p == 3) {
      bar_sync(BAR_QS + w, 160);
      if (lane == 0) load_x1(xs, tmX64, row, 4, 4, xf + 8);
      __syncwarp();
    }
    bar_sync(BAR_QS + w, 160);
    const uint32_t e1 = *(const uint32_t*)(cx.sp + SM_TAG + 4) + 1;
    if (lane == 0) {
#pragma unroll
      for (int i = 0; i < 2; i++)
        asm volatile("cp.async.bulk.global.shared::cta.bulk_group [%0], [%1], 8192;"
                     ::"l"(cx.g->q + (((f + (n & 12)) * 8 + 2 * p + i) * 2 + w) * 512), "r"(xs + 32768 + i * 8192) : "memory");
      asm volatile("cp.async.bulk.commit_group;" ::: "memory");
      asm volatile("cp.async.bulk.wait_group.read 0;" ::: "memory");
      if (n < 12 && (p == 0 || p == 3)) load_x1(xs + (p ? 32768 : 0), tmX64, row, p ? 8 : 0, p ? 1 : 4, xf + (p ? 16 : 0));
      asm volatile("cp.async.bulk.wait_group 0;\nfence.proxy.async.global;" ::: "memory");
      asm volatile("st.release.gpu.global.u32 [%0], %1;" ::"l"(&cx.g->qflag[((f + (n & 12)) * 4 + p) * 2 + w]), "r"(e1) : "memory");
    }
    __syncwarp();
    if (n < 12 && p == 1) {
#pragma unroll 1
      for (int i = 0, k = 0; i < 64 && k < (1 << 16); k++) {
        uint32_t m, r, z, t;
        ld_gran(cx.g->stats + row + i + lane, m, r, z, t);
        *(uint2*)(cx.sp + SM_STATS + 8 * (w * 64 + i + lane)) = make_uint2(m, r);
        if (__all_sync(0xffffffffu, t == e1)) i += 32;
      }
    }
    bar_arrive(BAR_QF + w, 160);
  }
}

__device__ __forceinline__ void ffn_consumer(const Ctx& cx, int f, int wg, int cw, int lane, const __nv_bfloat16* x) {
  const int r = lane >> 2, c = lane & 3, tid = cw * 32 + lane;
  const uint32_t full = cx.sb + SM_FFULL, empty = cx.sb + SM_FEMPTY;
  const bool signaller = (tid & 127) == 0;
  prof(wg, 8);
  const unsigned e = *(const uint32_t*)(cx.sp + SM_TAG + 4);
  uint32_t key[8];
#pragma unroll 1
  for (int n = 0; n < (1 << 16); n++) {
    uint32_t bad = 0;
#pragma unroll
    for (int i = 0; i < 8; i++) {
      uint32_t t;
      asm volatile("ld.relaxed.gpu.global.v2.b32 {%0, %1}, [%2];" : "=r"(key[i]), "=r"(t) : "l"(&cx.g->stats[i * 256 + tid].z) : "memory");
      bad |= t ^ (e + 1);
    }
    if (__all_sync(0xffffffffu, bad == 0)) break;
  }
  bar_sync(BAR_QF + wg, 160);
  bar_sync(3, 256);
  if (tid < 8) mbar_arrive(empty + 8 * tid);
  prof(wg, 9);
  int mysel = 0;
#pragma unroll 1
  for (int k = 0; k < TOPC; k++) {
    uint32_t m = key[0];
#pragma unroll
    for (int i = 1; i < 8; i++) m = max(m, key[i]);
    m = __reduce_max_sync(0xffffffffu, m);
    uint32_t* tk = (uint32_t*)(cx.sp + SM_TOPK) + (k & 1) * 8;
    if (lane == 0) tk[cw] = m;
    bar_sync(3, 256);
    m = __reduce_max_sync(0xffffffffu, tk[lane & 7]);
#pragma unroll
    for (int i = 0; i < 8; i++) if (key[i] == m) key[i] = 0;
    if (k == cw) mysel = 0xFFFF - (int)(m & 0xFFFF);
  }
  {
    const float4 st = __ldcg((const float4*)&cx.g->stats[mysel]);
    const uint32_t mm = pack2(st.x, st.x);
#pragma unroll 3
    for (int i = 0; i < 9; i++) {
      const uint32_t t = sub2(*(const uint32_t*)(x + (size_t)mysel * DM + i * 64 + 2 * lane), mm);
      *(uint32_t*)(cx.sp + SM_XSEL + i * 1024 + cw * 128 + (((lane >> 2) ^ cw) << 4) + (lane & 3) * 4) =
          pack2(bf_lo(t) * st.y, bf_hi(t) * st.y);
    }
    const uint32_t k = __float_as_uint(st.z);
    const float score = bf_hi(k ^ ((int)k < 0 ? 0x80000000u : 0xFFFF0000u));
    if (lane == 0 && f == 0) cx.g->sel[cw] = make_int2(mysel, __float_as_int(bfr(rcp(1.0f + ex2(-1.4426950408889634f * score)))));
  }
  asm volatile("fence.proxy.async.shared::cta;" ::: "memory");
  bar_sync(3, 256);
  prof(wg, 10);
  auto run = [&](float (&acc)[4], int st, int n, uint32_t b) {
#pragma unroll 1
    for (int u = 0; u < n; u++, st += 2, b += 3072) {
      const uint32_t sl = st & 7;
      mbar_wait(full + 8 * sl, (st >> 3) & 1);
      wg_fence();
      const uint64_t da = mkdesc(cx.sb + sl * FSTAGE, 16), db = mkdesc(b, 16);
#pragma unroll
      for (int k = 0; k < 12; k++) mma_n8(acc, da + k * 128, db + (k >> 2) * 64 + (k & 3) * 2, u > 0 || k > 0);
      wg_commit();
      wg_wait<0>();
      if (signaller) mbar_arrive(empty + 8 * sl);
    }
    pin(acc);
  };
#pragma unroll 1
  for (int unit = wg; unit < 27; unit += 2) {
    if (unit >> 1 == 9) {
      asm volatile("fence.proxy.async.shared::cta;" ::: "memory");
      bar_sync(3, 256);
      prof(wg, 11);
    }
    const bool gu = unit < 18;
    float a0[4], a1[4];
#pragma unroll 1
    for (int m = 0; m < (gu ? 2 : 1); m++) {
      run(a1, (unit >> 1) * 12 + m * 6 + wg, gu ? 3 : 6, cx.sb + (gu ? SM_XSEL : SM_H));
      if (m == 0) { a0[0] = a1[0]; a0[1] = a1[1]; a0[2] = a1[2]; a0[3] = a1[3]; }
    }
    float u0 = a1[0], u1 = a1[1];
#pragma unroll 1
    for (int i = 0; i < 2; i++) {
      const int fl = (cw & 3) * 16 + r + i * 8;
      if (gu) {
        const uint32_t g = pack2(a0[0], a0[1]);
        const uint32_t h = fma2(pack2(silu_f(bf_lo(g)), silu_f(bf_hi(g))), pack2(u0, u1), 0x80008000u);
        uint8_t* hp = cx.sp + SM_H + unit * 1024 + c * 256 + (fl & 7) * 2;
        *(uint16_t*)(hp + (((fl >> 3) ^ (2 * c)) << 4)) = (uint16_t)h;
        *(uint16_t*)(hp + 128 + (((fl >> 3) ^ (2 * c + 1)) << 4)) = (uint16_t)(h >> 16);
      } else {
        float* yp = cx.g->ypart + (f * TOPC + 2 * c) * DM + (unit - 18) * 64 + fl;
        yp[0] = u0;
        yp[DM] = u1;
      }
      a0[0] = a0[2]; a0[1] = a0[3]; u0 = a1[2]; u1 = a1[3];
    }
  }
  prof(wg, 12);
  bar_sync(3, 256);
  if (tid == 0) atom_add_acq_rel(&cx.g->ycnt);
  prof(wg, 13);
}

constexpr float SUM_HI = 1.8446744e19f, SUM_LO = 9.0949470e-13f;

template <int LO, int HI, int N>
__device__ __forceinline__ void softmax_exp(float (&s)[N]) {
#pragma unroll
  for (int i = LO; i < HI; i++) s[i] = ex2(s[i]);
}
__device__ __forceinline__ void sum_tree(const uint32_t (&pf)[28], bool big, uint32_t& h0, uint32_t& h1) {
  uint32_t t0 = add2(add2(pf[16], pf[18]), add2(pf[20], pf[22])), t1 = add2(add2(pf[17], pf[19]), add2(pf[21], pf[23]));
  if (big) { t0 = add2(t0, add2(pf[24], pf[26])); t1 = add2(t1, add2(pf[25], pf[27])); }
  h0 = add2(add2(add2(add2(pf[0], pf[2]), add2(pf[4], pf[6])), add2(add2(pf[8], pf[10]), add2(pf[12], pf[14]))), t0);
  h1 = add2(add2(add2(add2(pf[1], pf[3]), add2(pf[5], pf[7])), add2(add2(pf[9], pf[11]), add2(pf[13], pf[15]))), t1);
}
__device__ __forceinline__ void exact_attention(float (&o)[16], float& l0, float& l1, const uint32_t (&q)[32], const __nv_bfloat16* kp,
                                                const __nv_bfloat16* vp) {
  float m0 = -3.0e38f, m1 = -3.0e38f;
  l0 = l1 = 0.f;
#pragma unroll
  for (int i = 0; i < 16; i++) o[i] = 0.f;
#pragma unroll 1
  for (int key = 0; key < SEQ; key += 8, kp += 8 * DH, vp += 8 * DH) {
    float d[4] = {0.f, 0.f, 0.f, 0.f};
#pragma unroll
    for (int k = 0; k < 8; k++)
      hmma_k16(d, q[4 * k], q[4 * k + 1], q[4 * k + 2], q[4 * k + 3], *(const uint32_t*)(kp + k * 16), *(const uint32_t*)(kp + k * 16 + 8));
    float x0 = fmaxf(d[0], d[1]), x1 = fmaxf(d[2], d[3]);
    x0 = fmaxf(x0, __shfl_xor_sync(0xffffffffu, x0, 1));
    x1 = fmaxf(x1, __shfl_xor_sync(0xffffffffu, x1, 1));
    x0 = fmaxf(fmaxf(x0, __shfl_xor_sync(0xffffffffu, x0, 2)), m0);
    x1 = fmaxf(fmaxf(x1, __shfl_xor_sync(0xffffffffu, x1, 2)), m1);
    const float sc0 = ex2(m0 - x0), sc1 = ex2(m1 - x1);
    m0 = x0; m1 = x1;
    const uint32_t p0 = pack2(ex2(d[0] - m0), ex2(d[1] - m0)), p1 = pack2(ex2(d[2] - m1), ex2(d[3] - m1));
    l0 = fmaf(l0, sc0, bf_lo(p0) + bf_hi(p0));
    l1 = fmaf(l1, sc1, bf_lo(p1) + bf_hi(p1));
#pragma unroll
    for (int nb = 0; nb < 4; nb++) {
      uint32_t b;
      asm("movmatrix.sync.aligned.m8n8.trans.b16 %0, %1;" : "=r"(b) : "r"(*(const uint32_t*)(vp + nb * 8)));
      o[4 * nb] *= sc0; o[4 * nb + 1] *= sc0; o[4 * nb + 2] *= sc1; o[4 * nb + 3] *= sc1;
      asm volatile("mma.sync.aligned.m16n8k8.row.col.f32.bf16.bf16.f32 {%0, %1, %2, %3}, {%4, %5}, {%6}, {%0, %1, %2, %3};"
                   : "+f"(o[4 * nb]), "+f"(o[4 * nb + 1]), "+f"(o[4 * nb + 2]), "+f"(o[4 * nb + 3]) : "r"(p0), "r"(p1), "r"(b));
    }
  }
}
__device__ __forceinline__ bool inv_sums(float l0, float l1, float& i0, float& i1) {
  l0 += __shfl_xor_sync(0xffffffffu, l0, 1); l1 += __shfl_xor_sync(0xffffffffu, l1, 1);
  l0 += __shfl_xor_sync(0xffffffffu, l0, 2); l1 += __shfl_xor_sync(0xffffffffu, l1, 2);
  i0 = rcp(l0);
  i1 = rcp(l1);
  return !(l0 + l1 <= SUM_HI) | (fminf(l0, l1) < SUM_LO);
}
template <int LO, int HI, int N>
__device__ __forceinline__ void park(uint32_t a, const float (&o)[N], float i0, float i1, bool on = true) {
#pragma unroll
  for (int i = LO; i < HI; i++)
    asm volatile("{\n.reg .pred p;\nsetp.ne.u32 p, %5, 0;\n@p stmatrix.sync.aligned.m8n8.x4.shared.b16 [%0], {%1, %2, %3, %4};\n}"
                 ::"r"(a + i * 2048), "r"(pack2(o[8 * i] * i0, o[8 * i + 1] * i0)), "r"(pack2(o[8 * i + 2] * i1, o[8 * i + 3] * i1)),
                 "r"(pack2(o[8 * i + 4] * i0, o[8 * i + 5] * i0)), "r"(pack2(o[8 * i + 6] * i1, o[8 * i + 7] * i1)), "r"((uint32_t)on) : "memory");
}

template <int I, int HI>
__device__ __forceinline__ void park_paced(uint32_t a, const float (&o)[64], float i0, float i1, int id) {
  if constexpr (I < HI) {
    park<I, I + 2>(a, o, i0, i1);
    if (I + 2 < HI) block_fence(id + I);
    park_paced<I + 2, HI>(a, o, i0, i1, id);
  }
}

__device__ __forceinline__ void attn_consumer(const Ctx& cx, bool hlp, int qb, int hs, int wg, int cw, int lane, const __nv_bfloat16* x,
                                              const __nv_bfloat16* kc, const __nv_bfloat16* vc, __nv_bfloat16* out) {
  const uint32_t full = cx.sb + SM_FULL;
  const uint32_t ring = cx.sb + SM_RING;
  const uint32_t qwg = ring + wg * 16384;
  auto qlane = [&](int l) { return qwg + (cw & 3) * 256 + (l >> 4) * 1024 + (l & 15) * 16; };
  const bool signaller = lane == 0 && (cw & 3) < 2;
  const int my_turn = 1 + wg, other_turn = 2 - wg;
  const uint32_t empty_c = mapa(cx.sb + SM_EMPTY, cw & 1);

  float oA[64], oB[64], i0, i1;
  uint32_t xl[32];
  {
    const int r = lane >> 2, c = lane & 3;
    const int lr0 = cw * 16 + r;
    uint32_t xa[144];
    uint32_t mm0, mm1;
    float rstd0, rstd1, sq0 = 0.f, sq1 = 0.f;
    const uint32_t xf = cx.sb + SM_XFULL + wg * 32, xs = cx.sb + SM_SLOT + wg * 49152;
    auto lo_of = [&](int l) { return ((cw & 3) * 16 + (l & 15)) * 128 + (((l >> 4) ^ (l & 7)) << 4); };
    prof(wg, 0);
    {
      const uint32_t lo = lo_of(lane);
      const uint32_t xb = cx.sb + SM_X + wg * 73728;
      float sm[4][4] = {};
      const uint32_t ws = (lane & 7) == 1 ? 64 : 0;
      uint32_t wb = cx.sb + (ws ? SM_WR + (lane >> 3) * 16 : SM_ONES);
      uint32_t b0[24], b1[24], b2[24];
      mbar_wait(cx.sb + SM_BAR_W, 0);
      TS4(1)
      ln_fetch_b(b0, wb, ws);
      ln_fetch_b(b1, wb, ws);
      ln_fetch_b(b2, wb, ws);
      mbar_wait(xf, 0);
      TS4(2)
      ln_fetch<0, 12>(xa, xb, lo);
      mbar_wait(xf + 8, 0);
      TS4(3)
      ln_fetch<12, 24>(xa, xb, lo);
      ln_sums<0, 12>(xa, sm, b0);
      if (wg == 0) bar_arrive(BAR_XREL + after_fetch<12, 24>(xa), 224);
      mbar_wait(xf + 16, 0);
      TS4(4)
      prof(wg, 1);
      ln_fetch<24, 36>(xa, xb, lo);
      ln_sums<12, 24>(xa, sm, b1);
      ln_sums<24, 36>(xa, sm, b2);
#pragma unroll
      for (int i = 0; i < 4; i++) sm[0][i] = (sm[0][i] + sm[1][i]) + (sm[2][i] + sm[3][i]);
      if (cw == hs && c == 0) {
        *(float*)(cx.sp + SM_RAW + 4 * r) = sm[0][1];
        *(float*)(cx.sp + SM_RAW + 4 * r + 32) = sm[0][3];
      }
      rstd0 = sm[0][0];
      rstd1 = sm[0][2];
      mm0 = pack2(rstd0 * (1.0f / DM), rstd0 * (1.0f / DM));
      mm1 = pack2(rstd1 * (1.0f / DM), rstd1 * (1.0f / DM));
    }
#pragma unroll
    for (int i = 0; i < 16; i++) { xa[2 * i] = sub2(xa[2 * i], mm0); xa[2 * i + 1] = sub2(xa[2 * i + 1], mm1); }
    pin(xa);
    prof(wg, 2);
    TS4(5)

    float (&acc)[64] = oB;
    int st0 = 0;
#pragma unroll 1
    for (int n = 0; n < 16; n++) {
      const int p = n & 3, rb = n >> 2;
      const bool last = p == 3 && !hlp;
#pragma unroll
      for (int i = 0; i < 5; i++) {
        if (i == 4 && last) {
          wg_wait<1>();
          mbar_arrive_cluster(empty_c + 8 * 3, signaller && wg);
          wg_wait<0>();
          pin(acc);
          prof(wg, 6);
#pragma unroll
          for (int j = 0; j < 32; j++) xl[j] = xa[112 + j];
          i0 = rstd0;
          i1 = rstd1;
          goto attention;
        }
        const int st = st0 + i;
        const uint32_t sl = st & 3, slp = (st - 1) & 3;
        if (!wg) mbar_wait(full + 8 * sl, (st >> 2) & 1);
        TS4(8 + 2 * (p * 5 + i))
        const bool join = wg && last;
        if ((i || st0 + wg) && i != (wg ? 4 : 1) && !(join && i == 3)) bar_sync(my_turn, 256);
        wg_fence();
        const uint64_t db = mkdesc(ring + sl * STAGE, 16384);
        const int kb0 = i < 3 ? 8 * i : 8 * i - 4;
#pragma unroll
        for (int k = 0; k < (i == 2 ? 4 : 8); k++) {
          const int kb = kb0 + k;
          mma_n128t(acc, xa[4 * kb], xa[4 * kb + 1], xa[4 * kb + 2], xa[4 * kb + 3], db + k * 128, kb > 0);
        }
        wg_commit();
        TS4(9 + 2 * (p * 5 + i))
        if (wg ? (i == 4 ? st0 < 75 : (i < 2 || i == (join ? 3 : 2))) : i) bar_arrive(other_turn, 256);
        if (p == 0 && i < 4) {
          if (i == 1 && rb) {
            mbar_wait(xf + 8, rb & 1);
            ln_fetch<16, 32>(xa, xs - 32768, lo_of(fresh_lane()));
          }
          if (i == 2 && rb) {
            mbar_wait(xf + 16, rb & 1);
            ln_fetch<32, 36>(xa, xs - 32768, lo_of(fresh_lane()));
          }
#pragma unroll
          for (int j = 0; j < 72; j++)
            if (j >= 2 * (i < 2 ? 8 * i + 8 : 8 * i + 4) && j < 2 * (i == 0 ? 16 : 8 * i + 12)) {
              xa[2 * j] = sub2(xa[2 * j], mm0);
              xa[2 * j + 1] = sub2(xa[2 * j + 1], mm1);
            }
          pin(xa);
        }
        if (i == 4 && n == 0) {
          mbar_wait(cx.sb + SM_BAR_SQ, 0);
          float2* sp = (float2*)(cx.sp + SM_STATS) + lr0;
          float mean0, mean1;
          ln_row(rstd0, sp[0].y, mean0, rstd0);
          ln_row(rstd1, sp[8].y, mean1, rstd1);
          __syncwarp();
          if (c == 0) {
            sp[0] = make_float2(mean0, rstd0);
            sp[8] = make_float2(mean1, rstd1);
          }
          *((uint32_t*)(cx.sp + SM_COLD) + wg) = 0;
          if (!hlp) bar_arrive(BAR_GATE, 352);
          rstd0 *= SM_SCALE_LOG2;
          rstd1 *= SM_SCALE_LOG2;
        }
        if (i == 3 && hlp && p == 3 && rb < 3) bar_arrive(BAR_QS + wg + after_fetch<0, 16>(xa), 160);
        if (i == 4 && p == 3 && rb < 3) {
          const float2* sp = (const float2*)(cx.sp + SM_STATS) + cw * 16 + (fresh_lane() >> 2);
          mm0 = pack2(sp[0].x, sp[0].x);
          mm1 = pack2(sp[8].x, sp[8].x);
          sq0 = sp[0].y * SM_SCALE_LOG2;
          sq1 = sp[8].y * SM_SCALE_LOG2;
#pragma unroll
          for (int j = 0; j < 16; j++) { xa[2 * j] = sub2(xa[2 * j], mm0); xa[2 * j + 1] = sub2(xa[2 * j + 1], mm1); }
          pin(xa);
        }
        if (i == 0) {
          if (wg) {
            wg_wait<0>();
            mbar_arrive_cluster(empty_c + 8 * sl, signaller);
          }
        } else if (i == 2) {
          if (!join) {
            wg_wait<0>();
            mbar_arrive_cluster(empty_c + 8 * sl, signaller);
          }
          if (hlp && p == 3 && rb < 3) {
            mbar_wait(xf, ~rb & 1);
            ln_fetch<0, 16>(xa, xs, lo_of(fresh_lane()));
            pin(xa);
          }
        } else if (i != 3) {
          wg_wait<1>();
          mbar_arrive_cluster(empty_c + 8 * slp, signaller && (i == 4 || !wg));
          wg_wait<0>();
          mbar_arrive_cluster(empty_c + 8 * sl, signaller);
        }
      }
      pin(acc);
      prof(wg, 3 + p);
      TS4(50 + 2 * p)
      st0 += 5;
      if (hlp && st0 > 5) bar_sync(BAR_QF + wg, 160);
      park_paced<0, 8>(qlane(lane) + (hlp ? 5 + wg : 4 + p) * STAGE, acc, rstd0, rstd1, 300);
      if (p || hlp) asm volatile("fence.proxy.async.shared::cta;" ::: "memory");
      if (hlp) bar_arrive(BAR_QS + wg, 160);
      if (p == 3) { rstd0 = sq0; rstd1 = sq1; }
      TS4(51 + 2 * p)
      if (p == 1 && !hlp) {
        float (&ah)[32] = *(float (*)[32])&acc[0];
#pragma unroll
        for (int i = 0; i < 3; i++) {
          const uint32_t sl = (10 + i) & 3;
          if (!wg) mbar_wait(full + 8 * sl, ((10 + i) >> 2) & 1);
          TS4(28 + 2 * i)
          if (i == 0 || i == 2 - wg) bar_sync(my_turn, 256);
          wg_fence();
          const uint64_t db = mkdesc(ring + sl * STAGE, 16);
#pragma unroll
          for (int k = 0; k < 12; k++) {
            const int kb = 12 * i + k;
            if (kb) mma_n64t(ah, xa[4 * kb], xa[4 * kb + 1], xa[4 * kb + 2], xa[4 * kb + 3], db + k * 128, true);
            else mma_n64t_dyn(ah, xa[0], xa[1], xa[2], xa[3], db, blockIdx.y);
          }
          wg_commit();
          TS4(29 + 2 * i)
          if (i == 2 || i != wg) {
            bar_arrive(other_turn, 256);
            if (i) {
              wg_wait<1>();
              mbar_arrive_cluster(empty_c + 8 * ((9 + i) & 3), signaller && i == wg + 1);
            }
            wg_wait<0>();
            mbar_arrive_cluster(empty_c + 8 * sl, signaller);
          }
        }
        pin(ah);
        TS4(54)
        park<0, 4>(qlane(lane) + 6 * STAGE, ah, rstd0, rstd1);
        TS4(55)
        st0 = 13;
        n = 2;
      }
    }
    TS_DUMP()
    ffn_consumer(cx, blockIdx.x & 3, wg, cw, fresh_lane(), x);
    return;
  }

attention:
  uint32_t oa[128];
  float acc[32];
  {
    uint32_t pf[28];
    const uint32_t ql = qlane(fresh_lane());
    uint32_t bad = 0;
    float lA0 = 0.f, lA1 = 0.f, lB0 = 0.f, lB1 = 0.f;
    int t = 0;
    uint32_t ra = 2 * 2048, rb = 2048, rc = 2 * 2048, par = 0;
    const uint64_t dk0 = mkdesc(ring, 16), dv0 = mkdesc(ring, 16384);
    uint64_t dqA = mkdesc_q(qwg + 4 * STAGE), dqB = dqA + 2048;
    auto turn = [&](auto kc_, auto bc_) {
      constexpr int KIND = decltype(kc_)::value, BIG = decltype(bc_)::value;
      constexpr int HB = KIND == 1, ID = 10 * KIND + 30 * BIG, T0 = BIG ? 38 : 0;
      constexpr int NS = BIG ? 56 : 48, SPLIT = (BIG ? 36 : 30) + 2 * HB;
      float s[NS];
      float (&op)[64] = HB ? oA : oB;
      uint32_t h0 = 0, h1 = 0;
      TS2(0)
      bar_sync(my_turn, 256);
      TS2(1)
      if (KIND) { pin(pf); pin(op); }
      mma_qk(s, HB ? dqB : dqA, dk0 + (HB ? ra : rc));
      TS2(2)
      if (KIND) {
        const bool bigp = HB ? BIG : BIG ? t != 10 : t == 66;
        block_fence(ID + 9);
        pin(pf);
        sum_tree(pf, bigp, h0, h1);
        asm volatile("" : "+r"(h0), "+r"(h1)::"memory");
        if (HB) mbar_wait(full + (rb >> 8), par);
        mma_pv(op, pf, dv0 + rb, t != T0 + 2 - HB, bigp);
      } else {
        mbar_wait(full + (rb >> 8), (NST_Q - 1) >> 2 & 1);
#pragma unroll
        for (int k = 0; k < 8; k++) mma_n128t(op, xl[4 * k], xl[4 * k + 1], xl[4 * k + 2], xl[4 * k + 3], dv0 + rb + k * 128, 1);
        wg_commit();
      }
      TS2(3)
      bar_arrive(other_turn, 256);
      (HB ? lA0 : lB0) += bf_lo(h0) + bf_hi(h0);
      (HB ? lA1 : lB1) += bf_lo(h1) + bf_hi(h1);
      wg_wait<1>();
      pin(s);
      TS1(t)
      TS2(4)
      if (KIND == 1) mbar_arrive_cluster_now<ID + 3>(empty_c + (ra >> 8), signaller);
      if (BIG && t == T0 + HB) {
        const uint32_t a = ql + (4 + HB) * STAGE;
        const bool ok = !__any_sync(0xffffffffu, inv_sums(HB ? lB0 : lA0, HB ? lB1 : lA1, i0, i1));
        if (!ok) bad |= 1 << HB;
        (HB ? lB0 : lA0) = 0.f;
        (HB ? lB1 : lA1) = 0.f;
        constexpr int E0 = 10, E1 = (E0 + SPLIT) / 2;
        softmax_exp<0, E0>(s);
#pragma unroll
        for (int i = 0; i < E0; i++) asm volatile("" : "+f"(s[i])::"memory");
        block_fence(ID + 7);
        softmax_exp<E0, E1>(s);
        park<0, 4>(a, HB ? oB : oA, i0, i1, ok);
#pragma unroll
        for (int i = E0; i < E1; i++) asm volatile("" : "+f"(s[i])::"memory");
        block_fence(200 + ID);
        softmax_exp<E1, SPLIT>(s);
        park<4, 8>(a, HB ? oB : oA, i0, i1, ok);
        if (!HB) dqB += 2048;
        prof(wg, 8 + HB);
      } else {
        softmax_exp<0, SPLIT>(s);
      }
      pin(s);
      if (!BIG) block_fence(ID + 4);
      TS2(5)
      wg_wait<0>();
      TS2(6)
      pin(op);
      if (KIND) pin(pf); else pin(xl);
      if (HB) {
        par ^= rc == 2048;
        if (BIG && t == 37) dqA -= 4 * 2048;
        if (BIG && t == 33 && cw == 0) bar_arrive(BAR_HELPER, 64);
      } else {
        mbar_arrive_cluster_now<ID + 5>(empty_c + (rb >> 8), signaller);
        if (KIND) {
          par ^= ra == 2048;
          const uint32_t x = ra;
          ra = rc; rc = rb; rb = x;
        }
      }
      softmax_exp<SPLIT, NS>(s);
#pragma unroll
      for (int i = 0; i < NS / 2; i++) pf[i] = pack2(s[2 * i], s[2 * i + 1]);
      pin(pf);
      if (KIND == 0) {
        block_fence(ID + 6);
        park_paced<0, 6>(ql, oB, i0, i1, 310);

        prof(wg, 7);
      }
      if (HB && !BIG && t == 1) park<6, 8>(ql, oB, i0, i1);
      if (BIG && !HB && t == T0) mbar_wait(cx.sb + SM_BAR_Q + 8 * wg, 0);
      if (HB) mbar_wait(full + (rc >> 8), par);
      t++;
    };
#pragma unroll
    for (int i = 24; i < 28; i++) asm volatile("" : "=r"(pf[i]));
    mbar_wait(full + 8 * 2, 0);
    turn(IC<0>(), IC<0>());
    rb = 3 * 2048; rc = 2048;
    kill(oA);
    const bool never = blockIdx.y == 1;
#pragma unroll 1
    while (true) {
      turn(IC<1>(), IC<0>());
      if (t == 76) break;
      if (t == 10) {
        asm volatile("fence.proxy.async.shared::cta;" ::: "memory");
#pragma unroll 1
        do {
#pragma unroll 1
          do turn(IC<2>(), IC<1>()); while (never);
          turn(IC<1>(), IC<1>());
        } while (t != 66);
      }
#pragma unroll 1
      do turn(IC<2>(), IC<0>()); while (never);
    }
    auto scale = [&](auto lo, auto hi) {
#pragma unroll
      for (int i = decltype(lo)::value; i < decltype(hi)::value; i++) {
        oa[32 + 2 * i] = pack2(oA[4 * i] * i0, oA[4 * i + 1] * i0);
        oa[32 + 2 * i + 1] = pack2(oA[4 * i + 2] * i1, oA[4 * i + 3] * i1);
        asm volatile("" : "+r"(oa[32 + 2 * i]), "+r"(oa[32 + 2 * i + 1])::"memory");
      }
    };
    TS3(1)
    volatile uint32_t* const cold = (volatile uint32_t*)(cx.sp + SM_COLD) + wg;
    if (inv_sums(lA0, lA1, i0, i1)) bad |= 4;
#pragma unroll
    for (int i = 0; i < 8; i++) ldsm4(ql + 4 * STAGE + i * 2048, oa[4 * i], oa[4 * i + 1], oa[4 * i + 2], oa[4 * i + 3]);
    {
      uint32_t h0, h1;
      sum_tree(pf, false, h0, h1);
      lB0 += bf_lo(h0) + bf_hi(h0);
      lB1 += bf_lo(h1) + bf_hi(h1);
      asm volatile("" : "+f"(lB0), "+f"(lB1)::"memory");
    }
    scale(IC<0>(), IC<4>());
    if (bad) *cold = 1;
    block_fence(93);
    TS3(2)
    bar_sync(my_turn, 256);
    TS3(3)
    pin(pf); pin(oB);
    mma_pv(oB, pf, dv0 + 2 * 2048, true, false);
    block_fence(91);
    TS3(4)
    const uint32_t held = *cold;
    if (inv_sums(lB0, lB1, lB0, lB1)) bad |= 8;
    const uint64_t db = mkdesc(ring + 3 * STAGE, 16);
    scale(IC<4>(), IC<12>());
    mbar_arrive_cluster_now<94>(empty_c, signaller && !held);
#pragma unroll
    for (int i = 0; i < 32; i++) asm volatile("" : "+r"(oa[i])::"memory");
    wg_fence();
#pragma unroll
    for (int k = 0; k < 8; k++) mma_n64t(acc, oa[4 * k], oa[4 * k + 1], oa[4 * k + 2], oa[4 * k + 3], db + k * 128, k > 0);
    wg_commit();
    block_fence(95);
    scale(IC<12>(), IC<16>());
    TS3(5)
    wg_fence();
#pragma unroll
    for (int k = 8; k < 16; k++) mma_n64t(acc, oa[4 * k], oa[4 * k + 1], oa[4 * k + 2], oa[4 * k + 3], db + k * 128, 1);
    wg_commit();
    bar_arrive(other_turn, 256);
    if (bad) *cold = 1;
    bar_sync(4 + wg, 128);
    const uint32_t is_cold = *cold;
    wg_wait<2>();
    pin(oB); pin(pf);
    TS(76)
    TS3(6)
    mbar_arrive_cluster_now<97>(empty_c + 8 * 2, signaller);
#pragma unroll
    for (int i = 16; i < 24; i++) ldsm4(ql + 5 * STAGE + (i & 7) * 2048, oa[4 * i], oa[4 * i + 1], oa[4 * i + 2], oa[4 * i + 3]);
#pragma unroll
    for (int i = 0; i < 16; i++) {
      oa[96 + 2 * i] = pack2(oB[4 * i] * lB0, oB[4 * i + 1] * lB0);
      oa[96 + 2 * i + 1] = pack2(oB[4 * i + 2] * lB1, oB[4 * i + 3] * lB1);
    }
    TS3(7)
    if (!wg) mbar_wait(full + 8 * 1, 0);
    TS3(8)
    wg_wait<0>();
    pin(acc); pin(oa);
    if (__any_sync(0xffffffffu, is_cold)) {
      bad = __reduce_or_sync(0xffffffffu, bad);
      if (!(bad & 8)) {
#pragma unroll
        for (int i = 24; i < 32; i++) stsm4(ql + 6 * STAGE + (i & 7) * 2048, oa[4 * i], oa[4 * i + 1], oa[4 * i + 2], oa[4 * i + 3]);
      }
#pragma unroll 1
      for (int h = 0; h < 4; h++) {
        if (bad >> h & 1) {
          const uint32_t a = ql + ((0x6054 >> (4 * h)) & 7) * STAGE;
          const int l = fresh_lane(), o = (hs * 2 + (h >> 1)) * SEQ * DH + (l >> 2) * DH + (l & 3) * 2;
          uint32_t q[32];
#pragma unroll
          for (int i = 0; i < 8; i++) ldsm4(a + i * 2048, q[4 * i], q[4 * i + 1], q[4 * i + 2], q[4 * i + 3]);
#pragma unroll 1
          for (int i = 0; i < 4; i++) {
            float ox[16], l0, l1;
            exact_attention(ox, l0, l1, q, kc + o, vc + o + i * 32);
            inv_sums(l0, l1, l0, l1);
            park<0, 2>(a + i * 4096, ox, l0, l1);
          }
        }
      }
      __syncwarp();
#pragma unroll
      for (int i = 0; i < 32; i++)
        if ((i >> 3) != 1 || (bad & 4))
          ldsm4(ql + ((0x6504 >> (4 * (i >> 3))) & 7) * STAGE + (i & 7) * 2048, oa[4 * i], oa[4 * i + 1], oa[4 * i + 2], oa[4 * i + 3]);
      pin(oa);
      asm volatile("fence.proxy.async.shared::cta;" ::: "memory");
      bar_sync(4 + wg, 128);
      mbar_arrive_cluster(empty_c, signaller && held);
      wg_fence();
#pragma unroll
      for (int k = 0; k < 16; k++) mma_n64t(acc, oa[4 * k], oa[4 * k + 1], oa[4 * k + 2], oa[4 * k + 3], db + k * 128, k > 0);
      wg_commit();
      wg_wait<0>();
      pin(acc);
    }
    mbar_arrive_cluster(empty_c + 8 * 3, signaller);
  }

  prof(wg, 10);
  TS3(9)
  {
    lane = fresh_lane();
    const int tw = (cw & 3) * 32 + lane;
    float red[32];
    kill(red);
    const uint32_t tag = *(const uint32_t*)(cx.sp + SM_TAG);
    uint4* const xch = at(cx.g->part, ((qb * 64 * 2 + wg) * 4 * 128 + tw) * 16);
    int nrx = 1;
    auto region = [](int s, int h) { return h ? 1 + (s & 1) : (s & 1) ? 0 : 3; };
    auto half_step = [&](int s, auto hc, bool arrive) {
      constexpr int h = decltype(hc)::value;
      const uint64_t db = mkdesc(ring + region(s, h) * STAGE, 16);
      bar_sync(my_turn, 256);
      pin(oa);
      wg_fence();
#pragma unroll
      for (int k = 0; k < 16; k++) {
        const int kb = h * 16 + k;
        mma_n64t(acc, oa[4 * kb], oa[4 * kb + 1], oa[4 * kb + 2], oa[4 * kb + 3], db + k * 128, kb > 0);
      }
      wg_commit();
      if (arrive) bar_arrive(other_turn, 256);
    };
    auto await = [&](int s, int h) { mbar_wait(full + 8 * region(s, h), ((s >> 1) ^ h ^ 1) & 1); };
    auto fetch = [&](uint32_t (&g)[16], int n) {
      const uint4* p = at(xch, (hs * 7 + n - 1) * 16384);
#pragma unroll
      for (int i = 0; i < 4; i++) ld_gran(p + i * 128, g[4 * i], g[4 * i + 1], g[4 * i + 2], g[4 * i + 3]);
    };
    uint32_t g[16];
    bool pend = false;
#pragma unroll 1
    for (int s = 0;; s++) {
      half_step(s, IC<1>(), s + wg < 9);
      if (s == 8) break;
      TS3(s < 3 ? 16 + 8 * s : 75)
      if (s == 0) {
        bar_arrive(BAR_OA, 352);
#pragma unroll
        for (int i = 0; i < 32; i++) red[i] = 0.f;
      }
      await(s + 1, 0);
      TS3(s < 3 ? 17 + 8 * s : 75)
      wg_wait<0>();
      TS3(s < 3 ? 18 + 8 * s : 75)
      mbar_arrive_cluster(empty_c + 8 * region(s, 1), signaller && s < 7);
      pin(acc);
      TS(77 + s)
      prof(wg, 12 + s);
      uint4* p = at(xch, (s == 0 ? 56 + hs : ((hs + s) & 7) * 7 + s - 1) * 16384);
#pragma unroll
      for (int i = 0; i < 4; i++)
        st_gran(p + i * 128, (pack2(acc[8 * i], acc[8 * i + 1]) & ~TAG) | tag, pack2(acc[8 * i + 2], acc[8 * i + 3]),
                pack2(acc[8 * i + 4], acc[8 * i + 5]), pack2(acc[8 * i + 6], acc[8 * i + 7]));
      TS3(s < 3 ? 19 + 8 * s : 75)
      half_step(s + 1, IC<0>(), true);
      TS3(s < 3 ? 20 + 8 * s : 75)
      if (pend && granules_ok(g, tag)) { add_granules(red, g); nrx++; }
      pend = nrx < s;
      if (pend) fetch(g, nrx);
      await(s + 1, 1);
      TS3(s < 3 ? 21 + 8 * s : 75)
      wg_wait<0>();
      TS3(s < 3 ? 22 + 8 * s : 75)
      mbar_arrive_cluster(empty_c + 8 * region(s + 1, 0), signaller && s < 6);
    }
    uint32_t xv[16], gt[16], g2[16];
    TS3(42)
    const bool ok = granules_ok(g, tag);
    TS3(43)
    nrx += ok;
    fetch(g2, nrx);
    mbar_wait(cx.sb + SM_BAR_XG, 0);
    const uint32_t frag = (cw * 16 + (lane & 15)) * 128 + (((lane >> 4) ^ (lane & 7)) << 4);
#pragma unroll
    for (int i = 0; i < 4; i++) {
      ldsm4(cx.sb + SM_XO + (frag ^ (i << 5)), xv[4 * i], xv[4 * i + 1], xv[4 * i + 2], xv[4 * i + 3]);
      ldsm4(cx.sb + SM_GO + (frag ^ (i << 5)), gt[4 * i], gt[4 * i + 1], gt[4 * i + 2], gt[4 * i + 3]);
    }
    if (ok) add_granules(red, g);
    TS3(44)
    wg_wait<0>();
    pin(acc);
    TS(85)
#pragma unroll
    for (int i = 0; i < 32; i++) red[i] += acc[i];
    pin(red);
#pragma unroll 1
    for (int spins = 0; spins < (1 << 16); spins++) {
      if (granules_ok(g2, tag)) {
        add_granules(red, g2);
        if (++nrx == 8) break;
      }
      fetch(g2, nrx);
    }
    uint32_t ow[16];
#pragma unroll
    for (int i = 0; i < 16; i++) ow[i] = pack2(red[2 * i], red[2 * i + 1]);
    prof(wg, 20);
    TS(86)
#pragma unroll
    for (int i = 0; i < 16; i++) ow[i] = fma2(ow[i], gt[i], xv[i]);
#pragma unroll
    for (int i = 0; i < 4; i++) stsm4(cx.sb + SM_XO + (frag ^ (i << 5)), ow[4 * i], ow[4 * i + 1], ow[4 * i + 2], ow[4 * i + 3]);
    __syncwarp();
    __nv_bfloat16* const op = at(out, ((qb * 128 + cw * 16 + (lane >> 3)) * DM + hs * 64 + (lane & 7) * 8) * 2);
#pragma unroll
    for (int i = 0; i < 4; i++) {
      uint4 v;
      const int row = cw * 16 + i * 4 + (lane >> 3);
      lds128(cx.sb + SM_XO + row * 128 + (((lane ^ row) & 7) << 4), v.x, v.y, v.z, v.w);
      asm volatile("st.global.v4.b32 [%0], {%1, %2, %3, %4};" ::"l"(op + i * 4 * DM),
                   "r"(v.x), "r"(v.y), "r"(v.z), "r"(v.w) : "memory");
    }
    prof(wg, 22);
    TS(87)
    TS_DUMP()
  }
}

struct KvMaps { CUtensorMap m[4]; };
__global__ void __cluster_dims__(2, 1, 1) __launch_bounds__(THREADS, 1)
fused_kernel(const __nv_bfloat16* __restrict__ x, const __nv_bfloat16* __restrict__ w_r, const __nv_bfloat16* __restrict__ kc,
             const __nv_bfloat16* __restrict__ vc, __nv_bfloat16* __restrict__ out, Scratch* scratch,
             const __grid_constant__ CUtensorMap tmX, const __grid_constant__ CUtensorMap tmWq,
             const __grid_constant__ KvMaps tmKV, const __grid_constant__ CUtensorMap tmWo,
             const __grid_constant__ CUtensorMap tmG, const __grid_constant__ CUtensorMap tmU,
             const __grid_constant__ CUtensorMap tmD, const __grid_constant__ CUtensorMap tmX16,
             const __grid_constant__ CUtensorMap tmWq96, const __grid_constant__ CUtensorMap tmX64) {
  extern __shared__ __align__(1024) uint8_t smem_raw[];
  prof(0, 23, 511);
  Ctx cx;
  cx.sb = smem_u32(smem_raw);
  cx.sp = smem_raw;
  cx.g = scratch;
  cx.rank = blockIdx.x & 1;
  const int warp = __shfl_sync(0xffffffffu, threadIdx.x >> 5, 0);
  const int cluster = blockIdx.x >> 1;
  const bool is_ffn = blockIdx.x >= N_ATT_CTA;
  const int c7 = ((cluster - 36) * 37) >> 8;
  const int hs = cluster < 4 ? 4 + cluster : cluster < 36 ? (cluster - 4) >> 3 : 4 + c7;
  const int qb = (cluster < 4 ? 0 : cluster < 36 ? (cluster - 4) & 7 : cluster - (is_ffn ? 36 : 35) - 7 * c7) * 2 + cx.rank;

  auto load_x = [&](int w) {
#pragma unroll
    for (int i = 0; i < 3; i++) {
      mbar_expect_tx(cx.sb + SM_XFULL + 32 * w + 8 * i, 24576);
      tma3d(cx.sb + SM_X + (3 * w + i) * 24576, &tmX, qb * 128 + w * 64, i * 3, cx.sb + SM_XFULL + 32 * w + 8 * i);
    }
  };
  if (warp < 4) {
    asm volatile("setmaxnreg.dec.sync.aligned.u32 24;");
    if (elect_one()) {
      if (warp == 0) TSP(64)
      if (warp < 2) {
#pragma unroll
        for (int i = 0; i < 4; i++) mbar_init(cx.sb + SM_FULL + 32 * warp + 8 * i, 1 + 3 * warp);
        mbar_init(cx.sb + SM_BAR_XG + 8 * warp, 1);
        mbar_init(cx.sb + SM_BAR_Q + 8 * warp, 1);
        if (warp) mbar_init(cx.sb + SM_BAR_MISC, 1);
      } else if (is_ffn) {
#pragma unroll
        for (int i = 0; i < 8; i++) mbar_init(cx.sb + (warp == 2 ? SM_FFULL : SM_FEMPTY) + 8 * i, 1);
      }
      asm volatile("fence.mbarrier_init.release.cluster;" ::: "memory");
    }
    __syncwarp();
    cluster_arrive();
    if (warp == 0) TSP(70)
    cluster_wait();
    if (warp == 0) TSP(71)
    prof(0, 24, 511);
    if (warp == 0) {
      if (is_ffn) ffn_producer(cx, qb, &tmWq, &tmG, &tmU, &tmD);
      else attn_producer(cx, qb, hs, tmKV.m, &tmWq, &tmWq96, &tmWo);
      prof(0, 25, 511);
    } else {
      sq_publish(cx, qb, hs, warp - 1, read_lane());
      if (warp == 3) sq_collect(cx, qb, read_lane());
      if (!is_ffn) {
        attn_gate(cx, qb, hs, warp - 1, threadIdx.x - 32, x);
        if (warp == 1) TSP(65)
        asm volatile("fence.proxy.async.global;" ::: "memory");
        if (warp == 1) attn_helper(cx, qb, hs, fresh_lane(), &tmX16);
        else bar_arrive(BAR_OA, 352);
        attn_finish8(cx, qb, hs, warp - 1, fresh_lane(), out);
      } else if (warp < 3) {
        ffn_publish(cx, qb, warp - 1, fresh_lane(), &tmX64);
      }
    }
    __syncwarp();
    cluster_arrive();
    cluster_wait();
  } else {
    if (warp == 4 && elect_one()) {
#pragma unroll
      for (int i = 0; i < 3; i++) mbar_init(cx.sb + SM_XFULL + 8 * i, 1);
      TSP(66)
      load_x(0);
#pragma unroll
      for (int i = 4; i < 7; i++) mbar_init(cx.sb + SM_XFULL + 8 * i, 1);
      asm volatile("fence.mbarrier_init.release.cluster;" ::: "memory");
    }
    if (warp == 5 && elect_one()) {
      mbar_init(cx.sb + SM_BAR_W, 1);
      asm volatile("fence.mbarrier_init.release.cluster;" ::: "memory");
      *(uint4*)(cx.sp + SM_ONES) = make_uint4(0x3F803F80u, 0x3F803F80u, 0x3F803F80u, 0x3F803F80u);
      mbar_expect_tx(cx.sb + SM_BAR_W, DM * 2);
      bulk_load(cx.sb + SM_WR, w_r, DM * 2, cx.sb + SM_BAR_W);
    }
    __syncwarp();
    cluster_arrive();
    if (warp == 4 && elect_one()) {
      load_x(1);
      TSP(67)
    }
    __syncwarp();
    asm volatile("setmaxnreg.inc.sync.aligned.u32 240;");
    const int cw = warp - 4, wg = cw >> 2;
    cluster_wait();
    if (warp == 8 && elect_one()) {
      const uint64_t pol = policy_evict_first();
#pragma unroll
      for (int i = 0; i < 4; i++) {
        if (!(i & 1)) mbar_expect_tx(cx.sb + SM_FULL + 4 * i, 32768);
        tma2d_mc(cx.sb + SM_RING + (i >> 1) * STAGE + cx.rank * 16384 + (i & 1) * 8192, &tmWq,
                 is_ffn ? (cx.rank * 4 + 3) * DH + 64 : hs * 512 + cx.rank * 64, i * 64, cx.sb + SM_FULL + 8 * (i >> 1), pol);
      }
      TSP(72)
    }
    __syncwarp();
    attn_consumer(cx, is_ffn, qb, hs, wg, cw, read_lane(), x, kc, vc, out);
  }
}

typedef CUresult (*EncodeFn)(CUtensorMap*, CUtensorMapDataType, cuuint32_t, void*, const cuuint64_t*, const cuuint64_t*,
                             const cuuint32_t*, const cuuint32_t*, CUtensorMapInterleave, CUtensorMapSwizzle,
                             CUtensorMapL2promotion, CUtensorMapFloatOOBfill);

void encode(EncodeFn fn, CUtensorMap* m, const void* p, int rank, const cuuint64_t* dims, const cuuint64_t* strides,
            const cuuint32_t* box) {
  const cuuint32_t es[5] = {1, 1, 1, 1, 1};
  fn(m, CU_TENSOR_MAP_DATA_TYPE_BFLOAT16, rank, const_cast<void*>(p), dims, strides, box, es, CU_TENSOR_MAP_INTERLEAVE_NONE,
     CU_TENSOR_MAP_SWIZZLE_128B, CU_TENSOR_MAP_L2_PROMOTION_L2_128B, CU_TENSOR_MAP_FLOAT_OOB_FILL_NONE);
}
void encode2d(EncodeFn fn, CUtensorMap* m, const void* p, uint64_t rows, uint64_t cols, uint32_t box_rows) {
  const cuuint64_t dims[2] = {cols, rows}, strides[1] = {cols * 2};
  const cuuint32_t box[2] = {64, box_rows};
  encode(fn, m, p, 2, dims, strides, box);
}

}

extern "C" void kernel_launch(void* const* d_in, const int* in_sizes, int n_in, void* d_out, int out_size) {
  (void)in_sizes; (void)n_in; (void)out_size;
  void* fnp = nullptr;
  cudaDriverEntryPointQueryResult qr;
  cudaGetDriverEntryPoint("cuTensorMapEncodeTiled", &fnp, cudaEnableDefault, &qr);
  EncodeFn fn = (EncodeFn)fnp;
  CUtensorMap tmWq, tmWo, tmG, tmU, tmD, tmX, tmX16, tmWq96, tmX64;
  encode2d(fn, &tmX64, d_in[0], SEQ, DM, 64);
  encode2d(fn, &tmWq96, d_in[3], DM, 4096, 96);
  encode2d(fn, &tmX16, d_in[0], SEQ, DM, 16);
  KvMaps tmKV;
  for (int i = 0; i < 4; i++) encode2d(fn, &tmKV.m[i], d_in[1 + (i & 1)], 16 * SEQ, DH, i < 2 ? 112 : 96);
  encode2d(fn, &tmWq, d_in[3], DM, 4096, 64);
  {
    const cuuint64_t dims[3] = {64, SEQ, 9}, strides[2] = {DM * 2, 128};
    const cuuint32_t box[3] = {64, 64, 3};
    encode(fn, &tmX, d_in[0], 3, dims, strides, box);
  }
  encode2d(fn, &tmWo, d_in[4], 4096, DM, 128);
  encode2d(fn, &tmG, d_in[7], DM, FF, 192);
  encode2d(fn, &tmU, d_in[8], DM, FF, 192);
  encode2d(fn, &tmD, d_in[9], FF, DM, 192);
  cudaFuncSetAttribute(fused_kernel, cudaFuncAttributeMaxDynamicSharedMemorySize, SM_TOTAL);
  void* scratch = nullptr;
  cudaGetSymbolAddress(&scratch, g_scratch);
  fused_kernel<<<N_CTA, THREADS, SM_TOTAL>>>((const __nv_bfloat16*)d_in[0], (const __nv_bfloat16*)d_in[6], (const __nv_bfloat16*)d_in[1],
                                            (const __nv_bfloat16*)d_in[2], (__nv_bfloat16*)d_out, (Scratch*)scratch, tmX, tmWq, tmKV,
                                            tmWo, tmG, tmU, tmD, tmX16, tmWq96, tmX64);
}
```

```cpp
#include <cuda_runtime.h>
#include <cuda_bf16.h>
#include <cuda.h>
#include <stdint.h>

namespace {

constexpr int SEQ = 2048, DM = 576, DH = 128, FF = 4608, TOPC = 8;
constexpr int N_ATT_CTA = 128, N_CTA = 132;
constexpr int THREADS = 384;

constexpr uint32_t SM_RING = 0;
constexpr uint32_t STAGE = 32768;
constexpr uint32_t SM_SLOT = 131072;
constexpr uint32_t FSTAGE = 24576;
constexpr uint32_t SM_XSEL = 196608;
constexpr uint32_t SM_H = 205824;
constexpr uint32_t SM_MISC = 229376;
constexpr uint32_t SM_FULL = SM_MISC, SM_EMPTY = SM_MISC + 32, SM_FFULL = SM_MISC + 64, SM_BAR_MISC = SM_MISC + 128,
                   SM_COLD = SM_MISC + 136, SM_TAG = SM_MISC + 144, SM_BAR_W = SM_MISC + 152, SM_ONES = SM_MISC + 160,
                   SM_BAR_Q = SM_MISC + 176, SM_XFULL = SM_MISC + 192, SM_BAR_XG = SM_MISC + 304, SM_BAR_SQ = SM_MISC + 312,
                   SM_STATS = SM_MISC + 320, SM_FEMPTY = SM_MISC + 1344, SM_RAW = SM_FEMPTY, SM_WR = SM_MISC + 1408, SM_TOPK = SM_WR;
constexpr uint32_t SM_TOTAL = SM_MISC + 2560;
constexpr uint32_t SM_X = SM_MISC - 147456;

constexpr int BAR_GATE = 6, BAR_HELPER = 7, BAR_OA = 8, BAR_XREL = 13, BAR_QS = 9, BAR_QF = 11;
constexpr int NST_Q = 18, NST_KV = 76, NST_O = 18;
constexpr float SM_SCALE_LOG2 = 0.08838834764831845f * 1.4426950408889634f;

struct Scratch {
  uint4 part[16 * 64 * 2 * 4 * 128];
  uint4 gate[N_ATT_CTA * 1152];
  uint4 q[16 * 8 * 2 * 512];
  uint2 sq[SEQ];
  uint4 stats[SEQ];
  float ypart[4 * TOPC * DM];
  int2 sel[16];
  unsigned launch[160];
  unsigned pad0, ycnt, pad[30];
  unsigned qflag[128];
};
__device__ __align__(1024) Scratch g_scratch;

__device__ __forceinline__ void prof(int, int, int = 0) {}

#define TS(id) {}
#define TS_DUMP() {}
#define TSH(k) {}
#define TS4(k) {}
#define TSP(k) {}
#define TS1(id) TS(id)
#define TS2(k) {}
#define TS3(k) {}

__device__ __forceinline__ uint32_t smem_u32(const void* p) { return (uint32_t)__cvta_generic_to_shared(p); }
__device__ __forceinline__ void mbar_init(uint32_t bar, uint32_t cnt) {
  asm volatile("mbarrier.init.shared::cta.b64 [%0], %1;" ::"r"(bar), "r"(cnt) : "memory");
}
__device__ __forceinline__ void mbar_expect_tx(uint32_t bar, uint32_t bytes) {
  asm volatile("mbarrier.arrive.expect_tx.shared::cta.b64 _, [%0], %1;" ::"r"(bar), "r"(bytes) : "memory");
}
__device__ __forceinline__ void mbar_arrive(uint32_t bar) {
  asm volatile("mbarrier.arrive.shared::cta.b64 _, [%0];" ::"r"(bar) : "memory");
}
__device__ __forceinline__ void mbar_arrive_cluster(uint32_t bar_cluster_addr, bool pred) {
  asm volatile("{\n.reg .pred p;\nsetp.ne.u32 p, %1, 0;\n@p mbarrier.arrive.shared::cluster.b64 _, [%0];\n}"
               ::"r"(bar_cluster_addr), "r"((uint32_t)pred) : "memory");
}
template <int ID>
__device__ __forceinline__ void mbar_arrive_cluster_now(uint32_t bar_cluster_addr, bool pred) {
  asm volatile("{\n.reg .pred p, q;\nsetp.ne.u32 p, %1, 0;\nsetp.eq.u32 q, %2, %3;\n"
               "ARR_LOOP:\n@p mbarrier.arrive.shared::cluster.b64 _, [%0];\n@q bra.uni ARR_LOOP;\n}"
               ::"r"(bar_cluster_addr), "r"((uint32_t)pred), "r"(blockIdx.y), "n"(ID) : "memory");
}
__device__ __forceinline__ void block_fence(int id) {
  asm volatile("{\n.reg .pred q;\nsetp.eq.u32 q, %0, %1;\nBF_LOOP:\n@q st.volatile.shared.u32 [%0], %0;\n@q bra.uni BF_LOOP;\n}"
               ::"r"(blockIdx.y), "r"(id) : "memory");
}
__device__ __forceinline__ void mbar_wait(uint32_t bar, uint32_t parity) {
  asm volatile("{\n.reg .pred p, q;\n.reg .u32 n;\nmov.u32 n, 0;\n"
               "WAIT_LOOP:\nmbarrier.try_wait.parity.shared::cta.b64 p, [%0], %1;\n"
               "add.u32 n, n, 1;\nsetp.lt.u32 q, n, 262144;\nand.pred q, q, !p;\n@q bra WAIT_LOOP;\n}"
               ::"r"(bar), "r"(parity) : "memory");
}
__device__ __forceinline__ uint32_t mapa(uint32_t addr, uint32_t rank) {
  uint32_t r;
  asm volatile("mapa.shared::cluster.u32 %0, %1, %2;" : "=r"(r) : "r"(addr), "r"(rank));
  return r;
}
__device__ __forceinline__ void cluster_arrive() { asm volatile("barrier.cluster.arrive.relaxed.aligned;" ::: "memory"); }
__device__ __forceinline__ bool elect_one() {
  uint32_t p;
  asm volatile("{\n.reg .pred p;\nelect.sync _|p, 0xffffffff;\nselp.u32 %0, 1, 0, p;\n}" : "=r"(p));
  return p;
}
__device__ __forceinline__ int read_lane() { return threadIdx.x & 31; }
__device__ __forceinline__ int fresh_lane() {
  int l;
  asm volatile("mov.u32 %0, %%laneid;" : "=r"(l));
  return l;
}
template <class T> __device__ __forceinline__ T* at(T* p, uint32_t bytes) {
  asm("" : "+r"(bytes));
  return (T*)((const char*)p + bytes);
}
__device__ __forceinline__ void cluster_wait() { asm volatile("barrier.cluster.wait.acquire.aligned;" ::: "memory"); }
__device__ __forceinline__ void bar_sync(int id, int n) { asm volatile("barrier.cta.sync %0, %1;" ::"r"(id), "r"(n) : "memory"); }
__device__ __forceinline__ void bar_arrive(int id, int n) { asm volatile("barrier.cta.arrive %0, %1;" ::"r"(id), "r"(n) : "memory"); }

__device__ __forceinline__ uint64_t policy_evict_first() {
  uint64_t p;
  asm("createpolicy.fractional.L2::evict_first.b64 %0, 1.0;" : "=l"(p));
  return p;
}
__device__ __forceinline__ void tma2d_mc(uint32_t dst, const CUtensorMap* tm, int c0, int c1, uint32_t bar, uint64_t pol) {
  asm volatile("cp.async.bulk.tensor.2d.shared::cluster.global.mbarrier::complete_tx::bytes.multicast::cluster.L2::cache_hint"
               " [%0], [%1, {%2, %3}], [%4], %5, %6;"
               ::"r"(dst), "l"(tm), "r"(c0), "r"(c1), "r"(bar), "h"((uint16_t)3), "l"(pol) : "memory");
}
__device__ __forceinline__ void tma3d(uint32_t dst, const CUtensorMap* tm, int c1, int c2, uint32_t bar) {
  asm volatile("cp.async.bulk.tensor.3d.shared::cluster.global.mbarrier::complete_tx::bytes [%0], [%1, {%2, %3, %4}], [%5];"
               ::"r"(dst), "l"(tm), "r"(0), "r"(c1), "r"(c2), "r"(bar) : "memory");
}
__device__ __forceinline__ void tma2d(uint32_t dst, const CUtensorMap* tm, int c0, int c1, uint32_t bar) {
  asm volatile("cp.async.bulk.tensor.2d.shared::cluster.global.mbarrier::complete_tx::bytes [%0], [%1, {%2, %3}], [%4];"
               ::"r"(dst), "l"(tm), "r"(c0), "r"(c1), "r"(bar) : "memory");
}
__device__ __forceinline__ void tma2d_stream(uint32_t dst, const CUtensorMap* tm, int c0, int c1, uint32_t bar) {
  asm volatile("{\n.reg .b64 pol;\ncreatepolicy.fractional.L2::evict_first.b64 pol, 1.0;\n"
               "cp.async.bulk.tensor.2d.shared::cluster.global.mbarrier::complete_tx::bytes.L2::cache_hint [%0], [%1, {%2, %3}], [%4], pol;\n}"
               ::"r"(dst), "l"(tm), "r"(c0), "r"(c1), "r"(bar) : "memory");
}
__device__ __forceinline__ void bulk_load(uint32_t dst, const void* src, uint32_t bytes, uint32_t bar) {
  asm volatile("cp.async.bulk.shared::cluster.global.mbarrier::complete_tx::bytes [%0], [%1], %2, [%3];"
               ::"r"(dst), "l"(src), "r"(bytes), "r"(bar) : "memory");
}
__device__ __forceinline__ void tma2d_prefetch(const CUtensorMap* tm, int c0, int c1) {
  asm volatile("cp.async.bulk.prefetch.tensor.2d.L2.global [%0, {%1, %2}];" ::"l"(tm), "r"(c0), "r"(c1) : "memory");
}

__device__ __forceinline__ void wg_fence() { asm volatile("wgmma.fence.sync.aligned;" ::: "memory"); }
__device__ __forceinline__ void wg_commit() { asm volatile("wgmma.commit_group.sync.aligned;" ::: "memory"); }
template <int N> __device__ __forceinline__ void wg_wait() { asm volatile("wgmma.wait_group.sync.aligned %0;" ::"n"(N) : "memory"); }

__device__ __forceinline__ uint64_t mkdesc(uint32_t addr, uint32_t lbo_bytes) {
  return (uint64_t)(((addr & 0x3FFFF) >> 4) | ((lbo_bytes >> 4) << 16)) | ((uint64_t)0x40000040u << 32);
}
__device__ __forceinline__ uint64_t mkdesc_q(uint32_t addr) {
  return (uint64_t)(((addr & 0x3FFFF) >> 4) | (64u << 16)) | ((uint64_t)8 << 32);
}
template <int N> __device__ __forceinline__ void pin(float (&a)[N]) {
#pragma unroll
  for (int i = 0; i < N; i++) asm volatile("" : "+f"(a[i])::"memory");
}
template <int N> __device__ __forceinline__ void kill(float (&a)[N]) {
#pragma unroll
  for (int i = 0; i < N; i++) asm volatile("" : "=f"(a[i]));
}
template <int N> __device__ __forceinline__ void pin(uint32_t (&a)[N]) {
#pragma unroll
  for (int i = 0; i < N; i++) asm volatile("" : "+r"(a[i])::"memory");
}

#define F8(d, o) "+f"(d[o]), "+f"(d[o + 1]), "+f"(d[o + 2]), "+f"(d[o + 3]), "+f"(d[o + 4]), "+f"(d[o + 5]), "+f"(d[o + 6]), "+f"(d[o + 7])
#define R32A "%0, %1, %2, %3, %4, %5, %6, %7, %8, %9, %10, %11, %12, %13, %14, %15, %16, %17, %18, %19, %20, %21, %22, %23, %24, %25, %26, %27, %28, %29, %30, %31"
#define R32B "%32, %33, %34, %35, %36, %37, %38, %39, %40, %41, %42, %43, %44, %45, %46, %47, %48, %49, %50, %51, %52, %53, %54, %55, %56, %57, %58, %59, %60, %61, %62, %63"

#define O8(d, o) "=f"(d[o]), "=f"(d[o + 1]), "=f"(d[o + 2]), "=f"(d[o + 3]), "=f"(d[o + 4]), "=f"(d[o + 5]), "=f"(d[o + 6]), "=f"(d[o + 7])

__device__ __forceinline__ void mma_n128t(float (&d)[64], uint32_t a0, uint32_t a1, uint32_t a2, uint32_t a3, uint64_t db, bool acc) {
  if (acc)
    asm volatile("wgmma.mma_async.sync.aligned.m64n128k16.f32.bf16.bf16 {" R32A ", " R32B "}, {%64, %65, %66, %67}, %68, 1, 1, 1, 1;\n"
                 : F8(d, 0), F8(d, 8), F8(d, 16), F8(d, 24), F8(d, 32), F8(d, 40), F8(d, 48), F8(d, 56)
                 : "r"(a0), "r"(a1), "r"(a2), "r"(a3), "l"(db));
  else
    asm volatile("wgmma.mma_async.sync.aligned.m64n128k16.f32.bf16.bf16 {" R32A ", " R32B "}, {%64, %65, %66, %67}, %68, 0, 1, 1, 1;\n"
                 : O8(d, 0), O8(d, 8), O8(d, 16), O8(d, 24), O8(d, 32), O8(d, 40), O8(d, 48), O8(d, 56)
                 : "r"(a0), "r"(a1), "r"(a2), "r"(a3), "l"(db));
}
#define PV1(a0, a1, a2, a3, ob, acc) "add.s64 b, %92, " #ob ";\n" \
  "wgmma.mma_async.sync.aligned.m64n128k16.f32.bf16.bf16 {" R32A ", " R32B "}, {%" #a0 ", %" #a1 ", %" #a2 ", %" #a3 "}, b, " #acc ", 1, 1, 1;\n"
#define PV6 "wgmma.fence.sync.aligned;\n" PV1(64, 65, 66, 67, 0, p) PV1(68, 69, 70, 71, 128, 1) PV1(72, 73, 74, 75, 256, 1) \
  PV1(76, 77, 78, 79, 384, 1) PV1(80, 81, 82, 83, 512, 1) PV1(84, 85, 86, 87, 640, 1)
#define U4(a, o) "r"(a[o]), "r"(a[o + 1]), "r"(a[o + 2]), "r"(a[o + 3])
__device__ __forceinline__ void mma_pv(float (&d)[64], const uint32_t (&a)[28], uint64_t dv, bool acc, bool big) {
  asm volatile("{\n.reg .pred p, q;\n.reg .b64 b;\nsetp.ne.b32 p, %93, 0;\nsetp.eq.b32 q, %94, 0;\n@q bra.uni PV_SMALL;\n"
               PV6 PV1(88, 89, 90, 91, 768, 1) "wgmma.commit_group.sync.aligned;\nbra.uni PV_DONE;\n"
               "PV_SMALL:\n" PV6 "wgmma.commit_group.sync.aligned;\nPV_DONE:\n}\n"
               : F8(d, 0), F8(d, 8), F8(d, 16), F8(d, 24), F8(d, 32), F8(d, 40), F8(d, 48), F8(d, 56)
               : U4(a, 0), U4(a, 4), U4(a, 8), U4(a, 12), U4(a, 16), U4(a, 20), U4(a, 24), "l"(dv), "r"((int)acc), "r"((int)big) : "memory");
}
#define R48 R32A ", %32, %33, %34, %35, %36, %37, %38, %39, %40, %41, %42, %43, %44, %45, %46, %47"
#define R56 R48 ", %48, %49, %50, %51, %52, %53, %54, %55"
#define QK1(N, R, A, B, oa, ob, acc) "add.s64 a, " A ", " #oa ";\nadd.s64 b, " B ", " #ob ";\n" \
  "wgmma.mma_async.sync.aligned.m64n" #N "k16.f32.bf16.bf16 {" R "}, a, b, " #acc ", 1, 1, 0, 0;\n"
#define QK8(N, R, A, B) "{\n.reg .b64 a, b;\nwgmma.fence.sync.aligned;\n" QK1(N, R, A, B, 0, 0, 0) QK1(N, R, A, B, 128, 2, 1) \
  QK1(N, R, A, B, 256, 4, 1) QK1(N, R, A, B, 384, 6, 1) QK1(N, R, A, B, 512, 1024, 1) QK1(N, R, A, B, 640, 1026, 1) \
  QK1(N, R, A, B, 768, 1028, 1) QK1(N, R, A, B, 896, 1030, 1) "wgmma.commit_group.sync.aligned;\n}\n"
__device__ __forceinline__ void mma_qk(float (&d)[56], uint64_t dq, uint64_t dk) {
  asm volatile(QK8(112, R56, "%56", "%57")
               : O8(d, 0), O8(d, 8), O8(d, 16), O8(d, 24), O8(d, 32), O8(d, 40), O8(d, 48) : "l"(dq), "l"(dk) : "memory");
}
__device__ __forceinline__ void mma_qk(float (&d)[48], uint64_t dq, uint64_t dk) {
  asm volatile(QK8(96, R48, "%48", "%49")
               : O8(d, 0), O8(d, 8), O8(d, 16), O8(d, 24), O8(d, 32), O8(d, 40) : "l"(dq), "l"(dk) : "memory");
}
__device__ __forceinline__ void mma_n64t(float (&d)[32], uint32_t a0, uint32_t a1, uint32_t a2, uint32_t a3, uint64_t db, bool acc) {
  if (acc)
    asm volatile("wgmma.mma_async.sync.aligned.m64n64k16.f32.bf16.bf16 {" R32A "}, {%32, %33, %34, %35}, %36, 1, 1, 1, 1;\n"
                 : F8(d, 0), F8(d, 8), F8(d, 16), F8(d, 24) : "r"(a0), "r"(a1), "r"(a2), "r"(a3), "l"(db));
  else
    asm volatile("wgmma.mma_async.sync.aligned.m64n64k16.f32.bf16.bf16 {" R32A "}, {%32, %33, %34, %35}, %36, 0, 1, 1, 1;\n"
                 : O8(d, 0), O8(d, 8), O8(d, 16), O8(d, 24) : "r"(a0), "r"(a1), "r"(a2), "r"(a3), "l"(db));
}
__device__ __forceinline__ void mma_n64t_dyn(float (&d)[32], uint32_t a0, uint32_t a1, uint32_t a2, uint32_t a3, uint64_t db, int acc) {
  asm volatile("{\n.reg .pred p;\nsetp.ne.b32 p, %37, 0;\n"
               "wgmma.mma_async.sync.aligned.m64n64k16.f32.bf16.bf16 {" R32A "}, {%32, %33, %34, %35}, %36, p, 1, 1, 1;\n}\n"
               : F8(d, 0), F8(d, 8), F8(d, 16), F8(d, 24) : "r"(a0), "r"(a1), "r"(a2), "r"(a3), "l"(db), "r"(acc));
}
__device__ __forceinline__ void mma_n8(float (&d)[4], uint64_t da, uint64_t db, int acc) {
  asm volatile("{\n.reg .pred p;\nsetp.ne.b32 p, %6, 0;\n"
               "wgmma.mma_async.sync.aligned.m64n8k16.f32.bf16.bf16 {%0, %1, %2, %3}, %4, %5, p, 1, 1, 1, 0;\n}\n"
               : "+f"(d[0]), "+f"(d[1]), "+f"(d[2]), "+f"(d[3])
               : "l"(da), "l"(db), "r"(acc));
}
__device__ __forceinline__ void hmma_k16(float (&d)[4], uint32_t a0, uint32_t a1, uint32_t a2, uint32_t a3, uint32_t b0, uint32_t b1) {
  asm volatile("mma.sync.aligned.m16n8k16.row.col.f32.bf16.bf16.f32 {%0, %1, %2, %3}, {%4, %5, %6, %7}, {%8, %9}, {%0, %1, %2, %3};"
               : "+f"(d[0]), "+f"(d[1]), "+f"(d[2]), "+f"(d[3]) : "r"(a0), "r"(a1), "r"(a2), "r"(a3), "r"(b0), "r"(b1));
}

__device__ __forceinline__ uint32_t pack2(float lo, float hi) {
  uint32_t r;
  asm("cvt.rn.bf16x2.f32 %0, %1, %2;" : "=r"(r) : "f"(hi), "f"(lo));
  return r;
}
__device__ __forceinline__ float bf_lo(uint32_t w) { return __uint_as_float(w << 16); }
__device__ __forceinline__ float bf_hi(uint32_t w) { return __uint_as_float(w & 0xFFFF0000u); }
__device__ __forceinline__ float bfr(float x) { return __bfloat162float(__float2bfloat16_rn(x)); }
__device__ __forceinline__ uint32_t sub2(uint32_t a, uint32_t b) {
  uint32_t r;
  asm("sub.rn.bf16x2 %0, %1, %2;" : "=r"(r) : "r"(a), "r"(b));
  return r;
}
__device__ __forceinline__ uint32_t add2(uint32_t a, uint32_t b) {
  uint32_t r;
  asm("add.rn.bf16x2 %0, %1, %2;" : "=r"(r) : "r"(a), "r"(b));
  return r;
}
__device__ __forceinline__ uint32_t fma2(uint32_t a, uint32_t b, uint32_t c) {
  uint32_t r;
  asm("fma.rn.bf16x2 %0, %1, %2, %3;" : "=r"(r) : "r"(a), "r"(b), "r"(c));
  return r;
}
__device__ __forceinline__ float ex2(float x) {
  float r;
  asm("ex2.approx.ftz.f32 %0, %1;" : "=f"(r) : "f"(x));
  return r;
}
__device__ __forceinline__ float rcp(float x) {
  float r;
  asm("rcp.approx.ftz.f32 %0, %1;" : "=f"(r) : "f"(x));
  return r;
}
__device__ __forceinline__ float silu_f(float t) { return t * rcp(1.0f + ex2(-1.4426950408889634f * t)); }
__device__ __forceinline__ void lds128(uint32_t a, uint32_t& x, uint32_t& y, uint32_t& z, uint32_t& w) {
  asm volatile("ld.shared.v4.u32 {%0, %1, %2, %3}, [%4];" : "=r"(x), "=r"(y), "=r"(z), "=r"(w) : "r"(a) : "memory");
}
__device__ __forceinline__ void ldsm4(uint32_t a, uint32_t& x, uint32_t& y, uint32_t& z, uint32_t& w) {
  asm volatile("ldmatrix.sync.aligned.m8n8.x4.shared.b16 {%0, %1, %2, %3}, [%4];" : "=r"(x), "=r"(y), "=r"(z), "=r"(w) : "r"(a) : "memory");
}
constexpr uint32_t TAG = 0x10000;
__device__ __forceinline__ void st_gran(uint4* p, uint32_t x, uint32_t y, uint32_t z, uint32_t w) {
  asm volatile("st.relaxed.gpu.global.v4.b32 [%0], {%1, %2, %3, %4};" ::"l"(p), "r"(x), "r"(y), "r"(z), "r"(w) : "memory");
}
__device__ __forceinline__ void ld_gran(const uint4* p, uint32_t& x, uint32_t& y, uint32_t& z, uint32_t& w) {
  asm volatile("ld.relaxed.gpu.global.v4.b32 {%0, %1, %2, %3}, [%4];" : "=r"(x), "=r"(y), "=r"(z), "=r"(w) : "l"(p) : "memory");
}
__device__ __forceinline__ void stsm4(uint32_t a, uint32_t x, uint32_t y, uint32_t z, uint32_t w) {
  asm volatile("stmatrix.sync.aligned.m8n8.x4.shared.b16 [%0], {%1, %2, %3, %4};" ::"r"(a), "r"(x), "r"(y), "r"(z), "r"(w) : "memory");
}
__device__ __forceinline__ void cp16(uint32_t dst, const void* src) {
  asm volatile("cp.async.cg.shared.global [%0], [%1], 16;" ::"r"(dst), "l"(src) : "memory");
}
__device__ __forceinline__ void cp_wait_all() { asm volatile("cp.async.wait_all;" ::: "memory"); }
__device__ __forceinline__ void add_granules(float (&red)[32], const uint32_t (&g)[16]) {
#pragma unroll
  for (int i = 0; i < 16; i++) { red[2 * i] += bf_lo(g[i]); red[2 * i + 1] += bf_hi((i & 3) ? g[i] : g[i] & ~TAG); }
}
__device__ __forceinline__ bool granules_ok(const uint32_t (&g)[16], uint32_t tag) {
  uint32_t a, b;
  asm("lop3.b32 %0, %1, %2, %3, 0x7E;" : "=r"(a) : "r"(g[0]), "r"(g[4]), "r"(tag));
  asm("lop3.b32 %0, %1, %2, %3, 0x7E;" : "=r"(b) : "r"(g[8]), "r"(g[12]), "r"(tag));
  return __all_sync(0xffffffffu, ((a | b) & TAG) == 0);
}
__device__ __forceinline__ unsigned ld_acquire(const unsigned* p) {
  unsigned v;
  asm volatile("ld.acquire.gpu.global.u32 %0, [%1];" : "=r"(v) : "l"(p) : "memory");
  return v;
}
__device__ __forceinline__ unsigned atom_add_acq_rel(unsigned* p) {
  unsigned v;
  asm volatile("atom.acq_rel.gpu.global.add.u32 %0, [%1], 1;" : "=r"(v) : "l"(p) : "memory");
  return v;
}

template <int K0, int K1>
__device__ __forceinline__ void ln_fetch(uint32_t (&xa)[144], uint32_t boxes, uint32_t lo) {
#pragma unroll
  for (int k = K0; k < K1; k++) ldsm4(boxes + (k >> 2) * 8192 + (lo ^ ((k & 3) << 5)), xa[4 * k], xa[4 * k + 1], xa[4 * k + 2], xa[4 * k + 3]);
}
__device__ __forceinline__ void ln_fetch_b(uint32_t (&b)[24], uint32_t& wb, uint32_t ws) {
#pragma unroll
  for (int j = 0; j < 6; j++, wb += ws) ldsm4(wb, b[4 * j], b[4 * j + 1], b[4 * j + 2], b[4 * j + 3]);
}
template <int K0, int K1>
__device__ __forceinline__ void ln_sums(const uint32_t (&xa)[144], float (&sm)[4][4], const uint32_t (&b)[24]) {
#pragma unroll
  for (int k = K0; k < K1; k++)
    hmma_k16(sm[k & 3], xa[4 * k], xa[4 * k + 1], xa[4 * k + 2], xa[4 * k + 3], b[2 * (k % 12)], b[2 * (k % 12) + 1]);
}
template <int K0, int K1>
__device__ __forceinline__ uint32_t after_fetch(const uint32_t (&xa)[144]) {
  uint32_t d = blockIdx.y;
#pragma unroll
  for (int k = K0; k < K1; k++) d &= xa[4 * k];
  return d;
}
__device__ __forceinline__ void ln_row(float sum, float sq, float& mean_b, float& rstd) {
  const float mean = sum * (1.0f / DM);
  const uint32_t mv = pack2(mean, fmaxf(sq * (1.0f / DM) - mean * mean, 0.0f));
  mean_b = bf_lo(mv);
  float sd;
  asm("sqrt.approx.f32 %0, %1;" : "=f"(sd) : "f"(bf_lo(pack2(bf_hi(mv) + 1e-5f, 0.f))));
  rstd = rcp(bf_lo(pack2(sd, 0.f)));
}

template <bool ROUTED>
__device__ __forceinline__ uint32_t gate2(uint32_t xc, float rstd, float2 upd = make_float2(0.f, 0.f)) {
  uint32_t t = pack2(bf_lo(xc) * rstd, bf_hi(xc) * rstd);
  if (ROUTED) t = pack2(bf_lo(t) + upd.x, bf_hi(t) + upd.y);
  return pack2(silu_f(bf_lo(t)), silu_f(bf_hi(t)));
}

template <int V> struct IC { static constexpr int value = V; };

struct Ctx {
  uint32_t sb;
  uint8_t* sp;
  uint32_t rank;
  Scratch* g;
};

__device__ __forceinline__ bool acquire(const Ctx& cx, uint32_t r, uint32_t n, uint32_t bytes) {
  mbar_wait(cx.sb + SM_EMPTY + 8 * r, (n ^ (r >> 1) ^ 1) & 1);
  __syncwarp();
  const bool e = elect_one();
  if (e) mbar_expect_tx(cx.sb + SM_FULL + 8 * r, bytes);
  return e;
}
__device__ __forceinline__ void load_wq(const Ctx& cx, const CUtensorMap* tmWq, int st, int i, int n0, uint64_t pol) {
  const uint32_t r = st & 3, dst = cx.sb + SM_RING + r * STAGE + cx.rank * 16384, bar = cx.sb + SM_FULL + 8 * r;
  const int k0 = i < 3 ? 128 * i : 128 * i - 64;
  if (acquire(cx, r, st >> 2, i == 2 ? 16384 : 32768)) {
    tma2d_mc(dst, tmWq, n0, k0, bar, pol);
    if (i != 2) tma2d_mc(dst + 8192, tmWq, n0, k0 + 64, bar, pol);
  }
}
__device__ __forceinline__ void attn_producer(const Ctx& cx, int qb, int hs, const CUtensorMap* tmKV, const CUtensorMap* tmWq,
                                              const CUtensorMap* tmWq96, const CUtensorMap* tmWo) {
  const uint32_t full = cx.sb + SM_FULL, ring = cx.sb + SM_RING + cx.rank * 16384;
  const uint64_t last_use = policy_evict_first();
  int st = 0;
#pragma unroll 1
  for (int p = 0; p < 4; p++) {
#pragma unroll 1
    for (int i = 0; i < (p == 2 ? 3 : 5); i++, st++) {
      if (p == 2) {
        if (acquire(cx, st & 3, st >> 2, 24576))
          tma2d_mc(cx.sb + SM_RING + (st & 3) * STAGE + cx.rank * 12288, tmWq96, (hs * 4 + 3) * DH, 192 * i + 96 * cx.rank, full + 8 * (st & 3), last_use);
      } else {
        if (st > 1) load_wq(cx, tmWq, st, i, (hs * 4 + (p ^ (p >> 1))) * DH + cx.rank * 64, last_use);
      }
      if (st == 1 || st == 2) TSP(72 + st)
      if (st == 1) {
#pragma unroll 1
        for (int b = 0; b < 4; b++) {
          const bool k8 = b == 0 && qb < 8;
          if (elect_one()) tma2d_prefetch(tmWq, hs * 512 + (k8 ? qb * 64 : (b ^ (b >> 1)) * DH + (qb & 1) * 64), k8 ? 512 : (qb >> 1) * 64);
        }
      }
      if (st == 8 && qb < 8 && elect_one()) tma2d_prefetch(tmKV + ((qb >> 1) & 1), cx.rank * 64, hs * 2 * SEQ + (qb >> 2) * 96);
    }
  }
  uint32_t r = 2, n = 4;
  int row = hs * 2 * SEQ, rows = 96;
  const CUtensorMap* tm = tmKV + 2;
#pragma unroll 1
  for (int u = 0; u < NST_KV; u++) {
    if (acquire(cx, r, n, rows * 256)) {
      tma2d_mc(ring + r * STAGE, tm, cx.rank * 64, row, full + 8 * r, last_use);
      if (((u ^ (qb >> 1)) & 7) == 0 && u < NST_KV - 4) tma2d_prefetch(tmKV + (u & 1), cx.rank * 64, row + 208);
      if ((unsigned)(u - 32) < 36 && (u & 15) == qb) tma2d_prefetch(tmWo, ((u - 32) >> 2) * 64, hs * 512 + (u & 3) * 128);
    }
    if (++r == 4) { r = 1; n++; }
    if (u & 1) row += rows;
    const bool big = (unsigned)(u - 9) < 56;
    rows = big ? 112 : 96;
    tm = tmKV + (~u & 1) + (big ? 0 : 2);
  }
#pragma unroll 1
  for (int u = 0; u < NST_O; u++) {
    const int s = u >> 1;
    const int blk = s == 0 ? 8 : ((hs + s) & 7);
    r = (0x87 >> (2 * (u & 3))) & 3;
    if (acquire(cx, r, (u >> 2) ^ ~u, 32768))
      tma2d_mc(ring + r * STAGE, tmWo, blk * 64, hs * 512 + ((u & 1) + cx.rank * 2) * 128, full + 8 * r, last_use);
  }
}

__device__ __forceinline__ void sq_publish(const Ctx& cx, int qb, int hs, int j, int lane) {
  if (j == 2 && lane == 0) {
    const unsigned e = cx.g->launch[hs * 16 + qb]++;
    *(uint2*)(cx.sp + SM_TAG) = make_uint2((~e & 1) * TAG, e);
  }
  const int row = (hs & 3) * 16 + (lane >> 1);
  uint32_t a = cx.sb + SM_X + (hs >> 2) * 73728 + j * 8192 + row * 128 + (((lane & 1) ^ (row & 7)) << 4);
  float s0 = 0.f, s1 = 0.f;
#pragma unroll 1
  for (int b = 0; b < 6; b++) {
    if (b == (hs < 4 ? 4 : 0)) {
      const int n = 224 + (__float_as_uint(s1) & blockIdx.y);
      if (j == 1) {
        bar_sync(BAR_XREL, n);
        if (lane < 4) asm volatile("mbarrier.arrive.shared::cluster.b64 _, [%0], 2;" ::"r"(mapa(cx.sb + SM_EMPTY + 16 + 8 * (lane >> 1), lane & 1)) : "memory");
      } else {
        bar_arrive(BAR_XREL, n);
      }
      __syncwarp();
      if (hs == 8) return;
    }
    if (!(b & 1)) mbar_wait(cx.sb + SM_XFULL + 32 * (hs >> 2) + 4 * b, 0);
    uint32_t v[8];
    lds128(a, v[0], v[1], v[2], v[3]);
    lds128(a ^ 32, v[4], v[5], v[6], v[7]);
    a = (a ^ 64) + (b & 1) * 24576;
#pragma unroll
    for (int i = 0; i < 8; i++) { s0 = fmaf(bf_lo(v[i]), bf_lo(v[i]), s0); s1 = fmaf(bf_hi(v[i]), bf_hi(v[i]), s1); }
  }
  s0 += s1;
  s0 += __shfl_xor_sync(0xffffffffu, s0, 1);
  float* part = (float*)(cx.sp + SM_STATS) + (lane >> 1) * 2;
  if (j < 2) {
    part[32 * j] = s0;
    bar_arrive(BAR_HELPER, 96);
  } else {
    bar_sync(BAR_HELPER, 96);
    TSP(68)
    if (!(lane & 1))
      asm volatile("st.relaxed.gpu.global.v2.b32 [%0], {%1, %2};" ::"l"(cx.g->sq + qb * 128 + hs * 16 + (lane >> 1)),
                   "r"(__float_as_uint((part[0] + part[32]) + s0)), "r"(*(const uint32_t*)(cx.sp + SM_TAG + 4) + 1) : "memory");
  }
}
__device__ __forceinline__ void sq_collect(const Ctx& cx, int qb, int lane) {
  const uint32_t e1 = *(const uint32_t*)(cx.sp + SM_TAG + 4) + 1;
#pragma unroll 1
  for (int n = 0; n < (1 << 16); n++) {
    __nanosleep(300);
    uint32_t bad = 0;
#pragma unroll
    for (int i = 0; i < 2; i++) {
      uint32_t a, t0, b, t1;
      ld_gran((const uint4*)at(cx.g->sq, qb * 1024 + lane * 16) + i * 32, a, t0, b, t1);
      *(uint32_t*)(cx.sp + SM_STATS + (i * 32 + lane) * 16 + 4) = a;
      *(uint32_t*)(cx.sp + SM_STATS + (i * 32 + lane) * 16 + 12) = b;
      bad |= (t0 ^ e1) | (t1 ^ e1);
    }
    if (__all_sync(0xffffffffu, bad == 0)) break;
  }
  __syncwarp();
  if (lane == 0) mbar_arrive(cx.sb + SM_BAR_SQ);
  TSP(69)
}
__device__ __forceinline__ void attn_gate(const Ctx& cx, int qb, int hs, int j, int t, const __nv_bfloat16* x) {
  const uint4* xp = (const uint4*)(x + qb * 128 * DM) + (t >> 3) * 72 + hs * 8 + (t & 7);
  uint4 nx = *xp;
  float wsum = 0.f;
  if (j == 0) {
    mbar_wait(cx.sb + SM_BAR_W, 0);
#pragma unroll 3
    for (int i = 0; i < 9; i++) {
      const uint32_t w = *(const uint32_t*)(cx.sp + SM_WR + i * 128 + t * 4);
      wsum += bf_lo(w) + bf_hi(w);
    }
#pragma unroll
    for (int i = 1; i < 32; i *= 2) wsum += __shfl_xor_sync(0xffffffffu, wsum, i);
  }
  bar_sync(BAR_GATE, 352);
  if (t < 16) {
    const float2 st = *(const float2*)(cx.sp + SM_STATS + 8 * (hs * 16 + t));
    const int row = qb * 128 + hs * 16 + t;
    const uint32_t b = pack2(0.f, fmaf(-st.x, wsum, *(const float*)(cx.sp + SM_RAW + 4 * t)) * st.y);
    st_gran(at(cx.g->stats, row * 16), __float_as_uint(st.x), __float_as_uint(st.y), (b ^ ((int)b < 0 ? 0xFFFF0000u : 0x80000000u)) | (0xFFFF - row),
            *(const uint32_t*)(cx.sp + SM_TAG + 4) + 1);
  }
  __syncwarp();
  uint32_t sa = cx.sb + SM_STATS + (t & ~7);
  uint4* gp = cx.g->gate + blockIdx.x * 1152 + (t ^ ((t >> 3) & 7));
  const int cross = t < 64 ? 10 : 9;
#pragma unroll 1
  for (int i = 0; i < 12; i++) {
    float2 st;
    asm volatile("ld.shared.v2.f32 {%0, %1}, [%2];" : "=f"(st.x), "=f"(st.y) : "r"(sa));
    const uint32_t mm = pack2(st.x, st.x);
    const uint4 v = make_uint4(sub2(nx.x, mm), sub2(nx.y, mm), sub2(nx.z, mm), sub2(nx.w, mm));
    xp += 12 * 72;
    sa += 96;
    if (i == cross) { xp += (hs * 16 - 128) * 72 + 64 - hs * 8; sa += (hs * 16 - 128) * 8; }
    if (i < 11) nx = *xp;
    *gp = make_uint4(gate2<false>(v.x, st.y), gate2<false>(v.y, st.y), gate2<false>(v.z, st.y), gate2<false>(v.w, st.y));
    gp = (uint4*)((size_t)(gp + 96) ^ 64);
  }
}

constexpr uint32_t SM_XO = SM_SLOT, SM_GO = SM_SLOT + STAGE, SM_P8 = SM_SLOT + 2 * STAGE;
__device__ __forceinline__ void attn_helper(const Ctx& cx, int qb, int hs, int lane, const CUtensorMap* tmX16) {
  const unsigned e = *(const uint32_t*)(cx.sp + SM_TAG + 4);
  bar_sync(BAR_HELPER, 64);
  bool todo = lane < 2;
#pragma unroll 1
  for (int n = 0; __any_sync(0xffffffffu, todo); n++) {
    if (todo && (ld_acquire(at(cx.g->qflag, ((qb * 4 + (hs >> 1)) * 2 + lane) * 4)) == e + 1 || n == (1 << 16))) {
      asm volatile("fence.proxy.async.global;" ::: "memory");
      mbar_expect_tx(cx.sb + SM_BAR_Q + 8 * lane, 8192);
      bulk_load(cx.sb + SM_SLOT + 2 * STAGE + lane * 16384 + 8192, at(cx.g->q, ((qb * 8 + hs) * 2 + lane) * 8192), 8192, cx.sb + SM_BAR_Q + 8 * lane);
      todo = false;
    }
  }
  const uint32_t tag = (~e & 1) * TAG;
  const uint4* src = cx.g->part + (size_t)((qb * 64 + 56) * 2 + (hs >> 2)) * 4 * 128 + (hs & 3) * 32 + lane;
  const uint32_t stg = cx.sb + SM_P8 + lane * 16;
  bar_sync(BAR_OA, 352);
  asm volatile("fence.proxy.async.global;" ::: "memory");
  if (lane == 0) {
    mbar_expect_tx(cx.sb + SM_BAR_MISC, 2 * 18432);
    bulk_load(cx.sb + SM_GO, cx.g->gate + blockIdx.x * 1152, 18432, cx.sb + SM_BAR_MISC);
#pragma unroll 1
    for (int i = 0; i < 9; i++)
      tma2d(cx.sb + SM_XO + i * 2048, tmX16, i < 8 ? hs * 64 : 512, qb * 128 + (i < 8 ? i : hs) * 16, cx.sb + SM_BAR_MISC);
  }
#pragma unroll 1
  for (int n = 0; n < (1 << 16); n++) {
    __nanosleep(n ? 500 : 2000);
    uint32_t a, b, d, t;
    ld_gran(src - lane + (lane & 7) * (2 * 4 * 128) + 3 * 128 + 31, a, b, d, t);
    if (__all_sync(0xffffffffu, (a & TAG) == tag)) break;
  }
  TSH(46)
#pragma unroll 1
  for (int n = 0; n < (1 << 16); n++) {
#pragma unroll 1
    for (int i = 0; i < 8; i++) {
#pragma unroll
      for (int g = 0; g < 4; g++) cp16(stg + (i * 4 + g) * 512, src + i * (2 * 4 * 128) + g * 128);
    }
    cp_wait_all();
    uint32_t bad = 0;
#pragma unroll 4
    for (int i = 0; i < 32; i++) bad |= *(const volatile uint32_t*)(cx.sp + SM_P8 + lane * 16 + i * 512) ^ tag;
    if (__all_sync(0xffffffffu, (bad & TAG) == 0)) break;
  }
  TSH(47)
#pragma unroll 1
  for (int n = 0; n < (1 << 16) && ld_acquire(&cx.g->ycnt) != 4 * (e + 1); n++) __nanosleep(200);
  const int2 sel = __ldcg(at(cx.g->sel, (lane & 7) * 8));
  const int lr = sel.x - qb * 128;
  uint32_t m = __ballot_sync(0xffffffffu, lane < 16 && ((lane & 8) ? (lr >> 4) == hs : (lr >> 7) == 0));
  mbar_wait(cx.sb + SM_BAR_MISC, 0);
#pragma unroll 1
  for (; m; m &= m - 1) {
    const int i = __ffs(m) - 1, row = __shfl_sync(0xffffffffu, lr, i);
    const float rs = __int_as_float(__shfl_sync(0xffffffffu, sel.y, i));
    const float* p = cx.g->ypart + (i & 7) * DM + (i < 8 ? hs * 64 : 512) + 2 * lane;
    const float2 a = __ldcg((const float2*)p), b = __ldcg((const float2*)(p + TOPC * DM)), c = __ldcg((const float2*)(p + 2 * TOPC * DM)),
                 d = __ldcg((const float2*)(p + 3 * TOPC * DM));
    const uint32_t y = pack2((a.x + b.x) + (c.x + d.x), (a.y + b.y) + (c.y + d.y));
    const uint32_t u = pack2(bf_lo(y) * rs, bf_hi(y) * rs);
    const float2 st = *(const float2*)(cx.sp + SM_STATS + 8 * row);
    const int o = (i < 8 ? row : 128 + (row & 15)) * 128 + ((lane * 4) ^ ((row & 7) << 4));
    *(uint32_t*)(cx.sp + SM_GO + o) = gate2<true>(sub2(*(const uint32_t*)(cx.sp + SM_XO + o), pack2(st.x, st.x)), st.y, make_float2(bf_lo(u), bf_hi(u)));
  }
  __syncwarp();
  if (lane == 0) mbar_arrive(cx.sb + SM_BAR_XG);
  TSH(48)
}
__device__ __forceinline__ void attn_finish8(const Ctx& cx, int qb, int hs, int hw, int lane, __nv_bfloat16* out) {
  bar_sync(BAR_GATE, 96);
#pragma unroll 1
  for (int g = hw; g < 4; g += 3) {
    float acc[8] = {0.f, 0.f, 0.f, 0.f, 0.f, 0.f, 0.f, 0.f};
#pragma unroll 2
    for (int sidx = 0; sidx < 8; sidx++) {
      uint32_t a, b, d, t;
      lds128(cx.sb + SM_P8 + lane * 16 + (sidx * 4 + g) * 512, a, b, d, t);
      acc[0] += bf_lo(a); acc[1] += bf_hi(a & ~TAG); acc[2] += bf_lo(b); acc[3] += bf_hi(b);
      acc[4] += bf_lo(d); acc[5] += bf_hi(d); acc[6] += bf_lo(t); acc[7] += bf_hi(t);
    }
#pragma unroll
    for (int j = 0; j < 4; j++) {
      const int o = (128 + (lane >> 2) + (j & 1) * 8) * 128 + (((2 * g + (j >> 1)) ^ (lane >> 2)) << 4) + (lane & 3) * 4;
      uint32_t* xp = (uint32_t*)(cx.sp + SM_XO + o);
      *xp = fma2(pack2(acc[2 * j], acc[2 * j + 1]), *(const uint32_t*)(cx.sp + SM_GO + o), *xp);
    }
  }
  bar_sync(BAR_GATE, 96);
#pragma unroll 1
  for (int ch = threadIdx.x - 32; ch < 128; ch += 96)
    *(uint4*)at(out, ((qb * 128 + hs * 16 + (ch >> 3)) * DM + 512 + (ch & 7) * 8) * 2) =
        *(const uint4*)(cx.sp + SM_XO + 16384 + (ch ^ ((ch >> 3) & 7)) * 16);
}

__device__ __forceinline__ void ffn_producer(const Ctx& cx, int f, const CUtensorMap* tmWq, const CUtensorMap* tmG,
                                             const CUtensorMap* tmU, const CUtensorMap* tmD) {
  uint64_t keep;
  asm("createpolicy.fractional.L2::evict_normal.b64 %0, 1.0;" : "=l"(keep));
  int st = 0;
#pragma unroll 1
  for (int p = 0; p < 16; p++) {
#pragma unroll 1
    for (int i = 0; i < 5; i++, st++) if (st > 1) load_wq(cx, tmWq, st, i, ((2 * (p & 3) + cx.rank) * 4 + 3) * DH + 64, keep);
  }
  const uint32_t full = cx.sb + SM_FFULL, empty = cx.sb + SM_FEMPTY;
  int pair = 0, u = 0;
#pragma unroll 1
  for (st = 0; st < 14 * 12; st++) {
    const uint32_t sl = st & 7;
    const int unit = pair * 2 + (u & 1), k = u >> 1, k3 = k >= 3 ? k - 3 : k;
    if (unit < 27) {
      mbar_wait(empty + 8 * sl, (st >> 3) & 1);
      __syncwarp();
      if (elect_one()) {
        mbar_expect_tx(full + 8 * sl, FSTAGE);
        if (pair < 9) tma2d_stream(cx.sb + sl * FSTAGE, k < 3 ? tmG : tmU, f * 1152 + unit * 64, k3 * 192, full + 8 * sl);
        else tma2d_stream(cx.sb + sl * FSTAGE, tmD, (unit - 18) * 64, f * 1152 + k * 192, full + 8 * sl);
      }
    }
    if (++u == 12) { u = 0; pair++; }
  }
}
__device__ __forceinline__ void load_x1(uint32_t dst, const CUtensorMap* tmX64, int row, int box, int n, uint32_t bar) {
  mbar_expect_tx(bar, n * 8192);
#pragma unroll 1
  for (int i = 0; i < n; i++) tma2d(dst + i * 8192, tmX64, (box + i) * 64, row, bar);
}
__device__ __forceinline__ void ffn_publish(const Ctx& cx, int f, int w, int lane, const CUtensorMap* tmX64) {
  const uint32_t xs = cx.sb + SM_SLOT + w * 49152, xf = cx.sb + SM_XFULL + w * 32;
#pragma unroll 1
  for (int n = 0; n < 16; n++) {
    const int p = n & 3, row = (f + (n & 12) + 4) * 128 + w * 64;
    if (n < 12 && p == 3) {
      bar_sync(BAR_QS + w, 160);
      if (lane == 0) load_x1(xs, tmX64, row, 4, 4, xf + 8);
      __syncwarp();
    }
    bar_sync(BAR_QS + w, 160);
    const uint32_t e1 = *(const uint32_t*)(cx.sp + SM_TAG + 4) + 1;
    if (lane == 0) {
#pragma unroll
      for (int i = 0; i < 2; i++)
        asm volatile("cp.async.bulk.global.shared::cta.bulk_group [%0], [%1], 8192;"
                     ::"l"(cx.g->q + (((f + (n & 12)) * 8 + 2 * p + i) * 2 + w) * 512), "r"(xs + 32768 + i * 8192) : "memory");
      asm volatile("cp.async.bulk.commit_group;" ::: "memory");
      asm volatile("cp.async.bulk.wait_group.read 0;" ::: "memory");
      if (n < 12 && (p == 0 || p == 3)) load_x1(xs + (p ? 32768 : 0), tmX64, row, p ? 8 : 0, p ? 1 : 4, xf + (p ? 16 : 0));
      asm volatile("cp.async.bulk.wait_group 0;\nfence.proxy.async.global;" ::: "memory");
      asm volatile("st.release.gpu.global.u32 [%0], %1;" ::"l"(&cx.g->qflag[((f + (n & 12)) * 4 + p) * 2 + w]), "r"(e1) : "memory");
    }
    __syncwarp();
    if (n < 12 && p == 1) {
#pragma unroll 1
      for (int i = 0, k = 0; i < 64 && k < (1 << 16); k++) {
        uint32_t m, r, z, t;
        ld_gran(cx.g->stats + row + i + lane, m, r, z, t);
        *(uint2*)(cx.sp + SM_STATS + 8 * (w * 64 + i + lane)) = make_uint2(m, r);
        if (__all_sync(0xffffffffu, t == e1)) i += 32;
      }
    }
    bar_arrive(BAR_QF + w, 160);
  }
}

__device__ __forceinline__ void ffn_consumer(const Ctx& cx, int f, int wg, int cw, int lane, const __nv_bfloat16* x) {
  const int r = lane >> 2, c = lane & 3, tid = cw * 32 + lane;
  const uint32_t full = cx.sb + SM_FFULL, empty = cx.sb + SM_FEMPTY;
  const bool signaller = (tid & 127) == 0;
  prof(wg, 8);
  const unsigned e = *(const uint32_t*)(cx.sp + SM_TAG + 4);
  uint32_t key[8];
#pragma unroll 1
  for (int n = 0; n < (1 << 16); n++) {
    uint32_t bad = 0;
#pragma unroll
    for (int i = 0; i < 8; i++) {
      uint32_t t;
      asm volatile("ld.relaxed.gpu.global.v2.b32 {%0, %1}, [%2];" : "=r"(key[i]), "=r"(t) : "l"(&cx.g->stats[i * 256 + tid].z) : "memory");
      bad |= t ^ (e + 1);
    }
    if (__all_sync(0xffffffffu, bad == 0)) break;
  }
  bar_sync(BAR_QF + wg, 160);
  bar_sync(3, 256);
  if (tid < 8) mbar_arrive(empty + 8 * tid);
  prof(wg, 9);
  int mysel = 0;
#pragma unroll 1
  for (int k = 0; k < TOPC; k++) {
    uint32_t m = key[0];
#pragma unroll
    for (int i = 1; i < 8; i++) m = max(m, key[i]);
    m = __reduce_max_sync(0xffffffffu, m);
    uint32_t* tk = (uint32_t*)(cx.sp + SM_TOPK) + (k & 1) * 8;
    if (lane == 0) tk[cw] = m;
    bar_sync(3, 256);
    m = __reduce_max_sync(0xffffffffu, tk[lane & 7]);
#pragma unroll
    for (int i = 0; i < 8; i++) if (key[i] == m) key[i] = 0;
    if (k == cw) mysel = 0xFFFF - (int)(m & 0xFFFF);
  }
  {
    const float4 st = __ldcg((const float4*)&cx.g->stats[mysel]);
    const uint32_t mm = pack2(st.x, st.x);
#pragma unroll 3
    for (int i = 0; i < 9; i++) {
      const uint32_t t = sub2(*(const uint32_t*)(x + (size_t)mysel * DM + i * 64 + 2 * lane), mm);
      *(uint32_t*)(cx.sp + SM_XSEL + i * 1024 + cw * 128 + (((lane >> 2) ^ cw) << 4) + (lane & 3) * 4) =
          pack2(bf_lo(t) * st.y, bf_hi(t) * st.y);
    }
    const uint32_t k = __float_as_uint(st.z);
    const float score = bf_hi(k ^ ((int)k < 0 ? 0x80000000u : 0xFFFF0000u));
    if (lane == 0 && f == 0) cx.g->sel[cw] = make_int2(mysel, __float_as_int(bfr(rcp(1.0f + ex2(-1.4426950408889634f * score)))));
  }
  asm volatile("fence.proxy.async.shared::cta;" ::: "memory");
  bar_sync(3, 256);
  prof(wg, 10);
  auto run = [&](float (&acc)[4], int st, int n, uint32_t b) {
#pragma unroll 1
    for (int u = 0; u < n; u++, st += 2, b += 3072) {
      const uint32_t sl = st & 7;
      mbar_wait(full + 8 * sl, (st >> 3) & 1);
      wg_fence();
      const uint64_t da = mkdesc(cx.sb + sl * FSTAGE, 16), db = mkdesc(b, 16);
#pragma unroll
      for (int k = 0; k < 12; k++) mma_n8(acc, da + k * 128, db + (k >> 2) * 64 + (k & 3) * 2, u > 0 || k > 0);
      wg_commit();
      wg_wait<0>();
      if (signaller) mbar_arrive(empty + 8 * sl);
    }
    pin(acc);
  };
#pragma unroll 1
  for (int unit = wg; unit < 27; unit += 2) {
    if (unit >> 1 == 9) {
      asm volatile("fence.proxy.async.shared::cta;" ::: "memory");
      bar_sync(3, 256);
      prof(wg, 11);
    }
    const bool gu = unit < 18;
    float a0[4], a1[4];
#pragma unroll 1
    for (int m = 0; m < (gu ? 2 : 1); m++) {
      run(a1, (unit >> 1) * 12 + m * 6 + wg, gu ? 3 : 6, cx.sb + (gu ? SM_XSEL : SM_H));
      if (m == 0) { a0[0] = a1[0]; a0[1] = a1[1]; a0[2] = a1[2]; a0[3] = a1[3]; }
    }
    float u0 = a1[0], u1 = a1[1];
#pragma unroll 1
    for (int i = 0; i < 2; i++) {
      const int fl = (cw & 3) * 16 + r + i * 8;
      if (gu) {
        const uint32_t g = pack2(a0[0], a0[1]);
        const uint32_t h = fma2(pack2(silu_f(bf_lo(g)), silu_f(bf_hi(g))), pack2(u0, u1), 0x80008000u);
        uint8_t* hp = cx.sp + SM_H + unit * 1024 + c * 256 + (fl & 7) * 2;
        *(uint16_t*)(hp + (((fl >> 3) ^ (2 * c)) << 4)) = (uint16_t)h;
        *(uint16_t*)(hp + 128 + (((fl >> 3) ^ (2 * c + 1)) << 4)) = (uint16_t)(h >> 16);
      } else {
        float* yp = cx.g->ypart + (f * TOPC + 2 * c) * DM + (unit - 18) * 64 + fl;
        yp[0] = u0;
        yp[DM] = u1;
      }
      a0[0] = a0[2]; a0[1] = a0[3]; u0 = a1[2]; u1 = a1[3];
    }
  }
  prof(wg, 12);
  bar_sync(3, 256);
  if (tid == 0) atom_add_acq_rel(&cx.g->ycnt);
  prof(wg, 13);
}

constexpr float SUM_HI = 1.8446744e19f, SUM_LO = 9.0949470e-13f;

template <int LO, int HI, int N>
__device__ __forceinline__ void softmax_exp(float (&s)[N]) {
#pragma unroll
  for (int i = LO; i < HI; i++) s[i] = ex2(s[i]);
}
__device__ __forceinline__ void sum_tree(const uint32_t (&pf)[28], bool big, uint32_t& h0, uint32_t& h1) {
  uint32_t t0 = add2(add2(pf[16], pf[18]), add2(pf[20], pf[22])), t1 = add2(add2(pf[17], pf[19]), add2(pf[21], pf[23]));
  if (big) { t0 = add2(t0, add2(pf[24], pf[26])); t1 = add2(t1, add2(pf[25], pf[27])); }
  h0 = add2(add2(add2(add2(pf[0], pf[2]), add2(pf[4], pf[6])), add2(add2(pf[8], pf[10]), add2(pf[12], pf[14]))), t0);
  h1 = add2(add2(add2(add2(pf[1], pf[3]), add2(pf[5], pf[7])), add2(add2(pf[9], pf[11]), add2(pf[13], pf[15]))), t1);
}
__device__ __forceinline__ void exact_attention(float (&o)[16], float& l0, float& l1, const uint32_t (&q)[32], const __nv_bfloat16* kp,
                                                const __nv_bfloat16* vp) {
  float m0 = -3.0e38f, m1 = -3.0e38f;
  l0 = l1 = 0.f;
#pragma unroll
  for (int i = 0; i < 16; i++) o[i] = 0.f;
#pragma unroll 1
  for (int key = 0; key < SEQ; key += 8, kp += 8 * DH, vp += 8 * DH) {
    float d[4] = {0.f, 0.f, 0.f, 0.f};
#pragma unroll
    for (int k = 0; k < 8; k++)
      hmma_k16(d, q[4 * k], q[4 * k + 1], q[4 * k + 2], q[4 * k + 3], *(const uint32_t*)(kp + k * 16), *(const uint32_t*)(kp + k * 16 + 8));
    float x0 = fmaxf(d[0], d[1]), x1 = fmaxf(d[2], d[3]);
    x0 = fmaxf(x0, __shfl_xor_sync(0xffffffffu, x0, 1));
    x1 = fmaxf(x1, __shfl_xor_sync(0xffffffffu, x1, 1));
    x0 = fmaxf(fmaxf(x0, __shfl_xor_sync(0xffffffffu, x0, 2)), m0);
    x1 = fmaxf(fmaxf(x1, __shfl_xor_sync(0xffffffffu, x1, 2)), m1);
    const float sc0 = ex2(m0 - x0), sc1 = ex2(m1 - x1);
    m0 = x0; m1 = x1;
    const uint32_t p0 = pack2(ex2(d[0] - m0), ex2(d[1] - m0)), p1 = pack2(ex2(d[2] - m1), ex2(d[3] - m1));
    l0 = fmaf(l0, sc0, bf_lo(p0) + bf_hi(p0));
    l1 = fmaf(l1, sc1, bf_lo(p1) + bf_hi(p1));
#pragma unroll
    for (int nb = 0; nb < 4; nb++) {
      uint32_t b;
      asm("movmatrix.sync.aligned.m8n8.trans.b16 %0, %1;" : "=r"(b) : "r"(*(const uint32_t*)(vp + nb * 8)));
      o[4 * nb] *= sc0; o[4 * nb + 1] *= sc0; o[4 * nb + 2] *= sc1; o[4 * nb + 3] *= sc1;
      asm volatile("mma.sync.aligned.m16n8k8.row.col.f32.bf16.bf16.f32 {%0, %1, %2, %3}, {%4, %5}, {%6}, {%0, %1, %2, %3};"
                   : "+f"(o[4 * nb]), "+f"(o[4 * nb + 1]), "+f"(o[4 * nb + 2]), "+f"(o[4 * nb + 3]) : "r"(p0), "r"(p1), "r"(b));
    }
  }
}
__device__ __forceinline__ bool inv_sums(float l0, float l1, float& i0, float& i1) {
  l0 += __shfl_xor_sync(0xffffffffu, l0, 1); l1 += __shfl_xor_sync(0xffffffffu, l1, 1);
  l0 += __shfl_xor_sync(0xffffffffu, l0, 2); l1 += __shfl_xor_sync(0xffffffffu, l1, 2);
  i0 = rcp(l0);
  i1 = rcp(l1);
  return !(l0 + l1 <= SUM_HI) | (fminf(l0, l1) < SUM_LO);
}
template <int LO, int HI, int N>
__device__ __forceinline__ void park(uint32_t a, const float (&o)[N], float i0, float i1, bool on = true) {
#pragma unroll
  for (int i = LO; i < HI; i++)
    asm volatile("{\n.reg .pred p;\nsetp.ne.u32 p, %5, 0;\n@p stmatrix.sync.aligned.m8n8.x4.shared.b16 [%0], {%1, %2, %3, %4};\n}"
                 ::"r"(a + i * 2048), "r"(pack2(o[8 * i] * i0, o[8 * i + 1] * i0)), "r"(pack2(o[8 * i + 2] * i1, o[8 * i + 3] * i1)),
                 "r"(pack2(o[8 * i + 4] * i0, o[8 * i + 5] * i0)), "r"(pack2(o[8 * i + 6] * i1, o[8 * i + 7] * i1)), "r"((uint32_t)on) : "memory");
}

template <int I, int HI>
__device__ __forceinline__ void park_paced(uint32_t a, const float (&o)[64], float i0, float i1, int id) {
  if constexpr (I < HI) {
    park<I, I + 2>(a, o, i0, i1);
    if (I + 2 < HI) block_fence(id + I);
    park_paced<I + 2, HI>(a, o, i0, i1, id);
  }
}

__device__ __forceinline__ void attn_consumer(const Ctx& cx, bool hlp, int qb, int hs, int wg, int cw, int lane, const __nv_bfloat16* x,
                                              const __nv_bfloat16* kc, const __nv_bfloat16* vc, __nv_bfloat16* out) {
  const uint32_t full = cx.sb + SM_FULL;
  const uint32_t ring = cx.sb + SM_RING;
  const uint32_t qwg = ring + wg * 16384;
  auto qlane = [&](int l) { return qwg + (cw & 3) * 256 + (l >> 4) * 1024 + (l & 15) * 16; };
  const bool signaller = lane == 0 && (cw & 3) < 2;
  const int my_turn = 1 + wg, other_turn = 2 - wg;
  const uint32_t empty_c = mapa(cx.sb + SM_EMPTY, cw & 1);

  float oA[64], oB[64], i0, i1;
  uint32_t xl[32];
  {
    const int r = lane >> 2, c = lane & 3;
    const int lr0 = cw * 16 + r;
    uint32_t xa[144];
    uint32_t mm0, mm1;
    float rstd0, rstd1, sq0 = 0.f, sq1 = 0.f;
    const uint32_t xf = cx.sb + SM_XFULL + wg * 32, xs = cx.sb + SM_SLOT + wg * 49152;
    auto lo_of = [&](int l) { return ((cw & 3) * 16 + (l & 15)) * 128 + (((l >> 4) ^ (l & 7)) << 4); };
    prof(wg, 0);
    {
      const uint32_t lo = lo_of(lane);
      const uint32_t xb = cx.sb + SM_X + wg * 73728;
      float sm[4][4] = {};
      const uint32_t ws = (lane & 7) == 1 ? 64 : 0;
      uint32_t wb = cx.sb + (ws ? SM_WR + (lane >> 3) * 16 : SM_ONES);
      uint32_t b0[24], b1[24], b2[24];
      mbar_wait(cx.sb + SM_BAR_W, 0);
      TS4(1)
      ln_fetch_b(b0, wb, ws);
      ln_fetch_b(b1, wb, ws);
      ln_fetch_b(b2, wb, ws);
      mbar_wait(xf, 0);
      TS4(2)
      ln_fetch<0, 12>(xa, xb, lo);
      mbar_wait(xf + 8, 0);
      TS4(3)
      ln_fetch<12, 24>(xa, xb, lo);
      ln_sums<0, 12>(xa, sm, b0);
      if (wg == 0) bar_arrive(BAR_XREL + after_fetch<12, 24>(xa), 224);
      mbar_wait(xf + 16, 0);
      TS4(4)
      prof(wg, 1);
      ln_fetch<24, 36>(xa, xb, lo);
      ln_sums<12, 24>(xa, sm, b1);
      ln_sums<24, 36>(xa, sm, b2);
#pragma unroll
      for (int i = 0; i < 4; i++) sm[0][i] = (sm[0][i] + sm[1][i]) + (sm[2][i] + sm[3][i]);
      if (cw == hs && c == 0) {
        *(float*)(cx.sp + SM_RAW + 4 * r) = sm[0][1];
        *(float*)(cx.sp + SM_RAW + 4 * r + 32) = sm[0][3];
      }
      rstd0 = sm[0][0];
      rstd1 = sm[0][2];
      mm0 = pack2(rstd0 * (1.0f / DM), rstd0 * (1.0f / DM));
      mm1 = pack2(rstd1 * (1.0f / DM), rstd1 * (1.0f / DM));
    }
#pragma unroll
    for (int i = 0; i < 16; i++) { xa[2 * i] = sub2(xa[2 * i], mm0); xa[2 * i + 1] = sub2(xa[2 * i + 1], mm1); }
    pin(xa);
    prof(wg, 2);
    TS4(5)

    float (&acc)[64] = oB;
    int st0 = 0;
#pragma unroll 1
    for (int n = 0; n < 16; n++) {
      const int p = n & 3, rb = n >> 2;
      const bool last = p == 3 && !hlp;
#pragma unroll
      for (int i = 0; i < 5; i++) {
        if (i == 4 && last) {
          wg_wait<1>();
          mbar_arrive_cluster(empty_c + 8 * 3, signaller && wg);
          wg_wait<0>();
          pin(acc);
          prof(wg, 6);
#pragma unroll
          for (int j = 0; j < 32; j++) xl[j] = xa[112 + j];
          i0 = rstd0;
          i1 = rstd1;
          goto attention;
        }
        const int st = st0 + i;
        const uint32_t sl = st & 3, slp = (st - 1) & 3;
        if (!wg) mbar_wait(full + 8 * sl, (st >> 2) & 1);
        TS4(8 + 2 * (p * 5 + i))
        const bool join = wg && last;
        if ((i || st0 + wg) && i != (wg ? 4 : 1) && !(join && i == 3)) bar_sync(my_turn, 256);
        wg_fence();
        const uint64_t db = mkdesc(ring + sl * STAGE, 16384);
        const int kb0 = i < 3 ? 8 * i : 8 * i - 4;
#pragma unroll
        for (int k = 0; k < (i == 2 ? 4 : 8); k++) {
          const int kb = kb0 + k;
          mma_n128t(acc, xa[4 * kb], xa[4 * kb + 1], xa[4 * kb + 2], xa[4 * kb + 3], db + k * 128, kb > 0);
        }
        wg_commit();
        TS4(9 + 2 * (p * 5 + i))
        if (wg ? (i == 4 ? st0 < 75 : (i < 2 || i == (join ? 3 : 2))) : i) bar_arrive(other_turn, 256);
        if (p == 0 && i < 4) {
          if (i == 1 && rb) {
            mbar_wait(xf + 8, rb & 1);
            ln_fetch<16, 32>(xa, xs - 32768, lo_of(fresh_lane()));
          }
          if (i == 2 && rb) {
            mbar_wait(xf + 16, rb & 1);
            ln_fetch<32, 36>(xa, xs - 32768, lo_of(fresh_lane()));
          }
#pragma unroll
          for (int j = 0; j < 72; j++)
            if (j >= 2 * (i < 2 ? 8 * i + 8 : 8 * i + 4) && j < 2 * (i == 0 ? 16 : 8 * i + 12)) {
              xa[2 * j] = sub2(xa[2 * j], mm0);
              xa[2 * j + 1] = sub2(xa[2 * j + 1], mm1);
            }
          pin(xa);
        }
        if (i == 4 && n == 0) {
          mbar_wait(cx.sb + SM_BAR_SQ, 0);
          float2* sp = (float2*)(cx.sp + SM_STATS) + lr0;
          float mean0, mean1;
          ln_row(rstd0, sp[0].y, mean0, rstd0);
          ln_row(rstd1, sp[8].y, mean1, rstd1);
          __syncwarp();
          if (c == 0) {
            sp[0] = make_float2(mean0, rstd0);
            sp[8] = make_float2(mean1, rstd1);
          }
          *((uint32_t*)(cx.sp + SM_COLD) + wg) = 0;
          if (!hlp) bar_arrive(BAR_GATE, 352);
          rstd0 *= SM_SCALE_LOG2;
          rstd1 *= SM_SCALE_LOG2;
        }
        if (i == 3 && hlp && p == 3 && rb < 3) bar_arrive(BAR_QS + wg + after_fetch<0, 16>(xa), 160);
        if (i == 4 && p == 3 && rb < 3) {
          const float2* sp = (const float2*)(cx.sp + SM_STATS) + cw * 16 + (fresh_lane() >> 2);
          mm0 = pack2(sp[0].x, sp[0].x);
          mm1 = pack2(sp[8].x, sp[8].x);
          sq0 = sp[0].y * SM_SCALE_LOG2;
          sq1 = sp[8].y * SM_SCALE_LOG2;
#pragma unroll
          for (int j = 0; j < 16; j++) { xa[2 * j] = sub2(xa[2 * j], mm0); xa[2 * j + 1] = sub2(xa[2 * j + 1], mm1); }
          pin(xa);
        }
        if (i == 0) {
          if (wg) {
            wg_wait<0>();
            mbar_arrive_cluster(empty_c + 8 * sl, signaller);
          }
        } else if (i == 2) {
          if (!join) {
            wg_wait<0>();
            mbar_arrive_cluster(empty_c + 8 * sl, signaller);
          }
          if (hlp && p == 3 && rb < 3) {
            mbar_wait(xf, ~rb & 1);
            ln_fetch<0, 16>(xa, xs, lo_of(fresh_lane()));
            pin(xa);
          }
        } else if (i != 3) {
          wg_wait<1>();
          mbar_arrive_cluster(empty_c + 8 * slp, signaller && (i == 4 || !wg));
          wg_wait<0>();
          mbar_arrive_cluster(empty_c + 8 * sl, signaller);
        }
      }
      pin(acc);
      prof(wg, 3 + p);
      TS4(50 + 2 * p)
      st0 += 5;
      if (hlp && st0 > 5) bar_sync(BAR_QF + wg, 160);
      park_paced<0, 8>(qlane(lane) + (hlp ? 5 + wg : 4 + p) * STAGE, acc, rstd0, rstd1, 300);
      if (p || hlp) asm volatile("fence.proxy.async.shared::cta;" ::: "memory");
      if (hlp) bar_arrive(BAR_QS + wg, 160);
      if (p == 3) { rstd0 = sq0; rstd1 = sq1; }
      TS4(51 + 2 * p)
      if (p == 1 && !hlp) {
        float (&ah)[32] = *(float (*)[32])&acc[0];
#pragma unroll
        for (int i = 0; i < 3; i++) {
          const uint32_t sl = (10 + i) & 3;
          if (!wg) mbar_wait(full + 8 * sl, ((10 + i) >> 2) & 1);
          TS4(28 + 2 * i)
          if (i == 0 || i == 2 - wg) bar_sync(my_turn, 256);
          wg_fence();
          const uint64_t db = mkdesc(ring + sl * STAGE, 16);
#pragma unroll
          for (int k = 0; k < 12; k++) {
            const int kb = 12 * i + k;
            if (kb) mma_n64t(ah, xa[4 * kb], xa[4 * kb + 1], xa[4 * kb + 2], xa[4 * kb + 3], db + k * 128, true);
            else mma_n64t_dyn(ah, xa[0], xa[1], xa[2], xa[3], db, blockIdx.y);
          }
          wg_commit();
          TS4(29 + 2 * i)
          if (i == 2 || i != wg) {
            bar_arrive(other_turn, 256);
            if (i) {
              wg_wait<1>();
              mbar_arrive_cluster(empty_c + 8 * ((9 + i) & 3), signaller && i == wg + 1);
            }
            wg_wait<0>();
            mbar_arrive_cluster(empty_c + 8 * sl, signaller);
          }
        }
        pin(ah);
        TS4(54)
        park<0, 4>(qlane(lane) + 6 * STAGE, ah, rstd0, rstd1);
        TS4(55)
        st0 = 13;
        n = 2;
      }
    }
    TS_DUMP()
    ffn_consumer(cx, blockIdx.x & 3, wg, cw, fresh_lane(), x);
    return;
  }

attention:
  uint32_t oa[128];
  float acc[32];
  {
    uint32_t pf[28];
    const uint32_t ql = qlane(fresh_lane());
    uint32_t bad = 0;
    float lA0 = 0.f, lA1 = 0.f, lB0 = 0.f, lB1 = 0.f;
    int t = 0;
    uint32_t ra = 2 * 2048, rb = 2048, rc = 2 * 2048, par = 0;
    const uint64_t dk0 = mkdesc(ring, 16), dv0 = mkdesc(ring, 16384);
    uint64_t dqA = mkdesc_q(qwg + 4 * STAGE), dqB = dqA + 2048;
    auto turn = [&](auto kc_, auto bc_) {
      constexpr int KIND = decltype(kc_)::value, BIG = decltype(bc_)::value;
      constexpr int HB = KIND == 1, ID = 10 * KIND + 30 * BIG, T0 = BIG ? 38 : 0;
      constexpr int NS = BIG ? 56 : 48, SPLIT = (BIG ? 36 : 30) + 2 * HB;
      float s[NS];
      float (&op)[64] = HB ? oA : oB;
      uint32_t h0 = 0, h1 = 0;
      TS2(0)
      bar_sync(my_turn, 256);
      TS2(1)
      if (KIND) { pin(pf); pin(op); }
      mma_qk(s, HB ? dqB : dqA, dk0 + (HB ? ra : rc));
      TS2(2)
      if (KIND) {
        const bool bigp = HB ? BIG : BIG ? t != 10 : t == 66;
        block_fence(ID + 9);
        pin(pf);
        sum_tree(pf, bigp, h0, h1);
        asm volatile("" : "+r"(h0), "+r"(h1)::"memory");
        if (HB) mbar_wait(full + (rb >> 8), par);
        mma_pv(op, pf, dv0 + rb, t != T0 + 2 - HB, bigp);
      } else {
        mbar_wait(full + (rb >> 8), (NST_Q - 1) >> 2 & 1);
#pragma unroll
        for (int k = 0; k < 8; k++) mma_n128t(op, xl[4 * k], xl[4 * k + 1], xl[4 * k + 2], xl[4 * k + 3], dv0 + rb + k * 128, 1);
        wg_commit();
      }
      TS2(3)
      bar_arrive(other_turn, 256);
      (HB ? lA0 : lB0) += bf_lo(h0) + bf_hi(h0);
      (HB ? lA1 : lB1) += bf_lo(h1) + bf_hi(h1);
      wg_wait<1>();
      pin(s);
      TS1(t)
      TS2(4)
      if (KIND == 1) mbar_arrive_cluster_now<ID + 3>(empty_c + (ra >> 8), signaller);
      if (BIG && t == T0 + HB) {
        const uint32_t a = ql + (4 + HB) * STAGE;
        const bool ok = !__any_sync(0xffffffffu, inv_sums(HB ? lB0 : lA0, HB ? lB1 : lA1, i0, i1));
        if (!ok) bad |= 1 << HB;
        (HB ? lB0 : lA0) = 0.f;
        (HB ? lB1 : lA1) = 0.f;
        constexpr int E0 = 10, E1 = (E0 + SPLIT) / 2;
        softmax_exp<0, E0>(s);
#pragma unroll
        for (int i = 0; i < E0; i++) asm volatile("" : "+f"(s[i])::"memory");
        block_fence(ID + 7);
        softmax_exp<E0, E1>(s);
        park<0, 4>(a, HB ? oB : oA, i0, i1, ok);
#pragma unroll
        for (int i = E0; i < E1; i++) asm volatile("" : "+f"(s[i])::"memory");
        block_fence(200 + ID);
        softmax_exp<E1, SPLIT>(s);
        park<4, 8>(a, HB ? oB : oA, i0, i1, ok);
        if (!HB) dqB += 2048;
        prof(wg, 8 + HB);
      } else {
        softmax_exp<0, SPLIT>(s);
      }
      pin(s);
      if (!BIG) block_fence(ID + 4);
      TS2(5)
      wg_wait<0>();
      TS2(6)
      pin(op);
      if (KIND) pin(pf); else pin(xl);
      if (HB) {
        par ^= rc == 2048;
        if (BIG && t == 37) dqA -= 4 * 2048;
        if (BIG && t == 33 && cw == 0) bar_arrive(BAR_HELPER, 64);
      } else {
        mbar_arrive_cluster_now<ID + 5>(empty_c + (rb >> 8), signaller);
        if (KIND) {
          par ^= ra == 2048;
          const uint32_t x = ra;
          ra = rc; rc = rb; rb = x;
        }
      }
      softmax_exp<SPLIT, NS>(s);
#pragma unroll
      for (int i = 0; i < NS / 2; i++) pf[i] = pack2(s[2 * i], s[2 * i + 1]);
      pin(pf);
      if (KIND == 0) {
        block_fence(ID + 6);
        park_paced<0, 6>(ql, oB, i0, i1, 310);

        prof(wg, 7);
      }
      if (HB && !BIG && t == 1) park<6, 8>(ql, oB, i0, i1);
      if (BIG && !HB && t == T0) mbar_wait(cx.sb + SM_BAR_Q + 8 * wg, 0);
      if (HB) mbar_wait(full + (rc >> 8), par);
      t++;
    };
#pragma unroll
    for (int i = 24; i < 28; i++) asm volatile("" : "=r"(pf[i]));
    mbar_wait(full + 8 * 2, 0);
    turn(IC<0>(), IC<0>());
    rb = 3 * 2048; rc = 2048;
    kill(oA);
    const bool never = blockIdx.y == 1;
#pragma unroll 1
    while (true) {
      turn(IC<1>(), IC<0>());
      if (t == 76) break;
      if (t == 10) {
        asm volatile("fence.proxy.async.shared::cta;" ::: "memory");
#pragma unroll 1
        do {
#pragma unroll 1
          do turn(IC<2>(), IC<1>()); while (never);
          turn(IC<1>(), IC<1>());
        } while (t != 66);
      }
#pragma unroll 1
      do turn(IC<2>(), IC<0>()); while (never);
    }
    auto scale = [&](auto lo, auto hi) {
#pragma unroll
      for (int i = decltype(lo)::value; i < decltype(hi)::value; i++) {
        oa[32 + 2 * i] = pack2(oA[4 * i] * i0, oA[4 * i + 1] * i0);
        oa[32 + 2 * i + 1] = pack2(oA[4 * i + 2] * i1, oA[4 * i + 3] * i1);
        asm volatile("" : "+r"(oa[32 + 2 * i]), "+r"(oa[32 + 2 * i + 1])::"memory");
      }
    };
    TS3(1)
    volatile uint32_t* const cold = (volatile uint32_t*)(cx.sp + SM_COLD) + wg;
    if (inv_sums(lA0, lA1, i0, i1)) bad |= 4;
#pragma unroll
    for (int i = 0; i < 8; i++) ldsm4(ql + 4 * STAGE + i * 2048, oa[4 * i], oa[4 * i + 1], oa[4 * i + 2], oa[4 * i + 3]);
    {
      uint32_t h0, h1;
      sum_tree(pf, false, h0, h1);
      lB0 += bf_lo(h0) + bf_hi(h0);
      lB1 += bf_lo(h1) + bf_hi(h1);
      asm volatile("" : "+f"(lB0), "+f"(lB1)::"memory");
    }
    scale(IC<0>(), IC<4>());
    if (bad) *cold = 1;
    block_fence(93);
    TS3(2)
    bar_sync(my_turn, 256);
    TS3(3)
    pin(pf); pin(oB);
    mma_pv(oB, pf, dv0 + 2 * 2048, true, false);
    block_fence(91);
    TS3(4)
    const uint32_t held = *cold;
    if (inv_sums(lB0, lB1, lB0, lB1)) bad |= 8;
    const uint64_t db = mkdesc(ring + 3 * STAGE, 16);
    scale(IC<4>(), IC<12>());
    mbar_arrive_cluster_now<94>(empty_c, signaller && !held);
#pragma unroll
    for (int i = 0; i < 32; i++) asm volatile("" : "+r"(oa[i])::"memory");
    wg_fence();
#pragma unroll
    for (int k = 0; k < 8; k++) mma_n64t(acc, oa[4 * k], oa[4 * k + 1], oa[4 * k + 2], oa[4 * k + 3], db + k * 128, k > 0);
    wg_commit();
    block_fence(95);
    scale(IC<12>(), IC<16>());
    TS3(5)
    wg_fence();
#pragma unroll
    for (int k = 8; k < 16; k++) mma_n64t(acc, oa[4 * k], oa[4 * k + 1], oa[4 * k + 2], oa[4 * k + 3], db + k * 128, 1);
    wg_commit();
    bar_arrive(other_turn, 256);
    if (bad) *cold = 1;
    bar_sync(4 + wg, 128);
    const uint32_t is_cold = *cold;
    wg_wait<2>();
    pin(oB); pin(pf);
    TS(76)
    TS3(6)
    mbar_arrive_cluster_now<97>(empty_c + 8 * 2, signaller);
#pragma unroll
    for (int i = 16; i < 24; i++) ldsm4(ql + 5 * STAGE + (i & 7) * 2048, oa[4 * i], oa[4 * i + 1], oa[4 * i + 2], oa[4 * i + 3]);
#pragma unroll
    for (int i = 0; i < 16; i++) {
      oa[96 + 2 * i] = pack2(oB[4 * i] * lB0, oB[4 * i + 1] * lB0);
      oa[96 + 2 * i + 1] = pack2(oB[4 * i + 2] * lB1, oB[4 * i + 3] * lB1);
    }
    TS3(7)
    if (!wg) mbar_wait(full + 8 * 1, 0);
    TS3(8)
    wg_wait<0>();
    pin(acc); pin(oa);
    if (__any_sync(0xffffffffu, is_cold)) {
      bad = __reduce_or_sync(0xffffffffu, bad);
      if (!(bad & 8)) {
#pragma unroll
        for (int i = 24; i < 32; i++) stsm4(ql + 6 * STAGE + (i & 7) * 2048, oa[4 * i], oa[4 * i + 1], oa[4 * i + 2], oa[4 * i + 3]);
      }
#pragma unroll 1
      for (int h = 0; h < 4; h++) {
        if (bad >> h & 1) {
          const uint32_t a = ql + ((0x6054 >> (4 * h)) & 7) * STAGE;
          const int l = fresh_lane(), o = (hs * 2 + (h >> 1)) * SEQ * DH + (l >> 2) * DH + (l & 3) * 2;
          uint32_t q[32];
#pragma unroll
          for (int i = 0; i < 8; i++) ldsm4(a + i * 2048, q[4 * i], q[4 * i + 1], q[4 * i + 2], q[4 * i + 3]);
#pragma unroll 1
          for (int i = 0; i < 4; i++) {
            float ox[16], l0, l1;
            exact_attention(ox, l0, l1, q, kc + o, vc + o + i * 32);
            inv_sums(l0, l1, l0, l1);
            park<0, 2>(a + i * 4096, ox, l0, l1);
          }
        }
      }
      __syncwarp();
#pragma unroll
      for (int i = 0; i < 32; i++)
        if ((i >> 3) != 1 || (bad & 4))
          ldsm4(ql + ((0x6504 >> (4 * (i >> 3))) & 7) * STAGE + (i & 7) * 2048, oa[4 * i], oa[4 * i + 1], oa[4 * i + 2], oa[4 * i + 3]);
      pin(oa);
      asm volatile("fence.proxy.async.shared::cta;" ::: "memory");
      bar_sync(4 + wg, 128);
      mbar_arrive_cluster(empty_c, signaller && held);
      wg_fence();
#pragma unroll
      for (int k = 0; k < 16; k++) mma_n64t(acc, oa[4 * k], oa[4 * k + 1], oa[4 * k + 2], oa[4 * k + 3], db + k * 128, k > 0);
      wg_commit();
      wg_wait<0>();
      pin(acc);
    }
    mbar_arrive_cluster(empty_c + 8 * 3, signaller);
  }

  prof(wg, 10);
  TS3(9)
  {
    lane = fresh_lane();
    const int tw = (cw & 3) * 32 + lane;
    float red[32];
    kill(red);
    const uint32_t tag = *(const uint32_t*)(cx.sp + SM_TAG);
    uint4* const xch = at(cx.g->part, ((qb * 64 * 2 + wg) * 4 * 128 + tw) * 16);
    int nrx = 1;
    auto region = [](int s, int h) { return h ? 1 + (s & 1) : (s & 1) ? 0 : 3; };
    auto half_step = [&](int s, auto hc, bool arrive) {
      constexpr int h = decltype(hc)::value;
      const uint64_t db = mkdesc(ring + region(s, h) * STAGE, 16);
      bar_sync(my_turn, 256);
      pin(oa);
      wg_fence();
#pragma unroll
      for (int k = 0; k < 16; k++) {
        const int kb = h * 16 + k;
        mma_n64t(acc, oa[4 * kb], oa[4 * kb + 1], oa[4 * kb + 2], oa[4 * kb + 3], db + k * 128, kb > 0);
      }
      wg_commit();
      if (arrive) bar_arrive(other_turn, 256);
    };
    auto await = [&](int s, int h) { mbar_wait(full + 8 * region(s, h), ((s >> 1) ^ h ^ 1) & 1); };
    auto fetch = [&](uint32_t (&g)[16], int n) {
      const uint4* p = at(xch, (hs * 7 + n - 1) * 16384);
#pragma unroll
      for (int i = 0; i < 4; i++) ld_gran(p + i * 128, g[4 * i], g[4 * i + 1], g[4 * i + 2], g[4 * i + 3]);
    };
    uint32_t g[16];
    bool pend = false;
#pragma unroll 1
    for (int s = 0;; s++) {
      half_step(s, IC<1>(), s + wg < 9);
      if (s == 8) break;
      TS3(s < 3 ? 16 + 8 * s : 75)
      if (s == 0) {
        bar_arrive(BAR_OA, 352);
#pragma unroll
        for (int i = 0; i < 32; i++) red[i] = 0.f;
      }
      await(s + 1, 0);
      TS3(s < 3 ? 17 + 8 * s : 75)
      wg_wait<0>();
      TS3(s < 3 ? 18 + 8 * s : 75)
      mbar_arrive_cluster(empty_c + 8 * region(s, 1), signaller && s < 7);
      pin(acc);
      TS(77 + s)
      prof(wg, 12 + s);
      uint4* p = at(xch, (s == 0 ? 56 + hs : ((hs + s) & 7) * 7 + s - 1) * 16384);
#pragma unroll
      for (int i = 0; i < 4; i++)
        st_gran(p + i * 128, (pack2(acc[8 * i], acc[8 * i + 1]) & ~TAG) | tag, pack2(acc[8 * i + 2], acc[8 * i + 3]),
                pack2(acc[8 * i + 4], acc[8 * i + 5]), pack2(acc[8 * i + 6], acc[8 * i + 7]));
      TS3(s < 3 ? 19 + 8 * s : 75)
      half_step(s + 1, IC<0>(), true);
      TS3(s < 3 ? 20 + 8 * s : 75)
      if (pend && granules_ok(g, tag)) { add_granules(red, g); nrx++; }
      pend = nrx < s;
      if (pend) fetch(g, nrx);
      await(s + 1, 1);
      TS3(s < 3 ? 21 + 8 * s : 75)
      wg_wait<0>();
      TS3(s < 3 ? 22 + 8 * s : 75)
      mbar_arrive_cluster(empty_c + 8 * region(s + 1, 0), signaller && s < 6);
    }
    uint32_t xv[16], gt[16], g2[16];
    TS3(42)
    const bool ok = granules_ok(g, tag);
    TS3(43)
    nrx += ok;
    fetch(g2, nrx);
    mbar_wait(cx.sb + SM_BAR_XG, 0);
    const uint32_t frag = (cw * 16 + (lane & 15)) * 128 + (((lane >> 4) ^ (lane & 7)) << 4);
#pragma unroll
    for (int i = 0; i < 4; i++) {
      ldsm4(cx.sb + SM_XO + (frag ^ (i << 5)), xv[4 * i], xv[4 * i + 1], xv[4 * i + 2], xv[4 * i + 3]);
      ldsm4(cx.sb + SM_GO + (frag ^ (i << 5)), gt[4 * i], gt[4 * i + 1], gt[4 * i + 2], gt[4 * i + 3]);
    }
    if (ok) add_granules(red, g);
    TS3(44)
    wg_wait<0>();
    pin(acc);
    TS(85)
#pragma unroll
    for (int i = 0; i < 32; i++) red[i] += acc[i];
    pin(red);
#pragma unroll 1
    for (int spins = 0; spins < (1 << 16); spins++) {
      if (granules_ok(g2, tag)) {
        add_granules(red, g2);
        if (++nrx == 8) break;
      }
      fetch(g2, nrx);
    }
    uint32_t ow[16];
#pragma unroll
    for (int i = 0; i < 16; i++) ow[i] = pack2(red[2 * i], red[2 * i + 1]);
    prof(wg, 20);
    TS(86)
#pragma unroll
    for (int i = 0; i < 16; i++) ow[i] = fma2(ow[i], gt[i], xv[i]);
#pragma unroll
    for (int i = 0; i < 4; i++) stsm4(cx.sb + SM_XO + (frag ^ (i << 5)), ow[4 * i], ow[4 * i + 1], ow[4 * i + 2], ow[4 * i + 3]);
    __syncwarp();
    __nv_bfloat16* const op = at(out, ((qb * 128 + cw * 16 + (lane >> 3)) * DM + hs * 64 + (lane & 7) * 8) * 2);
#pragma unroll
    for (int i = 0; i < 4; i++) {
      uint4 v;
      const int row = cw * 16 + i * 4 + (lane >> 3);
      lds128(cx.sb + SM_XO + row * 128 + (((lane ^ row) & 7) << 4), v.x, v.y, v.z, v.w);
      asm volatile("st.global.v4.b32 [%0], {%1, %2, %3, %4};" ::"l"(op + i * 4 * DM),
                   "r"(v.x), "r"(v.y), "r"(v.z), "r"(v.w) : "memory");
    }
    prof(wg, 22);
    TS(87)
    TS_DUMP()
  }
}

struct KvMaps { CUtensorMap m[4]; };
__global__ void __cluster_dims__(2, 1, 1) __launch_bounds__(THREADS, 1)
fused_kernel(const __nv_bfloat16* __restrict__ x, const __nv_bfloat16* __restrict__ w_r, const __nv_bfloat16* __restrict__ kc,
             const __nv_bfloat16* __restrict__ vc, __nv_bfloat16* __restrict__ out, Scratch* scratch,
             const __grid_constant__ CUtensorMap tmX, const __grid_constant__ CUtensorMap tmWq,
             const __grid_constant__ KvMaps tmKV, const __grid_constant__ CUtensorMap tmWo,
             const __grid_constant__ CUtensorMap tmG, const __grid_constant__ CUtensorMap tmU,
             const __grid_constant__ CUtensorMap tmD, const __grid_constant__ CUtensorMap tmX16,
             const __grid_constant__ CUtensorMap tmWq96, const __grid_constant__ CUtensorMap tmX64) {
  extern __shared__ __align__(1024) uint8_t smem_raw[];
  prof(0, 23, 511);
  Ctx cx;
  cx.sb = smem_u32(smem_raw);
  cx.sp = smem_raw;
  cx.g = scratch;
  cx.rank = blockIdx.x & 1;
  if (threadIdx.x == 160) {
    mbar_init(cx.sb + SM_BAR_W, 1);
    asm volatile("fence.mbarrier_init.release.cluster;" ::: "memory");
    *(uint4*)(cx.sp + SM_ONES) = make_uint4(0x3F803F80u, 0x3F803F80u, 0x3F803F80u, 0x3F803F80u);
    mbar_expect_tx(cx.sb + SM_BAR_W, DM * 2);
    bulk_load(cx.sb + SM_WR, w_r, DM * 2, cx.sb + SM_BAR_W);
  }
  const int cluster = blockIdx.x >> 1;
  const bool is_ffn = blockIdx.x >= N_ATT_CTA;
  const int c7 = ((cluster - 36) * 37) >> 8;
  const int hs = cluster < 4 ? 4 + cluster : cluster < 36 ? (cluster - 4) >> 3 : 4 + c7;
  const int qb = (cluster < 4 ? 0 : cluster < 36 ? (cluster - 4) & 7 : cluster - (is_ffn ? 36 : 35) - 7 * c7) * 2 + cx.rank;

  auto x_bar = [&](int i) { return cx.sb + SM_XFULL + 32 * (i / 3) + 8 * (i % 3); };
  auto load_x = [&](int i0, int i1) {
#pragma unroll
    for (int i = i0; i < i1; i++) {
      mbar_expect_tx(x_bar(i), 24576);
      tma3d(cx.sb + SM_X + i * 24576, &tmX, qb * 128 + (i / 3) * 64, (i % 3) * 3, x_bar(i));
    }
  };
  if (threadIdx.x == 128) {
    mbar_init(x_bar(0), 1);
    load_x(0, 1);
    TSP(66)
#pragma unroll
    for (int i = 1; i < 6; i++) mbar_init(x_bar(i), 1);
    asm volatile("fence.mbarrier_init.release.cluster;" ::: "memory");
  }
  const int warp = __shfl_sync(0xffffffffu, threadIdx.x >> 5, 0);
  if (warp < 4) {
    asm volatile("setmaxnreg.dec.sync.aligned.u32 24;");
    if (elect_one()) {
      if (warp == 0) TSP(64)
      if (warp < 2) {
#pragma unroll
        for (int i = 0; i < 4; i++) mbar_init(cx.sb + SM_FULL + 32 * warp + 8 * i, 1 + 3 * warp);
        mbar_init(cx.sb + SM_BAR_XG + 8 * warp, 1);
        mbar_init(cx.sb + SM_BAR_Q + 8 * warp, 1);
        if (warp) mbar_init(cx.sb + SM_BAR_MISC, 1);
      } else if (is_ffn) {
#pragma unroll
        for (int i = 0; i < 8; i++) mbar_init(cx.sb + (warp == 2 ? SM_FFULL : SM_FEMPTY) + 8 * i, 1);
      }
      asm volatile("fence.mbarrier_init.release.cluster;" ::: "memory");
    }
    __syncwarp();
    cluster_arrive();
    if (warp == 0) TSP(70)
    cluster_wait();
    if (warp == 0) TSP(71)
    prof(0, 24, 511);
    if (warp == 0) {
      if (is_ffn) ffn_producer(cx, qb, &tmWq, &tmG, &tmU, &tmD);
      else attn_producer(cx, qb, hs, tmKV.m, &tmWq, &tmWq96, &tmWo);
      prof(0, 25, 511);
    } else {
      sq_publish(cx, qb, hs, warp - 1, read_lane());
      if (warp == 3) sq_collect(cx, qb, read_lane());
      if (!is_ffn) {
        attn_gate(cx, qb, hs, warp - 1, threadIdx.x - 32, x);
        if (warp == 1) TSP(65)
        asm volatile("fence.proxy.async.global;" ::: "memory");
        if (warp == 1) attn_helper(cx, qb, hs, fresh_lane(), &tmX16);
        else bar_arrive(BAR_OA, 352);
        attn_finish8(cx, qb, hs, warp - 1, fresh_lane(), out);
      } else if (warp < 3) {
        ffn_publish(cx, qb, warp - 1, fresh_lane(), &tmX64);
      }
    }
    __syncwarp();
    cluster_arrive();
    cluster_wait();
  } else {
    cluster_arrive();
    if (warp == 4 && elect_one()) {
      load_x(1, 6);
      TSP(67)
    }
    __syncwarp();
    asm volatile("setmaxnreg.inc.sync.aligned.u32 240;");
    const int cw = warp - 4, wg = cw >> 2;
    cluster_wait();
    if (warp == 8 && elect_one()) {
      const uint64_t pol = policy_evict_first();
#pragma unroll
      for (int i = 0; i < 4; i++) {
        if (!(i & 1)) mbar_expect_tx(cx.sb + SM_FULL + 4 * i, 32768);
        tma2d_mc(cx.sb + SM_RING + (i >> 1) * STAGE + cx.rank * 16384 + (i & 1) * 8192, &tmWq,
                 is_ffn ? (cx.rank * 4 + 3) * DH + 64 : hs * 512 + cx.rank * 64, i * 64, cx.sb + SM_FULL + 8 * (i >> 1), pol);
      }
      TSP(72)
    }
    __syncwarp();
    attn_consumer(cx, is_ffn, qb, hs, wg, cw, read_lane(), x, kc, vc, out);
  }
}

typedef CUresult (*EncodeFn)(CUtensorMap*, CUtensorMapDataType, cuuint32_t, void*, const cuuint64_t*, const cuuint64_t*,
                             const cuuint32_t*, const cuuint32_t*, CUtensorMapInterleave, CUtensorMapSwizzle,
                             CUtensorMapL2promotion, CUtensorMapFloatOOBfill);

void encode(EncodeFn fn, CUtensorMap* m, const void* p, int rank, const cuuint64_t* dims, const cuuint64_t* strides,
            const cuuint32_t* box) {
  const cuuint32_t es[5] = {1, 1, 1, 1, 1};
  fn(m, CU_TENSOR_MAP_DATA_TYPE_BFLOAT16, rank, const_cast<void*>(p), dims, strides, box, es, CU_TENSOR_MAP_INTERLEAVE_NONE,
     CU_TENSOR_MAP_SWIZZLE_128B, CU_TENSOR_MAP_L2_PROMOTION_L2_128B, CU_TENSOR_MAP_FLOAT_OOB_FILL_NONE);
}
void encode2d(EncodeFn fn, CUtensorMap* m, const void* p, uint64_t rows, uint64_t cols, uint32_t box_rows) {
  const cuuint64_t dims[2] = {cols, rows}, strides[1] = {cols * 2};
  const cuuint32_t box[2] = {64, box_rows};
  encode(fn, m, p, 2, dims, strides, box);
}

}

extern "C" void kernel_launch(void* const* d_in, const int* in_sizes, int n_in, void* d_out, int out_size) {
  (void)in_sizes; (void)n_in; (void)out_size;
  void* fnp = nullptr;
  cudaDriverEntryPointQueryResult qr;
  cudaGetDriverEntryPoint("cuTensorMapEncodeTiled", &fnp, cudaEnableDefault, &qr);
  EncodeFn fn = (EncodeFn)fnp;
  CUtensorMap tmWq, tmWo, tmG, tmU, tmD, tmX, tmX16, tmWq96, tmX64;
  encode2d(fn, &tmX64, d_in[0], SEQ, DM, 64);
  encode2d(fn, &tmWq96, d_in[3], DM, 4096, 96);
  encode2d(fn, &tmX16, d_in[0], SEQ, DM, 16);
  KvMaps tmKV;
  for (int i = 0; i < 4; i++) encode2d(fn, &tmKV.m[i], d_in[1 + (i & 1)], 16 * SEQ, DH, i < 2 ? 112 : 96);
  encode2d(fn, &tmWq, d_in[3], DM, 4096, 64);
  {
    const cuuint64_t dims[3] = {64, SEQ, 9}, strides[2] = {DM * 2, 128};
    const cuuint32_t box[3] = {64, 64, 3};
    encode(fn, &tmX, d_in[0], 3, dims, strides, box);
  }
  encode2d(fn, &tmWo, d_in[4], 4096, DM, 128);
  encode2d(fn, &tmG, d_in[7], DM, FF, 192);
  encode2d(fn, &tmU, d_in[8], DM, FF, 192);
  encode2d(fn, &tmD, d_in[9], FF, DM, 192);
  cudaFuncSetAttribute(fused_kernel, cudaFuncAttributeMaxDynamicSharedMemorySize, SM_TOTAL);
  void* scratch = nullptr;
  cudaGetSymbolAddress(&scratch, g_scratch);
  fused_kernel<<<N_CTA, THREADS, SM_TOTAL>>>((const __nv_bfloat16*)d_in[0], (const __nv_bfloat16*)d_in[6], (const __nv_bfloat16*)d_in[1],
                                            (const __nv_bfloat16*)d_in[2], (__nv_bfloat16*)d_out, (Scratch*)scratch, tmX, tmWq, tmKV,
                                            tmWo, tmG, tmU, tmD, tmX16, tmWq96, tmX64);
}
```

```cpp
#include <cuda_runtime.h>
#include <cuda_bf16.h>
#include <cuda.h>
#include <stdint.h>

namespace {

constexpr int SEQ = 2048, DM = 576, DH = 128, FF = 4608, TOPC = 8;
constexpr int N_ATT_CTA = 128, N_CTA = 132;
constexpr int THREADS = 384;

constexpr uint32_t SM_RING = 0;
constexpr uint32_t STAGE = 32768;
constexpr uint32_t SM_SLOT = 131072;
constexpr uint32_t FSTAGE = 24576;
constexpr uint32_t SM_XSEL = 196608;
constexpr uint32_t SM_H = 205824;
constexpr uint32_t SM_MISC = 229376;
constexpr uint32_t SM_FULL = SM_MISC, SM_EMPTY = SM_MISC + 32, SM_FFULL = SM_MISC + 64, SM_BAR_MISC = SM_MISC + 128,
                   SM_COLD = SM_MISC + 136, SM_TAG = SM_MISC + 144, SM_BAR_W = SM_MISC + 152, SM_ONES = SM_MISC + 160,
                   SM_BAR_Q = SM_MISC + 176, SM_XFULL = SM_MISC + 192, SM_BAR_XG = SM_MISC + 304, SM_BAR_SQ = SM_MISC + 312,
                   SM_STATS = SM_MISC + 320, SM_FEMPTY = SM_MISC + 1344, SM_RAW = SM_FEMPTY, SM_WR = SM_MISC + 1408, SM_TOPK = SM_WR;
constexpr uint32_t SM_TOTAL = SM_MISC + 2560;
constexpr uint32_t SM_X = SM_MISC - 147456;

constexpr int BAR_GATE = 6, BAR_HELPER = 7, BAR_OA = 8, BAR_XREL = 13, BAR_QS = 9, BAR_QF = 11, BAR_QX = 14;
constexpr int NST_Q = 18, NST_KV = 76, NST_O = 18;
constexpr float SM_SCALE_LOG2 = 0.08838834764831845f * 1.4426950408889634f;

struct Scratch {
  uint4 part[16 * 64 * 2 * 4 * 128];
  uint4 gate[N_ATT_CTA * 1152];
  uint4 q[16 * 8 * 2 * 512];
  uint2 sq[SEQ];
  uint4 stats[SEQ];
  float ypart[4 * TOPC * DM];
  int2 sel[16];
  unsigned launch[160];
  unsigned pad0, ycnt, pad[30];
  unsigned qflag[128];
};
__device__ __align__(1024) Scratch g_scratch;

__device__ __forceinline__ void prof(int, int, int = 0) {}

#define TS(id) {}
#define TS_DUMP() {}
#define TSH(k) {}
#define TS4(k) {}
#define TSP(k) {}
#define TS1(id) TS(id)
#define TS2(k) {}
#define TS3(k) {}

__device__ __forceinline__ uint32_t smem_u32(const void* p) { return (uint32_t)__cvta_generic_to_shared(p); }
__device__ __forceinline__ void mbar_init(uint32_t bar, uint32_t cnt) {
  asm volatile("mbarrier.init.shared::cta.b64 [%0], %1;" ::"r"(bar), "r"(cnt) : "memory");
}
__device__ __forceinline__ void mbar_expect_tx(uint32_t bar, uint32_t bytes) {
  asm volatile("mbarrier.arrive.expect_tx.shared::cta.b64 _, [%0], %1;" ::"r"(bar), "r"(bytes) : "memory");
}
__device__ __forceinline__ void mbar_arrive(uint32_t bar) {
  asm volatile("mbarrier.arrive.shared::cta.b64 _, [%0];" ::"r"(bar) : "memory");
}
__device__ __forceinline__ void mbar_arrive_cluster(uint32_t bar_cluster_addr, bool pred) {
  asm volatile("{\n.reg .pred p;\nsetp.ne.u32 p, %1, 0;\n@p mbarrier.arrive.shared::cluster.b64 _, [%0];\n}"
               ::"r"(bar_cluster_addr), "r"((uint32_t)pred) : "memory");
}
template <int ID>
__device__ __forceinline__ void mbar_arrive_cluster_now(uint32_t bar_cluster_addr, bool pred) {
  asm volatile("{\n.reg .pred p, q;\nsetp.ne.u32 p, %1, 0;\nsetp.eq.u32 q, %2, %3;\n"
               "ARR_LOOP:\n@p mbarrier.arrive.shared::cluster.b64 _, [%0];\n@q bra.uni ARR_LOOP;\n}"
               ::"r"(bar_cluster_addr), "r"((uint32_t)pred), "r"(blockIdx.y), "n"(ID) : "memory");
}
__device__ __forceinline__ void block_fence(int id) {
  asm volatile("{\n.reg .pred q;\nsetp.eq.u32 q, %0, %1;\nBF_LOOP:\n@q st.volatile.shared.u32 [%0], %0;\n@q bra.uni BF_LOOP;\n}"
               ::"r"(blockIdx.y), "r"(id) : "memory");
}
__device__ __forceinline__ void mbar_wait(uint32_t bar, uint32_t parity) {
  asm volatile("{\n.reg .pred p, q;\n.reg .u32 n;\nmov.u32 n, 0;\n"
               "WAIT_LOOP:\nmbarrier.try_wait.parity.shared::cta.b64 p, [%0], %1;\n"
               "add.u32 n, n, 1;\nsetp.lt.u32 q, n, 262144;\nand.pred q, q, !p;\n@q bra WAIT_LOOP;\n}"
               ::"r"(bar), "r"(parity) : "memory");
}
__device__ __forceinline__ uint32_t mapa(uint32_t addr, uint32_t rank) {
  uint32_t r;
  asm volatile("mapa.shared::cluster.u32 %0, %1, %2;" : "=r"(r) : "r"(addr), "r"(rank));
  return r;
}
__device__ __forceinline__ void cluster_arrive() { asm volatile("barrier.cluster.arrive.relaxed.aligned;" ::: "memory"); }
__device__ __forceinline__ bool elect_one() {
  uint32_t p;
  asm volatile("{\n.reg .pred p;\nelect.sync _|p, 0xffffffff;\nselp.u32 %0, 1, 0, p;\n}" : "=r"(p));
  return p;
}
__device__ __forceinline__ int read_lane() { return threadIdx.x & 31; }
__device__ __forceinline__ int fresh_lane() {
  int l;
  asm volatile("mov.u32 %0, %%laneid;" : "=r"(l));
  return l;
}
template <class T> __device__ __forceinline__ T* at(T* p, uint32_t bytes) {
  asm("" : "+r"(bytes));
  return (T*)((const char*)p + bytes);
}
__device__ __forceinline__ void cluster_wait() { asm volatile("barrier.cluster.wait.acquire.aligned;" ::: "memory"); }
__device__ __forceinline__ void bar_sync(int id, int n) { asm volatile("barrier.cta.sync %0, %1;" ::"r"(id), "r"(n) : "memory"); }
__device__ __forceinline__ void bar_arrive(int id, int n) { asm volatile("barrier.cta.arrive %0, %1;" ::"r"(id), "r"(n) : "memory"); }

__device__ __forceinline__ uint64_t policy_evict_first() {
  uint64_t p;
  asm("createpolicy.fractional.L2::evict_first.b64 %0, 1.0;" : "=l"(p));
  return p;
}
__device__ __forceinline__ void tma2d_mc(uint32_t dst, const CUtensorMap* tm, int c0, int c1, uint32_t bar, uint64_t pol) {
  asm volatile("cp.async.bulk.tensor.2d.shared::cluster.global.mbarrier::complete_tx::bytes.multicast::cluster.L2::cache_hint"
               " [%0], [%1, {%2, %3}], [%4], %5, %6;"
               ::"r"(dst), "l"(tm), "r"(c0), "r"(c1), "r"(bar), "h"((uint16_t)3), "l"(pol) : "memory");
}
__device__ __forceinline__ void tma3d(uint32_t dst, const CUtensorMap* tm, int c1, int c2, uint32_t bar) {
  asm volatile("cp.async.bulk.tensor.3d.shared::cluster.global.mbarrier::complete_tx::bytes [%0], [%1, {%2, %3, %4}], [%5];"
               ::"r"(dst), "l"(tm), "r"(0), "r"(c1), "r"(c2), "r"(bar) : "memory");
}
__device__ __forceinline__ void tma2d(uint32_t dst, const CUtensorMap* tm, int c0, int c1, uint32_t bar) {
  asm volatile("cp.async.bulk.tensor.2d.shared::cluster.global.mbarrier::complete_tx::bytes [%0], [%1, {%2, %3}], [%4];"
               ::"r"(dst), "l"(tm), "r"(c0), "r"(c1), "r"(bar) : "memory");
}
__device__ __forceinline__ void tma2d_stream(uint32_t dst, const CUtensorMap* tm, int c0, int c1, uint32_t bar) {
  asm volatile("{\n.reg .b64 pol;\ncreatepolicy.fractional.L2::evict_first.b64 pol, 1.0;\n"
               "cp.async.bulk.tensor.2d.shared::cluster.global.mbarrier::complete_tx::bytes.L2::cache_hint [%0], [%1, {%2, %3}], [%4], pol;\n}"
               ::"r"(dst), "l"(tm), "r"(c0), "r"(c1), "r"(bar) : "memory");
}
__device__ __forceinline__ void bulk_load(uint32_t dst, const void* src, uint32_t bytes, uint32_t bar) {
  asm volatile("cp.async.bulk.shared::cluster.global.mbarrier::complete_tx::bytes [%0], [%1], %2, [%3];"
               ::"r"(dst), "l"(src), "r"(bytes), "r"(bar) : "memory");
}
__device__ __forceinline__ void tma2d_prefetch(const CUtensorMap* tm, int c0, int c1) {
  asm volatile("cp.async.bulk.prefetch.tensor.2d.L2.global [%0, {%1, %2}];" ::"l"(tm), "r"(c0), "r"(c1) : "memory");
}

__device__ __forceinline__ void wg_fence() { asm volatile("wgmma.fence.sync.aligned;" ::: "memory"); }
__device__ __forceinline__ void wg_commit() { asm volatile("wgmma.commit_group.sync.aligned;" ::: "memory"); }
template <int N> __device__ __forceinline__ void wg_wait() { asm volatile("wgmma.wait_group.sync.aligned %0;" ::"n"(N) : "memory"); }

__device__ __forceinline__ uint64_t mkdesc(uint32_t addr, uint32_t lbo_bytes) {
  return (uint64_t)(((addr & 0x3FFFF) >> 4) | ((lbo_bytes >> 4) << 16)) | ((uint64_t)0x40000040u << 32);
}
__device__ __forceinline__ uint64_t mkdesc_q(uint32_t addr) {
  return (uint64_t)(((addr & 0x3FFFF) >> 4) | (64u << 16)) | ((uint64_t)8 << 32);
}
template <int N> __device__ __forceinline__ void pin(float (&a)[N]) {
#pragma unroll
  for (int i = 0; i < N; i++) asm volatile("" : "+f"(a[i])::"memory");
}
template <int N> __device__ __forceinline__ void kill(float (&a)[N]) {
#pragma unroll
  for (int i = 0; i < N; i++) asm volatile("" : "=f"(a[i]));
}
template <int N> __device__ __forceinline__ void pin(uint32_t (&a)[N]) {
#pragma unroll
  for (int i = 0; i < N; i++) asm volatile("" : "+r"(a[i])::"memory");
}

#define F8(d, o) "+f"(d[o]), "+f"(d[o + 1]), "+f"(d[o + 2]), "+f"(d[o + 3]), "+f"(d[o + 4]), "+f"(d[o + 5]), "+f"(d[o + 6]), "+f"(d[o + 7])
#define R32A "%0, %1, %2, %3, %4, %5, %6, %7, %8, %9, %10, %11, %12, %13, %14, %15, %16, %17, %18, %19, %20, %21, %22, %23, %24, %25, %26, %27, %28, %29, %30, %31"
#define R32B "%32, %33, %34, %35, %36, %37, %38, %39, %40, %41, %42, %43, %44, %45, %46, %47, %48, %49, %50, %51, %52, %53, %54, %55, %56, %57, %58, %59, %60, %61, %62, %63"

#define O8(d, o) "=f"(d[o]), "=f"(d[o + 1]), "=f"(d[o + 2]), "=f"(d[o + 3]), "=f"(d[o + 4]), "=f"(d[o + 5]), "=f"(d[o + 6]), "=f"(d[o + 7])

__device__ __forceinline__ void mma_n128t(float (&d)[64], uint32_t a0, uint32_t a1, uint32_t a2, uint32_t a3, uint64_t db, bool acc) {
  if (acc)
    asm volatile("wgmma.mma_async.sync.aligned.m64n128k16.f32.bf16.bf16 {" R32A ", " R32B "}, {%64, %65, %66, %67}, %68, 1, 1, 1, 1;\n"
                 : F8(d, 0), F8(d, 8), F8(d, 16), F8(d, 24), F8(d, 32), F8(d, 40), F8(d, 48), F8(d, 56)
                 : "r"(a0), "r"(a1), "r"(a2), "r"(a3), "l"(db));
  else
    asm volatile("wgmma.mma_async.sync.aligned.m64n128k16.f32.bf16.bf16 {" R32A ", " R32B "}, {%64, %65, %66, %67}, %68, 0, 1, 1, 1;\n"
                 : O8(d, 0), O8(d, 8), O8(d, 16), O8(d, 24), O8(d, 32), O8(d, 40), O8(d, 48), O8(d, 56)
                 : "r"(a0), "r"(a1), "r"(a2), "r"(a3), "l"(db));
}
#define PV1(a0, a1, a2, a3, ob, acc) "add.s64 b, %92, " #ob ";\n" \
  "wgmma.mma_async.sync.aligned.m64n128k16.f32.bf16.bf16 {" R32A ", " R32B "}, {%" #a0 ", %" #a1 ", %" #a2 ", %" #a3 "}, b, " #acc ", 1, 1, 1;\n"
#define PV6 "wgmma.fence.sync.aligned;\n" PV1(64, 65, 66, 67, 0, p) PV1(68, 69, 70, 71, 128, 1) PV1(72, 73, 74, 75, 256, 1) \
  PV1(76, 77, 78, 79, 384, 1) PV1(80, 81, 82, 83, 512, 1) PV1(84, 85, 86, 87, 640, 1)
#define U4(a, o) "r"(a[o]), "r"(a[o + 1]), "r"(a[o + 2]), "r"(a[o + 3])
__device__ __forceinline__ void mma_pv(float (&d)[64], const uint32_t (&a)[28], uint64_t dv, bool acc, bool big) {
  asm volatile("{\n.reg .pred p, q;\n.reg .b64 b;\nsetp.ne.b32 p, %93, 0;\nsetp.eq.b32 q, %94, 0;\n@q bra.uni PV_SMALL;\n"
               PV6 PV1(88, 89, 90, 91, 768, 1) "wgmma.commit_group.sync.aligned;\nbra.uni PV_DONE;\n"
               "PV_SMALL:\n" PV6 "wgmma.commit_group.sync.aligned;\nPV_DONE:\n}\n"
               : F8(d, 0), F8(d, 8), F8(d, 16), F8(d, 24), F8(d, 32), F8(d, 40), F8(d, 48), F8(d, 56)
               : U4(a, 0), U4(a, 4), U4(a, 8), U4(a, 12), U4(a, 16), U4(a, 20), U4(a, 24), "l"(dv), "r"((int)acc), "r"((int)big) : "memory");
}
#define R48 R32A ", %32, %33, %34, %35, %36, %37, %38, %39, %40, %41, %42, %43, %44, %45, %46, %47"
#define R56 R48 ", %48, %49, %50, %51, %52, %53, %54, %55"
#define QK1(N, R, A, B, oa, ob, acc) "add.s64 a, " A ", " #oa ";\nadd.s64 b, " B ", " #ob ";\n" \
  "wgmma.mma_async.sync.aligned.m64n" #N "k16.f32.bf16.bf16 {" R "}, a, b, " #acc ", 1, 1, 0, 0;\n"
#define QK8(N, R, A, B) "{\n.reg .b64 a, b;\nwgmma.fence.sync.aligned;\n" QK1(N, R, A, B, 0, 0, 0) QK1(N, R, A, B, 128, 2, 1) \
  QK1(N, R, A, B, 256, 4, 1) QK1(N, R, A, B, 384, 6, 1) QK1(N, R, A, B, 512, 1024, 1) QK1(N, R, A, B, 640, 1026, 1) \
  QK1(N, R, A, B, 768, 1028, 1) QK1(N, R, A, B, 896, 1030, 1) "wgmma.commit_group.sync.aligned;\n}\n"
__device__ __forceinline__ void mma_qk(float (&d)[56], uint64_t dq, uint64_t dk) {
  asm volatile(QK8(112, R56, "%56", "%57")
               : O8(d, 0), O8(d, 8), O8(d, 16), O8(d, 24), O8(d, 32), O8(d, 40), O8(d, 48) : "l"(dq), "l"(dk) : "memory");
}
__device__ __forceinline__ void mma_qk(float (&d)[48], uint64_t dq, uint64_t dk) {
  asm volatile(QK8(96, R48, "%48", "%49")
               : O8(d, 0), O8(d, 8), O8(d, 16), O8(d, 24), O8(d, 32), O8(d, 40) : "l"(dq), "l"(dk) : "memory");
}
__device__ __forceinline__ void mma_n64t(float (&d)[32], uint32_t a0, uint32_t a1, uint32_t a2, uint32_t a3, uint64_t db, bool acc) {
  if (acc)
    asm volatile("wgmma.mma_async.sync.aligned.m64n64k16.f32.bf16.bf16 {" R32A "}, {%32, %33, %34, %35}, %36, 1, 1, 1, 1;\n"
                 : F8(d, 0), F8(d, 8), F8(d, 16), F8(d, 24) : "r"(a0), "r"(a1), "r"(a2), "r"(a3), "l"(db));
  else
    asm volatile("wgmma.mma_async.sync.aligned.m64n64k16.f32.bf16.bf16 {" R32A "}, {%32, %33, %34, %35}, %36, 0, 1, 1, 1;\n"
                 : O8(d, 0), O8(d, 8), O8(d, 16), O8(d, 24) : "r"(a0), "r"(a1), "r"(a2), "r"(a3), "l"(db));
}
__device__ __forceinline__ void mma_n64t_dyn(float (&d)[32], uint32_t a0, uint32_t a1, uint32_t a2, uint32_t a3, uint64_t db, int acc) {
  asm volatile("{\n.reg .pred p;\nsetp.ne.b32 p, %37, 0;\n"
               "wgmma.mma_async.sync.aligned.m64n64k16.f32.bf16.bf16 {" R32A "}, {%32, %33, %34, %35}, %36, p, 1, 1, 1;\n}\n"
               : F8(d, 0), F8(d, 8), F8(d, 16), F8(d, 24) : "r"(a0), "r"(a1), "r"(a2), "r"(a3), "l"(db), "r"(acc));
}
__device__ __forceinline__ void mma_n8(float (&d)[4], uint64_t da, uint64_t db, int acc) {
  asm volatile("{\n.reg .pred p;\nsetp.ne.b32 p, %6, 0;\n"
               "wgmma.mma_async.sync.aligned.m64n8k16.f32.bf16.bf16 {%0, %1, %2, %3}, %4, %5, p, 1, 1, 1, 0;\n}\n"
               : "+f"(d[0]), "+f"(d[1]), "+f"(d[2]), "+f"(d[3])
               : "l"(da), "l"(db), "r"(acc));
}
__device__ __forceinline__ void hmma_k16(float (&d)[4], uint32_t a0, uint32_t a1, uint32_t a2, uint32_t a3, uint32_t b0, uint32_t b1) {
  asm volatile("mma.sync.aligned.m16n8k16.row.col.f32.bf16.bf16.f32 {%0, %1, %2, %3}, {%4, %5, %6, %7}, {%8, %9}, {%0, %1, %2, %3};"
               : "+f"(d[0]), "+f"(d[1]), "+f"(d[2]), "+f"(d[3]) : "r"(a0), "r"(a1), "r"(a2), "r"(a3), "r"(b0), "r"(b1));
}

__device__ __forceinline__ uint32_t pack2(float lo, float hi) {
  uint32_t r;
  asm("cvt.rn.bf16x2.f32 %0, %1, %2;" : "=r"(r) : "f"(hi), "f"(lo));
  return r;
}
__device__ __forceinline__ float bf_lo(uint32_t w) { return __uint_as_float(w << 16); }
__device__ __forceinline__ float bf_hi(uint32_t w) { return __uint_as_float(w & 0xFFFF0000u); }
__device__ __forceinline__ float bfr(float x) { return __bfloat162float(__float2bfloat16_rn(x)); }
__device__ __forceinline__ uint32_t sub2(uint32_t a, uint32_t b) {
  uint32_t r;
  asm("sub.rn.bf16x2 %0, %1, %2;" : "=r"(r) : "r"(a), "r"(b));
  return r;
}
__device__ __forceinline__ uint32_t add2(uint32_t a, uint32_t b) {
  uint32_t r;
  asm("add.rn.bf16x2 %0, %1, %2;" : "=r"(r) : "r"(a), "r"(b));
  return r;
}
__device__ __forceinline__ uint32_t fma2(uint32_t a, uint32_t b, uint32_t c) {
  uint32_t r;
  asm("fma.rn.bf16x2 %0, %1, %2, %3;" : "=r"(r) : "r"(a), "r"(b), "r"(c));
  return r;
}
__device__ __forceinline__ float ex2(float x) {
  float r;
  asm("ex2.approx.ftz.f32 %0, %1;" : "=f"(r) : "f"(x));
  return r;
}
__device__ __forceinline__ float rcp(float x) {
  float r;
  asm("rcp.approx.ftz.f32 %0, %1;" : "=f"(r) : "f"(x));
  return r;
}
__device__ __forceinline__ float silu_f(float t) { return t * rcp(1.0f + ex2(-1.4426950408889634f * t)); }
__device__ __forceinline__ void lds128(uint32_t a, uint32_t& x, uint32_t& y, uint32_t& z, uint32_t& w) {
  asm volatile("ld.shared.v4.u32 {%0, %1, %2, %3}, [%4];" : "=r"(x), "=r"(y), "=r"(z), "=r"(w) : "r"(a) : "memory");
}
__device__ __forceinline__ void ldsm4(uint32_t a, uint32_t& x, uint32_t& y, uint32_t& z, uint32_t& w) {
  asm volatile("ldmatrix.sync.aligned.m8n8.x4.shared.b16 {%0, %1, %2, %3}, [%4];" : "=r"(x), "=r"(y), "=r"(z), "=r"(w) : "r"(a) : "memory");
}
constexpr uint32_t TAG = 0x10000;
__device__ __forceinline__ void st_gran(uint4* p, uint32_t x, uint32_t y, uint32_t z, uint32_t w) {
  asm volatile("st.relaxed.gpu.global.v4.b32 [%0], {%1, %2, %3, %4};" ::"l"(p), "r"(x), "r"(y), "r"(z), "r"(w) : "memory");
}
__device__ __forceinline__ void ld_gran(const uint4* p, uint32_t& x, uint32_t& y, uint32_t& z, uint32_t& w) {
  asm volatile("ld.relaxed.gpu.global.v4.b32 {%0, %1, %2, %3}, [%4];" : "=r"(x), "=r"(y), "=r"(z), "=r"(w) : "l"(p) : "memory");
}
__device__ __forceinline__ void stsm4(uint32_t a, uint32_t x, uint32_t y, uint32_t z, uint32_t w) {
  asm volatile("stmatrix.sync.aligned.m8n8.x4.shared.b16 [%0], {%1, %2, %3, %4};" ::"r"(a), "r"(x), "r"(y), "r"(z), "r"(w) : "memory");
}
__device__ __forceinline__ void cp16(uint32_t dst, const void* src) {
  asm volatile("cp.async.cg.shared.global [%0], [%1], 16;" ::"r"(dst), "l"(src) : "memory");
}
__device__ __forceinline__ void cp_wait_all() { asm volatile("cp.async.wait_all;" ::: "memory"); }
__device__ __forceinline__ void add_granules(float (&red)[32], const uint32_t (&g)[16]) {
#pragma unroll
  for (int i = 0; i < 16; i++) { red[2 * i] += bf_lo(g[i]); red[2 * i + 1] += bf_hi((i & 3) ? g[i] : g[i] & ~TAG); }
}
__device__ __forceinline__ bool granules_ok(const uint32_t (&g)[16], uint32_t tag) {
  uint32_t a, b;
  asm("lop3.b32 %0, %1, %2, %3, 0x7E;" : "=r"(a) : "r"(g[0]), "r"(g[4]), "r"(tag));
  asm("lop3.b32 %0, %1, %2, %3, 0x7E;" : "=r"(b) : "r"(g[8]), "r"(g[12]), "r"(tag));
  return __all_sync(0xffffffffu, ((a | b) & TAG) == 0);
}
__device__ __forceinline__ unsigned ld_acquire(const unsigned* p) {
  unsigned v;
  asm volatile("ld.acquire.gpu.global.u32 %0, [%1];" : "=r"(v) : "l"(p) : "memory");
  return v;
}
__device__ __forceinline__ unsigned atom_add_acq_rel(unsigned* p) {
  unsigned v;
  asm volatile("atom.acq_rel.gpu.global.add.u32 %0, [%1], 1;" : "=r"(v) : "l"(p) : "memory");
  return v;
}

template <int K0, int K1>
__device__ __forceinline__ void ln_fetch(uint32_t (&xa)[144], uint32_t boxes, uint32_t lo) {
#pragma unroll
  for (int k = K0; k < K1; k++) ldsm4(boxes + (k >> 2) * 8192 + (lo ^ ((k & 3) << 5)), xa[4 * k], xa[4 * k + 1], xa[4 * k + 2], xa[4 * k + 3]);
}
__device__ __forceinline__ void ln_fetch_b(uint32_t (&b)[24], uint32_t& wb, uint32_t ws) {
#pragma unroll
  for (int j = 0; j < 6; j++, wb += ws) ldsm4(wb, b[4 * j], b[4 * j + 1], b[4 * j + 2], b[4 * j + 3]);
}
template <int K0, int K1>
__device__ __forceinline__ void ln_sums(const uint32_t (&xa)[144], float (&sm)[4][4], const uint32_t (&b)[24]) {
#pragma unroll
  for (int k = K0; k < K1; k++)
    hmma_k16(sm[k & 3], xa[4 * k], xa[4 * k + 1], xa[4 * k + 2], xa[4 * k + 3], b[2 * (k % 12)], b[2 * (k % 12) + 1]);
}
template <int K0, int K1>
__device__ __forceinline__ uint32_t after_fetch(const uint32_t (&xa)[144]) {
  uint32_t d = blockIdx.y;
#pragma unroll
  for (int k = K0; k < K1; k++) d &= xa[4 * k];
  return d;
}
__device__ __forceinline__ void ln_row(float sum, float sq, float& mean_b, float& rstd) {
  const float mean = sum * (1.0f / DM);
  const uint32_t mv = pack2(mean, fmaxf(sq * (1.0f / DM) - mean * mean, 0.0f));
  mean_b = bf_lo(mv);
  float sd;
  asm("sqrt.approx.f32 %0, %1;" : "=f"(sd) : "f"(bf_lo(pack2(bf_hi(mv) + 1e-5f, 0.f))));
  rstd = rcp(bf_lo(pack2(sd, 0.f)));
}

template <bool ROUTED>
__device__ __forceinline__ uint32_t gate2(uint32_t xc, float rstd, float2 upd = make_float2(0.f, 0.f)) {
  uint32_t t = pack2(bf_lo(xc) * rstd, bf_hi(xc) * rstd);
  if (ROUTED) t = pack2(bf_lo(t) + upd.x, bf_hi(t) + upd.y);
  return pack2(silu_f(bf_lo(t)), silu_f(bf_hi(t)));
}

template <int V> struct IC { static constexpr int value = V; };

struct Ctx {
  uint32_t sb;
  uint8_t* sp;
  uint32_t rank;
  Scratch* g;
};

__device__ __forceinline__ bool acquire(const Ctx& cx, uint32_t r, uint32_t n, uint32_t bytes) {
  mbar_wait(cx.sb + SM_EMPTY + 8 * r, (n ^ (r >> 1) ^ 1) & 1);
  __syncwarp();
  const bool e = elect_one();
  if (e) mbar_expect_tx(cx.sb + SM_FULL + 8 * r, bytes);
  return e;
}
__device__ __forceinline__ void load_wq(const Ctx& cx, const CUtensorMap* tmWq, int st, int i, int n0, uint64_t pol) {
  const uint32_t r = st & 3, dst = cx.sb + SM_RING + r * STAGE + cx.rank * 16384, bar = cx.sb + SM_FULL + 8 * r;
  const int k0 = i < 3 ? 128 * i : 128 * i - 64;
  if (acquire(cx, r, st >> 2, i == 2 ? 16384 : 32768)) {
    tma2d_mc(dst, tmWq, n0, k0, bar, pol);
    if (i != 2) tma2d_mc(dst + 8192, tmWq, n0, k0 + 64, bar, pol);
  }
}
__device__ __forceinline__ void attn_producer(const Ctx& cx, int qb, int hs, const CUtensorMap* tmKV, const CUtensorMap* tmWq,
                                              const CUtensorMap* tmWq96, const CUtensorMap* tmWo) {
  const uint32_t full = cx.sb + SM_FULL, ring = cx.sb + SM_RING + cx.rank * 16384;
  const uint64_t last_use = policy_evict_first();
  int st = 0;
#pragma unroll 1
  for (int p = 0; p < 4; p++) {
#pragma unroll 1
    for (int i = 0; i < (p == 2 ? 3 : 5); i++, st++) {
      if (p == 2) {
        if (acquire(cx, st & 3, st >> 2, 24576))
          tma2d_mc(cx.sb + SM_RING + (st & 3) * STAGE + cx.rank * 12288, tmWq96, (hs * 4 + 3) * DH, 192 * i + 96 * cx.rank, full + 8 * (st & 3), last_use);
      } else {
        if (st > 1) load_wq(cx, tmWq, st, i, (hs * 4 + (p ^ (p >> 1))) * DH + cx.rank * 64, last_use);
      }
      if (st == 1 || st == 2) TSP(72 + st)
      if (st == 1) {
#pragma unroll 1
        for (int b = 0; b < 4; b++) {
          const bool k8 = b == 0 && qb < 8;
          if (elect_one()) tma2d_prefetch(tmWq, hs * 512 + (k8 ? qb * 64 : (b ^ (b >> 1)) * DH + (qb & 1) * 64), k8 ? 512 : (qb >> 1) * 64);
        }
      }
      if (st == 8 && qb < 8 && elect_one()) tma2d_prefetch(tmKV + ((qb >> 1) & 1), cx.rank * 64, hs * 2 * SEQ + (qb >> 2) * 96);
    }
  }
  uint32_t r = 2, n = 4;
  int row = hs * 2 * SEQ, rows = 96;
  const CUtensorMap* tm = tmKV + 2;
#pragma unroll 1
  for (int u = 0; u < NST_KV; u++) {
    if (acquire(cx, r, n, rows * 256)) {
      tma2d_mc(ring + r * STAGE, tm, cx.rank * 64, row, full + 8 * r, last_use);
      if (((u ^ (qb >> 1)) & 7) == 0 && u < NST_KV - 4) tma2d_prefetch(tmKV + (u & 1), cx.rank * 64, row + 208);
      if ((unsigned)(u - 32) < 36 && (u & 15) == qb) tma2d_prefetch(tmWo, ((u - 32) >> 2) * 64, hs * 512 + (u & 3) * 128);
    }
    if (++r == 4) { r = 1; n++; }
    if (u & 1) row += rows;
    const bool big = (unsigned)(u - 9) < 56;
    rows = big ? 112 : 96;
    tm = tmKV + (~u & 1) + (big ? 0 : 2);
  }
#pragma unroll 1
  for (int u = 0; u < NST_O; u++) {
    const int s = u >> 1;
    const int blk = s == 0 ? 8 : ((hs + s) & 7);
    r = (0x87 >> (2 * (u & 3))) & 3;
    if (acquire(cx, r, (u >> 2) ^ ~u, 32768))
      tma2d_mc(ring + r * STAGE, tmWo, blk * 64, hs * 512 + ((u & 1) + cx.rank * 2) * 128, full + 8 * r, last_use);
  }
}

__device__ __forceinline__ void sq_publish(const Ctx& cx, int qb, int hs, int j, int lane) {
  if (j == 2 && lane == 0) {
    const unsigned e = cx.g->launch[hs * 16 + qb]++;
    *(uint2*)(cx.sp + SM_TAG) = make_uint2((~e & 1) * TAG, e);
  }
  const int row = (hs & 3) * 16 + (lane >> 1);
  uint32_t a = cx.sb + SM_X + (hs >> 2) * 73728 + j * 8192 + row * 128 + (((lane & 1) ^ (row & 7)) << 4);
  float s0 = 0.f, s1 = 0.f;
#pragma unroll 1
  for (int b = 0; b < 6; b++) {
    if (b == (hs < 4 ? 4 : 0)) {
      const int n = 224 + (__float_as_uint(s1) & blockIdx.y);
      if (j == 1) {
        bar_sync(BAR_XREL, n);
        if (lane < 4) asm volatile("mbarrier.arrive.shared::cluster.b64 _, [%0], 2;" ::"r"(mapa(cx.sb + SM_EMPTY + 16 + 8 * (lane >> 1), lane & 1)) : "memory");
      } else {
        bar_arrive(BAR_XREL, n);
      }
      __syncwarp();
      if (hs == 8) return;
    }
    if (!(b & 1)) mbar_wait(cx.sb + SM_XFULL + 32 * (hs >> 2) + 4 * b, 0);
    uint32_t v[8];
    lds128(a, v[0], v[1], v[2], v[3]);
    lds128(a ^ 32, v[4], v[5], v[6], v[7]);
    a = (a ^ 64) + (b & 1) * 24576;
#pragma unroll
    for (int i = 0; i < 8; i++) { s0 = fmaf(bf_lo(v[i]), bf_lo(v[i]), s0); s1 = fmaf(bf_hi(v[i]), bf_hi(v[i]), s1); }
  }
  s0 += s1;
  s0 += __shfl_xor_sync(0xffffffffu, s0, 1);
  float* part = (float*)(cx.sp + SM_STATS) + (lane >> 1) * 2;
  if (j < 2) {
    part[32 * j] = s0;
    bar_arrive(BAR_HELPER, 96);
  } else {
    bar_sync(BAR_HELPER, 96);
    TSP(68)
    if (!(lane & 1))
      asm volatile("st.relaxed.gpu.global.v2.b32 [%0], {%1, %2};" ::"l"(cx.g->sq + qb * 128 + hs * 16 + (lane >> 1)),
                   "r"(__float_as_uint((part[0] + part[32]) + s0)), "r"(*(const uint32_t*)(cx.sp + SM_TAG + 4) + 1) : "memory");
  }
}
__device__ __forceinline__ void sq_collect(const Ctx& cx, int qb, int lane) {
  const uint32_t e1 = *(const uint32_t*)(cx.sp + SM_TAG + 4) + 1;
#pragma unroll 1
  for (int n = 0; n < (1 << 16); n++) {
    __nanosleep(300);
    uint32_t bad = 0;
#pragma unroll
    for (int i = 0; i < 2; i++) {
      uint32_t a, t0, b, t1;
      ld_gran((const uint4*)at(cx.g->sq, qb * 1024 + lane * 16) + i * 32, a, t0, b, t1);
      *(uint32_t*)(cx.sp + SM_STATS + (i * 32 + lane) * 16 + 4) = a;
      *(uint32_t*)(cx.sp + SM_STATS + (i * 32 + lane) * 16 + 12) = b;
      bad |= (t0 ^ e1) | (t1 ^ e1);
    }
    if (__all_sync(0xffffffffu, bad == 0)) break;
  }
  mbar_arrive(cx.sb + SM_BAR_SQ);
  TSP(69)
}
__device__ __forceinline__ void attn_gate(const Ctx& cx, int qb, int hs, int j, int t, const __nv_bfloat16* x) {
  const uint4* xp = (const uint4*)(x + qb * 128 * DM) + (t >> 3) * 72 + hs * 8 + (t & 7);
  uint4 nx = *xp;
  float wsum = 0.f;
  if (j == 0) {
    mbar_wait(cx.sb + SM_BAR_W, 0);
#pragma unroll 3
    for (int i = 0; i < 9; i++) {
      const uint32_t w = *(const uint32_t*)(cx.sp + SM_WR + i * 128 + t * 4);
      wsum += bf_lo(w) + bf_hi(w);
    }
#pragma unroll
    for (int i = 1; i < 32; i *= 2) wsum += __shfl_xor_sync(0xffffffffu, wsum, i);
  }
  bar_sync(BAR_GATE, 352);
  if (t < 16) {
    const float2 st = *(const float2*)(cx.sp + SM_STATS + 8 * (hs * 16 + t));
    const int row = qb * 128 + hs * 16 + t;
    const uint32_t b = pack2(0.f, fmaf(-st.x, wsum, *(const float*)(cx.sp + SM_RAW + 4 * t)) * st.y);
    st_gran(at(cx.g->stats, row * 16), __float_as_uint(st.x), __float_as_uint(st.y), (b ^ ((int)b < 0 ? 0xFFFF0000u : 0x80000000u)) | (0xFFFF - row),
            *(const uint32_t*)(cx.sp + SM_TAG + 4) + 1);
  }
  __syncwarp();
  uint32_t sa = cx.sb + SM_STATS + (t & ~7);
  uint4* gp = cx.g->gate + blockIdx.x * 1152 + (t ^ ((t >> 3) & 7));
  const int cross = t < 64 ? 10 : 9;
#pragma unroll 1
  for (int i = 0; i < 12; i++) {
    float2 st;
    asm volatile("ld.shared.v2.f32 {%0, %1}, [%2];" : "=f"(st.x), "=f"(st.y) : "r"(sa));
    const uint32_t mm = pack2(st.x, st.x);
    const uint4 v = make_uint4(sub2(nx.x, mm), sub2(nx.y, mm), sub2(nx.z, mm), sub2(nx.w, mm));
    xp += 12 * 72;
    sa += 96;
    if (i == cross) { xp += (hs * 16 - 128) * 72 + 64 - hs * 8; sa += (hs * 16 - 128) * 8; }
    if (i < 11) nx = *xp;
    *gp = make_uint4(gate2<false>(v.x, st.y), gate2<false>(v.y, st.y), gate2<false>(v.z, st.y), gate2<false>(v.w, st.y));
    gp = (uint4*)((size_t)(gp + 96) ^ 64);
  }
}

constexpr uint32_t SM_XO = SM_SLOT, SM_GO = SM_SLOT + STAGE, SM_P8 = SM_SLOT + 2 * STAGE;
__device__ __forceinline__ void attn_helper(const Ctx& cx, int qb, int hs, int lane, const CUtensorMap* tmX16) {
  const unsigned e = *(const uint32_t*)(cx.sp + SM_TAG + 4);
  bar_sync(BAR_HELPER, 64);
  bool todo = lane < 2;
#pragma unroll 1
  for (int n = 0; __any_sync(0xffffffffu, todo); n++) {
    if (todo && (ld_acquire(at(cx.g->qflag, ((qb * 4 + (hs >> 1)) * 2 + lane) * 4)) == e + 1 || n == (1 << 16))) {
      asm volatile("fence.proxy.async.global;" ::: "memory");
      mbar_expect_tx(cx.sb + SM_BAR_Q + 8 * lane, 8192);
      bulk_load(cx.sb + SM_SLOT + 2 * STAGE + lane * 16384 + 8192, at(cx.g->q, ((qb * 8 + hs) * 2 + lane) * 8192), 8192, cx.sb + SM_BAR_Q + 8 * lane);
      todo = false;
    }
  }
  const uint32_t tag = (~e & 1) * TAG;
  const uint4* src = cx.g->part + (size_t)((qb * 64 + 56) * 2 + (hs >> 2)) * 4 * 128 + (hs & 3) * 32 + lane;
  const uint32_t stg = cx.sb + SM_P8 + lane * 16;
  bar_sync(BAR_OA, 352);
  asm volatile("fence.proxy.async.global;" ::: "memory");
  if (lane == 0) {
    mbar_expect_tx(cx.sb + SM_BAR_MISC, 2 * 18432);
    bulk_load(cx.sb + SM_GO, cx.g->gate + blockIdx.x * 1152, 18432, cx.sb + SM_BAR_MISC);
#pragma unroll 1
    for (int i = 0; i < 9; i++)
      tma2d(cx.sb + SM_XO + i * 2048, tmX16, i < 8 ? hs * 64 : 512, qb * 128 + (i < 8 ? i : hs) * 16, cx.sb + SM_BAR_MISC);
  }
#pragma unroll 1
  for (int n = 0; n < (1 << 16); n++) {
    __nanosleep(n ? 500 : 2000);
    uint32_t a, b, d, t;
    ld_gran(src - lane + (lane & 7) * (2 * 4 * 128) + 3 * 128 + 31, a, b, d, t);
    if (__all_sync(0xffffffffu, (a & TAG) == tag)) break;
  }
  TSH(46)
#pragma unroll 1
  for (int n = 0; n < (1 << 16); n++) {
#pragma unroll 1
    for (int i = 0; i < 8; i++) {
#pragma unroll
      for (int g = 0; g < 4; g++) cp16(stg + (i * 4 + g) * 512, src + i * (2 * 4 * 128) + g * 128);
    }
    cp_wait_all();
    uint32_t bad = 0;
#pragma unroll 4
    for (int i = 0; i < 32; i++) bad |= *(const volatile uint32_t*)(cx.sp + SM_P8 + lane * 16 + i * 512) ^ tag;
    if (__all_sync(0xffffffffu, (bad & TAG) == 0)) break;
  }
  TSH(47)
#pragma unroll 1
  for (int n = 0; n < (1 << 16) && ld_acquire(&cx.g->ycnt) != 4 * (e + 1); n++) __nanosleep(200);
  const int2 sel = __ldcg(at(cx.g->sel, (lane & 7) * 8));
  const int lr = sel.x - qb * 128;
  uint32_t m = __ballot_sync(0xffffffffu, lane < 16 && ((lane & 8) ? (lr >> 4) == hs : (lr >> 7) == 0));
  mbar_wait(cx.sb + SM_BAR_MISC, 0);
#pragma unroll 1
  for (; m; m &= m - 1) {
    const int i = __ffs(m) - 1, row = __shfl_sync(0xffffffffu, lr, i);
    const float rs = __int_as_float(__shfl_sync(0xffffffffu, sel.y, i));
    const float* p = cx.g->ypart + (i & 7) * DM + (i < 8 ? hs * 64 : 512) + 2 * lane;
    const float2 a = __ldcg((const float2*)p), b = __ldcg((const float2*)(p + TOPC * DM)), c = __ldcg((const float2*)(p + 2 * TOPC * DM)),
                 d = __ldcg((const float2*)(p + 3 * TOPC * DM));
    const uint32_t y = pack2((a.x + b.x) + (c.x + d.x), (a.y + b.y) + (c.y + d.y));
    const uint32_t u = pack2(bf_lo(y) * rs, bf_hi(y) * rs);
    const float2 st = *(const float2*)(cx.sp + SM_STATS + 8 * row);
    const int o = (i < 8 ? row : 128 + (row & 15)) * 128 + ((lane * 4) ^ ((row & 7) << 4));
    *(uint32_t*)(cx.sp + SM_GO + o) = gate2<true>(sub2(*(const uint32_t*)(cx.sp + SM_XO + o), pack2(st.x, st.x)), st.y, make_float2(bf_lo(u), bf_hi(u)));
  }
  mbar_arrive(cx.sb + SM_BAR_XG);
  TSH(48)
}
__device__ __forceinline__ void attn_finish8(const Ctx& cx, int qb, int hs, int hw, int lane, __nv_bfloat16* out) {
  bar_sync(BAR_GATE, 96);
#pragma unroll 1
  for (int g = hw; g < 4; g += 3) {
    float acc[8] = {0.f, 0.f, 0.f, 0.f, 0.f, 0.f, 0.f, 0.f};
#pragma unroll 2
    for (int sidx = 0; sidx < 8; sidx++) {
      uint32_t a, b, d, t;
      lds128(cx.sb + SM_P8 + lane * 16 + (sidx * 4 + g) * 512, a, b, d, t);
      acc[0] += bf_lo(a); acc[1] += bf_hi(a & ~TAG); acc[2] += bf_lo(b); acc[3] += bf_hi(b);
      acc[4] += bf_lo(d); acc[5] += bf_hi(d); acc[6] += bf_lo(t); acc[7] += bf_hi(t);
    }
#pragma unroll
    for (int j = 0; j < 4; j++) {
      const int o = (128 + (lane >> 2) + (j & 1) * 8) * 128 + (((2 * g + (j >> 1)) ^ (lane >> 2)) << 4) + (lane & 3) * 4;
      uint32_t* xp = (uint32_t*)(cx.sp + SM_XO + o);
      *xp = fma2(pack2(acc[2 * j], acc[2 * j + 1]), *(const uint32_t*)(cx.sp + SM_GO + o), *xp);
    }
  }
  bar_sync(BAR_GATE, 96);
#pragma unroll 1
  for (int ch = threadIdx.x - 32; ch < 128; ch += 96)
    *(uint4*)at(out, ((qb * 128 + hs * 16 + (ch >> 3)) * DM + 512 + (ch & 7) * 8) * 2) =
        *(const uint4*)(cx.sp + SM_XO + 16384 + (ch ^ ((ch >> 3) & 7)) * 16);
}

__device__ __forceinline__ void ffn_producer(const Ctx& cx, int f, const CUtensorMap* tmWq, const CUtensorMap* tmG,
                                             const CUtensorMap* tmU, const CUtensorMap* tmD) {
  uint64_t keep;
  asm("createpolicy.fractional.L2::evict_normal.b64 %0, 1.0;" : "=l"(keep));
  int st = 0;
#pragma unroll 1
  for (int p = 0; p < 16; p++) {
#pragma unroll 1
    for (int i = 0; i < 5; i++, st++) if (st > 1) load_wq(cx, tmWq, st, i, ((2 * (p & 3) + cx.rank) * 4 + 3) * DH + 64, keep);
  }
  const uint32_t full = cx.sb + SM_FFULL, empty = cx.sb + SM_FEMPTY;
  int pair = 0, u = 0;
#pragma unroll 1
  for (st = 0; st < 14 * 12; st++) {
    const uint32_t sl = st & 7;
    const int unit = pair * 2 + (u & 1), k = u >> 1, k3 = k >= 3 ? k - 3 : k;
    if (unit < 27) {
      mbar_wait(empty + 8 * sl, (st >> 3) & 1);
      __syncwarp();
      if (elect_one()) {
        mbar_expect_tx(full + 8 * sl, FSTAGE);
        if (pair < 9) tma2d_stream(cx.sb + sl * FSTAGE, k < 3 ? tmG : tmU, f * 1152 + unit * 64, k3 * 192, full + 8 * sl);
        else tma2d_stream(cx.sb + sl * FSTAGE, tmD, (unit - 18) * 64, f * 1152 + k * 192, full + 8 * sl);
      }
    }
    if (++u == 12) { u = 0; pair++; }
  }
}
__device__ __forceinline__ void load_x1(uint32_t dst, const CUtensorMap* tmX64, int row, int box, int n, uint32_t bar) {
  mbar_expect_tx(bar, n * 8192);
#pragma unroll 1
  for (int i = 0; i < n; i++) tma2d(dst + i * 8192, tmX64, (box + i) * 64, row, bar);
}
__device__ __forceinline__ void ffn_publish(const Ctx& cx, int f, int w, int lane, const CUtensorMap* tmX64) {
  const uint32_t xs = cx.sb + SM_SLOT + w * 49152, xf = cx.sb + SM_XFULL + w * 32;
#pragma unroll 1
  for (int n = 0; n < 16; n++) {
    const int p = n & 3, row = (f + (n & 12) + 4) * 128 + w * 64;
    if (n < 12 && p == 3) {
      bar_sync(BAR_QX + w, 160);
      if (lane == 0) load_x1(xs, tmX64, row, 4, 4, xf + 8);
      __syncwarp();
    }
    bar_sync(BAR_QS + w, 160);
    const uint32_t e1 = *(const uint32_t*)(cx.sp + SM_TAG + 4) + 1;
    if (lane == 0) {
#pragma unroll
      for (int i = 0; i < 2; i++)
        asm volatile("cp.async.bulk.global.shared::cta.bulk_group [%0], [%1], 8192;"
                     ::"l"(cx.g->q + (((f + (n & 12)) * 8 + 2 * p + i) * 2 + w) * 512), "r"(xs + 32768 + i * 8192) : "memory");
      asm volatile("cp.async.bulk.commit_group;" ::: "memory");
      asm volatile("cp.async.bulk.wait_group.read 0;" ::: "memory");
      if (n < 12 && (p == 0 || p == 3)) load_x1(xs + (p ? 32768 : 0), tmX64, row, p ? 8 : 0, p ? 1 : 4, xf + (p ? 16 : 0));
      asm volatile("cp.async.bulk.wait_group 0;\nfence.proxy.async.global;" ::: "memory");
      asm volatile("st.release.gpu.global.u32 [%0], %1;" ::"l"(&cx.g->qflag[((f + (n & 12)) * 4 + p) * 2 + w]), "r"(e1) : "memory");
    }
    __syncwarp();
    if (n < 12 && p == 1) {
#pragma unroll 1
      for (int i = 0, k = 0; i < 64 && k < (1 << 16); k++) {
        uint32_t m, r, z, t;
        ld_gran(cx.g->stats + row + i + lane, m, r, z, t);
        *(uint2*)(cx.sp + SM_STATS + 8 * (w * 64 + i + lane)) = make_uint2(m, r);
        if (__all_sync(0xffffffffu, t == e1)) i += 32;
      }
    }
    bar_arrive(BAR_QF + w, 160);
  }
}

__device__ __forceinline__ void ffn_consumer(const Ctx& cx, int f, int wg, int cw, int lane, const __nv_bfloat16* x) {
  const int r = lane >> 2, c = lane & 3, tid = cw * 32 + lane;
  const uint32_t full = cx.sb + SM_FFULL, empty = cx.sb + SM_FEMPTY;
  const bool signaller = (tid & 127) == 0;
  prof(wg, 8);
  const unsigned e = *(const uint32_t*)(cx.sp + SM_TAG + 4);
  uint32_t key[8];
#pragma unroll 1
  for (int n = 0; n < (1 << 16); n++) {
    uint32_t bad = 0;
#pragma unroll
    for (int i = 0; i < 8; i++) {
      uint32_t t;
      asm volatile("ld.relaxed.gpu.global.v2.b32 {%0, %1}, [%2];" : "=r"(key[i]), "=r"(t) : "l"(&cx.g->stats[i * 256 + tid].z) : "memory");
      bad |= t ^ (e + 1);
    }
    if (__all_sync(0xffffffffu, bad == 0)) break;
  }
  bar_sync(BAR_QF + wg, 160);
  bar_sync(3, 256);
  if (tid < 8) mbar_arrive(empty + 8 * tid);
  prof(wg, 9);
  int mysel = 0;
#pragma unroll 1
  for (int k = 0; k < TOPC; k++) {
    uint32_t m = key[0];
#pragma unroll
    for (int i = 1; i < 8; i++) m = max(m, key[i]);
    m = __reduce_max_sync(0xffffffffu, m);
    uint32_t* tk = (uint32_t*)(cx.sp + SM_TOPK) + (k & 1) * 8;
    if (lane == 0) tk[cw] = m;
    bar_sync(3, 256);
    m = __reduce_max_sync(0xffffffffu, tk[lane & 7]);
#pragma unroll
    for (int i = 0; i < 8; i++) if (key[i] == m) key[i] = 0;
    if (k == cw) mysel = 0xFFFF - (int)(m & 0xFFFF);
  }
  {
    const float4 st = __ldcg((const float4*)&cx.g->stats[mysel]);
    const uint32_t mm = pack2(st.x, st.x);
#pragma unroll 3
    for (int i = 0; i < 9; i++) {
      const uint32_t t = sub2(*(const uint32_t*)(x + (size_t)mysel * DM + i * 64 + 2 * lane), mm);
      *(uint32_t*)(cx.sp + SM_XSEL + i * 1024 + cw * 128 + (((lane >> 2) ^ cw) << 4) + (lane & 3) * 4) =
          pack2(bf_lo(t) * st.y, bf_hi(t) * st.y);
    }
    const uint32_t k = __float_as_uint(st.z);
    const float score = bf_hi(k ^ ((int)k < 0 ? 0x80000000u : 0xFFFF0000u));
    if (lane == 0 && f == 0) cx.g->sel[cw] = make_int2(mysel, __float_as_int(bfr(rcp(1.0f + ex2(-1.4426950408889634f * score)))));
  }
  asm volatile("fence.proxy.async.shared::cta;" ::: "memory");
  bar_sync(3, 256);
  prof(wg, 10);
  auto run = [&](float (&acc)[4], int st, int n, uint32_t b) {
#pragma unroll 1
    for (int u = 0; u < n; u++, st += 2, b += 3072) {
      const uint32_t sl = st & 7;
      mbar_wait(full + 8 * sl, (st >> 3) & 1);
      wg_fence();
      const uint64_t da = mkdesc(cx.sb + sl * FSTAGE, 16), db = mkdesc(b, 16);
#pragma unroll
      for (int k = 0; k < 12; k++) mma_n8(acc, da + k * 128, db + (k >> 2) * 64 + (k & 3) * 2, u > 0 || k > 0);
      wg_commit();
      wg_wait<0>();
      if (signaller) mbar_arrive(empty + 8 * sl);
    }
    pin(acc);
  };
#pragma unroll 1
  for (int unit = wg; unit < 27; unit += 2) {
    if (unit >> 1 == 9) {
      asm volatile("fence.proxy.async.shared::cta;" ::: "memory");
      bar_sync(3, 256);
      prof(wg, 11);
    }
    const bool gu = unit < 18;
    float a0[4], a1[4];
#pragma unroll 1
    for (int m = 0; m < (gu ? 2 : 1); m++) {
      run(a1, (unit >> 1) * 12 + m * 6 + wg, gu ? 3 : 6, cx.sb + (gu ? SM_XSEL : SM_H));
      if (m == 0) { a0[0] = a1[0]; a0[1] = a1[1]; a0[2] = a1[2]; a0[3] = a1[3]; }
    }
    float u0 = a1[0], u1 = a1[1];
#pragma unroll 1
    for (int i = 0; i < 2; i++) {
      const int fl = (cw & 3) * 16 + r + i * 8;
      if (gu) {
        const uint32_t g = pack2(a0[0], a0[1]);
        const uint32_t h = fma2(pack2(silu_f(bf_lo(g)), silu_f(bf_hi(g))), pack2(u0, u1), 0x80008000u);
        uint8_t* hp = cx.sp + SM_H + unit * 1024 + c * 256 + (fl & 7) * 2;
        *(uint16_t*)(hp + (((fl >> 3) ^ (2 * c)) << 4)) = (uint16_t)h;
        *(uint16_t*)(hp + 128 + (((fl >> 3) ^ (2 * c + 1)) << 4)) = (uint16_t)(h >> 16);
      } else {
        float* yp = cx.g->ypart + (f * TOPC + 2 * c) * DM + (unit - 18) * 64 + fl;
        yp[0] = u0;
        yp[DM] = u1;
      }
      a0[0] = a0[2]; a0[1] = a0[3]; u0 = a1[2]; u1 = a1[3];
    }
  }
  prof(wg, 12);
  bar_sync(3, 256);
  if (tid == 0) atom_add_acq_rel(&cx.g->ycnt);
  prof(wg, 13);
}

constexpr float SUM_HI = 1.8446744e19f, SUM_LO = 9.0949470e-13f;

template <int LO, int HI, int N>
__device__ __forceinline__ void softmax_exp(float (&s)[N]) {
#pragma unroll
  for (int i = LO; i < HI; i++) s[i] = ex2(s[i]);
}
__device__ __forceinline__ void sum_tree(const uint32_t (&pf)[28], bool big, uint32_t& h0, uint32_t& h1) {
  uint32_t t0 = add2(add2(pf[16], pf[18]), add2(pf[20], pf[22])), t1 = add2(add2(pf[17], pf[19]), add2(pf[21], pf[23]));
  if (big) { t0 = add2(t0, add2(pf[24], pf[26])); t1 = add2(t1, add2(pf[25], pf[27])); }
  h0 = add2(add2(add2(add2(pf[0], pf[2]), add2(pf[4], pf[6])), add2(add2(pf[8], pf[10]), add2(pf[12], pf[14]))), t0);
  h1 = add2(add2(add2(add2(pf[1], pf[3]), add2(pf[5], pf[7])), add2(add2(pf[9], pf[11]), add2(pf[13], pf[15]))), t1);
}
__device__ __forceinline__ void exact_attention(float (&o)[16], float& l0, float& l1, const uint32_t (&q)[32], const __nv_bfloat16* kp,
                                                const __nv_bfloat16* vp) {
  float m0 = -3.0e38f, m1 = -3.0e38f;
  l0 = l1 = 0.f;
#pragma unroll
  for (int i = 0; i < 16; i++) o[i] = 0.f;
#pragma unroll 1
  for (int key = 0; key < SEQ; key += 8, kp += 8 * DH, vp += 8 * DH) {
    float d[4] = {0.f, 0.f, 0.f, 0.f};
#pragma unroll
    for (int k = 0; k < 8; k++)
      hmma_k16(d, q[4 * k], q[4 * k + 1], q[4 * k + 2], q[4 * k + 3], *(const uint32_t*)(kp + k * 16), *(const uint32_t*)(kp + k * 16 + 8));
    float x0 = fmaxf(d[0], d[1]), x1 = fmaxf(d[2], d[3]);
    x0 = fmaxf(x0, __shfl_xor_sync(0xffffffffu, x0, 1));
    x1 = fmaxf(x1, __shfl_xor_sync(0xffffffffu, x1, 1));
    x0 = fmaxf(fmaxf(x0, __shfl_xor_sync(0xffffffffu, x0, 2)), m0);
    x1 = fmaxf(fmaxf(x1, __shfl_xor_sync(0xffffffffu, x1, 2)), m1);
    const float sc0 = ex2(m0 - x0), sc1 = ex2(m1 - x1);
    m0 = x0; m1 = x1;
    const uint32_t p0 = pack2(ex2(d[0] - m0), ex2(d[1] - m0)), p1 = pack2(ex2(d[2] - m1), ex2(d[3] - m1));
    l0 = fmaf(l0, sc0, bf_lo(p0) + bf_hi(p0));
    l1 = fmaf(l1, sc1, bf_lo(p1) + bf_hi(p1));
#pragma unroll
    for (int nb = 0; nb < 4; nb++) {
      uint32_t b;
      asm("movmatrix.sync.aligned.m8n8.trans.b16 %0, %1;" : "=r"(b) : "r"(*(const uint32_t*)(vp + nb * 8)));
      o[4 * nb] *= sc0; o[4 * nb + 1] *= sc0; o[4 * nb + 2] *= sc1; o[4 * nb + 3] *= sc1;
      asm volatile("mma.sync.aligned.m16n8k8.row.col.f32.bf16.bf16.f32 {%0, %1, %2, %3}, {%4, %5}, {%6}, {%0, %1, %2, %3};"
                   : "+f"(o[4 * nb]), "+f"(o[4 * nb + 1]), "+f"(o[4 * nb + 2]), "+f"(o[4 * nb + 3]) : "r"(p0), "r"(p1), "r"(b));
    }
  }
}
__device__ __forceinline__ bool inv_sums(float l0, float l1, float& i0, float& i1) {
  l0 += __shfl_xor_sync(0xffffffffu, l0, 1); l1 += __shfl_xor_sync(0xffffffffu, l1, 1);
  l0 += __shfl_xor_sync(0xffffffffu, l0, 2); l1 += __shfl_xor_sync(0xffffffffu, l1, 2);
  i0 = rcp(l0);
  i1 = rcp(l1);
  return !(l0 + l1 <= SUM_HI) | (fminf(l0, l1) < SUM_LO);
}
template <int LO, int HI, int N>
__device__ __forceinline__ void park(uint32_t a, const float (&o)[N], float i0, float i1, bool on = true) {
#pragma unroll
  for (int i = LO; i < HI; i++)
    asm volatile("{\n.reg .pred p;\nsetp.ne.u32 p, %5, 0;\n@p stmatrix.sync.aligned.m8n8.x4.shared.b16 [%0], {%1, %2, %3, %4};\n}"
                 ::"r"(a + i * 2048), "r"(pack2(o[8 * i] * i0, o[8 * i + 1] * i0)), "r"(pack2(o[8 * i + 2] * i1, o[8 * i + 3] * i1)),
                 "r"(pack2(o[8 * i + 4] * i0, o[8 * i + 5] * i0)), "r"(pack2(o[8 * i + 6] * i1, o[8 * i + 7] * i1)), "r"((uint32_t)on) : "memory");
}

template <int I, int HI>
__device__ __forceinline__ void park_paced(uint32_t a, const float (&o)[64], float i0, float i1, int id) {
  if constexpr (I < HI) {
    park<I, I + 2>(a, o, i0, i1);
    if (I + 2 < HI) block_fence(id + I);
    park_paced<I + 2, HI>(a, o, i0, i1, id);
  }
}

__device__ __forceinline__ void attn_consumer(const Ctx& cx, bool hlp, int qb, int hs, int wg, int cw, int lane, const __nv_bfloat16* x,
                                              const __nv_bfloat16* kc, const __nv_bfloat16* vc, __nv_bfloat16* out) {
  const uint32_t full = cx.sb + SM_FULL;
  const uint32_t ring = cx.sb + SM_RING;
  const uint32_t qwg = ring + wg * 16384;
  auto qlane = [&](int l) { return qwg + (cw & 3) * 256 + (l >> 4) * 1024 + (l & 15) * 16; };
  const bool signaller = lane == 0 && (cw & 3) < 2;
  const int my_turn = 1 + wg, other_turn = 2 - wg;
  const uint32_t empty_c = mapa(cx.sb + SM_EMPTY, cw & 1);

  float oA[64], oB[64], i0, i1;
  uint32_t xl[32];
  {
    const int r = lane >> 2, c = lane & 3;
    const int lr0 = cw * 16 + r;
    uint32_t xa[144];
    uint32_t mm0, mm1;
    float rstd0, rstd1, sq0 = 0.f, sq1 = 0.f;
    const uint32_t xf = cx.sb + SM_XFULL + wg * 32, xs = cx.sb + SM_SLOT + wg * 49152;
    auto lo_of = [&](int l) { return ((cw & 3) * 16 + (l & 15)) * 128 + (((l >> 4) ^ (l & 7)) << 4); };
    prof(wg, 0);
    {
      const uint32_t lo = lo_of(lane);
      const uint32_t xb = cx.sb + SM_X + wg * 73728;
      float sm[4][4] = {};
      const uint32_t ws = (lane & 7) == 1 ? 64 : 0;
      uint32_t wb = cx.sb + (ws ? SM_WR + (lane >> 3) * 16 : SM_ONES);
      uint32_t b0[24], b1[24], b2[24];
      mbar_wait(cx.sb + SM_BAR_W, 0);
      TS4(1)
      ln_fetch_b(b0, wb, ws);
      ln_fetch_b(b1, wb, ws);
      ln_fetch_b(b2, wb, ws);
      mbar_wait(xf, 0);
      TS4(2)
      ln_fetch<0, 12>(xa, xb, lo);
      mbar_wait(xf + 8, 0);
      TS4(3)
      ln_fetch<12, 24>(xa, xb, lo);
      ln_sums<0, 12>(xa, sm, b0);
      if (wg == 0) bar_arrive(BAR_XREL + after_fetch<12, 24>(xa), 224);
      mbar_wait(xf + 16, 0);
      TS4(4)
      prof(wg, 1);
      ln_fetch<24, 36>(xa, xb, lo);
      ln_sums<12, 24>(xa, sm, b1);
      ln_sums<24, 36>(xa, sm, b2);
#pragma unroll
      for (int i = 0; i < 4; i++) sm[0][i] = (sm[0][i] + sm[1][i]) + (sm[2][i] + sm[3][i]);
      if (cw == hs && c == 0) {
        *(float*)(cx.sp + SM_RAW + 4 * r) = sm[0][1];
        *(float*)(cx.sp + SM_RAW + 4 * r + 32) = sm[0][3];
      }
      rstd0 = sm[0][0];
      rstd1 = sm[0][2];
      mm0 = pack2(rstd0 * (1.0f / DM), rstd0 * (1.0f / DM));
      mm1 = pack2(rstd1 * (1.0f / DM), rstd1 * (1.0f / DM));
    }
#pragma unroll
    for (int i = 0; i < 16; i++) { xa[2 * i] = sub2(xa[2 * i], mm0); xa[2 * i + 1] = sub2(xa[2 * i + 1], mm1); }
    pin(xa);
    prof(wg, 2);
    TS4(5)

    float (&acc)[64] = oB;
    int st0 = 0;
#pragma unroll 1
    for (int n = 0; n < 16; n++) {
      const int p = n & 3, rb = n >> 2;
      const bool last = p == 3 && !hlp;
#pragma unroll
      for (int i = 0; i < 5; i++) {
        if (i == 4 && last) {
          wg_wait<1>();
          mbar_arrive_cluster(empty_c + 8 * 3, signaller && wg);
          wg_wait<0>();
          pin(acc);
          prof(wg, 6);
#pragma unroll
          for (int j = 0; j < 32; j++) xl[j] = xa[112 + j];
          i0 = rstd0;
          i1 = rstd1;
          goto attention;
        }
        const int st = st0 + i;
        const uint32_t sl = st & 3, slp = (st - 1) & 3;
        if (!wg) mbar_wait(full + 8 * sl, (st >> 2) & 1);
        TS4(8 + 2 * (p * 5 + i))
        const bool join = wg && last;
        if ((i || st0 + wg) && i != (wg ? 4 : 1) && !(join && i == 3)) bar_sync(my_turn, 256);
        wg_fence();
        const uint64_t db = mkdesc(ring + sl * STAGE, 16384);
        const int kb0 = i < 3 ? 8 * i : 8 * i - 4;
#pragma unroll
        for (int k = 0; k < (i == 2 ? 4 : 8); k++) {
          const int kb = kb0 + k;
          mma_n128t(acc, xa[4 * kb], xa[4 * kb + 1], xa[4 * kb + 2], xa[4 * kb + 3], db + k * 128, kb > 0);
        }
        wg_commit();
        TS4(9 + 2 * (p * 5 + i))
        if (wg ? (i == 4 ? st0 < 75 : (i < 2 || i == (join ? 3 : 2))) : i) bar_arrive(other_turn, 256);
        if (p == 0 && i < 4) {
          if (i == 1 && rb) {
            mbar_wait(xf + 8, rb & 1);
            ln_fetch<16, 32>(xa, xs - 32768, lo_of(fresh_lane()));
          }
          if (i == 2 && rb) {
            mbar_wait(xf + 16, rb & 1);
            ln_fetch<32, 36>(xa, xs - 32768, lo_of(fresh_lane()));
          }
#pragma unroll
          for (int j = 0; j < 72; j++)
            if (j >= 2 * (i < 2 ? 8 * i + 8 : 8 * i + 4) && j < 2 * (i == 0 ? 16 : 8 * i + 12)) {
              xa[2 * j] = sub2(xa[2 * j], mm0);
              xa[2 * j + 1] = sub2(xa[2 * j + 1], mm1);
            }
          pin(xa);
        }
        if (i == 4 && n == 0) {
          mbar_wait(cx.sb + SM_BAR_SQ, 0);
          float2* sp = (float2*)(cx.sp + SM_STATS) + lr0;
          float mean0, mean1;
          ln_row(rstd0, sp[0].y, mean0, rstd0);
          ln_row(rstd1, sp[8].y, mean1, rstd1);
          __syncwarp();
          if (c == 0) {
            sp[0] = make_float2(mean0, rstd0);
            sp[8] = make_float2(mean1, rstd1);
          }
          *((uint32_t*)(cx.sp + SM_COLD) + wg) = 0;
          if (!hlp) bar_arrive(BAR_GATE, 352);
          rstd0 *= SM_SCALE_LOG2;
          rstd1 *= SM_SCALE_LOG2;
        }
        if (i == 3 && hlp && p == 3 && rb < 3) bar_arrive(BAR_QX + wg + after_fetch<0, 16>(xa), 160);
        if (i == 4 && p == 3 && rb < 3) {
          const float2* sp = (const float2*)(cx.sp + SM_STATS) + cw * 16 + (fresh_lane() >> 2);
          mm0 = pack2(sp[0].x, sp[0].x);
          mm1 = pack2(sp[8].x, sp[8].x);
          sq0 = sp[0].y * SM_SCALE_LOG2;
          sq1 = sp[8].y * SM_SCALE_LOG2;
#pragma unroll
          for (int j = 0; j < 16; j++) { xa[2 * j] = sub2(xa[2 * j], mm0); xa[2 * j + 1] = sub2(xa[2 * j + 1], mm1); }
          pin(xa);
        }
        if (i == 0) {
          if (wg) {
            wg_wait<0>();
            mbar_arrive_cluster(empty_c + 8 * sl, signaller);
          }
        } else if (i == 2) {
          if (!join) {
            wg_wait<0>();
            mbar_arrive_cluster(empty_c + 8 * sl, signaller);
          }
          if (hlp && p == 3 && rb < 3) {
            mbar_wait(xf, ~rb & 1);
            ln_fetch<0, 16>(xa, xs, lo_of(fresh_lane()));
            pin(xa);
          }
        } else if (i != 3) {
          wg_wait<1>();
          mbar_arrive_cluster(empty_c + 8 * slp, signaller && (i == 4 || !wg));
          wg_wait<0>();
          mbar_arrive_cluster(empty_c + 8 * sl, signaller);
        }
      }
      pin(acc);
      prof(wg, 3 + p);
      TS4(50 + 2 * p)
      st0 += 5;
      if (hlp && st0 > 5) bar_sync(BAR_QF + wg, 160);
      park_paced<0, 8>(qlane(lane) + (hlp ? 5 + wg : 4 + p) * STAGE, acc, rstd0, rstd1, 300);
      if (p || hlp) asm volatile("fence.proxy.async.shared::cta;" ::: "memory");
      if (hlp) bar_arrive(BAR_QS + wg, 160);
      if (p == 3) { rstd0 = sq0; rstd1 = sq1; }
      TS4(51 + 2 * p)
      if (p == 1 && !hlp) {
        float (&ah)[32] = *(float (*)[32])&acc[0];
#pragma unroll
        for (int i = 0; i < 3; i++) {
          const uint32_t sl = (10 + i) & 3;
          if (!wg) mbar_wait(full + 8 * sl, ((10 + i) >> 2) & 1);
          TS4(28 + 2 * i)
          if (i == 0 || i == 2 - wg) bar_sync(my_turn, 256);
          wg_fence();
          const uint64_t db = mkdesc(ring + sl * STAGE, 16);
#pragma unroll
          for (int k = 0; k < 12; k++) {
            const int kb = 12 * i + k;
            if (kb) mma_n64t(ah, xa[4 * kb], xa[4 * kb + 1], xa[4 * kb + 2], xa[4 * kb + 3], db + k * 128, true);
            else mma_n64t_dyn(ah, xa[0], xa[1], xa[2], xa[3], db, blockIdx.y);
          }
          wg_commit();
          TS4(29 + 2 * i)
          if (i == 2 || i != wg) {
            bar_arrive(other_turn, 256);
            if (i) {
              wg_wait<1>();
              mbar_arrive_cluster(empty_c + 8 * ((9 + i) & 3), signaller && i == wg + 1);
            }
            wg_wait<0>();
            mbar_arrive_cluster(empty_c + 8 * sl, signaller);
          }
        }
        pin(ah);
        TS4(54)
        park<0, 4>(qlane(lane) + 6 * STAGE, ah, rstd0, rstd1);
        TS4(55)
        st0 = 13;
        n = 2;
      }
    }
    TS_DUMP()
    ffn_consumer(cx, blockIdx.x & 3, wg, cw, fresh_lane(), x);
    return;
  }

attention:
  uint32_t oa[128];
  float acc[32];
  {
    uint32_t pf[28];
    const uint32_t ql = qlane(fresh_lane());
    uint32_t bad = 0;
    float lA0 = 0.f, lA1 = 0.f, lB0 = 0.f, lB1 = 0.f;
    int t = 0;
    uint32_t ra = 2 * 2048, rb = 2048, rc = 2 * 2048, par = 0;
    const uint64_t dk0 = mkdesc(ring, 16), dv0 = mkdesc(ring, 16384);
    uint64_t dqA = mkdesc_q(qwg + 4 * STAGE), dqB = dqA + 2048;
    auto turn = [&](auto kc_, auto bc_) {
      constexpr int KIND = decltype(kc_)::value, BIG = decltype(bc_)::value;
      constexpr int HB = KIND == 1, ID = 10 * KIND + 30 * BIG, T0 = BIG ? 38 : 0;
      constexpr int NS = BIG ? 56 : 48, SPLIT = (BIG ? 36 : 30) + 2 * HB;
      float s[NS];
      float (&op)[64] = HB ? oA : oB;
      uint32_t h0 = 0, h1 = 0;
      TS2(0)
      bar_sync(my_turn, 256);
      TS2(1)
      if (KIND) { pin(pf); pin(op); }
      mma_qk(s, HB ? dqB : dqA, dk0 + (HB ? ra : rc));
      TS2(2)
      if (KIND) {
        const bool bigp = HB ? BIG : BIG ? t != 10 : t == 66;
        block_fence(ID + 9);
        pin(pf);
        sum_tree(pf, bigp, h0, h1);
        asm volatile("" : "+r"(h0), "+r"(h1)::"memory");
        if (HB) mbar_wait(full + (rb >> 8), par);
        mma_pv(op, pf, dv0 + rb, t != T0 + 2 - HB, bigp);
      } else {
        mbar_wait(full + (rb >> 8), (NST_Q - 1) >> 2 & 1);
#pragma unroll
        for (int k = 0; k < 8; k++) mma_n128t(op, xl[4 * k], xl[4 * k + 1], xl[4 * k + 2], xl[4 * k + 3], dv0 + rb + k * 128, 1);
        wg_commit();
      }
      TS2(3)
      bar_arrive(other_turn, 256);
      (HB ? lA0 : lB0) += bf_lo(h0) + bf_hi(h0);
      (HB ? lA1 : lB1) += bf_lo(h1) + bf_hi(h1);
      wg_wait<1>();
      pin(s);
      TS1(t)
      TS2(4)
      if (KIND == 1) mbar_arrive_cluster_now<ID + 3>(empty_c + (ra >> 8), signaller);
      if (BIG && t == T0 + HB) {
        const uint32_t a = ql + (4 + HB) * STAGE;
        const bool ok = !__any_sync(0xffffffffu, inv_sums(HB ? lB0 : lA0, HB ? lB1 : lA1, i0, i1));
        if (!ok) bad |= 1 << HB;
        (HB ? lB0 : lA0) = 0.f;
        (HB ? lB1 : lA1) = 0.f;
        constexpr int E0 = 10, E1 = (E0 + SPLIT) / 2;
        softmax_exp<0, E0>(s);
#pragma unroll
        for (int i = 0; i < E0; i++) asm volatile("" : "+f"(s[i])::"memory");
        block_fence(ID + 7);
        softmax_exp<E0, E1>(s);
        park<0, 4>(a, HB ? oB : oA, i0, i1, ok);
#pragma unroll
        for (int i = E0; i < E1; i++) asm volatile("" : "+f"(s[i])::"memory");
        block_fence(200 + ID);
        softmax_exp<E1, SPLIT>(s);
        park<4, 8>(a, HB ? oB : oA, i0, i1, ok);
        if (!HB) dqB += 2048;
        prof(wg, 8 + HB);
      } else {
        softmax_exp<0, SPLIT>(s);
      }
      pin(s);
      if (!BIG) block_fence(ID + 4);
      TS2(5)
      wg_wait<0>();
      TS2(6)
      pin(op);
      if (KIND) pin(pf); else pin(xl);
      if (HB) {
        par ^= rc == 2048;
        if (BIG && t == 37) dqA -= 4 * 2048;
        if (BIG && t == 33 && cw == 0) bar_arrive(BAR_HELPER, 64);
      } else {
        mbar_arrive_cluster_now<ID + 5>(empty_c + (rb >> 8), signaller);
        if (KIND) {
          par ^= ra == 2048;
          const uint32_t x = ra;
          ra = rc; rc = rb; rb = x;
        }
      }
      softmax_exp<SPLIT, NS>(s);
#pragma unroll
      for (int i = 0; i < NS / 2; i++) pf[i] = pack2(s[2 * i], s[2 * i + 1]);
      pin(pf);
      if (KIND == 0) {
        block_fence(ID + 6);
        park_paced<0, 6>(ql, oB, i0, i1, 310);

        prof(wg, 7);
      }
      if (HB && !BIG && t == 1) park<6, 8>(ql, oB, i0, i1);
      if (BIG && !HB && t == T0) mbar_wait(cx.sb + SM_BAR_Q + 8 * wg, 0);
      if (HB) mbar_wait(full + (rc >> 8), par);
      t++;
    };
#pragma unroll
    for (int i = 24; i < 28; i++) asm volatile("" : "=r"(pf[i]));
    mbar_wait(full + 8 * 2, 0);
    turn(IC<0>(), IC<0>());
    rb = 3 * 2048; rc = 2048;
    kill(oA);
    const bool never = blockIdx.y == 1;
#pragma unroll 1
    while (true) {
      turn(IC<1>(), IC<0>());
      if (t == 76) break;
      if (t == 10) {
        asm volatile("fence.proxy.async.shared::cta;" ::: "memory");
#pragma unroll 1
        do {
#pragma unroll 1
          do turn(IC<2>(), IC<1>()); while (never);
          turn(IC<1>(), IC<1>());
        } while (t != 66);
      }
#pragma unroll 1
      do turn(IC<2>(), IC<0>()); while (never);
    }
    auto scale = [&](auto lo, auto hi) {
#pragma unroll
      for (int i = decltype(lo)::value; i < decltype(hi)::value; i++) {
        oa[32 + 2 * i] = pack2(oA[4 * i] * i0, oA[4 * i + 1] * i0);
        oa[32 + 2 * i + 1] = pack2(oA[4 * i + 2] * i1, oA[4 * i + 3] * i1);
        asm volatile("" : "+r"(oa[32 + 2 * i]), "+r"(oa[32 + 2 * i + 1])::"memory");
      }
    };
    TS3(1)
    volatile uint32_t* const cold = (volatile uint32_t*)(cx.sp + SM_COLD) + wg;
    if (inv_sums(lA0, lA1, i0, i1)) bad |= 4;
#pragma unroll
    for (int i = 0; i < 8; i++) ldsm4(ql + 4 * STAGE + i * 2048, oa[4 * i], oa[4 * i + 1], oa[4 * i + 2], oa[4 * i + 3]);
    {
      uint32_t h0, h1;
      sum_tree(pf, false, h0, h1);
      lB0 += bf_lo(h0) + bf_hi(h0);
      lB1 += bf_lo(h1) + bf_hi(h1);
      asm volatile("" : "+f"(lB0), "+f"(lB1)::"memory");
    }
    scale(IC<0>(), IC<4>());
    if (bad) *cold = 1;
    block_fence(93);
    TS3(2)
    bar_sync(my_turn, 256);
    TS3(3)
    pin(pf); pin(oB);
    mma_pv(oB, pf, dv0 + 2 * 2048, true, false);
    block_fence(91);
    TS3(4)
    const uint32_t held = *cold;
    if (inv_sums(lB0, lB1, lB0, lB1)) bad |= 8;
    const uint64_t db = mkdesc(ring + 3 * STAGE, 16);
    scale(IC<4>(), IC<12>());
    mbar_arrive_cluster_now<94>(empty_c, signaller && !held);
#pragma unroll
    for (int i = 0; i < 32; i++) asm volatile("" : "+r"(oa[i])::"memory");
    wg_fence();
#pragma unroll
    for (int k = 0; k < 8; k++) mma_n64t(acc, oa[4 * k], oa[4 * k + 1], oa[4 * k + 2], oa[4 * k + 3], db + k * 128, k > 0);
    wg_commit();
    block_fence(95);
    scale(IC<12>(), IC<16>());
    TS3(5)
    wg_fence();
#pragma unroll
    for (int k = 8; k < 16; k++) mma_n64t(acc, oa[4 * k], oa[4 * k + 1], oa[4 * k + 2], oa[4 * k + 3], db + k * 128, 1);
    wg_commit();
    bar_arrive(other_turn, 256);
    if (bad) *cold = 1;
    bar_sync(4 + wg, 128);
    const uint32_t is_cold = *cold;
    wg_wait<2>();
    pin(oB); pin(pf);
    TS(76)
    TS3(6)
    mbar_arrive_cluster_now<97>(empty_c + 8 * 2, signaller);
#pragma unroll
    for (int i = 16; i < 24; i++) ldsm4(ql + 5 * STAGE + (i & 7) * 2048, oa[4 * i], oa[4 * i + 1], oa[4 * i + 2], oa[4 * i + 3]);
#pragma unroll
    for (int i = 0; i < 16; i++) {
      oa[96 + 2 * i] = pack2(oB[4 * i] * lB0, oB[4 * i + 1] * lB0);
      oa[96 + 2 * i + 1] = pack2(oB[4 * i + 2] * lB1, oB[4 * i + 3] * lB1);
    }
    TS3(7)
    if (!wg) mbar_wait(full + 8 * 1, 0);
    TS3(8)
    wg_wait<0>();
    pin(acc); pin(oa);
    if (__any_sync(0xffffffffu, is_cold)) {
      bad = __reduce_or_sync(0xffffffffu, bad);
      if (!(bad & 8)) {
#pragma unroll
        for (int i = 24; i < 32; i++) stsm4(ql + 6 * STAGE + (i & 7) * 2048, oa[4 * i], oa[4 * i + 1], oa[4 * i + 2], oa[4 * i + 3]);
      }
#pragma unroll 1
      for (int h = 0; h < 4; h++) {
        if (bad >> h & 1) {
          const uint32_t a = ql + ((0x6054 >> (4 * h)) & 7) * STAGE;
          const int l = fresh_lane(), o = (hs * 2 + (h >> 1)) * SEQ * DH + (l >> 2) * DH + (l & 3) * 2;
          uint32_t q[32];
#pragma unroll
          for (int i = 0; i < 8; i++) ldsm4(a + i * 2048, q[4 * i], q[4 * i + 1], q[4 * i + 2], q[4 * i + 3]);
#pragma unroll 1
          for (int i = 0; i < 4; i++) {
            float ox[16], l0, l1;
            exact_attention(ox, l0, l1, q, kc + o, vc + o + i * 32);
            inv_sums(l0, l1, l0, l1);
            park<0, 2>(a + i * 4096, ox, l0, l1);
          }
        }
      }
      __syncwarp();
#pragma unroll
      for (int i = 0; i < 32; i++)
        if ((i >> 3) != 1 || (bad & 4))
          ldsm4(ql + ((0x6504 >> (4 * (i >> 3))) & 7) * STAGE + (i & 7) * 2048, oa[4 * i], oa[4 * i + 1], oa[4 * i + 2], oa[4 * i + 3]);
      pin(oa);
      asm volatile("fence.proxy.async.shared::cta;" ::: "memory");
      bar_sync(4 + wg, 128);
      mbar_arrive_cluster(empty_c, signaller && held);
      wg_fence();
#pragma unroll
      for (int k = 0; k < 16; k++) mma_n64t(acc, oa[4 * k], oa[4 * k + 1], oa[4 * k + 2], oa[4 * k + 3], db + k * 128, k > 0);
      wg_commit();
      wg_wait<0>();
      pin(acc);
    }
    mbar_arrive_cluster(empty_c + 8 * 3, signaller);
  }

  prof(wg, 10);
  TS3(9)
  {
    lane = fresh_lane();
    const int tw = (cw & 3) * 32 + lane;
    float red[32];
    kill(red);
    const uint32_t tag = *(const uint32_t*)(cx.sp + SM_TAG);
    uint4* const xch = at(cx.g->part, ((qb * 64 * 2 + wg) * 4 * 128 + tw) * 16);
    int nrx = 1;
    auto region = [](int s, int h) { return h ? 1 + (s & 1) : (s & 1) ? 0 : 3; };
    auto half_step = [&](int s, auto hc, bool arrive) {
      constexpr int h = decltype(hc)::value;
      const uint64_t db = mkdesc(ring + region(s, h) * STAGE, 16);
      bar_sync(my_turn, 256);
      pin(oa);
      wg_fence();
#pragma unroll
      for (int k = 0; k < 16; k++) {
        const int kb = h * 16 + k;
        mma_n64t(acc, oa[4 * kb], oa[4 * kb + 1], oa[4 * kb + 2], oa[4 * kb + 3], db + k * 128, kb > 0);
      }
      wg_commit();
      if (arrive) bar_arrive(other_turn, 256);
    };
    auto await = [&](int s, int h) { mbar_wait(full + 8 * region(s, h), ((s >> 1) ^ h ^ 1) & 1); };
    auto fetch = [&](uint32_t (&g)[16], int n) {
      const uint4* p = at(xch, (hs * 7 + n - 1) * 16384);
#pragma unroll
      for (int i = 0; i < 4; i++) ld_gran(p + i * 128, g[4 * i], g[4 * i + 1], g[4 * i + 2], g[4 * i + 3]);
    };
    uint32_t g[16];
    bool pend = false;
#pragma unroll 1
    for (int s = 0;; s++) {
      half_step(s, IC<1>(), s + wg < 9);
      if (s == 8) break;
      TS3(s < 3 ? 16 + 8 * s : 75)
      if (s == 0) {
        bar_arrive(BAR_OA, 352);
#pragma unroll
        for (int i = 0; i < 32; i++) red[i] = 0.f;
      }
      await(s + 1, 0);
      TS3(s < 3 ? 17 + 8 * s : 75)
      wg_wait<0>();
      TS3(s < 3 ? 18 + 8 * s : 75)
      mbar_arrive_cluster(empty_c + 8 * region(s, 1), signaller && s < 7);
      pin(acc);
      TS(77 + s)
      prof(wg, 12 + s);
      uint4* p = at(xch, (s == 0 ? 56 + hs : ((hs + s) & 7) * 7 + s - 1) * 16384);
#pragma unroll
      for (int i = 0; i < 4; i++)
        st_gran(p + i * 128, (pack2(acc[8 * i], acc[8 * i + 1]) & ~TAG) | tag, pack2(acc[8 * i + 2], acc[8 * i + 3]),
                pack2(acc[8 * i + 4], acc[8 * i + 5]), pack2(acc[8 * i + 6], acc[8 * i + 7]));
      TS3(s < 3 ? 19 + 8 * s : 75)
      half_step(s + 1, IC<0>(), true);
      TS3(s < 3 ? 20 + 8 * s : 75)
      if (pend && granules_ok(g, tag)) { add_granules(red, g); nrx++; }
      pend = nrx < s;
      if (pend) fetch(g, nrx);
      await(s + 1, 1);
      TS3(s < 3 ? 21 + 8 * s : 75)
      wg_wait<0>();
      TS3(s < 3 ? 22 + 8 * s : 75)
      mbar_arrive_cluster(empty_c + 8 * region(s + 1, 0), signaller && s < 6);
    }
    uint32_t xv[16], gt[16], g2[16];
    TS3(42)
    const bool ok = granules_ok(g, tag);
    TS3(43)
    nrx += ok;
    fetch(g2, nrx);
    mbar_wait(cx.sb + SM_BAR_XG, 0);
    const uint32_t frag = (cw * 16 + (lane & 15)) * 128 + (((lane >> 4) ^ (lane & 7)) << 4);
#pragma unroll
    for (int i = 0; i < 4; i++) {
      ldsm4(cx.sb + SM_XO + (frag ^ (i << 5)), xv[4 * i], xv[4 * i + 1], xv[4 * i + 2], xv[4 * i + 3]);
      ldsm4(cx.sb + SM_GO + (frag ^ (i << 5)), gt[4 * i], gt[4 * i + 1], gt[4 * i + 2], gt[4 * i + 3]);
    }
    if (ok) add_granules(red, g);
    TS3(44)
    wg_wait<0>();
    pin(acc);
    TS(85)
#pragma unroll
    for (int i = 0; i < 32; i++) red[i] += acc[i];
    pin(red);
#pragma unroll 1
    for (int spins = 0; spins < (1 << 16); spins++) {
      if (granules_ok(g2, tag)) {
        add_granules(red, g2);
        if (++nrx == 8) break;
      }
      fetch(g2, nrx);
    }
    uint32_t ow[16];
#pragma unroll
    for (int i = 0; i < 16; i++) ow[i] = pack2(red[2 * i], red[2 * i + 1]);
    prof(wg, 20);
    TS(86)
#pragma unroll
    for (int i = 0; i < 16; i++) ow[i] = fma2(ow[i], gt[i], xv[i]);
#pragma unroll
    for (int i = 0; i < 4; i++) stsm4(cx.sb + SM_XO + (frag ^ (i << 5)), ow[4 * i], ow[4 * i + 1], ow[4 * i + 2], ow[4 * i + 3]);
    __syncwarp();
    __nv_bfloat16* const op = at(out, ((qb * 128 + cw * 16 + (lane >> 3)) * DM + hs * 64 + (lane & 7) * 8) * 2);
#pragma unroll
    for (int i = 0; i < 4; i++) {
      uint4 v;
      const int row = cw * 16 + i * 4 + (lane >> 3);
      lds128(cx.sb + SM_XO + row * 128 + (((lane ^ row) & 7) << 4), v.x, v.y, v.z, v.w);
      asm volatile("st.global.v4.b32 [%0], {%1, %2, %3, %4};" ::"l"(op + i * 4 * DM),
                   "r"(v.x), "r"(v.y), "r"(v.z), "r"(v.w) : "memory");
    }
    prof(wg, 22);
    TS(87)
    TS_DUMP()
  }
}

struct KvMaps { CUtensorMap m[4]; };
__global__ void __cluster_dims__(2, 1, 1) __launch_bounds__(THREADS, 1)
fused_kernel(const __nv_bfloat16* __restrict__ x, const __nv_bfloat16* __restrict__ w_r, const __nv_bfloat16* __restrict__ kc,
             const __nv_bfloat16* __restrict__ vc, __nv_bfloat16* __restrict__ out, Scratch* scratch,
             const __grid_constant__ CUtensorMap tmX, const __grid_constant__ CUtensorMap tmWq,
             const __grid_constant__ KvMaps tmKV, const __grid_constant__ CUtensorMap tmWo,
             const __grid_constant__ CUtensorMap tmG, const __grid_constant__ CUtensorMap tmU,
             const __grid_constant__ CUtensorMap tmD, const __grid_constant__ CUtensorMap tmX16,
             const __grid_constant__ CUtensorMap tmWq96, const __grid_constant__ CUtensorMap tmX64) {
  extern __shared__ __align__(1024) uint8_t smem_raw[];
  prof(0, 23, 511);
  Ctx cx;
  cx.sb = smem_u32(smem_raw);
  cx.sp = smem_raw;
  cx.g = scratch;
  cx.rank = blockIdx.x & 1;
  if (threadIdx.x == 160) {
    mbar_init(cx.sb + SM_BAR_W, 1);
    asm volatile("fence.mbarrier_init.release.cluster;" ::: "memory");
    *(uint4*)(cx.sp + SM_ONES) = make_uint4(0x3F803F80u, 0x3F803F80u, 0x3F803F80u, 0x3F803F80u);
    mbar_expect_tx(cx.sb + SM_BAR_W, DM * 2);
    bulk_load(cx.sb + SM_WR, w_r, DM * 2, cx.sb + SM_BAR_W);
  }
  const int cluster = blockIdx.x >> 1;
  const bool is_ffn = blockIdx.x >= N_ATT_CTA;
  const int c7 = ((cluster - 36) * 37) >> 8;
  const int hs = cluster < 4 ? 4 + cluster : cluster < 36 ? (cluster - 4) >> 3 : 4 + c7;
  const int qb = (cluster < 4 ? 0 : cluster < 36 ? (cluster - 4) & 7 : cluster - (is_ffn ? 36 : 35) - 7 * c7) * 2 + cx.rank;

  auto x_bar = [&](int i) { return cx.sb + SM_XFULL + 32 * (i / 3) + 8 * (i % 3); };
  auto load_x = [&](int i0, int i1) {
#pragma unroll
    for (int i = i0; i < i1; i++) {
      mbar_expect_tx(x_bar(i), 24576);
      tma3d(cx.sb + SM_X + i * 24576, &tmX, qb * 128 + (i / 3) * 64, (i % 3) * 3, x_bar(i));
    }
  };
  if (threadIdx.x == 128) {
    mbar_init(x_bar(0), 1);
    load_x(0, 1);
    TSP(66)
#pragma unroll
    for (int i = 1; i < 6; i++) mbar_init(x_bar(i), 1);
    asm volatile("fence.mbarrier_init.release.cluster;" ::: "memory");
  }
  const int warp = __shfl_sync(0xffffffffu, threadIdx.x >> 5, 0);
  if (warp < 4) {
    asm volatile("setmaxnreg.dec.sync.aligned.u32 24;");
    if (elect_one()) {
      if (warp == 0) TSP(64)
      if (warp < 2) {
#pragma unroll
        for (int i = 0; i < 4; i++) mbar_init(cx.sb + SM_FULL + 32 * warp + 8 * i, 1 + 3 * warp);
        mbar_init(cx.sb + SM_BAR_XG + 8 * warp, 32);
        mbar_init(cx.sb + SM_BAR_Q + 8 * warp, 1);
        if (warp) mbar_init(cx.sb + SM_BAR_MISC, 1);
      } else if (is_ffn) {
#pragma unroll
        for (int i = 0; i < 8; i++) mbar_init(cx.sb + (warp == 2 ? SM_FFULL : SM_FEMPTY) + 8 * i, 1);
      }
      asm volatile("fence.mbarrier_init.release.cluster;" ::: "memory");
    }
    __syncwarp();
    cluster_arrive();
    if (warp == 0) TSP(70)
    cluster_wait();
    if (warp == 0) TSP(71)
    prof(0, 24, 511);
    if (warp == 0) {
      if (is_ffn) ffn_producer(cx, qb, &tmWq, &tmG, &tmU, &tmD);
      else attn_producer(cx, qb, hs, tmKV.m, &tmWq, &tmWq96, &tmWo);
      prof(0, 25, 511);
    } else {
      sq_publish(cx, qb, hs, warp - 1, read_lane());
      if (warp == 3) sq_collect(cx, qb, read_lane());
      if (!is_ffn) {
        attn_gate(cx, qb, hs, warp - 1, threadIdx.x - 32, x);
        if (warp == 1) TSP(65)
        asm volatile("fence.proxy.async.global;" ::: "memory");
        if (warp == 1) attn_helper(cx, qb, hs, fresh_lane(), &tmX16);
        else bar_arrive(BAR_OA, 352);
        attn_finish8(cx, qb, hs, warp - 1, fresh_lane(), out);
      } else if (warp < 3) {
        ffn_publish(cx, qb, warp - 1, fresh_lane(), &tmX64);
      }
    }
    __syncwarp();
    cluster_arrive();
    cluster_wait();
  } else {
    cluster_arrive();
    if (warp == 4 && elect_one()) {
      load_x(1, 6);
      TSP(67)
    }
    __syncwarp();
    asm volatile("setmaxnreg.inc.sync.aligned.u32 240;");
    const int cw = warp - 4, wg = cw >> 2;
    cluster_wait();
    if (warp == 8 && elect_one()) {
      const uint64_t pol = policy_evict_first();
#pragma unroll
      for (int i = 0; i < 4; i++) {
        if (!(i & 1)) mbar_expect_tx(cx.sb + SM_FULL + 4 * i, 32768);
        tma2d_mc(cx.sb + SM_RING + (i >> 1) * STAGE + cx.rank * 16384 + (i & 1) * 8192, &tmWq,
                 is_ffn ? (cx.rank * 4 + 3) * DH + 64 : hs * 512 + cx.rank * 64, i * 64, cx.sb + SM_FULL + 8 * (i >> 1), pol);
      }
      TSP(72)
    }
    __syncwarp();
    attn_consumer(cx, is_ffn, qb, hs, wg, cw, read_lane(), x, kc, vc, out);
  }
}

typedef CUresult (*EncodeFn)(CUtensorMap*, CUtensorMapDataType, cuuint32_t, void*, const cuuint64_t*, const cuuint64_t*,
                             const cuuint32_t*, const cuuint32_t*, CUtensorMapInterleave, CUtensorMapSwizzle,
                             CUtensorMapL2promotion, CUtensorMapFloatOOBfill);

void encode(EncodeFn fn, CUtensorMap* m, const void* p, int rank, const cuuint64_t* dims, const cuuint64_t* strides,
            const cuuint32_t* box) {
  const cuuint32_t es[5] = {1, 1, 1, 1, 1};
  fn(m, CU_TENSOR_MAP_DATA_TYPE_BFLOAT16, rank, const_cast<void*>(p), dims, strides, box, es, CU_TENSOR_MAP_INTERLEAVE_NONE,
     CU_TENSOR_MAP_SWIZZLE_128B, CU_TENSOR_MAP_L2_PROMOTION_L2_128B, CU_TENSOR_MAP_FLOAT_OOB_FILL_NONE);
}
void encode2d(EncodeFn fn, CUtensorMap* m, const void* p, uint64_t rows, uint64_t cols, uint32_t box_rows) {
  const cuuint64_t dims[2] = {cols, rows}, strides[1] = {cols * 2};
  const cuuint32_t box[2] = {64, box_rows};
  encode(fn, m, p, 2, dims, strides, box);
}

}

extern "C" void kernel_launch(void* const* d_in, const int* in_sizes, int n_in, void* d_out, int out_size) {
  (void)in_sizes; (void)n_in; (void)out_size;
  void* fnp = nullptr;
  cudaDriverEntryPointQueryResult qr;
  cudaGetDriverEntryPoint("cuTensorMapEncodeTiled", &fnp, cudaEnableDefault, &qr);
  EncodeFn fn = (EncodeFn)fnp;
  CUtensorMap tmWq, tmWo, tmG, tmU, tmD, tmX, tmX16, tmWq96, tmX64;
  encode2d(fn, &tmX64, d_in[0], SEQ, DM, 64);
  encode2d(fn, &tmWq96, d_in[3], DM, 4096, 96);
  encode2d(fn, &tmX16, d_in[0], SEQ, DM, 16);
  KvMaps tmKV;
  for (int i = 0; i < 4; i++) encode2d(fn, &tmKV.m[i], d_in[1 + (i & 1)], 16 * SEQ, DH, i < 2 ? 112 : 96);
  encode2d(fn, &tmWq, d_in[3], DM, 4096, 64);
  {
    const cuuint64_t dims[3] = {64, SEQ, 9}, strides[2] = {DM * 2, 128};
    const cuuint32_t box[3] = {64, 64, 3};
    encode(fn, &tmX, d_in[0], 3, dims, strides, box);
  }
  encode2d(fn, &tmWo, d_in[4], 4096, DM, 128);
  encode2d(fn, &tmG, d_in[7], DM, FF, 192);
  encode2d(fn, &tmU, d_in[8], DM, FF, 192);
  encode2d(fn, &tmD, d_in[9], FF, DM, 192);
  cudaFuncSetAttribute(fused_kernel, cudaFuncAttributeMaxDynamicSharedMemorySize, SM_TOTAL);
  void* scratch = nullptr;
  cudaGetSymbolAddress(&scratch, g_scratch);
  fused_kernel<<<N_CTA, THREADS, SM_TOTAL>>>((const __nv_bfloat16*)d_in[0], (const __nv_bfloat16*)d_in[6], (const __nv_bfloat16*)d_in[1],
                                            (const __nv_bfloat16*)d_in[2], (__nv_bfloat16*)d_out, (Scratch*)scratch, tmX, tmWq, tmKV,
                                            tmWo, tmG, tmU, tmD, tmX16, tmWq96, tmX64);
}
```
